```python
import torch

def _softmax(x, axis=-1):
    return torch.softmax(x, dim=axis)
def _gelu(x):
    return torch.nn.functional.gelu(x, approximate="tanh")
def _silu(x):
    return torch.nn.functional.silu(x)
def _sigmoid(x):
    return torch.sigmoid(x)
def _layernorm(x, axis=-1, eps=1e-5):
    m = x.mean(dim=axis, keepdim=True)
    v = x.var(dim=axis, keepdim=True, unbiased=False)
    return (x - m) / torch.sqrt(v + eps)
def _scatter_add(tgt, idx, src, axis=0):
    return tgt.clone().index_add_(axis, idx, src)
def _segment_sum(src, seg, n):
    out = torch.zeros((n,) + src.shape[1:], dtype=src.dtype)
    return out.index_add_(0, seg, src)
def _pad(x, pw):
    flat = tuple(v for pair in reversed(pw) for v in pair)
    return torch.nn.functional.pad(x, flat)

kernel_name = 'standalone__cheap_equivariant_egnn__graph'

def setup_inputs():

    _w = (lambda a: (lambda t: t.to(torch.bfloat16) if t.is_floating_point() else t)(torch.as_tensor(a)))
    N, deg, D, De = 50000, 16, 64, max(16, 1)
    E = N * deg
    return {
        "h": _w((lambda *s: torch.randn(*s, dtype=torch.bfloat16) * 0.2)(N, D)),
        "pos": _w((lambda *s: torch.randn(*s, dtype=torch.bfloat16) * 0.8)(N, 3)),
        "e_attr": _w((lambda *s: torch.randn(*s, dtype=torch.bfloat16) * 0.8)(E, De)),
        "src": _w((lambda lo, hi, *s: torch.randint(lo, hi, s))(0, N, E).to(torch.int64)),
        "dst": _w((lambda lo, hi, *s: torch.randint(lo, hi, s))(0, N, E).to(torch.int64)),
        "w_e": _w(0.1 * (lambda *s: torch.randn(*s, dtype=torch.bfloat16) * 0.8)(2 * D + 1 + De, D)),
        "w_x": _w(0.1 * (lambda *s: torch.randn(*s, dtype=torch.bfloat16) * 0.2)(D, 1)),
        "w_h": _w(0.1 * (lambda *s: torch.randn(*s, dtype=torch.bfloat16) * 0.2)(2 * D, D)),
    }

def reference(h, pos, e_attr, src, dst, w_e, w_x, w_h):
    N, D = h.shape[0], h.shape[1]
    diff = pos[dst] - pos[src]
    dist2 = torch.sum(diff * diff, axis=-1, keepdims=True)
    e_in = torch.concatenate([h[dst], h[src], dist2, e_attr], axis=-1)
    m_ij = _silu(e_in @ w_e)
    coord_scale = m_ij @ w_x
    pos_new = pos + _segment_sum(diff * coord_scale, dst, N)
    m_i = _segment_sum(m_ij, dst, N)
    h_new = h + _silu(torch.concatenate([h, m_i], axis=-1) @ w_h)
    return h_new, pos_new
```

```cpp
#include <cuda_runtime.h>
#include <cuda_bf16.h>
#include <cuda_fp16.h>
#include <cuda.h>
#include <stdint.h>
#pragma nv_diag_suppress 549

#define PF2 0
#define PF3 8
#define FM 0
#define Q_AFTER_B 0
#define SRC_AFTER 0
#define H_AFTER 4
#define EHINT 0
namespace {

constexpr int G = 132;
constexpr int NTHR = 512, NWK = 352, NCH = 5;
constexpr int NST = 3, STG = 2560;
constexpr int SCAP = 448;

constexpr int OFF_H = 0;
constexpr int OFF_W = 49152;
constexpr int OFF_WD = OFF_W + 16384;
constexpr int OFF_W3 = OFF_WD + 1024;
constexpr int OFF_P2 = OFF_W3 + 2048;
constexpr int OFF_RING = OFF_P2 + 24576;
constexpr int OFF_TE = OFF_RING + 12 * NST * STG;
constexpr int OFF_TS = OFF_TE + SCAP * 64;
constexpr int OFF_GP = OFF_TS + SCAP * 32;
constexpr int OFF_WX = OFF_GP + 3072;
constexpr int OFF_LEN = OFF_WX + 128;
constexpr int OFF_MISC = OFF_LEN + 64;
constexpr int OFF_BAR = OFF_MISC + 32;
constexpr int SMEM = OFF_BAR + 256;
static_assert(SMEM <= 232448, "smem");
constexpr int XO = (G + 1) * 64;
constexpr int OFF_DST = OFF_H + 24576, OFF_SRCI = OFF_TE;
constexpr int OFF_SB = OFF_RING, OFF_SA = OFF_SB + 51200, OFF_XB = OFF_SB;
constexpr int OFF_CNT = OFF_P2 + 16384;
constexpr int OFF_DH = OFF_CNT + 1664;
constexpr int OFF_POS = OFF_DH + 256;
constexpr int OFF_EXT = OFF_POS + 3072;
constexpr int OFF_WS = OFF_SA + 25600 + 8192;
static_assert(OFF_EXT + 1024 <= OFF_RING && OFF_WS + 2304 <= OFF_TE && OFF_P2 % 1024 == 0 && OFF_SA % 1024 == 0 && SCAP * 64 >= 24576, "staging");
__host__ __device__ constexpr int qs_off(int b) { return b < 2 ? OFF_P2 + b * 8192 : b == 2 ? OFF_SA + 25600 : OFF_SA + (b - 3) * 8192; }
constexpr int BAR_DST = OFF_BAR, BAR_SRC = BAR_DST + 40, BAR_W = BAR_SRC + 8, BAR_T = BAR_W + 8, BAR_XA = BAR_T + 48, BAR_XB = BAR_XA + 8, BAR_AW = BAR_XB + 8,
              BAR_BW = BAR_AW + 8, BAR_QP = BAR_BW + 8, BAR_U = BAR_QP + 8, BAR_WH = BAR_U + 8, BAR_END = BAR_WH + 8;
constexpr uint32_t QBYTES = 8u << 20;

__device__ __align__(256) uint4 g_xa[G * G * 8];
__device__ __align__(256) uint4 g_xb[G * G * 16];
__device__ __align__(256) uint4 g_xe[G * G * 12];
__device__ __align__(256) uint4 g_q[2 * QBYTES / 16];
__device__ __align__(256) unsigned long long g_cnt[48];
#define STAMP(k)

struct Maps { CUtensorMap m[6]; };
constexpr int TM_H = 0, TM_WE = 128, TM_WH = 256, TM_Q = 384, TM_XA = 512, TM_XB = 640;
struct Params {
  const uint4* h; const uint16_t* pos; const uint4* ea; const int* src; const int* dst;
  const uint16_t* we; const uint16_t* wx; const uint16_t* wh; uint16_t* out; char* q;
  int N, E, NPC, EPC; uint32_t magic; int force_slow;
};
template<int V> struct IC { static constexpr int value = V; };

#define R32(d) "+f"(d[0]),"+f"(d[1]),"+f"(d[2]),"+f"(d[3]),"+f"(d[4]),"+f"(d[5]),"+f"(d[6]),"+f"(d[7]),"+f"(d[8]),"+f"(d[9]),"+f"(d[10]),"+f"(d[11]),"+f"(d[12]),"+f"(d[13]),"+f"(d[14]),"+f"(d[15]),"+f"(d[16]),"+f"(d[17]),"+f"(d[18]),"+f"(d[19]),"+f"(d[20]),"+f"(d[21]),"+f"(d[22]),"+f"(d[23]),"+f"(d[24]),"+f"(d[25]),"+f"(d[26]),"+f"(d[27]),"+f"(d[28]),"+f"(d[29]),"+f"(d[30]),"+f"(d[31])
#define S32 "{%0,%1,%2,%3,%4,%5,%6,%7,%8,%9,%10,%11,%12,%13,%14,%15,%16,%17,%18,%19,%20,%21,%22,%23,%24,%25,%26,%27,%28,%29,%30,%31}"
#define DI __device__ __forceinline__

constexpr uint64_t DHI = ((uint64_t)(1024 >> 4) << 32) | (1ull << 62);
template<int SD> DI void rs64b(float (&d)[32], uint32_t a0, uint32_t a1, uint32_t a2, uint32_t a3, uint64_t db) {
  asm volatile("wgmma.mma_async.sync.aligned.m64n64k16.f32.bf16.bf16 " S32 ", {%32,%33,%34,%35}, %36, %37, 1, 1, 1;" : R32(d) : "r"(a0), "r"(a1), "r"(a2), "r"(a3), "l"(db), "n"(SD)); }
template<int SD> DI void rs64h(float (&d)[32], uint32_t a0, uint32_t a1, uint32_t a2, uint32_t a3, uint64_t db) {
  asm volatile("wgmma.mma_async.sync.aligned.m64n64k16.f32.f16.f16 " S32 ", {%32,%33,%34,%35}, %36, %37, 1, 1, 1;" : R32(d) : "r"(a0), "r"(a1), "r"(a2), "r"(a3), "l"(db), "n"(SD)); }
template<int SD> DI void ss64(float (&d)[32], uint64_t da, uint64_t db) {
  asm volatile("wgmma.mma_async.sync.aligned.m64n64k16.f32.bf16.bf16 " S32 ", %32, %33, %34, 1, 1, 0, 1;" : R32(d) : "l"(da), "l"(db), "n"(SD)); }
DI void wg_fence() { asm volatile("wgmma.fence.sync.aligned;" ::: "memory"); }
DI void wg_commit() { asm volatile("wgmma.commit_group.sync.aligned;" ::: "memory"); }
DI void wg_wait0() { asm volatile("wgmma.wait_group.sync.aligned 0;" ::: "memory"); }
DI void fence_regs(float (&d)[32]) { asm volatile("" : R32(d) :: "memory"); }
DI void proxy_fence() { asm volatile("fence.proxy.async.shared::cta;" ::: "memory"); }
DI uint64_t pol_first() { uint64_t r; asm("createpolicy.fractional.L2::evict_first.b64 %0, 1.0;" : "=l"(r)); return r; }
DI float tanh_ap(float x) { float y; asm("tanh.approx.f32 %0, %1;" : "=f"(y) : "f"(x)); return y; }
DI float silu_h(float y) { return fmaf(y, tanh_ap(y), y); }
DI uint32_t pack_bf16(float lo, float hi) { uint32_t r; asm("cvt.rn.bf16x2.f32 %0, %1, %2;" : "=r"(r) : "f"(hi), "f"(lo)); return r; }
DI uint32_t pack_f16(float lo, float hi) { uint32_t r; asm("cvt.rn.f16x2.f32 %0, %1, %2;" : "=r"(r) : "f"(hi), "f"(lo)); return r; }
DI float bf_lo(uint32_t v) { return __uint_as_float(v << 16); }
DI float bf_hi(uint32_t v) { return __uint_as_float(v & 0xFFFF0000u); }
DI uint32_t b2h(uint32_t v, float s) { return pack_f16(s * bf_lo(v), s * bf_hi(v)); }
DI void mbar_wait(uint32_t bar, uint32_t parity = 0) {
  asm volatile("{.reg .pred p; .reg .u32 t0, t1;\n"
    "mbarrier.try_wait.parity.shared::cta.b64 p, [%0], %1;\n @p bra.uni LD_%=;\n mov.u32 t0, %%clock;\n"
    "LW_%=: mbarrier.try_wait.parity.shared::cta.b64 p, [%0], %1;\n"
    "@p bra.uni LD_%=;\n mov.u32 t1, %%clock; sub.u32 t1, t1, t0; setp.lt.u32 p, t1, 0x80000000;\n @p bra.uni LW_%=;\n trap;\n LD_%=:}" :: "r"(bar), "r"(parity) : "memory");
}
DI void mbar_arrive(uint32_t bar, int p = 1) { asm volatile("{.reg .pred p; setp.ne.b32 p, %1, 0; @p mbarrier.arrive.shared::cta.b64 _, [%0];}" :: "r"(bar), "r"(p) : "memory"); }
DI void bar_sync(int id, int n) { asm volatile("bar.sync %0, %1;" :: "r"(id), "r"(n) : "memory"); }
DI void bar_arrive(int id, int n) { asm volatile("bar.arrive %0, %1;" :: "r"(id), "r"(n) : "memory"); }
DI __nv_bfloat162 b2(uint32_t v) { return *(__nv_bfloat162*)&v; }
DI uint32_t u2(__nv_bfloat162 v) { return *(uint32_t*)&v; }
DI uint32_t hsq(uint32_t v) { return u2(__hmul2(b2(v), b2(v))); }
DI uint32_t hsub(uint32_t a, uint32_t b) { return u2(__hsub2(b2(a), b2(b))); }
DI uint32_t hhalf(uint32_t v) { return u2(__hmul2(b2(v), __floats2bfloat162_rn(0.5f, 0.5f))); }
DI uint32_t mag2(uint32_t m, uint32_t v) { return __vmaxu2(m, v & 0x7FFF7FFFu); }
DI uint32_t magr(uint32_t m) { return max(m & 0xFFFF, m >> 16); }
DI void sts128(uint32_t a, uint32_t x, uint32_t y, uint32_t z, uint32_t w) { asm volatile("st.shared.v4.u32 [%0], {%1,%2,%3,%4};" :: "r"(a), "r"(x), "r"(y), "r"(z), "r"(w) : "memory"); }
DI void sts64(uint32_t a, uint32_t x, uint32_t y) { asm volatile("st.shared.v2.u32 [%0], {%1,%2};" :: "r"(a), "r"(x), "r"(y) : "memory"); }
DI void sts32(uint32_t a, uint32_t x) { asm volatile("st.shared.u32 [%0], %1;" :: "r"(a), "r"(x) : "memory"); }
DI void sts16(uint32_t a, uint32_t x) { asm volatile("st.shared.u16 [%0], %1;" :: "r"(a), "h"((uint16_t)x) : "memory"); }
DI void lds128(uint32_t* v, uint32_t a) { asm volatile("ld.shared.v4.u32 {%0, %1, %2, %3}, [%4];" : "=r"(v[0]), "=r"(v[1]), "=r"(v[2]), "=r"(v[3]) : "r"(a) : "memory"); }
DI void lds64(uint32_t& x, uint32_t& y, uint32_t a) { asm volatile("ld.shared.v2.u32 {%0, %1}, [%2];" : "=r"(x), "=r"(y) : "r"(a) : "memory"); }
DI uint32_t lds32(uint32_t a) { uint32_t x; asm volatile("ld.shared.u32 %0, [%1];" : "=r"(x) : "r"(a) : "memory"); return x; }
DI uint32_t lds16(uint32_t a) { uint32_t x; asm volatile("ld.shared.u16 %0, [%1];" : "=r"(x) : "r"(a) : "memory"); return x; }
DI uint32_t atoms_add(uint32_t a, uint32_t v) { uint32_t r; asm volatile("atom.shared.add.u32 %0, [%1], %2;" : "=r"(r) : "r"(a), "r"(v) : "memory"); return r; }
DI void bulk_load(uint32_t dst, const void* src, uint32_t bytes, uint32_t bar) {
  asm volatile("cp.async.bulk.shared::cluster.global.mbarrier::complete_tx::bytes.L2::cache_hint [%0], [%1], %2, [%3], %4;" :: "r"(dst), "l"(src), "r"(bytes), "r"(bar), "l"(pol_first()) : "memory"); }
DI void bulk_store(void* dst, uint32_t src, uint32_t bytes) { asm volatile("cp.async.bulk.global.shared::cta.bulk_group [%0], [%1], %2;" :: "l"(dst), "r"(src), "r"(bytes) : "memory"); }
DI void mbar_expect(uint32_t bar, uint32_t bytes) { asm volatile("mbarrier.arrive.expect_tx.shared::cta.b64 _, [%0], %1;" :: "r"(bar), "r"(bytes) : "memory"); }
DI void mbar_init(uint32_t bar, int n) { asm volatile("mbarrier.init.shared::cta.b64 [%0], %1;" :: "r"(bar), "r"(n) : "memory"); }
DI void tma_load(uint32_t dst, uint64_t tm, int row, uint32_t bar) {
  asm volatile("cp.async.bulk.tensor.2d.shared::cluster.global.mbarrier::complete_tx::bytes.L2::cache_hint [%0], [%1, {%3, %4}], [%2], %5;" :: "r"(dst), "l"(tm), "r"(bar), "r"(0), "r"(row), "l"(pol_first()) : "memory"); }
DI void tma_store(uint64_t tm, int col, int row, uint32_t src) {
  asm volatile("cp.async.bulk.tensor.2d.global.shared::cta.bulk_group [%0, {%2, %3}], [%1];" :: "l"(tm), "r"(src), "r"(col), "r"(row) : "memory"); }
DI void bulk_commit() { asm volatile("cp.async.bulk.commit_group;" ::: "memory"); }
DI void bulk_wait() { asm volatile("cp.async.bulk.wait_group 0;" ::: "memory"); }
DI void grid_signal(unsigned long long* cnt, bool flag = false) { asm volatile("red.relaxed.gpu.global.add.u64 [%0], %1;" :: "l"(cnt), "l"(flag ? (1ull << 44) + 1 : 1ull) : "memory"); }
DI bool grid_wait(unsigned long long* cnt, unsigned long long c0) {
  const unsigned long long M = (1ull << 44) - 1, target = ((c0 & M) / G + 1) * G;
  unsigned long long c; int spin = 0;
  do { asm volatile("ld.acquire.gpu.global.u64 %0, [%1];" : "=l"(c) : "l"(cnt) : "memory"); if (++spin > 4000000) __trap(); } while ((c & M) < target);
  return (c ^ c0) >> 44;
}
DI unsigned long long ld_cnt(const unsigned long long* cnt) { unsigned long long c; asm volatile("ld.relaxed.gpu.global.u64 %0, [%1];" : "=l"(c) : "l"(cnt)); return c; }
DI void stsm4(uint32_t a, uint32_t x, uint32_t y, uint32_t z, uint32_t w) { asm volatile("stmatrix.sync.aligned.m8n8.x4.shared.b16 [%0], {%1,%2,%3,%4};" :: "r"(a), "r"(x), "r"(y), "r"(z), "r"(w) : "memory"); }
DI void ldsm4(uint32_t* v, uint32_t a) { asm volatile("ldmatrix.sync.aligned.m8n8.x4.shared.b16 {%0,%1,%2,%3}, [%4];" : "=r"(v[0]), "=r"(v[1]), "=r"(v[2]), "=r"(v[3]) : "r"(a) : "memory"); }
DI void ldsm4t(uint32_t* v, uint32_t a) { asm volatile("ldmatrix.sync.aligned.m8n8.x4.trans.shared.b16 {%0,%1,%2,%3}, [%4];" : "=r"(v[0]), "=r"(v[1]), "=r"(v[2]), "=r"(v[3]) : "r"(a) : "memory"); }
DI uint32_t fpos(uint32_t r) { return ((r << 3) & 0x3F0) | ((r & 1) << 1); }
DI bool wbad(uint32_t m, uint32_t hi) { return m > hi || (m && m < 0x3980); }

__device__ __noinline__ void slow_path(const Params& p, uint32_t sb, int wid, int lane, int node0, int nloc) {
  const uint32_t ab = sb + OFF_P2 + wid * 8704;
  for (int i = lane; i < 32 * 68; i += 32) sts32(ab + i * 4, 0);
  __syncwarp();
  const uint32_t wdv = __ldg((const uint32_t*)(p.we + 128 * 64) + lane), wxv = __ldg((const uint32_t*)p.wx + lane);
  const int nb0 = node0 + wid * 32, cntn = max(0, min(32, nloc - wid * 32));
  auto dot = [&](uint32_t hv, const uint16_t* w, int K2, float& y0, float& y1) {
#pragma unroll 4
    for (int k = 0; k < K2; k++) {
      const uint32_t hk = __shfl_sync(~0u, hv, k), wa = __ldg((const uint32_t*)(w + 2 * k * 64) + lane), wb = __ldg((const uint32_t*)(w + (2 * k + 1) * 64) + lane);
      y0 = fmaf(bf_lo(hk), bf_lo(wa), fmaf(bf_hi(hk), bf_lo(wb), y0)); y1 = fmaf(bf_lo(hk), bf_hi(wa), fmaf(bf_hi(hk), bf_hi(wb), y1));
    }
  };
  auto silu = [](float x) { return x / (1.f + __expf(-x)); };
#pragma unroll 1
  for (int base = 0; base < p.E; base += 32) {
    const int e = base + lane;
    const uint32_t dl = e < p.E ? (uint32_t)(__ldg(p.dst + e) - nb0) : 0xFFFFFFFFu;
    uint32_t mk = __ballot_sync(~0u, dl < (uint32_t)cntn);
    while (mk) {
      const int l = __ffs(mk) - 1; mk &= mk - 1;
      const int ee = base + l, n = __shfl_sync(~0u, dl, l), s = __ldg(p.src + ee);
      const uint16_t *po = p.pos + (size_t)(nb0 + n) * 3, *pp = p.pos + (size_t)s * 3;
      const uint32_t dxy = hsub(__ldg(po) | (__ldg(po + 1) << 16), __ldg(pp) | (__ldg(pp + 1) << 16)), dz = hsub(__ldg(po + 2), __ldg(pp + 2));
      const uint32_t sq = hsq(dxy); const float d2 = bf_lo(sq) + bf_hi(sq) + bf_lo(hsq(dz));
      float y0 = d2 * bf_lo(wdv), y1 = d2 * bf_hi(wdv);
      dot(__ldg((const uint32_t*)(p.h + (size_t)(nb0 + n) * 8) + lane), p.we, 32, y0, y1);
      dot(__ldg((const uint32_t*)(p.h + (size_t)s * 8) + lane), p.we + 64 * 64, 32, y0, y1);
      dot(__ldg((const uint32_t*)(p.ea + (size_t)ee * 2) + (lane & 7)), p.we + 129 * 64, 8, y0, y1);
      const uint32_t mm = pack_bf16(silu(y0), silu(y1));
      float c = bf_lo(mm) * bf_lo(wxv) + bf_hi(mm) * bf_hi(wxv);
#pragma unroll
      for (int o = 16; o; o >>= 1) c += __shfl_xor_sync(~0u, c, o);
      const uint32_t a = ab + n * 272;
      uint32_t x0, x1; lds64(x0, x1, a + lane * 8);
      sts64(a + lane * 8, __float_as_uint(__uint_as_float(x0) + bf_lo(mm)), __float_as_uint(__uint_as_float(x1) + bf_hi(mm)));
      if (lane < 3) { const float df = lane == 0 ? bf_lo(dxy) : lane == 1 ? bf_hi(dxy) : bf_lo(dz); sts32(a + 256 + lane * 4, __float_as_uint(fmaf(c, df, __uint_as_float(lds32(a + 256 + lane * 4))))); }
    }
  }
  __syncwarp();
#pragma unroll 1
  for (int n = 0; n < cntn; n++) {
    uint32_t x0, x1; lds64(x0, x1, ab + n * 272 + lane * 8);
    const uint32_t hv = __ldg((const uint32_t*)(p.h + (size_t)(nb0 + n) * 8) + lane);
    float y0 = 0.f, y1 = 0.f;
    dot(hv, p.wh, 32, y0, y1); dot(pack_bf16(__uint_as_float(x0), __uint_as_float(x1)), p.wh + 64 * 64, 32, y0, y1);
    ((uint32_t*)p.out)[(size_t)(nb0 + n) * 32 + lane] = u2(__hadd2(b2(hv), b2(pack_bf16(silu(y0), silu(y1)))));
    if (lane < 3) p.out[(size_t)p.N * 64 + (size_t)(nb0 + n) * 3 + lane] = (uint16_t)pack_bf16(bf_lo(__ldg(p.pos + (size_t)(nb0 + n) * 3 + lane)) + __uint_as_float(lds32(ab + n * 272 + 256 + lane * 4)), 0.f);
  }
}

__global__ void __launch_bounds__(NTHR, 1) egnn_kernel(const __grid_constant__ Params p, const __grid_constant__ Maps maps) {
  const uint64_t tmb = (uint64_t)&maps;
  extern __shared__ __align__(1024) unsigned char smraw[];
  const uint32_t sb = (uint32_t)__cvta_generic_to_shared(smraw);
  const int tid = threadIdx.x, cta = blockIdx.x;
  const int e0 = cta * p.EPC, n4 = max(0, min(p.EPC, p.E - e0)) >> 2;
  STAMP(0);
  if (tid == NWK) {
#pragma unroll
    for (int k = 0; k <= NCH; k++) mbar_init(sb + BAR_DST + k * 8, 1);
    asm volatile("fence.mbarrier_init.release.cluster;" ::: "memory");
#pragma unroll 1
    for (int k = 0; k < NCH; k++) { const int nb = max(0, min(NWK, n4 - k * NWK)) * 16;
      mbar_expect(sb + BAR_DST + k * 8, nb);
      if (nb) bulk_load(sb + OFF_DST + k * NWK * 16, (const char*)(p.dst + e0) + k * NWK * 16, nb, sb + BAR_DST + k * 8); }
    if (sb & 1023) __trap();
  }
  const int lane = tid & 31, wid = __shfl_sync(~0u, tid >> 5, 0), w = wid & 3;
  const int node0 = cta * p.NPC;
  const int nloc = max(0, min(p.NPC, p.N - node0));
  const uint32_t ealo = (uint32_t)(uint64_t)p.ea;
  const int epad = min(e0, p.E - 1);
  if (wid >= 12) {
    const int t = tid - 384;
    unsigned long long c0 = 0;
    if (t == 0) {
#pragma unroll
      for (int a = BAR_W; a < BAR_END; a += 8) mbar_init(sb + a, a == BAR_WH ? 4 : a == BAR_XA ? 2 : 1);
      asm volatile("fence.mbarrier_init.release.cluster;" ::: "memory");
      mbar_expect(sb + BAR_W, 2 * 8192 + 2304);
      tma_load(sb + OFF_W, tmb + TM_WE, 64, sb + BAR_W); tma_load(sb + OFF_W + 8192, tmb + TM_WE, 0, sb + BAR_W);
      bulk_load(sb + OFF_WS, p.we + 128 * 64, 2176, sb + BAR_W); bulk_load(sb + OFF_WS + 2176, p.wx, 128, sb + BAR_W);
      for (int b = 0; b < 6; b++) mbar_expect(sb + BAR_T + b * 8, 8192);
      c0 = ld_cnt(&g_cnt[32]);
    }
    if (w == 1 && lane < 6) asm volatile("prefetch.tensormap [%0];" :: "l"(tmb + lane * 128));
    uint32_t pv[9], ev = 0;
#pragma unroll
    for (int i = 0; i < 3; i++) { const uint16_t* pp = p.pos + (size_t)(node0 + t + 128 * i) * 3;
      pv[3 * i] = pv[3 * i + 1] = pv[3 * i + 2] = 0;
      asm volatile("{.reg .pred p; setp.lt.u32 p, %4, %5;\n @p ld.global.nc.u16 %0, [%3];\n @p ld.global.nc.u16 %1, [%3+2];\n @p ld.global.nc.u16 %2, [%3+4];}"
        : "+r"(pv[3 * i]), "+r"(pv[3 * i + 1]), "+r"(pv[3 * i + 2]) : "l"(pp), "r"(t + 128 * i), "r"(max(0, p.N - node0))); }
    if (t < 8) { ev = __ldg((const uint32_t*)(p.ea + (size_t)epad * 2) + t);
      ((uint4*)(p.q + (size_t)(p.N + cta) * 128))[t] = make_uint4(0xF700F700u, 0xF700F700u, 0xF700F700u, 0xF700F700u); }
    __syncthreads();
    mbar_wait(sb + BAR_W);
#pragma unroll 2
    for (int i = t; i < 1024; i += 128) { uint32_t v[4]; lds128(v, sb + OFF_W + i * 16); sts128(sb + OFF_W + i * 16, hhalf(v[0]), hhalf(v[1]), hhalf(v[2]), hhalf(v[3])); }
    {
      uint32_t v[4], u[4]; const int r = t >> 3, c = t & 7;
      lds128(v, sb + OFF_WS + 128 + t * 16); lds128(u, sb + OFF_WS + c * 16);
      const uint32_t x = lds32(sb + OFF_WS + 2176 + lane * 4);
      sts128(sb + OFF_W3 + r * 128 + ((c ^ (r & 7)) << 4), b2h(v[0], .5f), b2h(v[1], .5f), b2h(v[2], .5f), b2h(v[3], .5f));
      const float s = ((r & 1) || r == 6) ? 0.f : .5f;
      if (t < 64) sts128(sb + OFF_WD + r * 128 + ((c ^ r) << 4), b2h(u[0], s), b2h(u[1], s), b2h(u[2], s), b2h(u[3], s));
      if (t < 32) sts32(sb + OFF_WX + t * 4, b2h(x, 1.f));
      const uint32_t m3 = __reduce_max_sync(~0u, magr(mag2(mag2(mag2(mag2(0, v[0]), v[1]), v[2]), v[3]))), md = __reduce_max_sync(~0u, magr(mag2(mag2(mag2(mag2(0, u[0]), u[1]), u[2]), u[3])));
      uint32_t mp = 0;
#pragma unroll
      for (int i = 0; i < 3; i++) { sts64(sb + OFF_POS + (t + 128 * i) * 8, pv[3 * i] | (pv[3 * i + 1] << 16), pv[3 * i + 2]); mp = mag2(mag2(mp, pv[3 * i] | (pv[3 * i + 1] << 16)), pv[3 * i + 2]); }
      if (wbad(m3, 0x4000) || wbad(md, 0x4000) || wbad(__reduce_max_sync(~0u, magr(mag2(0, x))), 0x4700) || magr(mp) >= 0x4200 || magr(mag2(0, ev)) >= 0x4380) sts32(sb + OFF_MISC + 8, 1);
    }
    proxy_fence();
    if (t == 0) { mbar_wait(sb + BAR_DST + H_AFTER * 8); for (int b = 0; b < 3; b++) tma_load(sb + OFF_H + b * 8192, tmb + TM_H, node0 + b * 64, sb + BAR_T + b * 8); }
    bar_sync(3, 128);
    mbar_arrive(sb + BAR_XA, t == 0);
    STAMP(24);
    const uint32_t frag = (w * 16 + (lane & 15)) * 128 + (((lane >> 4) ^ (lane & 7)) << 4);
    uint32_t mq = 0;
#pragma unroll 1
    for (int b = 0; b < 6; b++) {
      uint32_t ff[6];
#pragma unroll
      for (int r = 0; r < 2; r++) { const uint32_t v = __byte_perm(lds16(sb + OFF_POS + (b * 64 + w * 16 + (lane >> 2) + 8 * r) * 8 + (lane & 3) * 2), 0, 0x4140);
#pragma unroll
        for (int j = 0; j < 3; j++) ff[2 * j + r] = (v >> (3 * j)) & 0x00070007u; }
      float acc[32];
      const uint64_t da = DHI | ((sb + OFF_H + b * 8192) >> 4), db = DHI | ((sb + OFF_W) >> 4);
      mbar_wait(sb + BAR_T + b * 8);
      if (b == 0) STAMP(25);
      if (b == 5) STAMP(26);
      wg_fence();
      ss64<0>(acc, da, db); ss64<1>(acc, da + 2, db + 128); ss64<1>(acc, da + 4, db + 256); ss64<1>(acc, da + 6, db + 384);
      wg_commit(); wg_wait0(); fence_regs(acc);
      uint32_t o[16];
#pragma unroll
      for (int j = 0; j < 16; j++) { o[j] = pack_f16(acc[2 * j], acc[2 * j + 1]); mq = mag2(mq, o[j]); }
#pragma unroll
      for (int j = 0; j < 6; j++)
        o[j] = (__viaddmax_s16x2(o[j] & 0x7FFF7FFFu, __vsub2(0x00040004u, ff[j]), 0) & 0xFFF8FFF8u) | ff[j] | (o[j] & 0x80008000u);
      if (b == 3) mbar_wait(sb + BAR_AW);
      const uint32_t qs = sb + (b < 2 ? OFF_P2 + b * 8192 : b == 2 ? OFF_SA + 25600 : OFF_SA - 24576 + b * 8192);
#pragma unroll
      for (int j = 0; j < 4; j++) stsm4((qs + frag) ^ (j << 5), o[4 * j], o[4 * j + 1], o[4 * j + 2], o[4 * j + 3]);
      proxy_fence();
      if (b == 5) { const uint32_t m = __reduce_max_sync(~0u, magr(mq)); if (lane == 0) sts32(sb + OFF_MISC + 16 + w * 4, m); }
      bar_sync(3, 128);
      if (!Q_AFTER_B && t == 0 && b * 64 < nloc) tma_store(tmb + TM_Q, 0, node0 + b * 64, qs);
    }
    asm volatile("setmaxnreg.dec.sync.aligned.u32 32;");
    if (t == 0) {
      auto prefetch_e = [&](int lo, int hi) {
        const uint32_t nb = (p.E / G) & ~15u;
        for (int i = lo; i < hi; i++)
          if (nb) asm volatile("cp.async.bulk.prefetch.L2.global [%0], %1;" :: "l"((const char*)p.ea + (size_t)(i * G + cta) * nb), "r"(nb) : "memory");
      };
      if (Q_AFTER_B) { mbar_wait(sb + BAR_BW);
#pragma unroll
        for (int b = 0; b < 6; b++) if (b * 64 < nloc) tma_store(tmb + TM_Q, 0, node0 + b * 64, sb + qs_off(b)); }
      bulk_commit();
      STAMP(18);
      prefetch_e(0, PF2);
      uint32_t mv[4]; lds128(mv, sb + OFF_MISC + 16);
      const uint32_t mx = max(max(mv[0], mv[1]), max(mv[2], mv[3]));
      mbar_wait(sb + BAR_XA);
      bulk_wait();
      STAMP(19);
      grid_signal(&g_cnt[32], nloc && (mx >= 0x7BF0 || mx < 0x1400));
      prefetch_e(PF2, PF3);
      if (grid_wait(&g_cnt[32], c0)) sts32(sb + OFF_MISC + 8, 1);
      STAMP(20);
      mbar_arrive(sb + BAR_QP);
    }
    __syncwarp();
    bar_sync(4, NTHR);
    if (t == 0) { mbar_expect(sb + BAR_U, 16384); tma_load(sb + OFF_W, tmb + TM_WH, 0, sb + BAR_U); tma_load(sb + OFF_W + 8192, tmb + TM_WH, 64, sb + BAR_U); }
    mbar_wait(sb + BAR_U);
    uint32_t mh = 0;
#pragma unroll 1
    for (int i = t; i < 512; i += 128) { uint32_t v[4]; const uint32_t a = sb + OFF_W + i * 16;
      lds128(v, a); sts128(a, hhalf(v[0]), hhalf(v[1]), hhalf(v[2]), hhalf(v[3]));
      lds128(v, a + 8192); sts128(a + 8192, b2h(v[0], .5f), b2h(v[1], .5f), b2h(v[2], .5f), b2h(v[3], .5f));
      mh = mag2(mag2(mag2(mag2(mh, v[0]), v[1]), v[2]), v[3]); }
    if (wbad(__reduce_max_sync(~0u, magr(mh)), 0x4700)) sts32(sb + OFF_MISC + 12, 1);
    proxy_fence();
    __syncwarp();
    mbar_arrive(sb + BAR_WH, lane == 0);
    return;
  }

  auto put = [&](uint32_t x, uint32_t bv, uint32_t eb, bool ok) {
    asm volatile("{.reg .pred p; setp.ne.b32 p, %0, 0;\n @p st.shared.u32 [%1], %3;\n @p st.shared.u16 [%2], %4;}"
      :: "r"((int)ok), "r"(sb + OFF_TE + x * 4), "r"(sb + OFF_TS + x * 2), "r"(eb + (bv >> 16) * 32), "h"((uint16_t)bv) : "memory");
  };
  {
    if (tid < 120) sts128(sb + OFF_CNT + tid * 16, 0, 0, 0, 0);
    if (tid == 120) sts128(sb + OFF_MISC, 0, 0, p.force_slow, 0);
    if (tid >= 128 && tid <= 128 + G) sts32(sb + OFF_SA + (tid - 128) * 128 + (tid & 31) * 4, 0);
    const uint32_t sp = (p.N + cta) * 0x10001u;
    for (int i = tid; i < SCAP * 2; i += 384) sts128(sb + OFF_TS + i * 16, sp, sp, sp, sp);
  }
  if (wid == 11) {
    unsigned long long ca = 0, cb = 0;
    if (lane == 0) { ca = ld_cnt(&g_cnt[0]); cb = ld_cnt(&g_cnt[16]); }
    __syncthreads();
    if (lane == 0) { mbar_wait(sb + BAR_DST + SRC_AFTER * 8);
      mbar_expect(sb + BAR_SRC, n4 * 16);
      for (int o = 0; o < n4 * 16; o += 8192) bulk_load(sb + OFF_SRCI + o, (const char*)(p.src + e0) + o, min(8192, n4 * 16 - o), sb + BAR_SRC); }
    __syncwarp();
    bar_sync(12, 384);
    uint32_t xm[5];
#pragma unroll
    for (int k = 0; k < 5; k++) xm[k] = __ballot_sync(~0u, lane + 32 * k < G && lds32(sb + OFF_SA + min(lane + 32 * k, G) * 128 + lane * 4) > 62);
    auto send = [&](int pl) {
#pragma unroll
      for (int k = 0; k < 5; k++) for (uint32_t m = xm[k]; m; m &= m - 1) { const int j = 32 * k + __ffs(m) - 1;
        bulk_store((char*)(g_xe + (j * G + cta) * 12) + pl * 64, pl ? sb + OFF_SB + (XO + j * 32) * 4 : sb + OFF_SA + (XO + j * 32) * 2, 64 << pl); }
      tma_store(tmb + TM_XA + pl * 128, cta * 64, 0, sb + (pl ? OFF_SB : OFF_SA));
      bulk_commit();
    };
    if (lane == 0) {
      send(0);
      for (int b = 3; b < 6; b++) tma_load(sb + OFF_H + b * 8192, tmb + TM_H, node0 + b * 64, sb + BAR_T + b * 8);
      bulk_wait();
      grid_signal(&g_cnt[0]);
      mbar_arrive(sb + BAR_AW);
      STAMP(16);
    }
    __syncwarp();
    bar_sync(13, 384);
    if (lane == 0) {
      send(1);
      grid_wait(&g_cnt[0], ca);
      mbar_arrive(sb + BAR_XA);
      STAMP(21);
      bulk_wait();
      grid_signal(&g_cnt[16]);
      mbar_arrive(sb + BAR_BW);
      STAMP(17);
      mbar_expect(sb + BAR_XB, G * 256);
      grid_wait(&g_cnt[16], cb);
      asm volatile("fence.proxy.async.global;" ::: "memory");
      for (int o = 0; o < 4; o++) bulk_load(sb + OFF_XB + o * (G * 64), (const char*)g_xb + (size_t)(cta * 4 + o) * (G * 64), G * 64, sb + BAR_XB);
      STAMP(22);
    }
    __syncwarp();
    bar_sync(1, 384);
    if (!lds32(sb + OFF_MISC + 8)) {
      const uint32_t nx = lds32(sb + OFF_MISC + 4);
      for (uint32_t k = lane; k < nx; k += 32) {
        const uint32_t x = lds32(sb + OFF_EXT + k * 4), y = __ldcg((const uint32_t*)(g_xe + (cta * G + ((x >> 9) & 255)) * 12 + 4) + ((x >> 17) & 31));
        put(lds32(sb + OFF_CNT + (x & 511) * 4) + fpos(x >> 22), y, ealo + ((x >> 9) & 255) * p.EPC * 32, true);
      }
    }
    __syncwarp();
  } else {
    __syncthreads();
    STAMP(15);
    uint32_t jj[4 * NCH];
    {
      uint32_t d[4 * NCH], rr[4 * NCH];
      auto count = [&](int k) {
        mbar_wait(sb + BAR_DST + k * 8);
        lds128(d + 4 * k, sb + OFF_DST + min(tid + NWK * k, 1535) * 16);
#pragma unroll
        for (int i = 4 * k; i < 4 * k + 4; i++) {
          const uint32_t dv = tid + NWK * k < n4 ? d[i] : G * p.NPC, j = __umulhi(dv, p.magic);
          rr[i] = atoms_add(sb + OFF_SA + j * 128 + (j & 31) * 4, 1);
          jj[i] = j; d[i] = dv - j * p.NPC;
        } };
      auto place = [&](int k) {
#pragma unroll
        for (int i = 4 * k; i < 4 * k + 4; i++) {
          const uint32_t j = jj[i], r = rr[i];
          jj[i] = r < 62 ? j * 64 + ((r + 2 * j + 2) & 63) : XO - 62 + j * 32 + min(r, 93u);
          sts16(sb + OFF_SA + jj[i] * 2, d[i]);
        } };
      const bool last = wid * 32 + NWK * (NCH - 1) < n4;
      count(0); STAMP(1); count(1); place(0); count(2); place(1); count(3); place(2);
      if (last) count(4);
      place(3);
      if (last) place(4);
      proxy_fence();
      bar_arrive(12, 384);
      STAMP(2);
      mbar_wait(sb + BAR_SRC);
      STAMP(12);
#pragma unroll
      for (int k = 0; k < NCH; k++) lds128(d + 4 * k, sb + OFF_SRCI + min(tid + NWK * k, 1535) * 16);
#pragma unroll
      for (int i = 0; i < 4 * NCH; i++) if (i < 4 * NCH - 4 || last) sts32(sb + OFF_SB + jj[i] * 4, d[i] | (((tid + NWK * (i >> 2)) * 4 + (i & 3)) << 16));
    }
    proxy_fence();
    bar_sync(13, 384);
    STAMP(3);
    { const uint32_t ep = ealo + epad * 32;
      for (int i = tid; i < SCAP * 4; i += NWK) sts128(sb + OFF_TE + i * 16, ep, ep, ep, ep); }
    uint32_t pk[12], rf[12];
    const uint32_t rot = (lane + cta) & 31;
    mbar_wait(sb + BAR_XA);
    STAMP(14);
#pragma unroll
    for (int k = 0; k < 12; k++) pk[k] = __ldcg((const uint32_t*)(g_xa + (cta * G + wid + 11 * k) * 8) + rot);
    uint32_t xm = 0, xc = 0, xv = 0;
#pragma unroll
    for (int k = 0; k < 12; k++) {
      const uint32_t cn = __shfl_sync(~0u, pk[k], 0);
      const int c = (int)cn - 2 * lane;
      const uint32_t dum = (384 + lane) * 0x10001u;
      pk[k] = (c < -1 || lane == 0) ? dum : (c < 0 ? __byte_perm(pk[k], dum, 0x7610) : pk[k]);
      xm |= (cn > 62) << k;
    }
    auto xload = [&]() { const int row = cta * G + wid + 11 * (__ffs(xm) - 1);
      xc = __ldcg((const uint32_t*)(g_xa + row * 8) + (cta & 31)); xv = __ldcg((const uint16_t*)(g_xe + row * 12) + lane); };
    if (xm) xload();
    {
      uint32_t r0[12], r1[12];
#pragma unroll
      for (int k = 0; k < 12; k++) { r0[k] = atoms_add(sb + OFF_CNT + (pk[k] & 0xFFFF) * 4, 1); r1[k] = atoms_add(sb + OFF_CNT + (pk[k] >> 16) * 4, 1); }
      while (xm) {
        if (xc > 93) { if (lane == 0) sts32(sb + OFF_MISC + 8, 1); }
        else if (lane < xc - 62) {
          const uint32_t r = atoms_add(sb + OFF_CNT + xv * 4, 1), idx = atoms_add(sb + OFF_MISC + 4, 1);
          if (idx < 256) sts32(sb + OFF_EXT + idx * 4, xv | ((wid + 11 * (__ffs(xm) - 1)) << 9) | (lane << 17) | (min(r, 255u) << 22));
          else sts32(sb + OFF_MISC + 8, 1);
        }
        __syncwarp();
        xm &= xm - 1;
        if (xm) xload();
      }
      if (wid >= 6) bar_arrive(11, NWK);
#pragma unroll
      for (int k = 0; k < 12; k++) { const uint32_t r = __byte_perm(r0[k], r1[k], 0x5410); rf[k] = ((r << 3) & 0x03F003F0u) | ((r << 1) & 0x00020002u); }
    }
    STAMP(4);
    if (wid < 6) {
      bar_sync(11, NWK);
      STAMP(5);
      uint32_t dg[2], ky[2], dr[2], sq[2], ps[4];
      lds64(dg[0], dg[1], sb + OFF_CNT + tid * 8);
      lds128(ps, sb + OFF_POS + tid * 16);
#pragma unroll
      for (int i = 0; i < 2; i++) { ky[i] = min((dg[i] + 1) >> 1, 63u); dr[i] = atoms_add(sb + OFF_DH + ky[i] * 4, 1); }
      if (max(dg[0], dg[1]) > 126) sts32(sb + OFF_MISC + 8, 1);
      bar_sync(10, 192);
      uint32_t hb, ha; lds64(hb, ha, sb + OFF_DH + (62 - 2 * lane) * 4);
      uint32_t inc = ha + hb;
#pragma unroll
      for (int o = 1; o < 32; o <<= 1) { const uint32_t y = __shfl_up_sync(~0u, inc, o); if (lane >= o) inc += y; }
#pragma unroll
      for (int i = 0; i < 2; i++) {
        const uint32_t idx = 63 - ky[i], e2 = __shfl_sync(~0u, (inc - hb) | ((inc - hb - ha) << 16), idx >> 1);
        const uint32_t pos = ((idx & 1) ? (e2 & 0xFFFF) : (e2 >> 16)) + dr[i];
        const uint32_t ak = (uint32_t)(0x1453AB297860ull >> ((pos >> 5) * 4)) & 15, l = (pos >> 3) & 3;
        sq[i] = (ak >> 2) * 16 + ((ak & 1) ? 3 - l : l) * 4 + (ak & 3);
        dr[i] = pos & 7;
        if (dr[i] == 0) asm volatile("st.shared.u8 [%0], %1;" :: "r"(sb + OFF_LEN + sq[i]), "r"(max(ky[i], 1u)) : "memory");
        sts64(sb + OFF_GP + sq[i] * 64 + dr[i] * 8, ps[2 * i], ps[2 * i + 1] | ((2 * tid + i) << 16));
      }
      bar_sync(10, 192);
      uint32_t ln[12], bs[2] = {0, 0}, tot = 0;
      lds128(ln, sb + OFF_LEN); lds128(ln + 4, sb + OFF_LEN + 16); lds128(ln + 8, sb + OFF_LEN + 32);
#pragma unroll
      for (int k = 0; k < 12; k++) {
#pragma unroll
        for (int i = 0; i < 2; i++) if ((sq[i] >> 2) == k) bs[i] = __dp4a(ln[k], 0x00010101u >> (24 - 8 * (sq[i] & 3)), tot);
        tot = __dp4a(ln[k], 0x01010101u, tot);
      }
      if (tot > SCAP) sts32(sb + OFF_MISC + 8, 1);
      sts64(sb + OFF_CNT + tid * 8, bs[0] * 16 + (dr[0] & 3) * 4 + (dr[0] >> 2), bs[1] * 16 + (dr[1] & 3) * 4 + (dr[1] >> 2));
    }
    uint2 vb[12];
    mbar_wait(sb + BAR_XB);
#pragma unroll
    for (int k = 0; k < 12; k++) lds64(vb[k].x, vb[k].y, sb + OFF_XB + (wid + 11 * k) * 256 + rot * 8);
    bar_sync(1, 384);
    STAMP(6);
    if (!lds32(sb + OFF_MISC + 8)) {
      uint32_t y0[12], y1[12];
#pragma unroll
      for (int k = 0; k < 12; k++) { y0[k] = lds32(sb + OFF_CNT + (pk[k] & 0xFFFF) * 4); y1[k] = lds32(sb + OFF_CNT + (pk[k] >> 16) * 4); }
#pragma unroll
      for (int k = 0; k < 12; k++) {
        const uint32_t eb = ealo + (wid + 11 * k) * p.EPC * 32;
        put(y0[k] + (rf[k] & 0xFFFF), vb[k].x, eb, (pk[k] & 0x180) != 0x180);
        put(y1[k] + (rf[k] >> 16), vb[k].y, eb, (pk[k] & 0x1800000) != 0x1800000);
      }
    }
    STAMP(7);
  }

  bar_sync(2, 384);
  mbar_wait(sb + BAR_QP);
  asm volatile("setmaxnreg.inc.sync.aligned.u32 160;");
  STAMP(13);
  uint32_t bad = lds32(sb + OFF_MISC + 8);
  if (!bad) {
    const uint32_t ring = sb + OFF_RING + wid * (NST * STG);
    uint32_t lens, rem;
    uint32_t a_s, a_e;
    { uint32_t ln[12], base = 0; lens = 0;
      lds128(ln, sb + OFF_LEN); lds128(ln + 4, sb + OFF_LEN + 16); lds128(ln + 8, sb + OFF_LEN + 32);
#pragma unroll
      for (int k = 0; k < 12; k++) { if (k < wid) base = __dp4a(ln[k], 0x01010101u, base); if (k == wid) lens = ln[k]; }
      lens = __shfl_sync(~0u, lens, 0); rem = __dp4a(lens, 0x01010101u, 0u);
      a_s = sb + OFF_TS + base * 32 + (lane >> 3) * 8; a_e = sb + OFF_TE + base * 64 + ((lane >> 1) & 3) * 16 + (lane >> 3) * 4; }
    uint32_t k0 = (uint32_t)(uint64_t)p.q + (((lane & 7) ^ (lane >> 3)) << 4), k1 = k0 ^ 64, ke = ((lane ^ (lane >> 3)) & 1) << 4;
    uint32_t dst0 = ring + lane * 16;
    const uint32_t qhi = (uint32_t)((uint64_t)p.q >> 32), ehi = (uint32_t)((uint64_t)p.ea >> 32);
    uint32_t s0, s1, ev, to = 0, so = 0;
    auto tl_ = [&]() { lds64(s0, s1, a_s + to); ev = lds32(a_e + 2 * to); to += 32; };
#define CPQ(LH, x, k, off) asm volatile("{.reg .b32 lo; .reg .b64 a; .reg .pred p; setp.le.u32 p, %4, %5; dp2a." LH ".u32.u32 lo, %1, 0x80000080, %2; mov.b64 a, {lo, %3}; @p cp.async.cg.shared.global [%0+" #off "], [a], 16;}" :: "r"(dst0 + so), "r"(x), "r"(k), "r"(qhi), "r"(to), "r"(rem) : "memory")
    rem *= 32;
    auto is0 = [&]() {
      asm volatile("{.reg .b32 lo; .reg .b64 a; .reg .pred p; setp.le.u32 p, %4, %5; or.b32 lo, %1, %2; mov.b64 a, {lo, %3}; @p cp.async.cg.shared.global [%0+2048], [a], 16;}" :: "r"(dst0 + so), "r"(ev), "r"(ke), "r"(ehi), "r"(to), "r"(rem) : "memory");
      CPQ("lo", s0, k0, 0); };
    auto is1 = [&]() { CPQ("hi", s0, k1, 512); CPQ("lo", s1, k0, 1024); CPQ("hi", s1, k1, 1536); asm volatile("cp.async.commit_group;" ::: "memory");
      so = so == (NST - 1) * STG ? 0 : so + STG; };
#pragma unroll
    for (int i = 0; i < NST; i++) { tl_(); is0(); is1(); }

    const int g = lane >> 2, qd = lane & 3;
    const uint32_t fr = (lane & 15) * 128 + (((lane >> 4) ^ (lane & 7)) << 4);
    uint32_t qa0 = ring + fr, qa1 = qa0 ^ 32, qa2 = qa0 ^ 64, qa3 = qa0 ^ 96;
    uint32_t eadr = ring + 2048 + (lane & 15) * 32 + ((((lane >> 4) ^ (lane >> 2)) & 1) << 4);
    uint32_t oh0 = g == 2 * qd ? 0x3C00u : g == 2 * qd + 1 ? 0x3C000000u : 0u, oh1 = oh0;
    uint32_t a_g = sb + OFF_GP + wid * 256 + lane * 2;
    uint32_t a_n = sb + OFF_GP + wid * 256 + (lane & 15) * 8 + 6;
    const uint32_t p2 = sb + OFF_P2 + wid * 2048;
    uint32_t a_p = ((lane & 8) ? p2 : sb + OFF_WD) + (lane & 7) * 128 + ((((lane >> 4) ^ lane) & 7) << 4);
    uint32_t lhi = lane & 16;
#define OPQ4(A, B, C, D) asm volatile("{st.volatile.shared.v4.b32 [%4], {%0,%1,%2,%3}; ld.volatile.shared.v4.b32 {%0,%1,%2,%3}, [%4];}" : "+r"(A), "+r"(B), "+r"(C), "+r"(D) : "r"(p2 + lane * 16) : "memory")
    OPQ4(lhi, oh0, oh1, dst0); OPQ4(qa0, qa1, qa2, qa3); OPQ4(k0, k1, ke, eadr); OPQ4(a_g, a_n, a_p, a_s);
    __syncwarp();
    uint32_t w3[16], wv[8], bp[16], sp[8], sum[8], Y[16], M[16], own, ownp, dpk; uint16_t tl[16], th[16];
    float pacc = 0.f, chk = 0.f;
    auto wload = [&]() {
#pragma unroll
      for (int j = 0; j < 4; j++) ldsm4t(w3 + 4 * j, (qa0 - ring + (sb + OFF_W3)) ^ (j << 5));
#pragma unroll
      for (int j = 0; j < 8; j++) wv[j] = lds32(sb + OFF_WX + j * 16 + (a_g & 6) * 2);
    };
    auto hload = [&](uint32_t (&hf)[16], uint32_t nd) {
      const uint32_t hrow = sb + OFF_H + nd * 128 + (((nd & 7) << 4) ^ lhi);
#pragma unroll
      for (int j = 0; j < 4; j++) ldsm4(hf + 4 * j, hrow ^ (j << 5));
      return hrow;
    };
    auto bload = [&](uint32_t o) {
#pragma unroll
      for (int j = 0; j < 4; j++) ldsm4t(bp + 4 * j, (a_p ^ (j << 5)) + o);
    };
    {
      uint32_t mp = 0;
#pragma unroll
      for (int pr = 0; pr < 2; pr++) {
        uint32_t hf[16]; float acc[32];
        hload(hf, lds16(a_n + pr * 128));
        const uint64_t db = DHI | ((sb + OFF_W + 8192) >> 4);
        wg_fence();
        rs64b<0>(acc, hf[0], hf[1], hf[2], hf[3], db); rs64b<1>(acc, hf[4], hf[5], hf[6], hf[7], db + 128); rs64b<1>(acc, hf[8], hf[9], hf[10], hf[11], db + 256); rs64b<1>(acc, hf[12], hf[13], hf[14], hf[15], db + 384);
        wg_commit(); wg_wait0(); fence_regs(acc);
        if (pr) bar_arrive(4, NTHR);
#pragma unroll
        for (int j = 0; j < 16; j++) { hf[j] = pack_f16(acc[2 * j], acc[2 * j + 1]); mp = mag2(mp, hf[j]); }
#pragma unroll
        for (int j = 0; j < 4; j++) stsm4((p2 + fr) ^ (j << 5), hf[4 * j], hf[4 * j + 1], hf[4 * j + 2], hf[4 * j + 3]);
        __syncwarp();
        if (!pr) { bload(0);
          const uint32_t a = p2 + 1024 + (lane & 7) * 128 + ((((lane >> 3) ^ lane) & 7) << 4);
          ldsm4t(sp, a); ldsm4t(sp + 4, a ^ 64);
          __syncwarp(); }
      }
      if (magr(mp) >= 0x7000) chk = __int_as_float(0x7FC00000);
    }
    wload();
    auto body = [&](auto MODE) {
      constexpr int mode = decltype(MODE)::value;
      uint32_t T[16], ef[4], q0, q1, x0, x1, x2; float e0_, e1_, cs[4];
      auto mu = [&](int j) {
#pragma unroll
        for (int i = 2 * j; i < 2 * j + 2; i++) asm volatile("{.reg .b16 l, h; mov.b32 {l, h}, %2; tanh.approx.f16 %0, l; tanh.approx.f16 %1, h;}" : "=h"(tl[i]), "=h"(th[i]) : "r"(Y[i])); };
      auto fi = [&](int j) {
#pragma unroll
        for (int i = 2 * j; i < 2 * j + 2; i++) asm volatile("{.reg .b32 t; mov.b32 t, {%2, %3}; fma.rn.f16x2 %0, %1, t, %1;}" : "=r"(M[i]) : "r"(Y[i]), "h"(tl[i]), "h"(th[i])); };
      auto ad = [&](int j) { asm volatile("add.rn.f16x2 %0, %0, %1; add.rn.f16x2 %0, %0, %2;" : "+r"(sum[j]) : "r"(M[2 * j]), "r"(M[2 * j + 1])); };
      auto he = [&](int j) { asm volatile("mma.sync.aligned.m16n8k16.row.col.f16.f16.f16.f16 {%0,%1}, {%2,%3,%4,%5}, {%6,%7}, {%0,%1};" : "+r"(T[2 * j]), "+r"(T[2 * j + 1]) : "r"(ef[0]), "r"(ef[1]), "r"(ef[2]), "r"(ef[3]), "r"(w3[2 * j]), "r"(w3[2 * j + 1])); };
      auto hs = [&](int j) { asm volatile("mma.sync.aligned.m16n8k16.row.col.f16.f16.f16.f16 {%0,%1}, {%2,%3,%4,%5}, {%6,%7}, {%8,%9};" : "=r"(Y[2 * j]), "=r"(Y[2 * j + 1]) : "r"(q0), "r"(q1), "r"(oh0), "r"(oh1), "r"(bp[2 * j]), "r"(bp[2 * j + 1]), "r"(T[2 * j]), "r"(T[2 * j + 1])); };
      auto hc = [&](int j) {
        if (j) asm volatile("mma.sync.aligned.m16n8k16.row.col.f32.f16.f16.f32 {%0,%1,%2,%3}, {%4,%5,%6,%7}, {%8,%9}, {%0,%1,%2,%3};" : "+f"(cs[0]), "+f"(cs[1]), "+f"(cs[2]), "+f"(cs[3]) : "r"(M[4 * j]), "r"(M[4 * j + 1]), "r"(M[4 * j + 2]), "r"(M[4 * j + 3]), "r"(wv[2 * j]), "r"(wv[2 * j + 1]));
        else asm volatile("mma.sync.aligned.m16n8k16.row.col.f32.f16.f16.f32 {%0,%1,%2,%3}, {%4,%5,%6,%7}, {%8,%9}, {%10,%10,%10,%10};" : "=f"(cs[0]), "=f"(cs[1]), "=f"(cs[2]), "=f"(cs[3]) : "r"(M[0]), "r"(M[1]), "r"(M[2]), "r"(M[3]), "r"(wv[0]), "r"(wv[1]), "f"(0.f)); };
      auto cv = [&](int i) { asm volatile("{.reg .b32 a, b; shl.b32 a, %0, 16; and.b32 b, %0, 0xFFFF0000; cvt.rn.f16x2.f32 %0, b, a;}" : "+r"(ef[i])); };
      auto un = [&]() { asm volatile("shl.b32 %0, %2, 16; and.b32 %1, %2, 0xFFFF0000;" : "=&f"(e0_), "=&f"(e1_) : "r"(dpk)); };
      auto ex0 = [&]() { asm volatile("prmt.b32 %0, %3, %4, 0x6420; prmt.b32 %1, %5, %6, 0x6420; prmt.b32 %2, %7, %8, 0x6420;" : "=&r"(x0), "=&r"(x1), "=&r"(x2) : "r"(T[0]), "r"(T[1]), "r"(T[2]), "r"(T[3]), "r"(T[4]), "r"(T[5])); };
      auto ex1 = [&]() { asm volatile("{.reg .b32 a, b; shl.b32 a, %2, 3; shl.b32 b, %3, 6; lop3.b32 a, %1, a, 0x38383838, 0xD8; lop3.b32 a, a, b, 0xC0C0C0C0, 0xD8; sub.rn.bf16x2 %0, %4, a;}" : "=r"(dpk) : "r"(x0), "r"(x1), "r"(x2), "r"(own)); };
      auto ex2 = [&]() { asm volatile("{.reg .b32 a, b, d, u; .reg .b16 l, h; shl.b32 a, %2, 16; and.b32 b, %2, 0xFFFF0000; cvt.rn.f16x2.f32 d, b, a; mul.rn.f16x2 %0, d, d; mov.b32 {l, h}, d; mov.b32 u, {h, h}; mul.rn.f16x2 %1, u, u;}" : "=&r"(q0), "=&r"(q1) : "r"(dpk)); };
      auto pf = [&]() { asm volatile("fma.rn.f32 %0, %1, %2, %0; fma.rn.f32 %0, %3, %4, %0;" : "+f"(pacc) : "f"(cs[0]), "f"(e0_), "f"(cs[2]), "f"(e1_)); };
#define FX(k) if (FM >> k & 1) asm volatile("pmevent 1;" ::: "memory")
      if (mode == 2) {
        hc(0); mu(3); fi(2); un(); ad(0); ad(1); mu(4); fi(3); hc(1); mu(5); fi(4); ad(2); mu(6); fi(5); ad(3); hc(2); mu(7); fi(6); fi(7); ad(4); ad(5); hc(3); ad(6); ad(7); pf();
        return;
      }
      asm volatile("cp.async.wait_group %0;" :: "n"(NST - 1) : "memory");
      __syncwarp();
      if (mode == 1) STAMP(8);
      ldsm4(ef, eadr + so); ldsm4(T, qa0 + so); ldsm4(T + 4, qa1 + so); ldsm4(T + 8, qa2 + so); ldsm4(T + 12, qa3 + so);
      tl_();
      if (mode == 1) {
        is0(); is1();
        cv(0); cv(1); cv(2); cv(3); ex0(); ex1(); ex2();
#pragma unroll
        for (int j = 0; j < 8; j++) { he(j); hs(j); }
        mu(0); mu(1); fi(0); mu(2); fi(1);
        return;
      }
      hc(0); mu(3); fi(2); un(); ad(0); ad(1);
      FX(0);
      mu(4); fi(3); cv(0); cv(1); cv(2); cv(3); ex0(); ex1();
      FX(1);
      he(0); he(1); hc(1); mu(5); fi(4); ex2(); ad(2);
      FX(2);
      hs(0); he(2); mu(6); fi(5); is0(); ad(3);
      FX(3);
      hs(1); he(3); hc(2); mu(7); fi(6); is1();
      FX(4);
      hs(2); hs(3); he(4); he(5); mu(0); fi(7); ad(4); ad(5);
      FX(5);
      hc(3); hs(4); he(6); he(7); mu(1); fi(0); ad(6);
      FX(6);
      hs(5); hs(6); hs(7); mu(2); fi(1); ad(7); pf();
      FX(7);
    };
#pragma unroll
    for (int j = 0; j < 8; j++) sum[j] = 0;
    own = lds16(a_g) * 0x10001u;
    body(IC<1>());
    int cnt = (lens & 255) - 1;
#pragma unroll 1
    for (int t = 0; t < 8; t++) {
#pragma unroll 1
      for (; cnt > 0; cnt--) body(IC<0>());
      if (!(t & 1)) {
        ownp = own;
        if (t < 6) {
          a_g += 64; own = lds16(a_g) * 0x10001u;
          if (t == 0) {
#pragma unroll
            for (int j = 0; j < 8; j++) bp[2 * j + 1] = sp[j];
          } else bload((a_g & 16) ? (t & 4) * 256 : 0);
          lens >>= 8; cnt = 1;
          continue;
        }
        body(IC<2>()); t++;
        STAMP(9);
      }
      cnt = (lens & 255) - 1;
      { const uint32_t ng = __shfl_sync(~0u, ownp, (a_g >> 1) | 3) >> 16, c3 = (a_g >> 1) & 3;
        asm volatile("{.reg .pred p; setp.lt.u32 p, %2, %3; @p st.global.u16 [%0], %1;}" :: "l"(p.out + (size_t)p.N * 64 + (size_t)node0 * 3 + (ng * 3 + c3)), "h"((uint16_t)pack_bf16(bf_hi(ownp) + pacc, 0.f)), "r"(ng), "r"(c3 < 3 ? nloc : 0) : "memory"); }
      chk = fmaf(pacc, 0.f, chk); pacc = 0.f;
      if (t & 2) {
        uint32_t hf[16]; float acc[32];
        const uint32_t nd = lds16(a_n); a_n += 128;
        const uint32_t hrow = hload(hf, nd);
        const uint64_t b1 = DHI | ((sb + OFF_W) >> 4), b2_ = b1 + 512;
        mbar_wait(sb + BAR_WH);
        wg_fence();
        rs64h<0>(acc, sp[0], sum[0], sp[1], sum[1], b2_); rs64h<1>(acc, sp[2], sum[2], sp[3], sum[3], b2_ + 128); rs64h<1>(acc, sp[4], sum[4], sp[5], sum[5], b2_ + 256); rs64h<1>(acc, sp[6], sum[6], sp[7], sum[7], b2_ + 384);
        rs64b<1>(acc, hf[0], hf[1], hf[2], hf[3], b1); rs64b<1>(acc, hf[4], hf[5], hf[6], hf[7], b1 + 128); rs64b<1>(acc, hf[8], hf[9], hf[10], hf[11], b1 + 256); rs64b<1>(acc, hf[12], hf[13], hf[14], hf[15], b1 + 384);
        wg_commit(); wg_wait0(); fence_regs(acc);
        if (t == 7) STAMP(10);
        chk = fmaf(acc[0], 0.f, fmaf(acc[2], 0.f, chk));
        auto fin = [&](uint32_t x, float y0, float y1) { return u2(__hadd2(b2(x), b2(pack_bf16(silu_h(y0), silu_h(y1))))); };
#pragma unroll
        for (int j = 0; j < 4; j++) stsm4(hrow ^ (j << 5), fin(hf[4 * j], acc[8 * j], acc[8 * j + 1]), fin(hf[4 * j + 1], acc[8 * j + 2], acc[8 * j + 3]), fin(hf[4 * j + 2], acc[8 * j + 4], acc[8 * j + 5]), fin(hf[4 * j + 3], acc[8 * j + 6], acc[8 * j + 7]));
        __syncwarp();
        const uint32_t c8 = (a_g << 3) & 0x70;
#pragma unroll
        for (int j = 0; j < 4; j++) { uint32_t v[4]; const uint32_t n = __shfl_sync(~0u, nd, 4 * j + ((a_g >> 4) & 3)); lds128(v, sb + OFF_H + n * 128 + (((n << 4) ^ c8) & 0x70));
          asm volatile("{.reg .pred p; setp.lt.u32 p, %5, %6; @p st.global.v4.b32 [%0], {%1,%2,%3,%4};}" :: "l"((const char*)p.out + (size_t)node0 * 128 + (n * 128 + c8)), "r"(v[0]), "r"(v[1]), "r"(v[2]), "r"(v[3]), "r"(n), "r"(nloc) : "memory"); }
        wload();
      }
#pragma unroll
      for (int j = 0; j < 8; j++) { sp[j] = sum[j]; asm volatile("mov.b32 %0, 0;" : "=r"(sum[j])); }
    }
    asm volatile("{.reg .pred p, q; setp.neu.f32 p, %1, 0f00000000; setp.ne.or.u32 p, %2, 0, p; bar.red.or.pred q, 5, 384, p; selp.u32 %0, 1, 0, q;}" : "=r"(bad) : "f"(chk), "r"(lds32(sb + OFF_MISC + 12)) : "memory");
    STAMP(11);
  } else bar_arrive(4, NTHR);
  if (bad) slow_path(p, sb, wid, lane, node0, nloc);
}

}

typedef CUresult (*EncodeFn)(CUtensorMap*, CUtensorMapDataType, cuuint32_t, void*, const cuuint64_t*, const cuuint64_t*, const cuuint32_t*, const cuuint32_t*,
                             CUtensorMapInterleave, CUtensorMapSwizzle, CUtensorMapL2promotion, CUtensorMapFloatOOBfill);

extern "C" void kernel_launch(void* const* d_in, const int* in_sizes, int n_in, void* d_out, int out_size) {
  Params p; Maps maps;
  p.h = (const uint4*)d_in[0]; p.pos = (const uint16_t*)d_in[1]; p.ea = (const uint4*)d_in[2];
  p.src = (const int*)d_in[3]; p.dst = (const int*)d_in[4];
  p.we = (const uint16_t*)d_in[5]; p.wx = (const uint16_t*)d_in[6]; p.wh = (const uint16_t*)d_in[7];
  p.out = (uint16_t*)d_out;
  p.N = in_sizes[0] / 64; p.E = in_sizes[3];
  p.NPC = (p.N + G - 1) / G;
  p.EPC = ((p.E + G * 4 - 1) / (G * 4)) * 4;
  p.magic = (uint32_t)((1ull << 32) / (uint64_t)p.NPC) + 1;
  const uint64_t ea0 = (uint64_t)d_in[2], ea1 = ea0 + (uint64_t)p.E * 32 - 1;
  p.force_slow = ((ea0 >> 32) != (ea1 >> 32)) || (ea0 & 31) || (p.E & 3);
  void* qp = nullptr;
  cudaGetSymbolAddress(&qp, g_q);
  p.q = (char*)qp;
  if (((uint64_t)p.q >> 32) != (((uint64_t)p.q + QBYTES) >> 32)) p.q += QBYTES;
  void* fn = nullptr; cudaDriverEntryPointQueryResult qr;
  cudaGetDriverEntryPoint("cuTensorMapEncodeTiled", &fn, cudaEnableDefault, &qr);
  auto mk = [&](CUtensorMap* tm, void* base, int rows) {
    const cuuint64_t dim[2] = {64, (cuuint64_t)rows}, str[1] = {128}; const cuuint32_t bx[2] = {64, 64}, es[2] = {1, 1};
    ((EncodeFn)fn)(tm, CU_TENSOR_MAP_DATA_TYPE_BFLOAT16, 2, base, dim, str, bx, es, CU_TENSOR_MAP_INTERLEAVE_NONE, CU_TENSOR_MAP_SWIZZLE_128B,
                   CU_TENSOR_MAP_L2_PROMOTION_NONE, CU_TENSOR_MAP_FLOAT_OOB_FILL_NONE);
  };
  mk(&maps.m[TM_H / 128], d_in[0], p.N); mk(&maps.m[TM_WE / 128], d_in[5], 145); mk(&maps.m[TM_WH / 128], d_in[7], 128); mk(&maps.m[TM_Q / 128], p.q, p.N);
  for (int k = 0; k < 2; k++) {
    void* xp = nullptr;
    if (k) cudaGetSymbolAddress(&xp, g_xb); else cudaGetSymbolAddress(&xp, g_xa);
    const cuuint64_t dim[2] = {(cuuint64_t)G * 64, (cuuint64_t)G}, str[1] = {(cuuint64_t)G * (128 << k)}; const cuuint32_t bx[2] = {64, G}, es[2] = {1, 1};
    ((EncodeFn)fn)(&maps.m[TM_XA / 128 + k], k ? CU_TENSOR_MAP_DATA_TYPE_UINT32 : CU_TENSOR_MAP_DATA_TYPE_UINT16, 2, xp, dim, str, bx, es, CU_TENSOR_MAP_INTERLEAVE_NONE,
                   CU_TENSOR_MAP_SWIZZLE_NONE, CU_TENSOR_MAP_L2_PROMOTION_NONE, CU_TENSOR_MAP_FLOAT_OOB_FILL_NONE);
  }
  cudaFuncSetAttribute(egnn_kernel, cudaFuncAttributeMaxDynamicSharedMemorySize, SMEM);
  egnn_kernel<<<G, NTHR, SMEM>>>(p, maps);
}
```

```cpp
#include <cuda_runtime.h>
#include <cuda_bf16.h>
#include <cuda_fp16.h>
#include <cuda.h>
#include <stdint.h>
#pragma nv_diag_suppress 549

#define PFN 8
#define PFNS 250
#define FM 0
#define OPQ 1
#define H0 0
#define HW 3
#define BROWS 132
#define B_HOLD 0
#define S0 0
#define S1 2
#define S2 3
namespace {

constexpr int G = 132;
constexpr int NTHR = 512, NWK = 352, NCH = 5;
constexpr int NST = 3, STG = 2560;
constexpr int SCAP = 448;

constexpr int OFF_H = 0;
constexpr int OFF_W = 49152;
constexpr int OFF_WD = OFF_W + 16384;
constexpr int OFF_W3 = OFF_WD + 1024;
constexpr int OFF_P2 = OFF_W3 + 2048;
constexpr int OFF_RING = OFF_P2 + 24576;
constexpr int OFF_TE = OFF_RING + 12 * NST * STG;
constexpr int OFF_TS = OFF_TE + SCAP * 64;
constexpr int OFF_GP = OFF_TS + SCAP * 32;
constexpr int OFF_WX = OFF_GP + 3072;
constexpr int OFF_LEN = OFF_WX + 128;
constexpr int OFF_MISC = OFF_LEN + 128;
constexpr int OFF_BAR = OFF_MISC + 48;
constexpr int SMEM = OFF_BAR + 256;
static_assert(SMEM <= 232448, "smem");
constexpr uint32_t sb = 1024;
constexpr int OFF_SRCI = OFF_TE;
constexpr int OFF_SB = OFF_RING, OFF_SA = OFF_SB + 34816, OFF_AX = OFF_SA + 32768, OFF_DST = OFF_H + 24576;
constexpr int OFF_WS = OFF_AX + 17408;
constexpr int OFF_BC = OFF_WS + 2304;
constexpr int OFF_CNT = OFF_P2 + 16384;
constexpr int OFF_DH = OFF_CNT + 2176;
constexpr int OFF_POS = OFF_DH + 128;
constexpr int OFF_EXT = OFF_POS + 3072;
static_assert(OFF_EXT + 1024 <= OFF_RING && OFF_BC + 544 <= OFF_TE && OFF_P2 % 1024 == 0 && OFF_SA % 1024 == 0 && SCAP * 64 >= 24576, "staging");
constexpr int BAR_DST = OFF_BAR, BAR_SRC = BAR_DST + 40, BAR_T = BAR_SRC + 24, BAR_W = BAR_T + 48, BAR_XA = BAR_W + 8, BAR_PS = BAR_XA + 8, BAR_AW = BAR_PS + 8,
              BAR_BW = BAR_AW + 8, BAR_QP = BAR_BW + 8, BAR_QR = BAR_QP + 8, BAR_HA = BAR_QR + 8, BAR_EP = BAR_HA + 8, BAR_U = BAR_EP + 8, BAR_WH = BAR_U + 8, BAR_END = BAR_WH + 8;
constexpr uint32_t QBYTES = 8u << 20;

__device__ __align__(256) uint4 g_xa[G * G * 8];
__device__ __align__(256) uint4 g_xb[G * G * 16];
__device__ __align__(256) uint2 g_xe[G * G * 64];
__device__ __align__(256) uint4 g_q[2 * QBYTES / 16];
__device__ __align__(256) unsigned long long g_cnt;
__device__ __align__(256) uint32_t g_sent[64];
#define STAMP(k)

struct Maps { CUtensorMap m[6]; };
constexpr int TM_H = 0, TM_WE = 128, TM_WH = 256, TM_Q = 384, TM_XA = 512, TM_XB = 640;
struct Params {
  const uint4* h; const uint16_t* pos; const uint4* ea; const int* src; const int* dst;
  const uint16_t* we; const uint16_t* wx; const uint16_t* wh; uint16_t* out; char* q;
  unsigned long long* cnt; uint32_t* sent; const uint4* xa; const uint4* xb; uint2* xe;
  int N, E, EPC; uint32_t magic; int force_slow; unsigned long long inv;
};
template<int V> struct IC { static constexpr int value = V; };

#define R32(d) "+f"(d[0]),"+f"(d[1]),"+f"(d[2]),"+f"(d[3]),"+f"(d[4]),"+f"(d[5]),"+f"(d[6]),"+f"(d[7]),"+f"(d[8]),"+f"(d[9]),"+f"(d[10]),"+f"(d[11]),"+f"(d[12]),"+f"(d[13]),"+f"(d[14]),"+f"(d[15]),"+f"(d[16]),"+f"(d[17]),"+f"(d[18]),"+f"(d[19]),"+f"(d[20]),"+f"(d[21]),"+f"(d[22]),"+f"(d[23]),"+f"(d[24]),"+f"(d[25]),"+f"(d[26]),"+f"(d[27]),"+f"(d[28]),"+f"(d[29]),"+f"(d[30]),"+f"(d[31])
#define S32 "{%0,%1,%2,%3,%4,%5,%6,%7,%8,%9,%10,%11,%12,%13,%14,%15,%16,%17,%18,%19,%20,%21,%22,%23,%24,%25,%26,%27,%28,%29,%30,%31}"
#define DI __device__ __forceinline__

constexpr uint64_t DHI = ((uint64_t)(1024 >> 4) << 32) | (1ull << 62);
template<int SD> DI void rs64b(float (&d)[32], uint32_t a0, uint32_t a1, uint32_t a2, uint32_t a3, uint64_t db) {
  asm volatile("wgmma.mma_async.sync.aligned.m64n64k16.f32.bf16.bf16 " S32 ", {%32,%33,%34,%35}, %36, %37, 1, 1, 1;" : R32(d) : "r"(a0), "r"(a1), "r"(a2), "r"(a3), "l"(db), "n"(SD)); }
template<int SD> DI void rs64h(float (&d)[32], uint32_t a0, uint32_t a1, uint32_t a2, uint32_t a3, uint64_t db) {
  asm volatile("wgmma.mma_async.sync.aligned.m64n64k16.f32.f16.f16 " S32 ", {%32,%33,%34,%35}, %36, %37, 1, 1, 1;" : R32(d) : "r"(a0), "r"(a1), "r"(a2), "r"(a3), "l"(db), "n"(SD)); }
template<int SD> DI void ss64(float (&d)[32], uint64_t da, uint64_t db) {
  asm volatile("wgmma.mma_async.sync.aligned.m64n64k16.f32.bf16.bf16 " S32 ", %32, %33, %34, 1, 1, 0, 1;" : R32(d) : "l"(da), "l"(db), "n"(SD)); }
DI void trap_if(bool c) { asm volatile("{.reg .pred p; setp.eq.u32 p, %0, 0; @p bra.uni LT_%=; trap; LT_%=:}" :: "r"((uint32_t)c)); }
DI void wg_fence() { asm volatile("wgmma.fence.sync.aligned;" ::: "memory"); }
DI void wg_commit() { asm volatile("wgmma.commit_group.sync.aligned;" ::: "memory"); }
DI void wg_wait0() { asm volatile("wgmma.wait_group.sync.aligned 0;" ::: "memory"); }
DI void fence_regs(float (&d)[32]) { asm volatile("" : R32(d) :: "memory"); }
DI void proxy_fence() { asm volatile("fence.proxy.async.shared::cta;" ::: "memory"); }
DI uint64_t pol_first() { uint64_t r; asm("createpolicy.fractional.L2::evict_first.b64 %0, 1.0;" : "=l"(r)); return r; }
DI float tanh_ap(float x) { float y; asm("tanh.approx.f32 %0, %1;" : "=f"(y) : "f"(x)); return y; }
DI float silu_h(float y) { return fmaf(y, tanh_ap(y), y); }
DI uint32_t pack_bf16(float lo, float hi) { uint32_t r; asm("cvt.rn.bf16x2.f32 %0, %1, %2;" : "=r"(r) : "f"(hi), "f"(lo)); return r; }
DI uint32_t pack_f16(float lo, float hi) { uint32_t r; asm("cvt.rn.f16x2.f32 %0, %1, %2;" : "=r"(r) : "f"(hi), "f"(lo)); return r; }
DI float bf_lo(uint32_t v) { return __uint_as_float(v << 16); }
DI float bf_hi(uint32_t v) { return __uint_as_float(v & 0xFFFF0000u); }
DI uint32_t b2h(uint32_t v, float s) { return pack_f16(s * bf_lo(v), s * bf_hi(v)); }
DI void mbar_wait(uint32_t bar, uint32_t parity = 0) {
  asm volatile("{.reg .pred p; .reg .u32 t0, t1;\n"
    "mbarrier.try_wait.parity.shared::cta.b64 p, [%0], %1;\n @p bra.uni LD_%=;\n mov.u32 t0, %%clock;\n"
    "LW_%=: mbarrier.try_wait.parity.shared::cta.b64 p, [%0], %1;\n"
    "@p bra.uni LD_%=;\n mov.u32 t1, %%clock; sub.u32 t1, t1, t0; setp.lt.u32 p, t1, 0x80000000;\n @p bra.uni LW_%=;\n trap;\n LD_%=:}" :: "r"(bar), "r"(parity) : "memory");
}
DI void mbar_arrive(uint32_t bar, int p = 1) { asm volatile("{.reg .pred p; setp.ne.b32 p, %1, 0; @p mbarrier.arrive.shared::cta.b64 _, [%0];}" :: "r"(bar), "r"(p) : "memory"); }
DI void bar_sync(int id, int n) { asm volatile("bar.sync %0, %1;" :: "r"(id), "r"(n) : "memory"); }
DI void bar_arrive(int id, int n) { asm volatile("bar.arrive %0, %1;" :: "r"(id), "r"(n) : "memory"); }
DI __nv_bfloat162 b2(uint32_t v) { return *(__nv_bfloat162*)&v; }
DI uint32_t u2(__nv_bfloat162 v) { return *(uint32_t*)&v; }
DI uint32_t hsq(uint32_t v) { return u2(__hmul2(b2(v), b2(v))); }
DI uint32_t hsub(uint32_t a, uint32_t b) { return u2(__hsub2(b2(a), b2(b))); }
DI uint32_t hhalf(uint32_t v) { return u2(__hmul2(b2(v), __floats2bfloat162_rn(0.5f, 0.5f))); }
DI uint32_t mag2(uint32_t m, uint32_t v) { return __vmaxu2(m, v & 0x7FFF7FFFu); }
DI uint32_t hmag(uint32_t m, uint32_t v) { const __half2 r = __hmax2(*(const __half2*)&m, __habs2(*(const __half2*)&v)); return *(const uint32_t*)&r; }
DI uint32_t magr(uint32_t m) { return max(m & 0xFFFF, m >> 16); }
DI void sts128(uint32_t a, uint32_t x, uint32_t y, uint32_t z, uint32_t w) { asm volatile("st.shared.v4.u32 [%0], {%1,%2,%3,%4};" :: "r"(a), "r"(x), "r"(y), "r"(z), "r"(w) : "memory"); }
DI void sts64(uint32_t a, uint32_t x, uint32_t y) { asm volatile("st.shared.v2.u32 [%0], {%1,%2};" :: "r"(a), "r"(x), "r"(y) : "memory"); }
DI void sts32(uint32_t a, uint32_t x) { asm volatile("st.shared.u32 [%0], %1;" :: "r"(a), "r"(x) : "memory"); }
DI void sts16(uint32_t a, uint32_t x) { asm volatile("st.shared.u16 [%0], %1;" :: "r"(a), "h"((uint16_t)x) : "memory"); }
DI void lds128(uint32_t* v, uint32_t a) { asm volatile("ld.shared.v4.u32 {%0, %1, %2, %3}, [%4];" : "=r"(v[0]), "=r"(v[1]), "=r"(v[2]), "=r"(v[3]) : "r"(a) : "memory"); }
DI void lds64(uint32_t& x, uint32_t& y, uint32_t a) { asm volatile("ld.shared.v2.u32 {%0, %1}, [%2];" : "=r"(x), "=r"(y) : "r"(a) : "memory"); }
DI uint32_t lds32(uint32_t a) { uint32_t x; asm volatile("ld.shared.u32 %0, [%1];" : "=r"(x) : "r"(a) : "memory"); return x; }
DI uint32_t lds16(uint32_t a) { uint32_t x; asm volatile("ld.shared.u16 %0, [%1];" : "=r"(x) : "r"(a) : "memory"); return x; }
DI uint32_t atoms_add(uint32_t a, uint32_t v) { uint32_t r; asm volatile("atom.shared.add.u32 %0, [%1], %2;" : "=r"(r) : "r"(a), "r"(v) : "memory"); return r; }
DI void bulk_load(uint32_t dst, const void* src, uint32_t bytes, uint32_t bar) {
  asm volatile("cp.async.bulk.shared::cluster.global.mbarrier::complete_tx::bytes.L2::cache_hint [%0], [%1], %2, [%3], %4;" :: "r"(dst), "l"(src), "r"(bytes), "r"(bar), "l"(pol_first()) : "memory"); }
DI void bulk_store(void* dst, uint32_t src, uint32_t bytes) { asm volatile("cp.async.bulk.global.shared::cta.bulk_group [%0], [%1], %2;" :: "l"(dst), "r"(src), "r"(bytes) : "memory"); }
DI void mbar_expect(uint32_t bar, uint32_t bytes) { asm volatile("mbarrier.arrive.expect_tx.shared::cta.b64 _, [%0], %1;" :: "r"(bar), "r"(bytes) : "memory"); }
DI void mbar_init(uint32_t bar, int n) { asm volatile("mbarrier.init.shared::cta.b64 [%0], %1;" :: "r"(bar), "r"(n) : "memory"); }
DI void tma_load(uint32_t dst, uint64_t tm, int row, uint32_t bar) {
  asm volatile("cp.async.bulk.tensor.2d.shared::cluster.global.mbarrier::complete_tx::bytes.L2::cache_hint [%0], [%1, {%3, %4}], [%2], %5;" :: "r"(dst), "l"(tm), "r"(bar), "r"(0), "r"(row), "l"(pol_first()) : "memory"); }
DI void tma_store(uint64_t tm, int col, int row, uint32_t src) {
  asm volatile("cp.async.bulk.tensor.2d.global.shared::cta.bulk_group [%0, {%2, %3}], [%1];" :: "l"(tm), "r"(src), "r"(col), "r"(row) : "memory"); }
DI void bulk_commit() { asm volatile("cp.async.bulk.commit_group;" ::: "memory"); }
DI void bulk_wait_read() { asm volatile("cp.async.bulk.wait_group.read 0;" ::: "memory"); }
DI uint2 ld_poll2(const void* a) { uint2 v; asm volatile("ld.relaxed.gpu.global.v2.u32 {%0, %1}, [%2];" : "=r"(v.x), "=r"(v.y) : "l"(a) : "memory"); return v; }
DI void st_ext(uint2* a, uint32_t v, uint32_t ep) { asm volatile("st.relaxed.gpu.global.v2.u32 [%0], {%1, %2};" :: "l"(a), "r"(v), "r"(ep) : "memory"); }
DI uint32_t ext_get(const uint2* a, uint32_t ep) { uint2 v; int spin = 0; do { v = ld_poll2(a); trap_if(++spin > 4000000); } while (__any_sync(~0u, v.y != ep)); return v.x; }
DI void bulk_wait() { asm volatile("cp.async.bulk.wait_group 0;" ::: "memory"); }
DI void grid_signal(unsigned long long* cnt, bool flag = false) {
  asm volatile("red.release.gpu.global.add.u64 [%0], %1;" :: "l"(cnt), "l"(flag ? (1ull << 44) + 1 : 1ull) : "memory"); }
DI bool grid_wait(unsigned long long* cnt, unsigned long long c0) {
  const unsigned long long M = (1ull << 44) - 1, target = ((c0 & M) / G + 1) * G;
  unsigned long long c; int spin = 0;
  do { asm volatile("ld.acquire.gpu.global.u64 %0, [%1];" : "=l"(c) : "l"(cnt) : "memory"); trap_if(++spin > 4000000); } while (__any_sync(~0u, (c & M) < target));
  return (c ^ c0) >> 44;
}
DI void hint_signal(uint32_t* c) { asm volatile("red.relaxed.gpu.global.add.u32 [%0], 1;" :: "l"(c) : "memory"); }
DI void hint_wait(const uint32_t* c, uint32_t target, uint32_t v) { int spin = 0;
  trap_if(target - __shfl_sync(~0u, v, 0) - 1 >= G);
  do { asm volatile("ld.relaxed.gpu.global.u32 %0, [%1];" : "=r"(v) : "l"(c) : "memory"); trap_if(++spin > 4000000); } while (__any_sync(~0u, (int)(v - target) < 0)); }
DI unsigned long long ld_cnt(const unsigned long long* cnt) { unsigned long long c; asm volatile("ld.relaxed.gpu.global.u64 %0, [%1];" : "=l"(c) : "l"(cnt)); return c; }
DI void stsm4(uint32_t a, uint32_t x, uint32_t y, uint32_t z, uint32_t w) { asm volatile("stmatrix.sync.aligned.m8n8.x4.shared.b16 [%0], {%1,%2,%3,%4};" :: "r"(a), "r"(x), "r"(y), "r"(z), "r"(w) : "memory"); }
DI void ldsm4(uint32_t* v, uint32_t a) { asm volatile("ldmatrix.sync.aligned.m8n8.x4.shared.b16 {%0,%1,%2,%3}, [%4];" : "=r"(v[0]), "=r"(v[1]), "=r"(v[2]), "=r"(v[3]) : "r"(a) : "memory"); }
DI void ldsm4t(uint32_t* v, uint32_t a) { asm volatile("ldmatrix.sync.aligned.m8n8.x4.trans.shared.b16 {%0,%1,%2,%3}, [%4];" : "=r"(v[0]), "=r"(v[1]), "=r"(v[2]), "=r"(v[3]) : "r"(a) : "memory"); }
DI uint32_t mad16(uint32_t x, uint32_t m, uint32_t c) { uint32_t r; asm("dp2a.lo.u32.u32 %0, %1, %2, %3;" : "=r"(r) : "r"(x), "r"(m), "r"(c)); return r; }
DI bool wbad(uint32_t m, uint32_t hi) { return m > hi || (m && m < 0x3980); }

__device__ __noinline__ void slow_path(const Params& p, int wid, int lane, int node0, int nloc) {
  const uint32_t ab = sb + OFF_P2 + wid * 8704;
  for (int i = lane; i < 32 * 68; i += 32) sts32(ab + i * 4, 0);
  __syncwarp();
  const uint32_t wdv = __ldg((const uint32_t*)(p.we + 128 * 64) + lane), wxv = __ldg((const uint32_t*)p.wx + lane);
  const int nb0 = node0 + wid * 32, cntn = max(0, min(32, nloc - wid * 32));
  auto dot = [&](uint32_t hv, const uint16_t* w, int K2, float& y0, float& y1) {
#pragma unroll 4
    for (int k = 0; k < K2; k++) {
      const uint32_t hk = __shfl_sync(~0u, hv, k), wa = __ldg((const uint32_t*)(w + 2 * k * 64) + lane), wb = __ldg((const uint32_t*)(w + (2 * k + 1) * 64) + lane);
      y0 = fmaf(bf_lo(hk), bf_lo(wa), fmaf(bf_hi(hk), bf_lo(wb), y0)); y1 = fmaf(bf_lo(hk), bf_hi(wa), fmaf(bf_hi(hk), bf_hi(wb), y1));
    }
  };
  auto silu = [](float x) { return x / (1.f + __expf(-x)); };
#pragma unroll 1
  for (int base = 0; base < p.E; base += 32) {
    const int e = base + lane;
    const uint32_t dl = e < p.E ? (uint32_t)(__ldg(p.dst + e) - nb0) : 0xFFFFFFFFu;
    uint32_t mk = __ballot_sync(~0u, dl < (uint32_t)cntn);
    while (mk) {
      const int l = __ffs(mk) - 1; mk &= mk - 1;
      const int ee = base + l, n = __shfl_sync(~0u, dl, l), s = __ldg(p.src + ee);
      const uint16_t *po = p.pos + (size_t)(nb0 + n) * 3, *pp = p.pos + (size_t)s * 3;
      const uint32_t dxy = hsub(__ldg(po) | (__ldg(po + 1) << 16), __ldg(pp) | (__ldg(pp + 1) << 16)), dz = hsub(__ldg(po + 2), __ldg(pp + 2));
      const uint32_t sq = hsq(dxy); const float d2 = bf_lo(sq) + bf_hi(sq) + bf_lo(hsq(dz));
      float y0 = d2 * bf_lo(wdv), y1 = d2 * bf_hi(wdv);
      dot(__ldg((const uint32_t*)(p.h + (size_t)(nb0 + n) * 8) + lane), p.we, 32, y0, y1);
      dot(__ldg((const uint32_t*)(p.h + (size_t)s * 8) + lane), p.we + 64 * 64, 32, y0, y1);
      dot(__ldg((const uint32_t*)(p.ea + (size_t)ee * 2) + (lane & 7)), p.we + 129 * 64, 8, y0, y1);
      const uint32_t mm = pack_bf16(silu(y0), silu(y1));
      float c = bf_lo(mm) * bf_lo(wxv) + bf_hi(mm) * bf_hi(wxv);
#pragma unroll
      for (int o = 16; o; o >>= 1) c += __shfl_xor_sync(~0u, c, o);
      const uint32_t a = ab + n * 272;
      uint32_t x0, x1; lds64(x0, x1, a + lane * 8);
      sts64(a + lane * 8, __float_as_uint(__uint_as_float(x0) + bf_lo(mm)), __float_as_uint(__uint_as_float(x1) + bf_hi(mm)));
      if (lane < 3) { const float df = lane == 0 ? bf_lo(dxy) : lane == 1 ? bf_hi(dxy) : bf_lo(dz); sts32(a + 256 + lane * 4, __float_as_uint(fmaf(c, df, __uint_as_float(lds32(a + 256 + lane * 4))))); }
    }
  }
  __syncwarp();
#pragma unroll 1
  for (int n = 0; n < cntn; n++) {
    uint32_t x0, x1; lds64(x0, x1, ab + n * 272 + lane * 8);
    const uint32_t hv = __ldg((const uint32_t*)(p.h + (size_t)(nb0 + n) * 8) + lane);
    float y0 = 0.f, y1 = 0.f;
    dot(hv, p.wh, 32, y0, y1); dot(pack_bf16(__uint_as_float(x0), __uint_as_float(x1)), p.wh + 64 * 64, 32, y0, y1);
    ((uint32_t*)p.out)[(size_t)(nb0 + n) * 32 + lane] = u2(__hadd2(b2(hv), b2(pack_bf16(silu(y0), silu(y1)))));
    if (lane < 3) p.out[(size_t)p.N * 64 + (size_t)(nb0 + n) * 3 + lane] = (uint16_t)pack_bf16(bf_lo(__ldg(p.pos + (size_t)(nb0 + n) * 3 + lane)) + __uint_as_float(lds32(ab + n * 272 + 256 + lane * 4)), 0.f);
  }
}

__global__ void __launch_bounds__(NTHR, 1) egnn_kernel(const __grid_constant__ Params p, const __grid_constant__ Maps maps) {
  const uint64_t tmb = (uint64_t)&maps;
  extern __shared__ __align__(1024) unsigned char smraw[];
  const int tid = threadIdx.x, cta = blockIdx.x;
  const int e0 = cta * p.EPC, n4 = max(0, min(p.EPC, p.E - e0)) >> 2;
  STAMP(0);
  unsigned long long c0 = 0;
  uint32_t s0_ = 0;
  asm volatile("{.reg .pred p, q; setp.eq.u32 p, %4, 384; setp.eq.u32 q, %5, 320; @p ld.relaxed.gpu.global.u64 %0, [%2]; @q ld.relaxed.gpu.global.u32 %1, [%3];}"
    : "+l"(c0), "+r"(s0_) : "l"(p.cnt), "l"(p.sent + (tid & 32)), "r"(tid & 415), "r"(tid & 479));
  if (tid == NWK) {
#pragma unroll
    for (int k = 0; k < NCH; k++) mbar_init(sb + BAR_DST + k * 8, 1);
    asm volatile("fence.mbarrier_init.release.cluster;" ::: "memory");
#pragma unroll 1
    for (int k = 0; k < NCH; k++) { const int nb = max(0, min(NWK, n4 - k * NWK)) * 16;
      mbar_expect(sb + BAR_DST + k * 8, nb);
      if (nb) bulk_load(sb + OFF_DST + k * NWK * 16, (const char*)(p.dst + e0) + k * NWK * 16, nb, sb + BAR_DST + k * 8); }
  }
  const int lane = tid & 31, wid = __shfl_sync(~0u, tid >> 5, 0), w = wid & 3;

  auto first_node = [&](int c) { return (int)((c * p.inv + 0xFFFFFFFFull) >> 32); };
  const int node0 = first_node(cta), nloc = min(first_node(cta + 1), p.N) - node0;
  const uint32_t ealo = (uint32_t)(uint64_t)p.ea;
  const int epad = min(e0, p.E - 1);
  if (wid >= 12) {
    const int t = tid - 384;
    auto prefetch_e = [&](int i) {
      const uint32_t nb = (p.E / G) & ~15u;
      if (nb && i < PFN) asm volatile("cp.async.bulk.prefetch.L2.global [%0], %1;" :: "l"((const char*)p.ea + (size_t)(i * G + cta) * nb), "r"(nb) : "memory");
    };
    auto load_h = [&](int b) { mbar_expect(sb + BAR_T + b * 8, 8192); tma_load(sb + OFF_H + b * 8192, tmb + TM_H, node0 + b * 64, sb + BAR_T + b * 8); };
    uint32_t pv[9], ev = 0;
#pragma unroll
    for (int i = 0; i < 3; i++) { const uint16_t* pp = p.pos + (size_t)(node0 + t + 128 * i) * 3;
      pv[3 * i] = pv[3 * i + 1] = pv[3 * i + 2] = 0;
      asm volatile("{.reg .pred p; setp.lt.s32 p, %4, %5;\n @p ld.global.nc.u16 %0, [%3];\n @p ld.global.nc.u16 %1, [%3+2];\n @p ld.global.nc.u16 %2, [%3+4];}"
        : "+r"(pv[3 * i]), "+r"(pv[3 * i + 1]), "+r"(pv[3 * i + 2]) : "l"(pp), "r"(t + 128 * i), "r"(p.N - node0)); }
    asm volatile("{.reg .pred p; setp.lt.u32 p, %3, 8; @p ld.global.nc.u32 %0, [%1]; @p st.global.v4.u32 [%2], {%4, %4, %4, %4};}"
      : "+r"(ev) : "l"((const uint32_t*)(p.ea + (size_t)epad * 2) + t), "l"(p.q + (size_t)(p.N + cta) * 128 + t * 16), "r"(t), "r"(0xF700F700u) : "memory");
    c0 = __shfl_sync(~0u, c0, 0);
    {
      const uint32_t e = (uint32_t)((c0 & ((1ull << 44) - 1)) / G) + 1, tg = (1 + e % 3) << 30, v = ((tg >> 16) + 512 + (lane & 7) * 4) * 0x10001u;
      if (t == 0) sts32(sb + OFF_MISC + 32, e);
#pragma unroll
      for (int i = 0; i < 9; i++) sts128(sb + OFF_SA + t * 16 + i * 2048, v, v + 0x10001u, v + 0x20002u, v + 0x30003u);
      bar_sync(6, NTHR);
      mbar_arrive(sb + BAR_EP, lane == 0);
      if (w == 0) STAMP(27);
#pragma unroll
      for (int i = 0; i < 17; i++) sts128(sb + OFF_SB + t * 16 + i * 2048, tg, tg, tg, tg); }
    uint32_t mp = 0;
#pragma unroll
    for (int i = 0; i < 3; i++) { sts64(sb + OFF_POS + (t + 128 * i) * 8, pv[3 * i] | (pv[3 * i + 1] << 16), pv[3 * i + 2]); mp = mag2(mag2(mp, pv[3 * i] | (pv[3 * i + 1] << 16)), pv[3 * i + 2]); }
    proxy_fence();
    __syncwarp();
    mbar_arrive(sb + BAR_PS, lane == 0);
    mbar_wait(sb + BAR_W);
#pragma unroll
    for (int i = 0; i < 8; i += 4) { uint32_t v[16];
#pragma unroll
      for (int k = 0; k < 4; k++) lds128(v + 4 * k, sb + OFF_W + t * 16 + (i + k) * 2048);
#pragma unroll
      for (int k = 0; k < 4; k++) sts128(sb + OFF_W + t * 16 + (i + k) * 2048, hhalf(v[4 * k]), hhalf(v[4 * k + 1]), hhalf(v[4 * k + 2]), hhalf(v[4 * k + 3])); }
    {
      uint32_t v[4], u[4]; const int r = t >> 3, c = t & 7;
      lds128(v, sb + OFF_WS + 128 + t * 16); lds128(u, sb + OFF_WS + c * 16);
      const uint32_t x = lds32(sb + OFF_WS + 2176 + lane * 4);
      sts128(sb + OFF_W3 + r * 128 + ((c ^ (r & 7)) << 4), b2h(v[0], .5f), b2h(v[1], .5f), b2h(v[2], .5f), b2h(v[3], .5f));
      const float s = ((r & 1) || r == 6) ? 0.f : .5f;
      if (t < 64) sts128(sb + OFF_WD + r * 128 + ((c ^ r) << 4), b2h(u[0], s), b2h(u[1], s), b2h(u[2], s), b2h(u[3], s));
      if (t < 32) sts32(sb + OFF_WX + (t & 3) * 32 + (t >> 2) * 4, b2h(x, 1.f));
      const uint32_t m3 = __reduce_max_sync(~0u, magr(mag2(mag2(mag2(mag2(0, v[0]), v[1]), v[2]), v[3]))), md = __reduce_max_sync(~0u, magr(mag2(mag2(mag2(mag2(0, u[0]), u[1]), u[2]), u[3])));
      if (wbad(m3, 0x4000) || wbad(md, 0x4000) || wbad(__reduce_max_sync(~0u, magr(mag2(0, x))), 0x4700) || magr(mp) >= 0x4200 || magr(mag2(0, ev)) >= 0x4380) sts32(sb + OFF_MISC + 8, 1);
    }
    proxy_fence();
    if (w == 1) STAMP(23);
    if (w == 1) {
#pragma unroll 1
      for (int b = 0; b < HW; b++) { mbar_wait(sb + BAR_SRC + max(0, H0 + b) * 8); if (lane == 0) load_h(b); }
    }
    bar_sync(3, 128);
    STAMP(24);
    const uint32_t frag = (w * 16 + (lane & 15)) * 128 + (((lane >> 4) ^ (lane & 7)) << 4);
    uint32_t mq = 0;
#pragma unroll 1
    for (int b = 0; b < 6; b++) {
      float acc[32];
      const uint64_t da = DHI | (((sb + OFF_H) >> 4) + b * 512), db = DHI | ((sb + OFF_W) >> 4);
      const uint32_t v0 = lds16(sb + OFF_POS + b * 512 + w * 128 + lane * 2), v1 = lds16(sb + OFF_POS + 64 + b * 512 + w * 128 + lane * 2);
      mbar_wait(sb + BAR_T + b * 8);
      if (b == 0) STAMP(25);
      if (b == 5) { mbar_arrive(sb + BAR_BW, t == 0); STAMP(26); }
      wg_fence();
      ss64<0>(acc, da, db); ss64<1>(acc, da + 2, db + 128); ss64<1>(acc, da + 4, db + 256); ss64<1>(acc, da + 6, db + 384);
      wg_commit();
      if (b == 0) mbar_wait(sb + BAR_AW);
      if (t == 32) { if (b + HW < 6) load_h(b + HW); else prefetch_e(b + HW - 6); }
      __syncwarp();
      uint32_t ff[6], fg[6];
#pragma unroll
      for (int j = 0; j < 6; j++) { ff[j] = (__byte_perm((j & 1) ? v1 : v0, 0, 0x4140) >> (3 * (j >> 1))) & 0x00070007u; fg[j] = __vsub2(0x00040004u, ff[j]);
        asm volatile("" : "+r"(ff[j]), "+r"(fg[j])); }
      wg_wait0(); fence_regs(acc);
      uint32_t o[16];
#pragma unroll
      for (int j = 0; j < 16; j++) o[j] = pack_f16(acc[2 * j], acc[2 * j + 1]);
#pragma unroll
      for (int j = 0; j < 6; j++) {
        const uint32_t m = o[j] & 0x7FFF7FFFu; mq = __vmaxu2(mq, m);
        o[j] = (__viaddmax_s16x2(m, fg[j], 0) & 0xFFF8FFF8u) | ff[j] | (o[j] & 0x80008000u); }
      const uint32_t qs = sb + (b < 2 ? OFF_P2 : OFF_SA - 16384) + b * 8192;
#pragma unroll
      for (int j = 0; j < 4; j++) stsm4((qs + frag) ^ (j << 5), o[4 * j], o[4 * j + 1], o[4 * j + 2], o[4 * j + 3]);
      proxy_fence();
      if (b == 5) { const uint32_t m = __reduce_max_sync(~0u, magr(mq)); if (lane == 0) sts32(sb + OFF_MISC + 16 + w * 4, m); }
      bar_sync(3, 128);
      if (t == 0 && b * 64 < nloc) tma_store(tmb + TM_Q, 0, node0 + b * 64, qs);
    }
    if (t == 0) bulk_commit();
    __syncwarp();
    asm volatile("setmaxnreg.dec.sync.aligned.u32 32;");
    if (w == 0) {
      STAMP(18);
      uint32_t mv[4]; lds128(mv, sb + OFF_MISC + 16);
      const uint32_t mx = max(max(mv[0], mv[1]), max(mv[2], mv[3]));
      bulk_wait();
      mbar_arrive(sb + BAR_QR, lane == 0);
      mbar_wait(sb + BAR_XA);
      STAMP(19);
      if (lane == 0) grid_signal(p.cnt, nloc > 0 && (mx >= 0x7BF0 || mx < 0x1400));
      if (grid_wait(p.cnt, c0)) sts32(sb + OFF_MISC + 8, 1);
      STAMP(20);
      __syncwarp();
      mbar_arrive(sb + BAR_QP, lane == 0);
    }
    if (w == 1) {
#pragma unroll 1
      for (int i = HW; i < PFN; i++) { if (lane == 0) prefetch_e(i); __nanosleep(PFNS); }
    }
    __syncwarp();
    bar_sync(4, NTHR);
    if (t == 0) { mbar_expect(sb + BAR_U, 16384); tma_load(sb + OFF_W, tmb + TM_WH, 0, sb + BAR_U); tma_load(sb + OFF_W + 8192, tmb + TM_WH, 64, sb + BAR_U); }
    mbar_wait(sb + BAR_U);
    uint32_t mh = 0;
#pragma unroll 1
    for (int i = t; i < 512; i += 128) { uint32_t v[4]; const uint32_t a = sb + OFF_W + i * 16;
      lds128(v, a); sts128(a, hhalf(v[0]), hhalf(v[1]), hhalf(v[2]), hhalf(v[3]));
      lds128(v, a + 8192); sts128(a + 8192, b2h(v[0], .5f), b2h(v[1], .5f), b2h(v[2], .5f), b2h(v[3], .5f));
      mh = mag2(mag2(mag2(mag2(mh, v[0]), v[1]), v[2]), v[3]); }
    if (wbad(__reduce_max_sync(~0u, magr(mh)), 0x4700)) sts32(sb + OFF_MISC + 12, 1);
    proxy_fence();
    __syncwarp();
    mbar_arrive(sb + BAR_WH, lane == 0);
    return;
  }

  auto put = [&](uint32_t x, uint32_t bv, uint32_t eb, uint32_t skip) {
    asm volatile("{.reg .pred p; setp.eq.b32 p, %0, 0;\n @p st.shared.u32 [%1], %3;\n @p st.shared.u16 [%2], %4;}"
      :: "r"(skip), "r"(sb + OFF_TE + x * 2), "r"(sb + OFF_TS + x), "r"(mad16(bv, 0x2000u, eb)), "h"((uint16_t)bv) : "memory");
  };
  uint32_t pa[8], sp[8], pq[16]; float chk = 0.f;
  auto p_phase = [&]() {
    uint32_t hf[32], mp = 0; float a0[32], a1[32];
    const uint32_t an = sb + OFF_GP + wid * 256 + (lane & 15) * 8 + 6, n0 = lds16(an), n1 = lds16(an + 128);
    mbar_wait(sb + BAR_BW);
#pragma unroll
    for (int j = 0; j < 8; j++) { const uint32_t nd = j < 4 ? n0 : n1; ldsm4(hf + 4 * j, (sb + OFF_H + nd * 128 + (((nd & 7) << 4) ^ (lane & 16))) ^ ((j & 3) << 5)); }
    const uint64_t db = DHI | ((sb + OFF_W + 8192) >> 4);
    wg_fence();
    rs64b<0>(a0, hf[0], hf[1], hf[2], hf[3], db); rs64b<1>(a0, hf[4], hf[5], hf[6], hf[7], db + 128); rs64b<1>(a0, hf[8], hf[9], hf[10], hf[11], db + 256); rs64b<1>(a0, hf[12], hf[13], hf[14], hf[15], db + 384);
    wg_commit();
    rs64b<0>(a1, hf[16], hf[17], hf[18], hf[19], db); rs64b<1>(a1, hf[20], hf[21], hf[22], hf[23], db + 128); rs64b<1>(a1, hf[24], hf[25], hf[26], hf[27], db + 256); rs64b<1>(a1, hf[28], hf[29], hf[30], hf[31], db + 384);
    wg_commit();
    asm volatile("wgmma.wait_group.sync.aligned 1;" ::: "memory"); fence_regs(a0);
#pragma unroll
    for (int j = 0; j < 8; j++) { const uint32_t x = pack_f16(a0[4 * j], a0[4 * j + 1]), y = pack_f16(a0[4 * j + 2], a0[4 * j + 3]); mp = hmag(hmag(mp, x), y);
      asm volatile("movmatrix.sync.aligned.m8n8.trans.b16 %0, %1;" : "=r"(pa[j]) : "r"(x)); asm volatile("movmatrix.sync.aligned.m8n8.trans.b16 %0, %1;" : "=r"(sp[j]) : "r"(y)); }
    wg_wait0(); fence_regs(a1);
    bar_arrive(4, NTHR);
#pragma unroll
    for (int j = 0; j < 16; j++) { pq[j] = pack_f16(a1[2 * j], a1[2 * j + 1]); mp = hmag(mp, pq[j]); }
    if (magr(mp) >= 0x7000) chk = __int_as_float(0x7FC00000);
  };
  if (tid == 320) {
    mbar_init(sb + BAR_W, 1);
    asm volatile("fence.mbarrier_init.release.cluster;" ::: "memory");
    mbar_expect(sb + BAR_W, 2 * 8192 + 2304);
    tma_load(sb + OFF_W, tmb + TM_WE, 64, sb + BAR_W); tma_load(sb + OFF_W + 8192, tmb + TM_WE, 0, sb + BAR_W);
    bulk_load(sb + OFF_WS, p.we + 128 * 64, 2176, sb + BAR_W); bulk_load(sb + OFF_WS + 2176, p.wx, 128, sb + BAR_W);
  }
  if (tid == 288) {
#pragma unroll
    for (int a = BAR_SRC; a < BAR_END; a += 8) if (a != BAR_W) mbar_init(sb + a, a == BAR_WH || a == BAR_PS || a == BAR_EP ? 4 : a == BAR_XA ? 11 : 1);
    asm volatile("fence.mbarrier_init.release.cluster;" ::: "memory");
    asm volatile("prefetch.tensormap [%0];" :: "l"(tmb + TM_XA)); asm volatile("prefetch.tensormap [%0];" :: "l"(tmb + TM_H));
    asm volatile("prefetch.tensormap [%0];" :: "l"(tmb + TM_XB)); asm volatile("prefetch.tensormap [%0];" :: "l"(tmb + TM_Q));
  }
  {
    if (tid < 144) sts128(sb + OFF_CNT + tid * 16, 0, 0, 0, 0);
    else if (tid <= 144 + G) sts32(sb + OFF_BC + (tid - 144) * 4, ((tid - 144) & 31) * 4);
    const uint32_t sp = (p.N + cta) * 0x10001u, em = first_node(G);
    if (wid < 7) {
#pragma unroll
      for (int i = 0; i < 4; i++) sts128(sb + OFF_TS + tid * 16 + i * 3584, sp, sp, sp, sp);
    }
    static_assert(SCAP * 32 == 4 * 3584, "fill");
#pragma unroll 1
    for (int i = n4 + tid; i < 1536; i += 384) sts128(sb + OFF_DST + i * 16, em, em, em, em);
    if (tid == 321) sts128(sb + OFF_MISC, 0, 0, p.force_slow, 0);
  }
  bar_arrive(6, NTHR);
  bar_sync(0, 384);
  uint32_t ep, tag, eb0;
  auto get_tag = [&]() { mbar_wait(sb + BAR_EP); ep = lds32(sb + OFF_MISC + 32); tag = (1 + ep % 3) << 30; eb0 = ealo - (tag >> 11); };
  if (wid == 11) {
    trap_if(sb != (uint32_t)__cvta_generic_to_shared(smraw));
#pragma unroll 1
    for (int k = 0; k < 3; k++) { const int nb = max(0, min(8192, n4 * 16 - k * 8192));
      mbar_wait(sb + BAR_DST + (k == 0 ? S0 : k == 1 ? S1 : S2) * 8);
      if (lane == 0) { mbar_expect(sb + BAR_SRC + k * 8, nb);
        if (nb) bulk_load(sb + OFF_SRCI + k * 8192, (const char*)(p.src + e0) + k * 8192, nb, sb + BAR_SRC + k * 8); } }
    get_tag();
    mbar_wait(sb + BAR_PS);
    bar_sync(12, 384);
    if (lane == 0) { tma_store(tmb + TM_XA, cta * 64, 0, sb + OFF_SA); bulk_commit(); }
    __syncwarp();
    uint32_t xm = 0;
#pragma unroll
    for (int k = 0; k < 5; k++) xm |= (lds32(sb + OFF_BC + min(lane + 32 * k, G - 1) * 4) >= (64 << 9) && lane + 32 * k < G) << k;
    auto ext_send = [&](int pl) {
      uint32_t x = xm;
      for (uint32_t m; (m = __ballot_sync(~0u, x));) {
        const uint32_t l = __ffs(m) - 1, j = l + 32 * (__ffs(__shfl_sync(~0u, x, l)) - 1);
        if (lane == l) x &= x - 1;
        const uint32_t e = min(lds16(sb + OFF_AX + j * 128 + ((4 * l + 2 * lane) & 126)), 6143u);
        st_ext(p.xe + (j * G + cta) * 64 + pl * 32 + lane, pl ? lds32(sb + OFF_SRCI + e * 4) + tag + (e << 16) : (lds32(sb + OFF_DST + e * 4) & 511) | (lds32(sb + OFF_BC + j * 4) & ~511u), ep);
      }
    };
    ext_send(0);
    proxy_fence();
    __syncwarp();
    if (lane == 0) { bulk_wait(); hint_signal(p.sent); mbar_arrive(sb + BAR_AW); STAMP(16); }
    __syncwarp();
    mbar_wait(sb + BAR_SRC); mbar_wait(sb + BAR_SRC + 8); mbar_wait(sb + BAR_SRC + 16);
    ext_send(1);
    bar_sync(13, 384);
    if (B_HOLD) mbar_wait(sb + BAR_HA);
    if (lane == 0) {
#pragma unroll 1
      for (int r = 0; r < G; r += BROWS) { tma_store(tmb + TM_XB, cta * 64, r, sb + OFF_SB + r * 256); bulk_commit(); bulk_wait(); }
      hint_signal(p.sent + 32);
      STAMP(17);
    }
    __syncwarp();
    hint_wait(p.sent + 32, ep * G, s0_);
    STAMP(21);
    bar_sync(1, 384);
    if (!__shfl_sync(~0u, lds32(sb + OFF_MISC + 8), 0)) {
      const uint32_t nx = __shfl_sync(~0u, lds32(sb + OFF_MISC + 4), 0);
      for (uint32_t k = 0; k < nx; k += 32) {
        const uint32_t x = lds32(sb + OFF_EXT + min(k + lane, nx - 1) * 4), y = ext_get(p.xe + (cta * G + ((x >> 9) & 255)) * 64 + 32 + ((x >> 17) & 31), ep);
        put(lds32(sb + OFF_CNT + (x & 511) * 4) + (x >> 22) * 16, y, eb0 + ((x >> 9) & 255) * p.EPC * 32, 0);
      }
    }
    __syncwarp();
  } else {
    STAMP(15);
    {
      uint32_t d[4 * NCH], jj[4 * NCH], rr[4 * NCH];
      auto count = [&](int k) {
        mbar_wait(sb + BAR_DST + k * 8);
        lds128(d + 4 * k, sb + OFF_DST + (tid + NWK * k) * 16);
#pragma unroll
        for (int i = 4 * k; i < 4 * k + 4; i++) { jj[i] = d[i] * p.magic; rr[i] = atoms_add(__dp4a(jj[i], 0x04000000u, sb + OFF_BC), 0x202u); }
      };
      auto place = [&](int k) {
#pragma unroll
        for (int i = 4 * k; i < 4 * k + 4; i++) {
          const uint32_t o = __dp4a(jj[i], 0x80000000u, rr[i] & 0x807Eu);
          d[i] = (d[i] & 511) | (tag >> 16);
          asm("{.reg .pred p; setp.ge.u32 p, %1, 0x8000; @p add.u32 %0, %2, %3;}" : "+r"(d[i]) : "r"(o), "r"(tid * 4), "r"(NWK * k * 4 + (i & 3)));
          sts16(sb + OFF_SA + o, d[i]); jj[i] = __viaddmin_u32(o, o, G * 256);
        }
      };
      count(0); STAMP(1); count(1); get_tag(); place(0); count(2); place(1); count(3); place(2);
      if (wid < 4) { count(4); place(3); place(4); } else place(3);
      proxy_fence();
      bar_arrive(12, 384);
      STAMP(2);
      mbar_wait(sb + BAR_PS);
      mbar_wait(sb + BAR_SRC); mbar_wait(sb + BAR_SRC + 8); mbar_wait(sb + BAR_SRC + 16);
      STAMP(12);
#pragma unroll
      for (int k = 0; k < NCH; k++) lds128(d + 4 * k, sb + OFF_SRCI + (tid + NWK * k) * 16);
      const uint32_t tb = tag + (tid << 18);
#pragma unroll
      for (int i = 0; i < 4 * NCH; i++) if (i < 4 * NCH - 4 || wid < 4) sts32(sb + OFF_SB + jj[i], d[i] + tb + ((NWK * (i >> 2) * 4 + (i & 3)) << 16));
      proxy_fence();
      bar_sync(13, 384);
      STAMP(3);
    }
    const uint32_t rot = (lane + cta) & 31;
    uint32_t pk[12], r0[12], r1[12];
    const uint32_t cb = sb + OFF_CNT - (tag >> 14);
    {
      const uint32_t* xa = (const uint32_t*)(p.xa + (cta * G + wid) * 8) + rot;
      if (wid < 8) { const uint32_t e_ = ealo + epad * 32;
#pragma unroll
        for (int i = 0; i < 7; i++) sts128(sb + OFF_TE + tid * 16 + i * 4096, e_, e_, e_, e_); }
      static_assert(SCAP * 64 == 7 * 4096, "fill");
      if (wid == 10) { hint_wait(p.sent, ep * G, s0_); mbar_arrive(sb + BAR_HA, lane == 0); }
      mbar_wait(sb + BAR_HA);
      STAMP(14);
      uint32_t all;
      for (int spin = 0;; spin++) {
        uint32_t st = 0; all = ~0u;
#pragma unroll
        for (int k = 0; k < 12; k++) asm volatile("ld.relaxed.gpu.global.u32 %0, [%1];" : "=r"(pk[k]) : "l"(xa + k * 352) : "memory");
#pragma unroll
        for (int k = 0; k < 12; k++) { st |= pk[k] ^ (tag | (tag >> 16)); all &= pk[k]; }
        if (!__any_sync(~0u, st & 0xC000C000u)) break;
        trap_if(spin > 2000000);
      }
      if (wid == 0) STAMP(22);
      uint32_t xm = 0; uint2 xv;
      auto xadr = [&]() { return p.xe + (cta * G + wid + 11 * (__ffs(xm) - 1)) * 64 + lane; };
      if (!(__shfl_sync(~0u, all, 31) & 0x2000000u)) {
#pragma unroll
        for (int k = 0; k < 12; k++) xm |= (~pk[k] >> 25 & 1) << k;
        xm = __shfl_sync(~0u, xm, 31);
        xv = ld_poll2(xadr());
      }
#pragma unroll
      for (int k = 0; k < 12; k++) { r0[k] = atoms_add(mad16(pk[k], 0x0004u, cb), 16); r1[k] = atoms_add(mad16(pk[k], 0x0400u, cb), 16); }
      mbar_arrive(sb + BAR_XA, lane == 0);
      for (; xm; xm &= xm - 1) {
        if (__any_sync(~0u, xv.y != ep)) xv.x = ext_get(xadr(), ep);
        const uint32_t cn = xv.x >> 9, n = xv.x & 511;
        if (cn > 96) sts32(sb + OFF_MISC + 8, 1);
        else if (lane < cn - 64) {
          const uint32_t r = atoms_add(sb + OFF_CNT + n * 4, 16), idx = atoms_add(sb + OFF_MISC + 4, 1);
          if (idx < 256) sts32(sb + OFF_EXT + idx * 4, n | ((wid + 11 * (__ffs(xm) - 1)) << 9) | (lane << 17) | (min(r >> 4, 255u) << 22));
          else sts32(sb + OFF_MISC + 8, 1);
        }
        xv.y = ~ep;
        __syncwarp();
      }
    }
    STAMP(4);
    if (wid < 6) {
      uint32_t ca[2], ky[2], dr[2], sq[2], ps[4];
#pragma unroll
      for (int i = 0; i < 2; i++) { ca[i] = sb + OFF_CNT + ((node0 + tid + 192 * i) & 511) * 4; lds64(ps[2 * i], ps[2 * i + 1], sb + OFF_POS + (tid + 192 * i) * 8); ps[2 * i + 1] |= (tid + 192 * i) << 16; }
      bar_sync(11, NWK);
      STAMP(5);
#pragma unroll
      for (int i = 0; i < 2; i++) ky[i] = (lds32(ca[i]) + 16) >> 5;
      if (max(ky[0], ky[1]) > 31) sts32(sb + OFF_MISC + 8, 1);
#pragma unroll
      for (int i = 0; i < 2; i++) { ky[i] = min(ky[i], 31u); dr[i] = atoms_add(sb + OFF_DH + ky[i] * 4, 1); }
      bar_sync(10, 192);
      const uint32_t hv = lds32(sb + OFF_DH + lane * 4);
      uint32_t inc = hv;
#pragma unroll
      for (int o = 1; o < 32; o <<= 1) asm("{.reg .pred p; .reg .b32 y; shfl.sync.down.b32 y|p, %0, %1, 31, -1; @p add.u32 %0, %0, y;}" : "+r"(inc) : "r"(o));
#pragma unroll
      for (int i = 0; i < 2; i++) {
        const uint32_t pos = __shfl_sync(~0u, inc - hv, ky[i]) + dr[i];
        const uint32_t ak = (uint32_t)(0x1453AB297860ull >> ((pos >> 5) * 4)) & 15, l = (pos >> 3) & 3;
        sq[i] = (ak >> 2) * 16 + ((ak & 1) ? 3 - l : l) * 4 + (ak & 3);
        dr[i] = pos & 7;
        asm volatile("{.reg .pred p; setp.eq.u32 p, %2, 0; @p st.shared.u8 [%0], %1;}" :: "r"(sb + OFF_LEN + sq[i]), "r"(max(ky[i], 1u)), "r"(dr[i]) : "memory");
        sts64(sb + OFF_GP + sq[i] * 64 + dr[i] * 8, ps[2 * i], ps[2 * i + 1]);
      }
      bar_sync(10, 192);
      const uint32_t ln = lds32(sb + OFF_LEN + min(lane, 11) * 4), tot = __dp4a(ln, 0x01010101u, 0u);
      inc = tot;
#pragma unroll
      for (int o = 1; o < 16; o <<= 1) asm("{.reg .pred p; .reg .b32 y; shfl.sync.up.b32 y|p, %0, %1, 0, -1; @p add.u32 %0, %0, y;}" : "+r"(inc) : "r"(o));
      if (tid < 12) { sts32(sb + OFF_LEN + 64 + tid * 4, inc - tot); if (inc > SCAP) sts32(sb + OFF_MISC + 8, 1); }
#pragma unroll
      for (int i = 0; i < 2; i++) sts32(ca[i], __dp4a(__shfl_sync(~0u, ln, sq[i] >> 2), 0x00010101u >> (24 - 8 * (sq[i] & 3)), __shfl_sync(~0u, inc - tot, sq[i] >> 2)) * 32 + dr[i] * 2);
    } else bar_arrive(11, NWK);
    bar_sync(1, 384);
    STAMP(6);
    if (!__shfl_sync(~0u, lds32(sb + OFF_MISC + 8), 0)) {
      const uint2* xb = (const uint2*)(p.xb + (cta * G + wid) * 16) + rot;
      uint2 vb[12];
#pragma unroll
      for (int k = 0; k < 12; k++) vb[k] = ld_poll2(xb + k * 352);
#pragma unroll
      for (int k = 0; k < 12; k++) { r0[k] += lds32(mad16(pk[k], 0x0004u, cb)); r1[k] += lds32(mad16(pk[k], 0x0400u, cb)); }
      for (int spin = 0;; spin++) {
        uint32_t st = 0;
#pragma unroll
        for (int k = 0; k < 12; k++) st |= (vb[k].x ^ tag) | (vb[k].y ^ tag);
        if (!__any_sync(~0u, st >> 30)) break;
        trap_if(spin > 2000000);
#pragma unroll
        for (int k = 0; k < 12; k++) vb[k] = ld_poll2(xb + k * 352);
      }
#pragma unroll
      for (int k = 0; k < 12; k++) {
        const uint32_t eb = eb0 + (wid + 11 * k) * p.EPC * 32;
        put(r0[k], vb[k].x, eb, pk[k] & 0x200u); put(r1[k], vb[k].y, eb, pk[k] & 0x2000000u);
      }
    }
  }
  STAMP(7);
  p_phase();

  mbar_wait(sb + BAR_QR);
  asm volatile("setmaxnreg.inc.sync.aligned.u32 160;");
  uint32_t bad;
  {
    const uint32_t ring = sb + OFF_RING + wid * (NST * STG), p2 = sb + OFF_P2 + wid * 2048;
    uint32_t lens = __shfl_sync(~0u, lds32(sb + OFF_LEN + wid * 4), 0);
    uint32_t rem = __dp4a(lens, 0x20202020u, 0u);
    const uint32_t base = min(lds32(sb + OFF_LEN + 64 + wid * 4), SCAP);
    uint32_t a_s = sb + OFF_TS + base * 32 + (lane >> 3) * 8, a_e = sb + OFF_TE + base * 64 + (lane >> 1) * 4;
    uint32_t k0 = (uint32_t)(uint64_t)p.q + (((lane & 7) ^ ((lane >> 1) & 4)) << 4), k1 = k0 ^ 16, k2 = k0 ^ 32, k3 = k0 ^ 48, ke = ((lane ^ (lane >> 3)) & 1) << 4;
    uint32_t dst0 = ring + (lane >> 3) * 640 + (lane & 7) * 16;
    const uint32_t qhi = (uint32_t)((uint64_t)p.q >> 32), ehi = (uint32_t)((uint64_t)p.ea >> 32);
    uint32_t s0, s1, ev, to = 0, so = 0;
    auto tl_ = [&]() { lds64(s0, s1, a_s + to); asm volatile("ld.shared.u32 %0, [%1]; add.u32 %1, %1, 64;" : "=&r"(ev), "+r"(a_e) :: "memory"); to += 32; };
#define CPQ(LH, x, k, off) "dp2a." LH ".u32.u32 lo, " x ", 0x80000080, " k "; mov.b64 a, {lo, %7}; @p cp.async.cg.shared.global [%0+" #off "], [a], 16;\n"
#define CPE "or.b32 lo, %10, %11; mov.b64 a, {lo, %12}; @p cp.async.cg.shared.global [%0+512], [a], 16;\n"
#define CPA(BODY) asm volatile("{.reg .b32 lo; .reg .b64 a; .reg .pred p; setp.le.u32 p, %8, %9;\n" BODY "}" \
      :: "r"(dst0 + so), "r"(s0), "r"(s1), "r"(k0), "r"(k1), "r"(k2), "r"(k3), "r"(qhi), "r"(to), "r"(rem), "r"(ev), "r"(ke), "r"(ehi) : "memory")
#define CPQ4 CPQ("lo", "%1", "%3", 0) CPQ("hi", "%1", "%4", 128) CPQ("lo", "%2", "%5", 256) CPQ("hi", "%2", "%6", 384) "cp.async.commit_group;"
    auto issue = [&]() { CPA(CPE CPQ4); so = so == (NST - 1) * STG ? 0 : so + STG; };
    const int g = lane >> 2, qd = lane & 3;
    const uint32_t sw = ((lane >> 4) ^ (lane & 7)) << 4, fr = (lane & 15) * 128 + sw;
    uint32_t qa0 = ring + (g & 3) * 640 + qd * 128 + sw, qa1 = qa0 ^ 32, qa2 = qa0 ^ 64, qa3 = qa0 ^ 96;
    uint32_t eadr = ring + 512 + (g & 3) * 640 + qd * 32 + ((((lane >> 4) ^ g) & 1) << 4);
    uint32_t oh0 = g == 2 * qd ? 0x3C00u : g == 2 * qd + 1 ? 0x3C000000u : 0u, oh1 = oh0;
    uint32_t a_g = sb + OFF_GP + wid * 256 + lane * 2;
    uint32_t a_n = sb + OFF_GP + wid * 256 + (lane & 15) * 8 + 6;
    uint32_t a_p = ((lane & 8) ? p2 : sb + OFF_WD) + (lane & 7) * 128 + ((((lane >> 4) ^ lane) & 7) << 4);
    uint32_t a_w = sb + OFF_W3 + fr;
#define OPQ4(A, B, C, D, o) asm volatile("{st.volatile.shared.v4.b32 [%4], {%0,%1,%2,%3}; ld.volatile.shared.v4.b32 {%0,%1,%2,%3}, [%4];}" : "+r"(A), "+r"(B), "+r"(C), "+r"(D) : "r"(ring + lane * 16 + o) : "memory")
    if (OPQ) { OPQ4(a_w, oh0, oh1, dst0, 0); OPQ4(qa0, qa1, qa2, qa3, 512); OPQ4(k0, k1, k2, k3, 1024); OPQ4(a_g, a_n, a_p, eadr, 1536); }
    uint32_t w3[16], wv[8], bp[16], sum[8], Y[16], M[16], own, ownp, dpk; uint16_t tl[16], th[16];
    float pacc = 0.f;
    auto wload = [&]() {
#pragma unroll
      for (int j = 0; j < 4; j++) ldsm4t(w3 + 4 * j, a_w ^ (j << 5));
      lds128(wv, sb + OFF_WX + (a_g & 6) * 16); lds128(wv + 4, sb + OFF_WX + 16 + (a_g & 6) * 16);
    };
    auto hload = [&](uint32_t (&hf)[16], uint32_t nd) {
      const uint32_t hrow = sb + OFF_H + nd * 128 + (((nd & 7) << 4) ^ ((a_g >> 1) & 16));
#pragma unroll
      for (int j = 0; j < 4; j++) ldsm4(hf + 4 * j, hrow ^ (j << 5));
      return hrow;
    };
    auto bload = [&](uint32_t o) {
#pragma unroll
      for (int j = 0; j < 4; j++) ldsm4t(bp + 4 * j, (a_p ^ (j << 5)) + o);
    };
    { uint32_t wd[8]; const uint32_t a = sb + OFF_WD + (lane & 7) * 128 + ((((lane >> 3) ^ lane) & 7) << 4);
      ldsm4t(wd, a); ldsm4t(wd + 4, a ^ 64);
#pragma unroll
      for (int j = 0; j < 8; j++) { bp[2 * j] = wd[j]; bp[2 * j + 1] = pa[j]; } }
    wload();
    own = lds16(a_g) * 0x10001u;
    bar_sync(2, 384);
    if (__shfl_sync(~0u, lds32(sb + OFF_MISC + 8), 0)) rem = 0;
#pragma unroll
    for (int j = 0; j < 4; j++) stsm4((p2 + fr) ^ (j << 5), pq[4 * j], pq[4 * j + 1], pq[4 * j + 2], pq[4 * j + 3]);
    uint32_t sv[2 * NST];
#pragma unroll
    for (int i = 0; i < NST; i++) { tl_(); so = i * STG; CPA(CPE); sv[2 * i] = s0; sv[2 * i + 1] = s1; }
    mbar_wait(sb + BAR_QP);
    STAMP(13);
    bad = __shfl_sync(~0u, lds32(sb + OFF_MISC + 8), 0);
   if (!bad) {
#pragma unroll
    for (int i = 0; i < NST; i++) { to = 32 * i + 32; so = i * STG; s0 = sv[2 * i]; s1 = sv[2 * i + 1]; CPA(CPQ4); }
    so = 0;
    auto body = [&](auto MODE) {
      constexpr int mode = decltype(MODE)::value;
      uint32_t T[16], ef[4], q0, q1, x0, x1, x2; float e0_, e1_, cs[4];
      auto mu = [&](int j) {
#pragma unroll
        for (int i = 2 * j; i < 2 * j + 2; i++) asm volatile("{.reg .b16 l, h; mov.b32 {l, h}, %2; tanh.approx.f16 %0, l; tanh.approx.f16 %1, h;}" : "=h"(tl[i]), "=h"(th[i]) : "r"(Y[i])); };
      auto fi = [&](int j) {
#pragma unroll
        for (int i = 2 * j; i < 2 * j + 2; i++) asm volatile("{.reg .b32 t; mov.b32 t, {%2, %3}; fma.rn.f16x2 %0, %1, t, %1;}" : "=r"(M[i]) : "r"(Y[i]), "h"(tl[i]), "h"(th[i])); };
      auto ad = [&](int j) { asm volatile("add.rn.f16x2 %0, %0, %1; add.rn.f16x2 %0, %0, %2;" : "+r"(sum[j]) : "r"(M[2 * j]), "r"(M[2 * j + 1])); };
      auto he = [&](int j) { asm volatile("mma.sync.aligned.m16n8k16.row.col.f16.f16.f16.f16 {%0,%1}, {%2,%3,%4,%5}, {%6,%7}, {%0,%1};" : "+r"(T[2 * j]), "+r"(T[2 * j + 1]) : "r"(ef[0]), "r"(ef[1]), "r"(ef[2]), "r"(ef[3]), "r"(w3[2 * j]), "r"(w3[2 * j + 1])); };
      auto hs = [&](int j) { asm volatile("mma.sync.aligned.m16n8k16.row.col.f16.f16.f16.f16 {%0,%1}, {%2,%3,%4,%5}, {%6,%7}, {%8,%9};" : "=r"(Y[2 * j]), "=r"(Y[2 * j + 1]) : "r"(q0), "r"(q1), "r"(oh0), "r"(oh1), "r"(bp[2 * j]), "r"(bp[2 * j + 1]), "r"(T[2 * j]), "r"(T[2 * j + 1])); };
      auto hc = [&](int j) {
        if (j) asm volatile("mma.sync.aligned.m16n8k16.row.col.f32.f16.f16.f32 {%0,%1,%2,%3}, {%4,%5,%6,%7}, {%8,%9}, {%0,%1,%2,%3};" : "+f"(cs[0]), "+f"(cs[1]), "+f"(cs[2]), "+f"(cs[3]) : "r"(M[4 * j]), "r"(M[4 * j + 1]), "r"(M[4 * j + 2]), "r"(M[4 * j + 3]), "r"(wv[2 * j]), "r"(wv[2 * j + 1]));
        else asm volatile("mma.sync.aligned.m16n8k16.row.col.f32.f16.f16.f32 {%0,%1,%2,%3}, {%4,%5,%6,%7}, {%8,%9}, {%10,%10,%10,%10};" : "=f"(cs[0]), "=f"(cs[1]), "=f"(cs[2]), "=f"(cs[3]) : "r"(M[0]), "r"(M[1]), "r"(M[2]), "r"(M[3]), "r"(wv[0]), "r"(wv[1]), "f"(0.f)); };
      auto cv = [&](int i) { asm volatile("{.reg .b32 a, b; shl.b32 a, %0, 16; and.b32 b, %0, 0xFFFF0000; cvt.rn.f16x2.f32 %0, b, a;}" : "+r"(ef[i])); };
      auto un = [&]() { asm volatile("shl.b32 %0, %2, 16; and.b32 %1, %2, 0xFFFF0000;" : "=&f"(e0_), "=&f"(e1_) : "r"(dpk)); };
      auto ex0 = [&]() { asm volatile("prmt.b32 %0, %3, %4, 0x6420; prmt.b32 %1, %5, %6, 0x6420; prmt.b32 %2, %7, %8, 0x6420;" : "=&r"(x0), "=&r"(x1), "=&r"(x2) : "r"(T[0]), "r"(T[1]), "r"(T[2]), "r"(T[3]), "r"(T[4]), "r"(T[5])); };
      auto ex1 = [&]() { asm volatile("{.reg .b32 a, b; shl.b32 a, %2, 3; shl.b32 b, %3, 6; lop3.b32 a, %1, a, 0x38383838, 0xD8; lop3.b32 a, a, b, 0xC0C0C0C0, 0xD8; sub.rn.bf16x2 %0, %4, a;}" : "=r"(dpk) : "r"(x0), "r"(x1), "r"(x2), "r"(own)); };
      auto ex2 = [&]() { asm volatile("{.reg .b32 a, b, d, u; .reg .b16 l, h; shl.b32 a, %2, 16; and.b32 b, %2, 0xFFFF0000; cvt.rn.f16x2.f32 d, b, a; mul.rn.f16x2 %0, d, d; mov.b32 {l, h}, d; mov.b32 u, {h, h}; mul.rn.f16x2 %1, u, u;}" : "=&r"(q0), "=&r"(q1) : "r"(dpk)); };
      auto pf = [&]() { asm volatile("fma.rn.f32 %0, %1, %2, %0; fma.rn.f32 %0, %3, %4, %0;" : "+f"(pacc) : "f"(cs[0]), "f"(e0_), "f"(cs[2]), "f"(e1_)); };
#define FX(k) if (FM >> k & 1) asm volatile("pmevent 1;" ::: "memory")
      if (mode == 2) {
        hc(0); mu(3); fi(2); un(); ad(0); ad(1); mu(4); fi(3); hc(1); mu(5); fi(4); ad(2); mu(6); fi(5); ad(3); hc(2); mu(7); fi(6); fi(7); ad(4); ad(5); hc(3); ad(6); ad(7); pf();
        return;
      }
      asm volatile("cp.async.wait_group %0;" :: "n"(NST - 1) : "memory");
      __syncwarp();
      if (mode == 1) STAMP(8);
      ldsm4(ef, eadr + so); ldsm4(T, qa0 + so); ldsm4(T + 4, qa1 + so); ldsm4(T + 8, qa2 + so); ldsm4(T + 12, qa3 + so);
      tl_();
      if (mode == 1) {
        issue();
        cv(0); cv(1); cv(2); cv(3); ex0(); ex1(); ex2();
#pragma unroll
        for (int j = 0; j < 8; j++) { he(j); hs(j); }
        mu(0); mu(1); fi(0); mu(2); fi(1);
        return;
      }
      hc(0); mu(3); fi(2); un(); ad(0); ad(1);
      FX(0);
      mu(4); fi(3); cv(0); cv(1); cv(2); cv(3); ex0(); ex1();
      FX(1);
      he(0); he(1); hc(1); mu(5); fi(4); ex2(); ad(2);
      FX(2);
      hs(0); he(2); mu(6); fi(5); issue(); ad(3);
      FX(3);
      hs(1); he(3); hc(2); mu(7); fi(6);
      FX(4);
      hs(2); hs(3); he(4); he(5); mu(0); fi(7); ad(4); ad(5);
      FX(5);
      hc(3); hs(4); he(6); he(7); mu(1); fi(0); ad(6);
      FX(6);
      hs(5); hs(6); hs(7); mu(2); fi(1); ad(7); pf();
      FX(7);
    };
#pragma unroll
    for (int j = 0; j < 8; j++) sum[j] = 0;
    body(IC<1>());
    int cnt = (lens & 255) - 1;
#pragma unroll 1
    for (int t = 0; t < 8; t++) {
#pragma unroll 1
      for (; cnt > 0; cnt--) body(IC<0>());
      if (!(t & 1)) {
        ownp = own;
        if (t < 6) {
          a_g += 64; own = lds16(a_g) * 0x10001u;
          if (t == 0) {
#pragma unroll
            for (int j = 0; j < 8; j++) bp[2 * j + 1] = sp[j];
          } else bload((a_g & 16) ? (t & 4) * 256 : 0);
          lens >>= 8; cnt = 1;
          continue;
        }
        body(IC<2>()); t++;
        STAMP(9);
      }
      cnt = (lens & 255) - 1;
      { const uint32_t ng = __shfl_sync(~0u, ownp, (a_g >> 1) | 3) >> 16, c3 = (a_g >> 1) & 3;
        asm volatile("{.reg .pred p; setp.lt.u32 p, %2, %3; @p st.global.u16 [%0], %1;}" :: "l"(p.out + (size_t)p.N * 64 + (size_t)node0 * 3 + (ng * 3 + c3)), "h"((uint16_t)pack_bf16(bf_hi(ownp) + pacc, 0.f)), "r"(ng), "r"(c3 < 3 ? nloc : 0) : "memory"); }
      chk = fmaf(pacc, 0.f, chk); pacc = 0.f;
      if (t & 2) {
        uint32_t hf[16]; float acc[32];
        const uint32_t nd = lds16(a_n); a_n += 128;
        const uint32_t hrow = hload(hf, nd);
        const uint64_t b1 = DHI | ((sb + OFF_W) >> 4), b2_ = b1 + 512;
        mbar_wait(sb + BAR_WH);
        wg_fence();
        rs64h<0>(acc, sp[0], sum[0], sp[1], sum[1], b2_); rs64h<1>(acc, sp[2], sum[2], sp[3], sum[3], b2_ + 128); rs64h<1>(acc, sp[4], sum[4], sp[5], sum[5], b2_ + 256); rs64h<1>(acc, sp[6], sum[6], sp[7], sum[7], b2_ + 384);
        rs64b<1>(acc, hf[0], hf[1], hf[2], hf[3], b1); rs64b<1>(acc, hf[4], hf[5], hf[6], hf[7], b1 + 128); rs64b<1>(acc, hf[8], hf[9], hf[10], hf[11], b1 + 256); rs64b<1>(acc, hf[12], hf[13], hf[14], hf[15], b1 + 384);
        wg_commit(); wg_wait0(); fence_regs(acc);
        if (t == 7) STAMP(10);
        chk = fmaf(acc[0], 0.f, fmaf(acc[2], 0.f, chk));
        auto fin = [&](uint32_t x, float y0, float y1) { return u2(__hadd2(b2(x), b2(pack_bf16(silu_h(y0), silu_h(y1))))); };
#pragma unroll
        for (int j = 0; j < 4; j++) stsm4(hrow ^ (j << 5), fin(hf[4 * j], acc[8 * j], acc[8 * j + 1]), fin(hf[4 * j + 1], acc[8 * j + 2], acc[8 * j + 3]), fin(hf[4 * j + 2], acc[8 * j + 4], acc[8 * j + 5]), fin(hf[4 * j + 3], acc[8 * j + 6], acc[8 * j + 7]));
        __syncwarp();
        const uint32_t c8 = (a_g << 3) & 0x70;
#pragma unroll
        for (int j = 0; j < 4; j++) { uint32_t v[4]; const uint32_t n = __shfl_sync(~0u, nd, 4 * j + ((a_g >> 4) & 3)); lds128(v, sb + OFF_H + n * 128 + (((n << 4) ^ c8) & 0x70));
          asm volatile("{.reg .pred p; setp.lt.u32 p, %5, %6; @p st.global.v4.b32 [%0], {%1,%2,%3,%4};}" :: "l"((const char*)p.out + (size_t)node0 * 128 + (n * 128 + c8)), "r"(v[0]), "r"(v[1]), "r"(v[2]), "r"(v[3]), "r"(n), "r"(nloc) : "memory"); }
        wload();
      }
#pragma unroll
      for (int j = 0; j < 8; j++) { sp[j] = sum[j]; asm volatile("mov.b32 %0, 0;" : "=r"(sum[j])); }
    }
    asm volatile("{.reg .pred p, q; setp.neu.f32 p, %1, 0f00000000; setp.ne.or.u32 p, %2, 0, p; bar.red.or.pred q, 5, 384, p; selp.u32 %0, 1, 0, q;}" : "=r"(bad) : "f"(chk), "r"(lds32(sb + OFF_MISC + 12)) : "memory");
    STAMP(11);
   } else { asm volatile("cp.async.wait_all;" ::: "memory"); bar_sync(5, 384); }
  }
  if (bad) slow_path(p, wid, lane, node0, nloc);
}

}

typedef CUresult (*EncodeFn)(CUtensorMap*, CUtensorMapDataType, cuuint32_t, void*, const cuuint64_t*, const cuuint64_t*, const cuuint32_t*, const cuuint32_t*,
                             CUtensorMapInterleave, CUtensorMapSwizzle, CUtensorMapL2promotion, CUtensorMapFloatOOBfill);

extern "C" void kernel_launch(void* const* d_in, const int* in_sizes, int n_in, void* d_out, int out_size) {
  Params p; Maps maps;
  p.h = (const uint4*)d_in[0]; p.pos = (const uint16_t*)d_in[1]; p.ea = (const uint4*)d_in[2];
  p.src = (const int*)d_in[3]; p.dst = (const int*)d_in[4];
  p.we = (const uint16_t*)d_in[5]; p.wx = (const uint16_t*)d_in[6]; p.wh = (const uint16_t*)d_in[7];
  p.out = (uint16_t*)d_out;
  p.N = in_sizes[0] / 64; p.E = in_sizes[3];
  p.EPC = ((p.E + G * 4 - 1) / (G * 4)) * 4;
  p.magic = (uint32_t)(((uint64_t)G << 24) / (uint64_t)p.N);
  p.inv = (1ull << 56) / p.magic;
  const uint64_t ea0 = (uint64_t)d_in[2], ea1 = ea0 + (uint64_t)p.E * 32 - 1;
  p.force_slow = ((ea0 >> 32) != (ea1 >> 32)) || (ea0 & 31) || (p.E & 3);
  void* qp = nullptr;
  cudaGetSymbolAddress(&qp, g_q);
  p.q = (char*)qp;
  if (((uint64_t)p.q >> 32) != (((uint64_t)p.q + QBYTES) >> 32)) p.q += QBYTES;
  cudaGetSymbolAddress((void**)&p.cnt, g_cnt); cudaGetSymbolAddress((void**)&p.sent, g_sent); cudaGetSymbolAddress((void**)&p.xe, g_xe);
  cudaGetSymbolAddress((void**)&p.xa, g_xa); cudaGetSymbolAddress((void**)&p.xb, g_xb);
  void* fn = nullptr; cudaDriverEntryPointQueryResult qr;
  cudaGetDriverEntryPoint("cuTensorMapEncodeTiled", &fn, cudaEnableDefault, &qr);
  auto mk = [&](CUtensorMap* tm, void* base, int rows) {
    const cuuint64_t dim[2] = {64, (cuuint64_t)rows}, str[1] = {128}; const cuuint32_t bx[2] = {64, 64}, es[2] = {1, 1};
    ((EncodeFn)fn)(tm, CU_TENSOR_MAP_DATA_TYPE_BFLOAT16, 2, base, dim, str, bx, es, CU_TENSOR_MAP_INTERLEAVE_NONE, CU_TENSOR_MAP_SWIZZLE_128B,
                   CU_TENSOR_MAP_L2_PROMOTION_NONE, CU_TENSOR_MAP_FLOAT_OOB_FILL_NONE);
  };
  mk(&maps.m[TM_H / 128], d_in[0], p.N); mk(&maps.m[TM_WE / 128], d_in[5], 145); mk(&maps.m[TM_WH / 128], d_in[7], 128); mk(&maps.m[TM_Q / 128], p.q, p.N);
  for (int k = 0; k < 2; k++) {
    void* xp = (void*)(k ? p.xb : p.xa);
    const cuuint64_t dim[2] = {(cuuint64_t)G * 64, (cuuint64_t)G}, str[1] = {(cuuint64_t)G * (128 << k)}; const cuuint32_t bx[2] = {64, (cuuint32_t)(k ? BROWS : G)}, es[2] = {1, 1};
    ((EncodeFn)fn)(&maps.m[TM_XA / 128 + k], k ? CU_TENSOR_MAP_DATA_TYPE_UINT32 : CU_TENSOR_MAP_DATA_TYPE_UINT16, 2, xp, dim, str, bx, es, CU_TENSOR_MAP_INTERLEAVE_NONE,
                   CU_TENSOR_MAP_SWIZZLE_NONE, CU_TENSOR_MAP_L2_PROMOTION_NONE, CU_TENSOR_MAP_FLOAT_OOB_FILL_NONE);
  }
  cudaFuncSetAttribute(egnn_kernel, cudaFuncAttributeMaxDynamicSharedMemorySize, SMEM);
  egnn_kernel<<<G, NTHR, SMEM>>>(p, maps);
}
```

```cpp
#include <cuda_runtime.h>
#include <cuda_bf16.h>
#include <cuda_fp16.h>
#include <cuda.h>
#include <stdint.h>
#pragma nv_diag_suppress 549

#define PFN 8
#define PFNS 250
#define FM 0
#define OPQ 1
#define H0 0
#define HALL 0
#define PF0NS 500
#define HW 3
#define BROWS 132
#define B_HOLD 0
#define S0 0
#define S1 2
#define S2 3
namespace {

constexpr int G = 132;
constexpr int NTHR = 512, NWK = 352, NCH = 5;
constexpr int NST = 3, STG = 2560;
constexpr int SCAP = 448;

constexpr int OFF_H = 0;
constexpr int OFF_W = 49152;
constexpr int OFF_WD = OFF_W + 16384;
constexpr int OFF_W3 = OFF_WD + 1024;
constexpr int OFF_P2 = OFF_W3 + 2048;
constexpr int OFF_RING = OFF_P2 + 24576;
constexpr int OFF_TE = OFF_RING + 12 * NST * STG;
constexpr int OFF_TS = OFF_TE + SCAP * 64;
constexpr int OFF_GP = OFF_TS + SCAP * 32;
constexpr int OFF_WX = OFF_GP + 3072;
constexpr int OFF_LEN = OFF_WX + 128;
constexpr int OFF_MISC = OFF_LEN + 128;
constexpr int OFF_BAR = OFF_MISC + 48;
constexpr int SMEM = OFF_BAR + 256;
static_assert(SMEM <= 232448, "smem");
constexpr uint32_t sb = 1024;
constexpr int OFF_SRCI = OFF_TE;
constexpr int OFF_SB = OFF_RING, OFF_SA = OFF_SB + 34816, OFF_AX = OFF_SA + 32768, OFF_DST = OFF_H + 24576;
constexpr int OFF_PT = OFF_SB - 16384, PTX = OFF_AX - OFF_PT;
constexpr int OFF_WS = OFF_AX + 17408;
constexpr int OFF_BC = OFF_WS + 2304;
constexpr int OFF_CNT = OFF_P2 + 16384;
constexpr int OFF_DH = OFF_CNT + 2176;
constexpr int OFF_POS = OFF_DH + 128;
constexpr int OFF_EXT = OFF_POS + 3072;
static_assert(OFF_EXT + 1024 <= OFF_RING && OFF_BC + 544 <= OFF_TE && OFF_P2 % 1024 == 0 && OFF_SA % 1024 == 0 && SCAP * 64 >= 24576, "staging");
constexpr int BAR_DST = OFF_BAR, BAR_SRC = BAR_DST + 40, BAR_T = BAR_SRC + 24, BAR_W = BAR_T + 48, BAR_XA = BAR_W + 8, BAR_PS = BAR_XA + 8, BAR_AW = BAR_PS + 8,
              BAR_BW = BAR_AW + 8, BAR_QP = BAR_BW + 8, BAR_QR = BAR_QP + 8, BAR_HA = BAR_QR + 8, BAR_EP = BAR_HA + 8, BAR_AX = BAR_EP + 8, BAR_BS = BAR_AX + 8, BAR_HB = BAR_BS + 8, BAR_U = BAR_HB + 8, BAR_WH = BAR_U + 8, BAR_END = BAR_WH + 8;
constexpr uint32_t QBYTES = 8u << 20;

__device__ __align__(256) uint4 g_xa[G * G * 8];
__device__ __align__(256) uint4 g_xb[G * G * 16];
__device__ __align__(256) uint2 g_xe[G * G * 64];
__device__ __align__(256) uint4 g_q[2 * QBYTES / 16];
__device__ __align__(256) unsigned long long g_cnt;
__device__ __align__(256) uint32_t g_sent[64];
#define STAMP(k)

struct Maps { CUtensorMap m[6]; };
constexpr int TM_H = 0, TM_WE = 128, TM_WH = 256, TM_Q = 384, TM_XA = 512, TM_XB = 640;
struct Params {
  const uint4* h; const uint16_t* pos; const uint4* ea; const int* src; const int* dst;
  const uint16_t* we; const uint16_t* wx; const uint16_t* wh; uint16_t* out; char* q;
  unsigned long long* cnt; uint32_t* sent; const uint4* xa; const uint4* xb; uint2* xe;
  int N, E, EPC; uint32_t magic; int force_slow; unsigned long long inv;
};
template<int V> struct IC { static constexpr int value = V; };

#define R32(d) "+f"(d[0]),"+f"(d[1]),"+f"(d[2]),"+f"(d[3]),"+f"(d[4]),"+f"(d[5]),"+f"(d[6]),"+f"(d[7]),"+f"(d[8]),"+f"(d[9]),"+f"(d[10]),"+f"(d[11]),"+f"(d[12]),"+f"(d[13]),"+f"(d[14]),"+f"(d[15]),"+f"(d[16]),"+f"(d[17]),"+f"(d[18]),"+f"(d[19]),"+f"(d[20]),"+f"(d[21]),"+f"(d[22]),"+f"(d[23]),"+f"(d[24]),"+f"(d[25]),"+f"(d[26]),"+f"(d[27]),"+f"(d[28]),"+f"(d[29]),"+f"(d[30]),"+f"(d[31])
#define S32 "{%0,%1,%2,%3,%4,%5,%6,%7,%8,%9,%10,%11,%12,%13,%14,%15,%16,%17,%18,%19,%20,%21,%22,%23,%24,%25,%26,%27,%28,%29,%30,%31}"
#define DI __device__ __forceinline__

constexpr uint64_t DHI = ((uint64_t)(1024 >> 4) << 32) | (1ull << 62);
template<int SD> DI void rs64b(float (&d)[32], uint32_t a0, uint32_t a1, uint32_t a2, uint32_t a3, uint64_t db) {
  asm volatile("wgmma.mma_async.sync.aligned.m64n64k16.f32.bf16.bf16 " S32 ", {%32,%33,%34,%35}, %36, %37, 1, 1, 1;" : R32(d) : "r"(a0), "r"(a1), "r"(a2), "r"(a3), "l"(db), "n"(SD)); }
template<int SD> DI void rs64h(float (&d)[32], uint32_t a0, uint32_t a1, uint32_t a2, uint32_t a3, uint64_t db) {
  asm volatile("wgmma.mma_async.sync.aligned.m64n64k16.f32.f16.f16 " S32 ", {%32,%33,%34,%35}, %36, %37, 1, 1, 1;" : R32(d) : "r"(a0), "r"(a1), "r"(a2), "r"(a3), "l"(db), "n"(SD)); }
template<int SD> DI void ss64(float (&d)[32], uint64_t da, uint64_t db) {
  asm volatile("wgmma.mma_async.sync.aligned.m64n64k16.f32.bf16.bf16 " S32 ", %32, %33, %34, 1, 1, 0, 1;" : R32(d) : "l"(da), "l"(db), "n"(SD)); }
DI void trap_if(bool c) { asm volatile("{.reg .pred p; setp.eq.u32 p, %0, 0; @p bra.uni LT_%=; trap; LT_%=:}" :: "r"((uint32_t)c)); }
DI void wg_fence() { asm volatile("wgmma.fence.sync.aligned;" ::: "memory"); }
DI void wg_commit() { asm volatile("wgmma.commit_group.sync.aligned;" ::: "memory"); }
DI void wg_wait0() { asm volatile("wgmma.wait_group.sync.aligned 0;" ::: "memory"); }
DI void fence_regs(float (&d)[32]) { asm volatile("" : R32(d) :: "memory"); }
DI void proxy_fence() { asm volatile("fence.proxy.async.shared::cta;" ::: "memory"); }
DI uint64_t pol_first() { uint64_t r; asm("createpolicy.fractional.L2::evict_first.b64 %0, 1.0;" : "=l"(r)); return r; }
DI float tanh_ap(float x) { float y; asm("tanh.approx.f32 %0, %1;" : "=f"(y) : "f"(x)); return y; }
DI float silu_h(float y) { return fmaf(y, tanh_ap(y), y); }
DI uint32_t pack_bf16(float lo, float hi) { uint32_t r; asm("cvt.rn.bf16x2.f32 %0, %1, %2;" : "=r"(r) : "f"(hi), "f"(lo)); return r; }
DI uint32_t pack_f16(float lo, float hi) { uint32_t r; asm("cvt.rn.f16x2.f32 %0, %1, %2;" : "=r"(r) : "f"(hi), "f"(lo)); return r; }
DI float bf_lo(uint32_t v) { return __uint_as_float(v << 16); }
DI float bf_hi(uint32_t v) { return __uint_as_float(v & 0xFFFF0000u); }
DI uint32_t b2h(uint32_t v, float s) { return pack_f16(s * bf_lo(v), s * bf_hi(v)); }
DI void mbar_wait(uint32_t bar, uint32_t parity = 0) {
  asm volatile("{.reg .pred p; .reg .u32 t0, t1;\n"
    "mbarrier.try_wait.parity.shared::cta.b64 p, [%0], %1;\n @p bra.uni LD_%=;\n mov.u32 t0, %%clock;\n"
    "LW_%=: mbarrier.try_wait.parity.shared::cta.b64 p, [%0], %1;\n"
    "@p bra.uni LD_%=;\n mov.u32 t1, %%clock; sub.u32 t1, t1, t0; setp.lt.u32 p, t1, 0x80000000;\n @p bra.uni LW_%=;\n trap;\n LD_%=:}" :: "r"(bar), "r"(parity) : "memory");
}
DI void mbar_arrive(uint32_t bar, int p = 1) { asm volatile("{.reg .pred p; setp.ne.b32 p, %1, 0; @p mbarrier.arrive.shared::cta.b64 _, [%0];}" :: "r"(bar), "r"(p) : "memory"); }
DI void bar_sync(int id, int n) { asm volatile("bar.sync %0, %1;" :: "r"(id), "r"(n) : "memory"); }
DI void bar_arrive(int id, int n) { asm volatile("bar.arrive %0, %1;" :: "r"(id), "r"(n) : "memory"); }
DI __nv_bfloat162 b2(uint32_t v) { return *(__nv_bfloat162*)&v; }
DI uint32_t u2(__nv_bfloat162 v) { return *(uint32_t*)&v; }
DI uint32_t hsq(uint32_t v) { return u2(__hmul2(b2(v), b2(v))); }
DI uint32_t hsub(uint32_t a, uint32_t b) { return u2(__hsub2(b2(a), b2(b))); }
DI uint32_t hhalf(uint32_t v) { return u2(__hmul2(b2(v), __floats2bfloat162_rn(0.5f, 0.5f))); }
DI uint32_t mag2(uint32_t m, uint32_t v) { return __vmaxu2(m, v & 0x7FFF7FFFu); }
DI uint32_t hmag(uint32_t m, uint32_t v) { const __half2 r = __hmax2(*(const __half2*)&m, __habs2(*(const __half2*)&v)); return *(const uint32_t*)&r; }
DI uint32_t magr(uint32_t m) { return max(m & 0xFFFF, m >> 16); }
DI void sts128(uint32_t a, uint32_t x, uint32_t y, uint32_t z, uint32_t w) { asm volatile("st.shared.v4.u32 [%0], {%1,%2,%3,%4};" :: "r"(a), "r"(x), "r"(y), "r"(z), "r"(w) : "memory"); }
DI void sts64(uint32_t a, uint32_t x, uint32_t y) { asm volatile("st.shared.v2.u32 [%0], {%1,%2};" :: "r"(a), "r"(x), "r"(y) : "memory"); }
DI void sts32(uint32_t a, uint32_t x) { asm volatile("st.shared.u32 [%0], %1;" :: "r"(a), "r"(x) : "memory"); }
DI void sts16(uint32_t a, uint32_t x) { asm volatile("st.shared.u16 [%0], %1;" :: "r"(a), "h"((uint16_t)x) : "memory"); }
DI void lds128(uint32_t* v, uint32_t a) { asm volatile("ld.shared.v4.u32 {%0, %1, %2, %3}, [%4];" : "=r"(v[0]), "=r"(v[1]), "=r"(v[2]), "=r"(v[3]) : "r"(a) : "memory"); }
DI void lds64(uint32_t& x, uint32_t& y, uint32_t a) { asm volatile("ld.shared.v2.u32 {%0, %1}, [%2];" : "=r"(x), "=r"(y) : "r"(a) : "memory"); }
DI uint32_t lds32(uint32_t a) { uint32_t x; asm volatile("ld.shared.u32 %0, [%1];" : "=r"(x) : "r"(a) : "memory"); return x; }
DI uint32_t lds16(uint32_t a) { uint32_t x; asm volatile("ld.shared.u16 %0, [%1];" : "=r"(x) : "r"(a) : "memory"); return x; }
DI uint32_t atoms_add(uint32_t a, uint32_t v) { uint32_t r; asm volatile("atom.shared.add.u32 %0, [%1], %2;" : "=r"(r) : "r"(a), "r"(v) : "memory"); return r; }
DI void bulk_load(uint32_t dst, const void* src, uint32_t bytes, uint32_t bar) {
  asm volatile("cp.async.bulk.shared::cluster.global.mbarrier::complete_tx::bytes.L2::cache_hint [%0], [%1], %2, [%3], %4;" :: "r"(dst), "l"(src), "r"(bytes), "r"(bar), "l"(pol_first()) : "memory"); }
DI void bulk_store(void* dst, uint32_t src, uint32_t bytes) { asm volatile("cp.async.bulk.global.shared::cta.bulk_group [%0], [%1], %2;" :: "l"(dst), "r"(src), "r"(bytes) : "memory"); }
DI void mbar_expect(uint32_t bar, uint32_t bytes) { asm volatile("mbarrier.arrive.expect_tx.shared::cta.b64 _, [%0], %1;" :: "r"(bar), "r"(bytes) : "memory"); }
DI void mbar_init(uint32_t bar, int n) { asm volatile("mbarrier.init.shared::cta.b64 [%0], %1;" :: "r"(bar), "r"(n) : "memory"); }
DI void tma_load(uint32_t dst, uint64_t tm, int row, uint32_t bar) {
  asm volatile("cp.async.bulk.tensor.2d.shared::cluster.global.mbarrier::complete_tx::bytes.L2::cache_hint [%0], [%1, {%3, %4}], [%2], %5;" :: "r"(dst), "l"(tm), "r"(bar), "r"(0), "r"(row), "l"(pol_first()) : "memory"); }
DI void tma_store(uint64_t tm, int col, int row, uint32_t src) {
  asm volatile("cp.async.bulk.tensor.2d.global.shared::cta.bulk_group [%0, {%2, %3}], [%1];" :: "l"(tm), "r"(src), "r"(col), "r"(row) : "memory"); }
DI void bulk_commit() { asm volatile("cp.async.bulk.commit_group;" ::: "memory"); }
DI void bulk_wait_read() { asm volatile("cp.async.bulk.wait_group.read 0;" ::: "memory"); }
DI uint2 ld_poll2(const void* a) { uint2 v; asm volatile("ld.relaxed.gpu.global.v2.u32 {%0, %1}, [%2];" : "=r"(v.x), "=r"(v.y) : "l"(a) : "memory"); return v; }
DI void st_ext(uint2* a, uint32_t v, uint32_t ep) { asm volatile("st.relaxed.gpu.global.v2.u32 [%0], {%1, %2};" :: "l"(a), "r"(v), "r"(ep) : "memory"); }
DI uint32_t ext_get(const uint2* a, uint32_t ep) { uint2 v; int spin = 0; do { v = ld_poll2(a); trap_if(++spin > 4000000); } while (__any_sync(~0u, v.y != ep)); return v.x; }
DI void bulk_wait() { asm volatile("cp.async.bulk.wait_group 0;" ::: "memory"); }
DI void grid_signal(unsigned long long* cnt, bool flag = false) {
  asm volatile("red.release.gpu.global.add.u64 [%0], %1;" :: "l"(cnt), "l"(flag ? (1ull << 44) + 1 : 1ull) : "memory"); }
DI bool grid_wait(unsigned long long* cnt, unsigned long long c0) {
  const unsigned long long M = (1ull << 44) - 1, target = ((c0 & M) / G + 1) * G;
  unsigned long long c; int spin = 0;
  do { asm volatile("ld.acquire.gpu.global.u64 %0, [%1];" : "=l"(c) : "l"(cnt) : "memory"); trap_if(++spin > 4000000); } while (__any_sync(~0u, (c & M) < target));
  return (c ^ c0) >> 44;
}
DI void hint_signal(uint32_t* c) { asm volatile("red.relaxed.gpu.global.add.u32 [%0], 1;" :: "l"(c) : "memory"); }
DI void hint_wait(const uint32_t* c, uint32_t target, uint32_t v) { int spin = 0;
  trap_if(target - __shfl_sync(~0u, v, 0) - 1 >= G);
  do { asm volatile("ld.relaxed.gpu.global.u32 %0, [%1];" : "=r"(v) : "l"(c) : "memory"); trap_if(++spin > 4000000); } while (__any_sync(~0u, (int)(v - target) < 0)); }
DI unsigned long long ld_cnt(const unsigned long long* cnt) { unsigned long long c; asm volatile("ld.relaxed.gpu.global.u64 %0, [%1];" : "=l"(c) : "l"(cnt)); return c; }
DI void stsm4(uint32_t a, uint32_t x, uint32_t y, uint32_t z, uint32_t w) { asm volatile("stmatrix.sync.aligned.m8n8.x4.shared.b16 [%0], {%1,%2,%3,%4};" :: "r"(a), "r"(x), "r"(y), "r"(z), "r"(w) : "memory"); }
DI void ldsm4(uint32_t* v, uint32_t a) { asm volatile("ldmatrix.sync.aligned.m8n8.x4.shared.b16 {%0,%1,%2,%3}, [%4];" : "=r"(v[0]), "=r"(v[1]), "=r"(v[2]), "=r"(v[3]) : "r"(a) : "memory"); }
DI void ldsm4t(uint32_t* v, uint32_t a) { asm volatile("ldmatrix.sync.aligned.m8n8.x4.trans.shared.b16 {%0,%1,%2,%3}, [%4];" : "=r"(v[0]), "=r"(v[1]), "=r"(v[2]), "=r"(v[3]) : "r"(a) : "memory"); }
DI uint32_t mad16(uint32_t x, uint32_t m, uint32_t c) { uint32_t r; asm("dp2a.lo.u32.u32 %0, %1, %2, %3;" : "=r"(r) : "r"(x), "r"(m), "r"(c)); return r; }
DI bool wbad(uint32_t m, uint32_t hi) { return m > hi || (m && m < 0x3980); }

__device__ __noinline__ void slow_path(const Params& p, int wid, int lane, int node0, int nloc) {
  const uint32_t ab = sb + OFF_P2 + wid * 8704;
  for (int i = lane; i < 32 * 68; i += 32) sts32(ab + i * 4, 0);
  __syncwarp();
  const uint32_t wdv = __ldg((const uint32_t*)(p.we + 128 * 64) + lane), wxv = __ldg((const uint32_t*)p.wx + lane);
  const int nb0 = node0 + wid * 32, cntn = max(0, min(32, nloc - wid * 32));
  auto dot = [&](uint32_t hv, const uint16_t* w, int K2, float& y0, float& y1) {
#pragma unroll 4
    for (int k = 0; k < K2; k++) {
      const uint32_t hk = __shfl_sync(~0u, hv, k), wa = __ldg((const uint32_t*)(w + 2 * k * 64) + lane), wb = __ldg((const uint32_t*)(w + (2 * k + 1) * 64) + lane);
      y0 = fmaf(bf_lo(hk), bf_lo(wa), fmaf(bf_hi(hk), bf_lo(wb), y0)); y1 = fmaf(bf_lo(hk), bf_hi(wa), fmaf(bf_hi(hk), bf_hi(wb), y1));
    }
  };
  auto silu = [](float x) { return x / (1.f + __expf(-x)); };
#pragma unroll 1
  for (int base = 0; base < p.E; base += 32) {
    const int e = base + lane;
    const uint32_t dl = e < p.E ? (uint32_t)(__ldg(p.dst + e) - nb0) : 0xFFFFFFFFu;
    uint32_t mk = __ballot_sync(~0u, dl < (uint32_t)cntn);
    while (mk) {
      const int l = __ffs(mk) - 1; mk &= mk - 1;
      const int ee = base + l, n = __shfl_sync(~0u, dl, l), s = __ldg(p.src + ee);
      const uint16_t *po = p.pos + (size_t)(nb0 + n) * 3, *pp = p.pos + (size_t)s * 3;
      const uint32_t dxy = hsub(__ldg(po) | (__ldg(po + 1) << 16), __ldg(pp) | (__ldg(pp + 1) << 16)), dz = hsub(__ldg(po + 2), __ldg(pp + 2));
      const uint32_t sq = hsq(dxy); const float d2 = bf_lo(sq) + bf_hi(sq) + bf_lo(hsq(dz));
      float y0 = d2 * bf_lo(wdv), y1 = d2 * bf_hi(wdv);
      dot(__ldg((const uint32_t*)(p.h + (size_t)(nb0 + n) * 8) + lane), p.we, 32, y0, y1);
      dot(__ldg((const uint32_t*)(p.h + (size_t)s * 8) + lane), p.we + 64 * 64, 32, y0, y1);
      dot(__ldg((const uint32_t*)(p.ea + (size_t)ee * 2) + (lane & 7)), p.we + 129 * 64, 8, y0, y1);
      const uint32_t mm = pack_bf16(silu(y0), silu(y1));
      float c = bf_lo(mm) * bf_lo(wxv) + bf_hi(mm) * bf_hi(wxv);
#pragma unroll
      for (int o = 16; o; o >>= 1) c += __shfl_xor_sync(~0u, c, o);
      const uint32_t a = ab + n * 272;
      uint32_t x0, x1; lds64(x0, x1, a + lane * 8);
      sts64(a + lane * 8, __float_as_uint(__uint_as_float(x0) + bf_lo(mm)), __float_as_uint(__uint_as_float(x1) + bf_hi(mm)));
      if (lane < 3) { const float df = lane == 0 ? bf_lo(dxy) : lane == 1 ? bf_hi(dxy) : bf_lo(dz); sts32(a + 256 + lane * 4, __float_as_uint(fmaf(c, df, __uint_as_float(lds32(a + 256 + lane * 4))))); }
    }
  }
  __syncwarp();
#pragma unroll 1
  for (int n = 0; n < cntn; n++) {
    uint32_t x0, x1; lds64(x0, x1, ab + n * 272 + lane * 8);
    const uint32_t hv = __ldg((const uint32_t*)(p.h + (size_t)(nb0 + n) * 8) + lane);
    float y0 = 0.f, y1 = 0.f;
    dot(hv, p.wh, 32, y0, y1); dot(pack_bf16(__uint_as_float(x0), __uint_as_float(x1)), p.wh + 64 * 64, 32, y0, y1);
    ((uint32_t*)p.out)[(size_t)(nb0 + n) * 32 + lane] = u2(__hadd2(b2(hv), b2(pack_bf16(silu(y0), silu(y1)))));
    if (lane < 3) p.out[(size_t)p.N * 64 + (size_t)(nb0 + n) * 3 + lane] = (uint16_t)pack_bf16(bf_lo(__ldg(p.pos + (size_t)(nb0 + n) * 3 + lane)) + __uint_as_float(lds32(ab + n * 272 + 256 + lane * 4)), 0.f);
  }
}

__global__ void __launch_bounds__(NTHR, 1) egnn_kernel(const __grid_constant__ Params p, const __grid_constant__ Maps maps) {
  const uint64_t tmb = (uint64_t)&maps;
  extern __shared__ __align__(1024) unsigned char smraw[];
  const int tid = threadIdx.x, cta = blockIdx.x;
  const int e0 = cta * p.EPC, n4 = max(0, min(p.EPC, p.E - e0)) >> 2;
  STAMP(0);
  unsigned long long c0 = 0;
  uint32_t s0_ = 0;
  asm volatile("{.reg .pred p, q; setp.eq.u32 p, %4, 384; setp.eq.u32 q, %5, 320; @p ld.relaxed.gpu.global.u64 %0, [%2]; @q ld.relaxed.gpu.global.u32 %1, [%3];}"
    : "+l"(c0), "+r"(s0_) : "l"(p.cnt), "l"(p.sent + (tid & 32)), "r"(tid & 415), "r"(tid & 479));
  if (tid == NWK) {
#pragma unroll
    for (int k = 0; k < NCH; k++) mbar_init(sb + BAR_DST + k * 8, 1);
    asm volatile("fence.mbarrier_init.release.cluster;" ::: "memory");
#pragma unroll 1
    for (int k = 0; k < NCH; k++) { const int nb = max(0, min(NWK, n4 - k * NWK)) * 16;
      mbar_expect(sb + BAR_DST + k * 8, nb);
      if (nb) bulk_load(sb + OFF_DST + k * NWK * 16, (const char*)(p.dst + e0) + k * NWK * 16, nb, sb + BAR_DST + k * 8); }
  }
  const int lane = tid & 31, wid = __shfl_sync(~0u, tid >> 5, 0), w = wid & 3;

  auto first_node = [&](int c) { return (int)((c * p.inv + 0xFFFFFFFFull) >> 32); };
  const int node0 = first_node(cta), nloc = min(first_node(cta + 1), p.N) - node0;
  const uint32_t ealo = (uint32_t)(uint64_t)p.ea;
  const int epad = min(e0, p.E - 1);
  if (wid >= 12) {
    const int t = tid - 384;
    auto prefetch_e = [&](int i) {
      const uint32_t nb = (p.E / G) & ~15u;
      if (nb && i < PFN) asm volatile("cp.async.bulk.prefetch.L2.global [%0], %1;" :: "l"((const char*)p.ea + (size_t)(i * G + cta) * nb), "r"(nb) : "memory");
    };
    auto load_h = [&](int b) { mbar_expect(sb + BAR_T + b * 8, 8192); tma_load(sb + OFF_H + b * 8192, tmb + TM_H, node0 + b * 64, sb + BAR_T + b * 8); };
    uint32_t pv[9], ev = 0;
#pragma unroll
    for (int i = 0; i < 3; i++) { const uint16_t* pp = p.pos + (size_t)(node0 + t + 128 * i) * 3;
      pv[3 * i] = pv[3 * i + 1] = pv[3 * i + 2] = 0;
      asm volatile("{.reg .pred p; setp.lt.s32 p, %4, %5;\n @p ld.global.nc.u16 %0, [%3];\n @p ld.global.nc.u16 %1, [%3+2];\n @p ld.global.nc.u16 %2, [%3+4];}"
        : "+r"(pv[3 * i]), "+r"(pv[3 * i + 1]), "+r"(pv[3 * i + 2]) : "l"(pp), "r"(t + 128 * i), "r"(p.N - node0)); }
    asm volatile("{.reg .pred p; setp.lt.u32 p, %3, 8; @p ld.global.nc.u32 %0, [%1]; @p st.global.v4.u32 [%2], {%4, %4, %4, %4};}"
      : "+r"(ev) : "l"((const uint32_t*)(p.ea + (size_t)epad * 2) + t), "l"(p.q + (size_t)(p.N + cta) * 128 + t * 16), "r"(t), "r"(0xF700F700u) : "memory");
    c0 = __shfl_sync(~0u, c0, 0);
    {
      const uint32_t e = (uint32_t)((c0 & ((1ull << 44) - 1)) / G) + 1, tg = (1 + e % 3) << 30, v = ((tg >> 16) + 512 + (lane & 7) * 4) * 0x10001u;
      if (t == 0) sts32(sb + OFF_MISC + 32, e);
#pragma unroll
      for (int i = 0; i < 9; i++) sts128(sb + OFF_SA + t * 16 + i * 2048, v, v + 0x10001u, v + 0x20002u, v + 0x30003u);
      bar_sync(6, NTHR);
      mbar_arrive(sb + BAR_EP, lane == 0);
      if (w == 0) STAMP(27);
#pragma unroll
      for (int i = 0; i < 17; i++) sts128(sb + OFF_SB + t * 16 + i * 2048, tg, tg, tg, tg); }
    uint32_t mp = 0;
#pragma unroll
    for (int i = 0; i < 3; i++) { sts64(sb + OFF_POS + (t + 128 * i) * 8, pv[3 * i] | (pv[3 * i + 1] << 16), pv[3 * i + 2]); mp = mag2(mag2(mp, pv[3 * i] | (pv[3 * i + 1] << 16)), pv[3 * i + 2]); }
    proxy_fence();
    __syncwarp();
    mbar_arrive(sb + BAR_PS, lane == 0);
    mbar_wait(sb + BAR_W);
#pragma unroll
    for (int i = 0; i < 8; i += 4) { uint32_t v[16];
#pragma unroll
      for (int k = 0; k < 4; k++) lds128(v + 4 * k, sb + OFF_W + t * 16 + (i + k) * 2048);
#pragma unroll
      for (int k = 0; k < 4; k++) sts128(sb + OFF_W + t * 16 + (i + k) * 2048, hhalf(v[4 * k]), hhalf(v[4 * k + 1]), hhalf(v[4 * k + 2]), hhalf(v[4 * k + 3])); }
    {
      uint32_t v[4], u[4]; const int r = t >> 3, c = t & 7;
      lds128(v, sb + OFF_WS + 128 + t * 16); lds128(u, sb + OFF_WS + c * 16);
      const uint32_t x = lds32(sb + OFF_WS + 2176 + lane * 4);
      sts128(sb + OFF_W3 + r * 128 + ((c ^ (r & 7)) << 4), b2h(v[0], .5f), b2h(v[1], .5f), b2h(v[2], .5f), b2h(v[3], .5f));
      const float s = ((r & 1) || r == 6) ? 0.f : .5f;
      if (t < 64) sts128(sb + OFF_WD + r * 128 + ((c ^ r) << 4), b2h(u[0], s), b2h(u[1], s), b2h(u[2], s), b2h(u[3], s));
      if (t < 32) sts32(sb + OFF_WX + (t & 3) * 32 + (t >> 2) * 4, b2h(x, 1.f));
      const uint32_t m3 = __reduce_max_sync(~0u, magr(mag2(mag2(mag2(mag2(0, v[0]), v[1]), v[2]), v[3]))), md = __reduce_max_sync(~0u, magr(mag2(mag2(mag2(mag2(0, u[0]), u[1]), u[2]), u[3])));
      if (wbad(m3, 0x4000) || wbad(md, 0x4000) || wbad(__reduce_max_sync(~0u, magr(mag2(0, x))), 0x4700) || magr(mp) >= 0x4200 || magr(mag2(0, ev)) >= 0x4380) sts32(sb + OFF_MISC + 8, 1);
    }
    proxy_fence();
    if (w == 1) STAMP(23);
    if (w == 1) {
#pragma unroll 1
      for (int b = 0; b < HW; b++) { mbar_wait(sb + BAR_SRC + max(0, H0 + b) * 8); if (lane == 0) load_h(b); }
    }
    bar_sync(3, 128);
    STAMP(24);
    const uint32_t frag = (w * 16 + (lane & 15)) * 128 + (((lane >> 4) ^ (lane & 7)) << 4);
    uint32_t mq = 0; mp = 0;
#pragma unroll 1
    for (int b = 0; b < 6; b++) {
      float acc[32], ac2[32];
      const uint64_t da = DHI | (((sb + OFF_H) >> 4) + b * 512), db = DHI | ((sb + OFF_W) >> 4);
      const uint32_t v0 = lds16(sb + OFF_POS + b * 512 + w * 128 + lane * 2), v1 = lds16(sb + OFF_POS + 64 + b * 512 + w * 128 + lane * 2);
      mbar_wait(sb + BAR_T + b * 8);
      if (b == 0) STAMP(25);
      if (b == 5) STAMP(26);
      wg_fence();
      ss64<0>(acc, da, db); ss64<1>(acc, da + 2, db + 128); ss64<1>(acc, da + 4, db + 256); ss64<1>(acc, da + 6, db + 384);
      wg_commit();
      ss64<0>(ac2, da, db + 512); ss64<1>(ac2, da + 2, db + 640); ss64<1>(ac2, da + 4, db + 768); ss64<1>(ac2, da + 6, db + 896);
      wg_commit();
      if (b == 0) mbar_wait(sb + BAR_AW);
      if (t == 32) { if (HALL) { if (b == 0) for (int k = HW; k < 6; k++) load_h(k); } else if (b + HW < 6) load_h(b + HW); }
      __syncwarp();
      uint32_t ff[6], fg[6];
#pragma unroll
      for (int j = 0; j < 6; j++) { ff[j] = (__byte_perm((j & 1) ? v1 : v0, 0, 0x4140) >> (3 * (j >> 1))) & 0x00070007u; fg[j] = __vsub2(0x00040004u, ff[j]);
        asm volatile("" : "+r"(ff[j]), "+r"(fg[j])); }
      asm volatile("wgmma.wait_group.sync.aligned 1;" ::: "memory"); fence_regs(acc);
      uint32_t o[16];
#pragma unroll
      for (int j = 0; j < 16; j++) o[j] = pack_f16(acc[2 * j], acc[2 * j + 1]);
#pragma unroll
      for (int j = 0; j < 6; j++) {
        const uint32_t m = o[j] & 0x7FFF7FFFu; mq = __vmaxu2(mq, m);
        o[j] = (__viaddmax_s16x2(m, fg[j], 0) & 0xFFF8FFF8u) | ff[j] | (o[j] & 0x80008000u); }
      const uint32_t qs = sb + (b < 2 ? OFF_P2 : OFF_SA - 16384) + b * 8192;
#pragma unroll
      for (int j = 0; j < 4; j++) stsm4((qs + frag) ^ (j << 5), o[4 * j], o[4 * j + 1], o[4 * j + 2], o[4 * j + 3]);
      proxy_fence();
      if (b == 5) { const uint32_t m = __reduce_max_sync(~0u, magr(mq)); if (lane == 0) sts32(sb + OFF_MISC + 16 + w * 4, m); }
      bar_sync(3, 128);
      if (t == 0) { if (b * 64 < nloc) tma_store(tmb + TM_Q, 0, node0 + b * 64, qs); if (b == 5) bulk_commit(); }
      __syncwarp();
      wg_wait0(); fence_regs(ac2);
#pragma unroll
      for (int j = 0; j < 16; j++) { o[j] = pack_f16(ac2[2 * j], ac2[2 * j + 1]); mp = hmag(mp, o[j]); }
      if (!(b & 5)) mbar_wait(sb + BAR_AX + b * 4);
      const uint32_t ps = sb + OFF_PT + b * 8192 + (b < 2 ? PTX : 0);
#pragma unroll
      for (int j = 0; j < 4; j++) stsm4((ps + frag) ^ (j << 5), o[4 * j], o[4 * j + 1], o[4 * j + 2], o[4 * j + 3]);
    }
    if (magr(mp) >= 0x7000) sts32(sb + OFF_MISC + 12, 1);
    __syncwarp();
    mbar_arrive(sb + BAR_BW, lane == 0);
    asm volatile("setmaxnreg.dec.sync.aligned.u32 32;");
    if (w == 0) {
      STAMP(18);
      uint32_t mv[4]; lds128(mv, sb + OFF_MISC + 16);
      const uint32_t mx = max(max(mv[0], mv[1]), max(mv[2], mv[3]));
      bulk_wait();
      mbar_arrive(sb + BAR_QR, lane == 0);
      mbar_wait(sb + BAR_XA);
      STAMP(19);
      if (lane == 0) grid_signal(p.cnt, nloc > 0 && (mx >= 0x7BF0 || mx < 0x1400));
      if (grid_wait(p.cnt, c0)) sts32(sb + OFF_MISC + 8, 1);
      STAMP(20);
      __syncwarp();
      mbar_arrive(sb + BAR_QP, lane == 0);
    }
    if (w == 1) {
      __nanosleep(PF0NS);
#pragma unroll 1
      for (int i = 0; i < PFN; i++) { if (lane == 0) prefetch_e(i); __nanosleep(PFNS); }
    }
    bar_sync(3, 128);
    if (t == 0) { mbar_expect(sb + BAR_U, 16384); tma_load(sb + OFF_W, tmb + TM_WH, 0, sb + BAR_U); tma_load(sb + OFF_W + 8192, tmb + TM_WH, 64, sb + BAR_U); }
    mbar_wait(sb + BAR_U);
    uint32_t mh = 0;
#pragma unroll 1
    for (int i = t; i < 512; i += 128) { uint32_t v[4]; const uint32_t a = sb + OFF_W + i * 16;
      lds128(v, a); sts128(a, hhalf(v[0]), hhalf(v[1]), hhalf(v[2]), hhalf(v[3]));
      lds128(v, a + 8192); sts128(a + 8192, b2h(v[0], .5f), b2h(v[1], .5f), b2h(v[2], .5f), b2h(v[3], .5f));
      mh = mag2(mag2(mag2(mag2(mh, v[0]), v[1]), v[2]), v[3]); }
    if (wbad(__reduce_max_sync(~0u, magr(mh)), 0x4700)) sts32(sb + OFF_MISC + 12, 1);
    proxy_fence();
    __syncwarp();
    mbar_arrive(sb + BAR_WH, lane == 0);
    return;
  }

  auto put = [&](uint32_t x, uint32_t bv, uint32_t eb, uint32_t skip) {
    asm volatile("{.reg .pred p; setp.eq.b32 p, %0, 0;\n @p st.shared.u32 [%1], %3;\n @p st.shared.u16 [%2], %4;}"
      :: "r"(skip), "r"(sb + OFF_TE + x * 2), "r"(sb + OFF_TS + x), "r"(mad16(bv, 0x2000u, eb)), "h"((uint16_t)bv) : "memory");
  };
  if (tid == 320) {
    mbar_init(sb + BAR_W, 1);
    asm volatile("fence.mbarrier_init.release.cluster;" ::: "memory");
    mbar_expect(sb + BAR_W, 2 * 8192 + 2304);
    tma_load(sb + OFF_W, tmb + TM_WE, 64, sb + BAR_W); tma_load(sb + OFF_W + 8192, tmb + TM_WE, 0, sb + BAR_W);
    bulk_load(sb + OFF_WS, p.we + 128 * 64, 2176, sb + BAR_W); bulk_load(sb + OFF_WS + 2176, p.wx, 128, sb + BAR_W);
  }
  if (tid == 288) {
#pragma unroll
    for (int a = BAR_SRC; a < BAR_END; a += 8) if (a != BAR_W) mbar_init(sb + a, a == BAR_WH || a == BAR_PS || a == BAR_EP || a == BAR_BW ? 4 : a == BAR_XA ? 11 : 1);
    asm volatile("fence.mbarrier_init.release.cluster;" ::: "memory");
    asm volatile("prefetch.tensormap [%0];" :: "l"(tmb + TM_XA)); asm volatile("prefetch.tensormap [%0];" :: "l"(tmb + TM_H));
    asm volatile("prefetch.tensormap [%0];" :: "l"(tmb + TM_XB)); asm volatile("prefetch.tensormap [%0];" :: "l"(tmb + TM_Q));
  }
  {
    if (tid < 144) sts128(sb + OFF_CNT + tid * 16, 0, 0, 0, 0);
    else if (tid <= 144 + G) sts32(sb + OFF_BC + (tid - 144) * 4, ((tid - 144) & 31) * 4);
    const uint32_t sp = (p.N + cta) * 0x10001u, em = first_node(G);
    if (wid < 7) {
#pragma unroll
      for (int i = 0; i < 4; i++) sts128(sb + OFF_TS + tid * 16 + i * 3584, sp, sp, sp, sp);
    }
    static_assert(SCAP * 32 == 4 * 3584, "fill");
#pragma unroll 1
    for (int i = n4 + tid; i < 1536; i += 384) sts128(sb + OFF_DST + i * 16, em, em, em, em);
    if (tid == 321) sts128(sb + OFF_MISC, 0, 0, p.force_slow, 0);
  }
  bar_arrive(6, NTHR);
  bar_sync(0, 384);
  uint32_t ep, tag, eb0;
  auto get_tag = [&]() { mbar_wait(sb + BAR_EP); ep = lds32(sb + OFF_MISC + 32); tag = (1 + ep % 3) << 30; eb0 = ealo - (tag >> 11); };
  if (wid == 11) {
    trap_if(sb != (uint32_t)__cvta_generic_to_shared(smraw));
#pragma unroll 1
    for (int k = 0; k < 3; k++) { const int nb = max(0, min(8192, n4 * 16 - k * 8192));
      mbar_wait(sb + BAR_DST + (k == 0 ? S0 : k == 1 ? S1 : S2) * 8);
      if (lane == 0) { mbar_expect(sb + BAR_SRC + k * 8, nb);
        if (nb) bulk_load(sb + OFF_SRCI + k * 8192, (const char*)(p.src + e0) + k * 8192, nb, sb + BAR_SRC + k * 8); } }
    get_tag();
    mbar_wait(sb + BAR_PS);
    bar_sync(12, 384);
    if (lane == 0) { tma_store(tmb + TM_XA, cta * 64, 0, sb + OFF_SA); bulk_commit(); }
    __syncwarp();
    uint32_t xm = 0;
#pragma unroll
    for (int k = 0; k < 5; k++) xm |= (lds32(sb + OFF_BC + min(lane + 32 * k, G - 1) * 4) >= (64 << 9) && lane + 32 * k < G) << k;
    auto ext_send = [&](int pl) {
      uint32_t x = xm;
      for (uint32_t m; (m = __ballot_sync(~0u, x));) {
        const uint32_t l = __ffs(m) - 1, j = l + 32 * (__ffs(__shfl_sync(~0u, x, l)) - 1);
        if (lane == l) x &= x - 1;
        const uint32_t e = min(lds16(sb + OFF_AX + j * 128 + ((4 * l + 2 * lane) & 126)), 6143u);
        st_ext(p.xe + (j * G + cta) * 64 + pl * 32 + lane, pl ? lds32(sb + OFF_SRCI + e * 4) + tag + (e << 16) : (lds32(sb + OFF_DST + e * 4) & 511) | (lds32(sb + OFF_BC + j * 4) & ~511u), ep);
      }
    };
    ext_send(0);
    proxy_fence();
    __syncwarp();
    if (lane == 0) { bulk_wait(); hint_signal(p.sent); mbar_arrive(sb + BAR_AW); STAMP(16); }
    __syncwarp();
    mbar_wait(sb + BAR_SRC); mbar_wait(sb + BAR_SRC + 8); mbar_wait(sb + BAR_SRC + 16);
    ext_send(1);
    mbar_arrive(sb + BAR_AX, lane == 0);
    bar_sync(13, 384);
    if (B_HOLD) mbar_wait(sb + BAR_HA);
    if (lane == 0) {
#pragma unroll 1
      for (int r = 0; r < G; r += BROWS) { tma_store(tmb + TM_XB, cta * 64, r, sb + OFF_SB + r * 256); bulk_commit(); bulk_wait(); }
      hint_signal(p.sent + 32);
      mbar_arrive(sb + BAR_BS);
      STAMP(17);
    }
    __syncwarp();
    hint_wait(p.sent + 32, ep * G, s0_);
    mbar_arrive(sb + BAR_HB, lane == 0);
    STAMP(21);
    bar_sync(1, 384);
    if (!__shfl_sync(~0u, lds32(sb + OFF_MISC + 8), 0)) {
      const uint32_t nx = __shfl_sync(~0u, lds32(sb + OFF_MISC + 4), 0);
      for (uint32_t k = 0; k < nx; k += 32) {
        const uint32_t x = lds32(sb + OFF_EXT + min(k + lane, nx - 1) * 4), y = ext_get(p.xe + (cta * G + ((x >> 9) & 255)) * 64 + 32 + ((x >> 17) & 31), ep);
        put(lds32(sb + OFF_CNT + (x & 511) * 4) + (x >> 22) * 16, y, eb0 + ((x >> 9) & 255) * p.EPC * 32, 0);
      }
    }
    __syncwarp();
  } else {
    STAMP(15);
    {
      uint32_t d[4 * NCH], jj[4 * NCH], rr[4 * NCH];
      auto count = [&](int k) {
        mbar_wait(sb + BAR_DST + k * 8);
        lds128(d + 4 * k, sb + OFF_DST + (tid + NWK * k) * 16);
#pragma unroll
        for (int i = 4 * k; i < 4 * k + 4; i++) { jj[i] = d[i] * p.magic; rr[i] = atoms_add(__dp4a(jj[i], 0x04000000u, sb + OFF_BC), 0x202u); }
      };
      auto place = [&](int k) {
#pragma unroll
        for (int i = 4 * k; i < 4 * k + 4; i++) {
          const uint32_t o = __dp4a(jj[i], 0x80000000u, rr[i] & 0x807Eu);
          d[i] = (d[i] & 511) | (tag >> 16);
          asm("{.reg .pred p; setp.ge.u32 p, %1, 0x8000; @p add.u32 %0, %2, %3;}" : "+r"(d[i]) : "r"(o), "r"(tid * 4), "r"(NWK * k * 4 + (i & 3)));
          sts16(sb + OFF_SA + o, d[i]); jj[i] = __viaddmin_u32(o, o, G * 256);
        }
      };
      count(0); STAMP(1); count(1); get_tag(); place(0); count(2); place(1); count(3); place(2);
      if (wid < 4) { count(4); place(3); place(4); } else place(3);
      proxy_fence();
      bar_arrive(12, 384);
      STAMP(2);
      mbar_wait(sb + BAR_PS);
      mbar_wait(sb + BAR_SRC); mbar_wait(sb + BAR_SRC + 8); mbar_wait(sb + BAR_SRC + 16);
      STAMP(12);
#pragma unroll
      for (int k = 0; k < NCH; k++) lds128(d + 4 * k, sb + OFF_SRCI + (tid + NWK * k) * 16);
      const uint32_t tb = tag + (tid << 18);
#pragma unroll
      for (int i = 0; i < 4 * NCH; i++) if (i < 4 * NCH - 4 || wid < 4) sts32(sb + OFF_SB + jj[i], d[i] + tb + ((NWK * (i >> 2) * 4 + (i & 3)) << 16));
      proxy_fence();
      bar_sync(13, 384);
      STAMP(3);
    }
    const uint32_t rot = (lane + cta) & 31;
    uint32_t pk[12], r0[12], r1[12];
    const uint32_t cb = sb + OFF_CNT - (tag >> 14);
    {
      const uint32_t* xa = (const uint32_t*)(p.xa + (cta * G + wid) * 8) + rot;
      if (wid < 8) { const uint32_t e_ = ealo + epad * 32;
#pragma unroll
        for (int i = 0; i < 7; i++) sts128(sb + OFF_TE + tid * 16 + i * 4096, e_, e_, e_, e_); }
      static_assert(SCAP * 64 == 7 * 4096, "fill");
      if (wid == 10) { hint_wait(p.sent, ep * G, s0_); mbar_arrive(sb + BAR_HA, lane == 0); }
      mbar_wait(sb + BAR_HA);
      STAMP(14);
      uint32_t all;
      for (int spin = 0;; spin++) {
        uint32_t st = 0; all = ~0u;
#pragma unroll
        for (int k = 0; k < 12; k++) asm volatile("ld.relaxed.gpu.global.u32 %0, [%1];" : "=r"(pk[k]) : "l"(xa + k * 352) : "memory");
#pragma unroll
        for (int k = 0; k < 12; k++) { st |= pk[k] ^ (tag | (tag >> 16)); all &= pk[k]; }
        if (!__any_sync(~0u, st & 0xC000C000u)) break;
        trap_if(spin > 2000000);
      }
      if (wid == 0) STAMP(22);
      uint32_t xm = 0; uint2 xv;
      auto xadr = [&]() { return p.xe + (cta * G + wid + 11 * (__ffs(xm) - 1)) * 64 + lane; };
      if (!(__shfl_sync(~0u, all, 31) & 0x2000000u)) {
#pragma unroll
        for (int k = 0; k < 12; k++) xm |= (~pk[k] >> 25 & 1) << k;
        xm = __shfl_sync(~0u, xm, 31);
        xv = ld_poll2(xadr());
      }
#pragma unroll
      for (int k = 0; k < 12; k++) { r0[k] = atoms_add(mad16(pk[k], 0x0004u, cb), 16); r1[k] = atoms_add(mad16(pk[k], 0x0400u, cb), 16); }
      mbar_arrive(sb + BAR_XA, lane == 0);
      for (; xm; xm &= xm - 1) {
        if (__any_sync(~0u, xv.y != ep)) xv.x = ext_get(xadr(), ep);
        const uint32_t cn = xv.x >> 9, n = xv.x & 511;
        if (cn > 96) sts32(sb + OFF_MISC + 8, 1);
        else if (lane < cn - 64) {
          const uint32_t r = atoms_add(sb + OFF_CNT + n * 4, 16), idx = atoms_add(sb + OFF_MISC + 4, 1);
          if (idx < 256) sts32(sb + OFF_EXT + idx * 4, n | ((wid + 11 * (__ffs(xm) - 1)) << 9) | (lane << 17) | (min(r >> 4, 255u) << 22));
          else sts32(sb + OFF_MISC + 8, 1);
        }
        xv.y = ~ep;
        __syncwarp();
      }
    }
    STAMP(4);
    const uint2* xb = (const uint2*)(p.xb + (cta * G + wid) * 16) + rot;
    uint2 vb[12];
    auto bload_ = [&]() {
#pragma unroll
      for (int k = 0; k < 12; k++) { vb[k].x = vb[k].y = tag;
        asm volatile("{.reg .pred p; setp.eq.u32 p, %3, 0; @p ld.relaxed.gpu.global.v2.u32 {%0, %1}, [%2];}" : "+r"(vb[k].x), "+r"(vb[k].y) : "l"(xb + k * 352), "r"(pk[k] & 0x200u) : "memory"); }
    };
    uint32_t early = 1;
    if (wid >= 6) { bar_arrive(11, NWK); mbar_wait(sb + BAR_HB); }
    else asm volatile("{.reg .pred p; mbarrier.test_wait.parity.shared::cta.b64 p, [%1], 0; vote.sync.all.pred p, p, -1; selp.u32 %0, 1, 0, p;}" : "=r"(early) : "r"(sb + BAR_HB) : "memory");
    if (early) bload_();
    if (wid < 6) {
      uint32_t ca[2], ky[2], dr[2], sq[2], ps[4];
#pragma unroll
      for (int i = 0; i < 2; i++) { ca[i] = sb + OFF_CNT + ((node0 + tid + 192 * i) & 511) * 4; lds64(ps[2 * i], ps[2 * i + 1], sb + OFF_POS + (tid + 192 * i) * 8); ps[2 * i + 1] |= (tid + 192 * i) << 16; }
      bar_sync(11, NWK);
      STAMP(5);
#pragma unroll
      for (int i = 0; i < 2; i++) ky[i] = (lds32(ca[i]) + 16) >> 5;
      if (max(ky[0], ky[1]) > 31) sts32(sb + OFF_MISC + 8, 1);
#pragma unroll
      for (int i = 0; i < 2; i++) { ky[i] = min(ky[i], 31u); dr[i] = atoms_add(sb + OFF_DH + ky[i] * 4, 1); }
      bar_sync(10, 192);
      const uint32_t hv = lds32(sb + OFF_DH + lane * 4);
      uint32_t inc = hv;
#pragma unroll
      for (int o = 1; o < 32; o <<= 1) asm("{.reg .pred p; .reg .b32 y; shfl.sync.down.b32 y|p, %0, %1, 31, -1; @p add.u32 %0, %0, y;}" : "+r"(inc) : "r"(o));
#pragma unroll
      for (int i = 0; i < 2; i++) {
        const uint32_t pos = __shfl_sync(~0u, inc - hv, ky[i]) + dr[i];
        const uint32_t ak = (uint32_t)(0x1453AB297860ull >> ((pos >> 5) * 4)) & 15, l = (pos >> 3) & 3;
        sq[i] = (ak >> 2) * 16 + ((ak & 1) ? 3 - l : l) * 4 + (ak & 3);
        dr[i] = pos & 7;
        asm volatile("{.reg .pred p; setp.eq.u32 p, %2, 0; @p st.shared.u8 [%0], %1;}" :: "r"(sb + OFF_LEN + sq[i]), "r"(max(ky[i], 1u)), "r"(dr[i]) : "memory");
        sts64(sb + OFF_GP + sq[i] * 64 + dr[i] * 8, ps[2 * i], ps[2 * i + 1]);
      }
      bar_sync(10, 192);
      const uint32_t ln = lds32(sb + OFF_LEN + min(lane, 11) * 4), tot = __dp4a(ln, 0x01010101u, 0u);
      inc = tot;
#pragma unroll
      for (int o = 1; o < 16; o <<= 1) asm("{.reg .pred p; .reg .b32 y; shfl.sync.up.b32 y|p, %0, %1, 0, -1; @p add.u32 %0, %0, y;}" : "+r"(inc) : "r"(o));
      if (tid < 12) { sts32(sb + OFF_LEN + 64 + tid * 4, inc - tot); if (inc > SCAP) sts32(sb + OFF_MISC + 8, 1); }
#pragma unroll
      for (int i = 0; i < 2; i++) sts32(ca[i], __dp4a(__shfl_sync(~0u, ln, sq[i] >> 2), 0x00010101u >> (24 - 8 * (sq[i] & 3)), __shfl_sync(~0u, inc - tot, sq[i] >> 2)) * 32 + dr[i] * 2);
    }
    bar_sync(1, 384);
    STAMP(6);
    if (!__shfl_sync(~0u, lds32(sb + OFF_MISC + 8), 0)) {
      for (int spin = 0;; spin++) {
        if (!early) bload_();
        if (spin == 0) {
#pragma unroll
          for (int k = 0; k < 12; k++) { r0[k] += lds32(mad16(pk[k], 0x0004u, cb)); r1[k] += lds32(mad16(pk[k], 0x0400u, cb)); }
        }
        uint32_t st = 0;
#pragma unroll
        for (int k = 0; k < 12; k++) st |= (vb[k].x ^ tag) | (vb[k].y ^ tag);
        if (!__any_sync(~0u, st >> 30)) break;
        trap_if(spin > 2000000);
        early = 0;
      }
#pragma unroll
      for (int k = 0; k < 12; k++) {
        const uint32_t eb = eb0 + (wid + 11 * k) * p.EPC * 32;
        put(r0[k], vb[k].x, eb, pk[k] & 0x200u); put(r1[k], vb[k].y, eb, pk[k] & 0x2000000u);
      }
    }
  }
  STAMP(7);

  mbar_wait(sb + BAR_QR);
  asm volatile("setmaxnreg.inc.sync.aligned.u32 160;");
  uint32_t bad;
  {
    const uint32_t ring = sb + OFF_RING + wid * (NST * STG), p2 = sb + OFF_P2 + wid * 2048;
    uint32_t lens = __shfl_sync(~0u, lds32(sb + OFF_LEN + wid * 4), 0);
    uint32_t rem = __dp4a(lens, 0x20202020u, 0u);
    const uint32_t base = min(lds32(sb + OFF_LEN + 64 + wid * 4), SCAP);
    uint32_t a_s = sb + OFF_TS + base * 32 + (lane >> 3) * 8, a_e = sb + OFF_TE + base * 64 + (lane >> 1) * 4;
    uint32_t k0 = (uint32_t)(uint64_t)p.q + (((lane & 7) ^ ((lane >> 1) & 4)) << 4), k1 = k0 ^ 16, k2 = k0 ^ 32, k3 = k0 ^ 48, ke = ((lane ^ (lane >> 3)) & 1) << 4;
    uint32_t dst0 = ring + (lane >> 3) * 640 + (lane & 7) * 16;
    const uint32_t qhi = (uint32_t)((uint64_t)p.q >> 32), ehi = (uint32_t)((uint64_t)p.ea >> 32);
    uint32_t s0, s1, ev, to = 0, so = 0;
    auto tl_ = [&]() { lds64(s0, s1, a_s + to); asm volatile("ld.shared.u32 %0, [%1]; add.u32 %1, %1, 64;" : "=&r"(ev), "+r"(a_e) :: "memory"); to += 32; };
#define CPQ(LH, x, k, off) "dp2a." LH ".u32.u32 lo, " x ", 0x80000080, " k "; mov.b64 a, {lo, %7}; @p cp.async.cg.shared.global [%0+" #off "], [a], 16;\n"
#define CPE "or.b32 lo, %10, %11; mov.b64 a, {lo, %12}; @p cp.async.cg.shared.global [%0+512], [a], 16;\n"
#define CPA(BODY) asm volatile("{.reg .b32 lo; .reg .b64 a; .reg .pred p; setp.le.u32 p, %8, %9;\n" BODY "}" \
      :: "r"(dst0 + so), "r"(s0), "r"(s1), "r"(k0), "r"(k1), "r"(k2), "r"(k3), "r"(qhi), "r"(to), "r"(rem), "r"(ev), "r"(ke), "r"(ehi) : "memory")
#define CPQ4 CPQ("lo", "%1", "%3", 0) CPQ("hi", "%1", "%4", 128) CPQ("lo", "%2", "%5", 256) CPQ("hi", "%2", "%6", 384) "cp.async.commit_group;"
    auto issue = [&]() { CPA(CPE CPQ4); so = so == (NST - 1) * STG ? 0 : so + STG; };
    const int g = lane >> 2, qd = lane & 3;
    const uint32_t sw = ((lane >> 4) ^ (lane & 7)) << 4, fr = (lane & 15) * 128 + sw;
    uint32_t qa0 = ring + (g & 3) * 640 + qd * 128 + sw, qa1 = qa0 ^ 32, qa2 = qa0 ^ 64, qa3 = qa0 ^ 96;
    uint32_t eadr = ring + 512 + (g & 3) * 640 + qd * 32 + ((((lane >> 4) ^ g) & 1) << 4);
    uint32_t oh0 = g == 2 * qd ? 0x3C00u : g == 2 * qd + 1 ? 0x3C000000u : 0u, oh1 = oh0;
    uint32_t a_g = sb + OFF_GP + wid * 256 + lane * 2;
    uint32_t a_n = sb + OFF_GP + wid * 256 + (lane & 15) * 8 + 6;
    uint32_t a_p = ((lane & 8) ? p2 : sb + OFF_WD) + (lane & 7) * 128 + ((((lane >> 4) ^ lane) & 7) << 4);
    uint32_t a_w = sb + OFF_W3 + fr;
#define OPQ4(A, B, C, D, o) asm volatile("{st.volatile.shared.v4.b32 [%4], {%0,%1,%2,%3}; ld.volatile.shared.v4.b32 {%0,%1,%2,%3}, [%4];}" : "+r"(A), "+r"(B), "+r"(C), "+r"(D) : "r"(sb + OFF_SA + wid * 2048 + lane * 16 + o) : "memory")
    if (OPQ) { OPQ4(a_w, oh0, oh1, dst0, 0); OPQ4(qa0, qa1, qa2, qa3, 512); OPQ4(k0, k1, k2, k3, 1024); OPQ4(a_g, a_n, a_p, eadr, 1536); }
    uint32_t w3[16], wv[8], bp[16], sp[8], pq[16], sum[8], Y[16], M[16], own, ownp, dpk; uint16_t tl[16], th[16];
    float pacc = 0.f, chk = 0.f;
    auto wload = [&]() {
#pragma unroll
      for (int j = 0; j < 4; j++) ldsm4t(w3 + 4 * j, a_w ^ (j << 5));
      lds128(wv, sb + OFF_WX + (a_g & 6) * 16); lds128(wv + 4, sb + OFF_WX + 16 + (a_g & 6) * 16);
    };
    auto hload = [&](uint32_t (&hf)[16], uint32_t nd) {
      const uint32_t hrow = sb + OFF_H + nd * 128 + (((nd & 7) << 4) ^ ((a_g >> 1) & 16));
#pragma unroll
      for (int j = 0; j < 4; j++) ldsm4(hf + 4 * j, hrow ^ (j << 5));
      return hrow;
    };
    auto bload = [&](uint32_t o) {
#pragma unroll
      for (int j = 0; j < 4; j++) ldsm4t(bp + 4 * j, (a_p ^ (j << 5)) + o);
    };
    {
      const uint32_t an = sb + OFF_GP + wid * 256 + (lane & 7) * 8 + 6, n0 = lds16(an), n1 = lds16(an + 64), n2 = lds16(a_n + 128);
      auto prow = [&](uint32_t n, uint32_t c) { return sb + OFF_PT + n * 128 + (n < 128 ? PTX : 0) + (((n ^ c) & 7) << 4); };
      const uint32_t r0 = (lane & 8) ? prow(n0, lane >> 4) : a_p, r1 = prow(n1, lane >> 3), r2 = prow(n2, lane >> 4);
      mbar_wait(sb + BAR_BW);
#pragma unroll
      for (int j = 0; j < 4; j++) { ldsm4t(bp + 4 * j, r0 ^ (j << 5)); ldsm4(pq + 4 * j, r2 ^ (j << 5)); }
      ldsm4t(sp, r1); ldsm4t(sp + 4, r1 ^ 64);
    }
    wload();
    own = lds16(a_g) * 0x10001u;
    bar_sync(2, 384);
    if (__shfl_sync(~0u, lds32(sb + OFF_MISC + 8), 0)) rem = 0;
#pragma unroll
    for (int j = 0; j < 4; j++) stsm4((p2 + fr) ^ (j << 5), pq[4 * j], pq[4 * j + 1], pq[4 * j + 2], pq[4 * j + 3]);
    uint32_t sv[2 * NST];
#pragma unroll
    for (int i = 0; i < NST; i++) { tl_(); so = i * STG; CPA(CPE); sv[2 * i] = s0; sv[2 * i + 1] = s1; }
    mbar_wait(sb + BAR_QP);
    STAMP(13);
    bad = __shfl_sync(~0u, lds32(sb + OFF_MISC + 8), 0);
   if (!bad) {
#pragma unroll
    for (int i = 0; i < NST; i++) { to = 32 * i + 32; so = i * STG; s0 = sv[2 * i]; s1 = sv[2 * i + 1]; CPA(CPQ4); }
    so = 0;
    auto body = [&](auto MODE) {
      constexpr int mode = decltype(MODE)::value;
      uint32_t T[16], ef[4], q0, q1, x0, x1, x2; float e0_, e1_, cs[4];
      auto mu = [&](int j) {
#pragma unroll
        for (int i = 2 * j; i < 2 * j + 2; i++) asm volatile("{.reg .b16 l, h; mov.b32 {l, h}, %2; tanh.approx.f16 %0, l; tanh.approx.f16 %1, h;}" : "=h"(tl[i]), "=h"(th[i]) : "r"(Y[i])); };
      auto fi = [&](int j) {
#pragma unroll
        for (int i = 2 * j; i < 2 * j + 2; i++) asm volatile("{.reg .b32 t; mov.b32 t, {%2, %3}; fma.rn.f16x2 %0, %1, t, %1;}" : "=r"(M[i]) : "r"(Y[i]), "h"(tl[i]), "h"(th[i])); };
      auto ad = [&](int j) { asm volatile("add.rn.f16x2 %0, %0, %1; add.rn.f16x2 %0, %0, %2;" : "+r"(sum[j]) : "r"(M[2 * j]), "r"(M[2 * j + 1])); };
      auto he = [&](int j) { asm volatile("mma.sync.aligned.m16n8k16.row.col.f16.f16.f16.f16 {%0,%1}, {%2,%3,%4,%5}, {%6,%7}, {%0,%1};" : "+r"(T[2 * j]), "+r"(T[2 * j + 1]) : "r"(ef[0]), "r"(ef[1]), "r"(ef[2]), "r"(ef[3]), "r"(w3[2 * j]), "r"(w3[2 * j + 1])); };
      auto hs = [&](int j) { asm volatile("mma.sync.aligned.m16n8k16.row.col.f16.f16.f16.f16 {%0,%1}, {%2,%3,%4,%5}, {%6,%7}, {%8,%9};" : "=r"(Y[2 * j]), "=r"(Y[2 * j + 1]) : "r"(q0), "r"(q1), "r"(oh0), "r"(oh1), "r"(bp[2 * j]), "r"(bp[2 * j + 1]), "r"(T[2 * j]), "r"(T[2 * j + 1])); };
      auto hc = [&](int j) {
        if (j) asm volatile("mma.sync.aligned.m16n8k16.row.col.f32.f16.f16.f32 {%0,%1,%2,%3}, {%4,%5,%6,%7}, {%8,%9}, {%0,%1,%2,%3};" : "+f"(cs[0]), "+f"(cs[1]), "+f"(cs[2]), "+f"(cs[3]) : "r"(M[4 * j]), "r"(M[4 * j + 1]), "r"(M[4 * j + 2]), "r"(M[4 * j + 3]), "r"(wv[2 * j]), "r"(wv[2 * j + 1]));
        else asm volatile("mma.sync.aligned.m16n8k16.row.col.f32.f16.f16.f32 {%0,%1,%2,%3}, {%4,%5,%6,%7}, {%8,%9}, {%10,%10,%10,%10};" : "=f"(cs[0]), "=f"(cs[1]), "=f"(cs[2]), "=f"(cs[3]) : "r"(M[0]), "r"(M[1]), "r"(M[2]), "r"(M[3]), "r"(wv[0]), "r"(wv[1]), "f"(0.f)); };
      auto cv = [&](int i) { asm volatile("{.reg .b32 a, b; shl.b32 a, %0, 16; and.b32 b, %0, 0xFFFF0000; cvt.rn.f16x2.f32 %0, b, a;}" : "+r"(ef[i])); };
      auto un = [&]() { asm volatile("shl.b32 %0, %2, 16; and.b32 %1, %2, 0xFFFF0000;" : "=&f"(e0_), "=&f"(e1_) : "r"(dpk)); };
      auto ex0 = [&]() { asm volatile("prmt.b32 %0, %3, %4, 0x6420; prmt.b32 %1, %5, %6, 0x6420; prmt.b32 %2, %7, %8, 0x6420;" : "=&r"(x0), "=&r"(x1), "=&r"(x2) : "r"(T[0]), "r"(T[1]), "r"(T[2]), "r"(T[3]), "r"(T[4]), "r"(T[5])); };
      auto ex1 = [&]() { asm volatile("{.reg .b32 a, b; shl.b32 a, %2, 3; shl.b32 b, %3, 6; lop3.b32 a, %1, a, 0x38383838, 0xD8; lop3.b32 a, a, b, 0xC0C0C0C0, 0xD8; sub.rn.bf16x2 %0, %4, a;}" : "=r"(dpk) : "r"(x0), "r"(x1), "r"(x2), "r"(own)); };
      auto ex2 = [&]() { asm volatile("{.reg .b32 a, b, d, u; .reg .b16 l, h; shl.b32 a, %2, 16; and.b32 b, %2, 0xFFFF0000; cvt.rn.f16x2.f32 d, b, a; mul.rn.f16x2 %0, d, d; mov.b32 {l, h}, d; mov.b32 u, {h, h}; mul.rn.f16x2 %1, u, u;}" : "=&r"(q0), "=&r"(q1) : "r"(dpk)); };
      auto pf = [&]() { asm volatile("fma.rn.f32 %0, %1, %2, %0; fma.rn.f32 %0, %3, %4, %0;" : "+f"(pacc) : "f"(cs[0]), "f"(e0_), "f"(cs[2]), "f"(e1_)); };
#define FX(k) if (FM >> k & 1) asm volatile("pmevent 1;" ::: "memory")
      if (mode == 2) {
        hc(0); mu(3); fi(2); un(); ad(0); ad(1); mu(4); fi(3); hc(1); mu(5); fi(4); ad(2); mu(6); fi(5); ad(3); hc(2); mu(7); fi(6); fi(7); ad(4); ad(5); hc(3); ad(6); ad(7); pf();
        return;
      }
      asm volatile("cp.async.wait_group %0;" :: "n"(NST - 1) : "memory");
      __syncwarp();
      if (mode == 1) STAMP(8);
      ldsm4(ef, eadr + so); ldsm4(T, qa0 + so); ldsm4(T + 4, qa1 + so); ldsm4(T + 8, qa2 + so); ldsm4(T + 12, qa3 + so);
      tl_();
      if (mode == 1) {
        issue();
        cv(0); cv(1); cv(2); cv(3); ex0(); ex1(); ex2();
#pragma unroll
        for (int j = 0; j < 8; j++) { he(j); hs(j); }
        mu(0); mu(1); fi(0); mu(2); fi(1);
        return;
      }
      hc(0); mu(3); fi(2); un(); ad(0); ad(1);
      FX(0);
      mu(4); fi(3); cv(0); cv(1); cv(2); cv(3); ex0(); ex1();
      FX(1);
      he(0); he(1); hc(1); mu(5); fi(4); ex2(); ad(2);
      FX(2);
      hs(0); he(2); mu(6); fi(5); issue(); ad(3);
      FX(3);
      hs(1); he(3); hc(2); mu(7); fi(6);
      FX(4);
      hs(2); hs(3); he(4); he(5); mu(0); fi(7); ad(4); ad(5);
      FX(5);
      hc(3); hs(4); he(6); he(7); mu(1); fi(0); ad(6);
      FX(6);
      hs(5); hs(6); hs(7); mu(2); fi(1); ad(7); pf();
      FX(7);
    };
#pragma unroll
    for (int j = 0; j < 8; j++) sum[j] = 0;
    body(IC<1>());
    int cnt = (lens & 255) - 1;
#pragma unroll 1
    for (int t = 0; t < 8; t++) {
#pragma unroll 1
      for (; cnt > 0; cnt--) body(IC<0>());
      if (!(t & 1)) {
        ownp = own;
        if (t < 6) {
          a_g += 64; own = lds16(a_g) * 0x10001u;
          if (t == 0) {
#pragma unroll
            for (int j = 0; j < 8; j++) bp[2 * j + 1] = sp[j];
          } else bload((a_g & 16) ? (t & 4) * 256 : 0);
          lens >>= 8; cnt = 1;
          continue;
        }
        body(IC<2>()); t++;
        STAMP(9);
      }
      cnt = (lens & 255) - 1;
      { const uint32_t ng = __shfl_sync(~0u, ownp, (a_g >> 1) | 3) >> 16, c3 = (a_g >> 1) & 3;
        asm volatile("{.reg .pred p; setp.lt.u32 p, %2, %3; @p st.global.u16 [%0], %1;}" :: "l"(p.out + (size_t)p.N * 64 + (size_t)node0 * 3 + (ng * 3 + c3)), "h"((uint16_t)pack_bf16(bf_hi(ownp) + pacc, 0.f)), "r"(ng), "r"(c3 < 3 ? nloc : 0) : "memory"); }
      chk = fmaf(pacc, 0.f, chk); pacc = 0.f;
      if (t & 2) {
        uint32_t hf[16]; float acc[32];
        const uint32_t nd = lds16(a_n); a_n += 128;
        const uint32_t hrow = hload(hf, nd);
        const uint64_t b1 = DHI | ((sb + OFF_W) >> 4), b2_ = b1 + 512;
        mbar_wait(sb + BAR_WH);
        wg_fence();
        rs64h<0>(acc, sp[0], sum[0], sp[1], sum[1], b2_); rs64h<1>(acc, sp[2], sum[2], sp[3], sum[3], b2_ + 128); rs64h<1>(acc, sp[4], sum[4], sp[5], sum[5], b2_ + 256); rs64h<1>(acc, sp[6], sum[6], sp[7], sum[7], b2_ + 384);
        rs64b<1>(acc, hf[0], hf[1], hf[2], hf[3], b1); rs64b<1>(acc, hf[4], hf[5], hf[6], hf[7], b1 + 128); rs64b<1>(acc, hf[8], hf[9], hf[10], hf[11], b1 + 256); rs64b<1>(acc, hf[12], hf[13], hf[14], hf[15], b1 + 384);
        wg_commit(); wg_wait0(); fence_regs(acc);
        if (t == 7) STAMP(10);
        chk = fmaf(acc[0], 0.f, fmaf(acc[2], 0.f, chk));
        auto fin = [&](uint32_t x, float y0, float y1) { return u2(__hadd2(b2(x), b2(pack_bf16(silu_h(y0), silu_h(y1))))); };
#pragma unroll
        for (int j = 0; j < 4; j++) stsm4(hrow ^ (j << 5), fin(hf[4 * j], acc[8 * j], acc[8 * j + 1]), fin(hf[4 * j + 1], acc[8 * j + 2], acc[8 * j + 3]), fin(hf[4 * j + 2], acc[8 * j + 4], acc[8 * j + 5]), fin(hf[4 * j + 3], acc[8 * j + 6], acc[8 * j + 7]));
        __syncwarp();
        const uint32_t c8 = (a_g << 3) & 0x70;
#pragma unroll
        for (int j = 0; j < 4; j++) { uint32_t v[4]; const uint32_t n = __shfl_sync(~0u, nd, 4 * j + ((a_g >> 4) & 3)); lds128(v, sb + OFF_H + n * 128 + (((n << 4) ^ c8) & 0x70));
          asm volatile("{.reg .pred p; setp.lt.u32 p, %5, %6; @p st.global.v4.b32 [%0], {%1,%2,%3,%4};}" :: "l"((const char*)p.out + (size_t)node0 * 128 + (n * 128 + c8)), "r"(v[0]), "r"(v[1]), "r"(v[2]), "r"(v[3]), "r"(n), "r"(nloc) : "memory"); }
        wload();
      }
#pragma unroll
      for (int j = 0; j < 8; j++) { sp[j] = sum[j]; asm volatile("mov.b32 %0, 0;" : "=r"(sum[j])); }
    }
    asm volatile("{.reg .pred p, q; setp.neu.f32 p, %1, 0f00000000; setp.ne.or.u32 p, %2, 0, p; bar.red.or.pred q, 5, 384, p; selp.u32 %0, 1, 0, q;}" : "=r"(bad) : "f"(chk), "r"(lds32(sb + OFF_MISC + 12)) : "memory");
    STAMP(11);
   } else { asm volatile("cp.async.wait_all;" ::: "memory"); bar_sync(5, 384); }
  }
  if (bad) slow_path(p, wid, lane, node0, nloc);
}

}

typedef CUresult (*EncodeFn)(CUtensorMap*, CUtensorMapDataType, cuuint32_t, void*, const cuuint64_t*, const cuuint64_t*, const cuuint32_t*, const cuuint32_t*,
                             CUtensorMapInterleave, CUtensorMapSwizzle, CUtensorMapL2promotion, CUtensorMapFloatOOBfill);

extern "C" void kernel_launch(void* const* d_in, const int* in_sizes, int n_in, void* d_out, int out_size) {
  Params p; Maps maps;
  p.h = (const uint4*)d_in[0]; p.pos = (const uint16_t*)d_in[1]; p.ea = (const uint4*)d_in[2];
  p.src = (const int*)d_in[3]; p.dst = (const int*)d_in[4];
  p.we = (const uint16_t*)d_in[5]; p.wx = (const uint16_t*)d_in[6]; p.wh = (const uint16_t*)d_in[7];
  p.out = (uint16_t*)d_out;
  p.N = in_sizes[0] / 64; p.E = in_sizes[3];
  p.EPC = ((p.E + G * 4 - 1) / (G * 4)) * 4;
  p.magic = (uint32_t)(((uint64_t)G << 24) / (uint64_t)p.N);
  p.inv = (1ull << 56) / p.magic;
  const uint64_t ea0 = (uint64_t)d_in[2], ea1 = ea0 + (uint64_t)p.E * 32 - 1;
  p.force_slow = ((ea0 >> 32) != (ea1 >> 32)) || (ea0 & 31) || (p.E & 3);
  void* qp = nullptr;
  cudaGetSymbolAddress(&qp, g_q);
  p.q = (char*)qp;
  if (((uint64_t)p.q >> 32) != (((uint64_t)p.q + QBYTES) >> 32)) p.q += QBYTES;
  cudaGetSymbolAddress((void**)&p.cnt, g_cnt); cudaGetSymbolAddress((void**)&p.sent, g_sent); cudaGetSymbolAddress((void**)&p.xe, g_xe);
  cudaGetSymbolAddress((void**)&p.xa, g_xa); cudaGetSymbolAddress((void**)&p.xb, g_xb);
  void* fn = nullptr; cudaDriverEntryPointQueryResult qr;
  cudaGetDriverEntryPoint("cuTensorMapEncodeTiled", &fn, cudaEnableDefault, &qr);
  auto mk = [&](CUtensorMap* tm, void* base, int rows) {
    const cuuint64_t dim[2] = {64, (cuuint64_t)rows}, str[1] = {128}; const cuuint32_t bx[2] = {64, 64}, es[2] = {1, 1};
    ((EncodeFn)fn)(tm, CU_TENSOR_MAP_DATA_TYPE_BFLOAT16, 2, base, dim, str, bx, es, CU_TENSOR_MAP_INTERLEAVE_NONE, CU_TENSOR_MAP_SWIZZLE_128B,
                   CU_TENSOR_MAP_L2_PROMOTION_NONE, CU_TENSOR_MAP_FLOAT_OOB_FILL_NONE);
  };
  mk(&maps.m[TM_H / 128], d_in[0], p.N); mk(&maps.m[TM_WE / 128], d_in[5], 145); mk(&maps.m[TM_WH / 128], d_in[7], 128); mk(&maps.m[TM_Q / 128], p.q, p.N);
  for (int k = 0; k < 2; k++) {
    void* xp = (void*)(k ? p.xb : p.xa);
    const cuuint64_t dim[2] = {(cuuint64_t)G * 64, (cuuint64_t)G}, str[1] = {(cuuint64_t)G * (128 << k)}; const cuuint32_t bx[2] = {64, (cuuint32_t)(k ? BROWS : G)}, es[2] = {1, 1};
    ((EncodeFn)fn)(&maps.m[TM_XA / 128 + k], k ? CU_TENSOR_MAP_DATA_TYPE_UINT32 : CU_TENSOR_MAP_DATA_TYPE_UINT16, 2, xp, dim, str, bx, es, CU_TENSOR_MAP_INTERLEAVE_NONE,
                   CU_TENSOR_MAP_SWIZZLE_NONE, CU_TENSOR_MAP_L2_PROMOTION_NONE, CU_TENSOR_MAP_FLOAT_OOB_FILL_NONE);
  }
  cudaFuncSetAttribute(egnn_kernel, cudaFuncAttributeMaxDynamicSharedMemorySize, SMEM);
  egnn_kernel<<<G, NTHR, SMEM>>>(p, maps);
}
```

```cpp
#include <cuda_runtime.h>
#include <cuda_bf16.h>
#include <cuda_fp16.h>
#include <cuda.h>
#include <stdint.h>
#pragma nv_diag_suppress 549

#define PFN 8
#define PFNS 250
#define FM 0
#define OPQ 1
#define H0 0
#define HALL 0
#define PF0NS 500
#define HW 3
#define BROWS 132
#define B_HOLD 0
#define S0 0
#define S1 2
#define S2 3
namespace {

constexpr int G = 132;
constexpr int NTHR = 512, NWK = 352, NCH = 5;
constexpr int NST = 3, STG = 2560;
constexpr int SCAP = 448;

constexpr int OFF_H = 0;
constexpr int OFF_W = 49152;
constexpr int OFF_WD = OFF_W + 16384;
constexpr int OFF_W3 = OFF_WD + 1024;
constexpr int OFF_P2 = OFF_W3 + 2048;
constexpr int OFF_RING = OFF_P2 + 24576;
constexpr int OFF_TE = OFF_RING + 12 * NST * STG;
constexpr int OFF_TS = OFF_TE + SCAP * 64;
constexpr int OFF_GP = OFF_TS + SCAP * 32;
constexpr int OFF_WX = OFF_GP + 3072;
constexpr int OFF_LEN = OFF_WX + 128;
constexpr int OFF_MISC = OFF_LEN + 128;
constexpr int OFF_BAR = OFF_MISC + 48;
constexpr int SMEM = OFF_BAR + 256;
static_assert(SMEM <= 232448, "smem");
constexpr uint32_t sb = 1024;
constexpr int OFF_SRCI = OFF_TE;
constexpr int OFF_SB = OFF_RING, OFF_SA = OFF_SB + 34816, OFF_AX = OFF_SA + 32768, OFF_DST = OFF_H + 24576;
constexpr int OFF_PT = OFF_SB - 16384, PTX = OFF_AX - OFF_PT;
constexpr int OFF_WS = OFF_AX + 17408;
constexpr int OFF_BC = OFF_WS + 2304;
constexpr int OFF_CNT = OFF_P2 + 16384;
constexpr int OFF_DH = OFF_CNT + 2176;
constexpr int OFF_POS = OFF_DH + 128;
constexpr int OFF_EXT = OFF_POS + 3072;
static_assert(OFF_EXT + 1024 <= OFF_RING && OFF_BC + 544 <= OFF_TE && OFF_P2 % 1024 == 0 && OFF_SA % 1024 == 0 && SCAP * 64 >= 24576, "staging");
constexpr int BAR_DST = OFF_BAR, BAR_SRC = BAR_DST + 40, BAR_T = BAR_SRC + 24, BAR_W = BAR_T + 48, BAR_XA = BAR_W + 8, BAR_PS = BAR_XA + 8, BAR_AW = BAR_PS + 8,
              BAR_BW = BAR_AW + 8, BAR_QP = BAR_BW + 8, BAR_QR = BAR_QP + 8, BAR_HA = BAR_QR + 8, BAR_EP = BAR_HA + 8, BAR_AX = BAR_EP + 8, BAR_BS = BAR_AX + 8, BAR_HB = BAR_BS + 8, BAR_U = BAR_HB + 8, BAR_WH = BAR_U + 8, BAR_END = BAR_WH + 8;
constexpr uint32_t QBYTES = 8u << 20;

__device__ __align__(256) uint4 g_xa[G * G * 8];
__device__ __align__(256) uint4 g_xb[G * G * 16];
__device__ __align__(256) uint2 g_xe[G * G * 64];
__device__ __align__(256) uint4 g_q[2 * QBYTES / 16];
__device__ __align__(256) unsigned long long g_cnt;
__device__ __align__(256) uint32_t g_sent[64];
#define STAMP(k)

struct Maps { CUtensorMap m[6]; };
constexpr int TM_H = 0, TM_WE = 128, TM_WH = 256, TM_Q = 384, TM_XA = 512, TM_XB = 640;
struct Params {
  const uint4* h; const uint16_t* pos; const uint4* ea; const int* src; const int* dst;
  const uint16_t* we; const uint16_t* wx; const uint16_t* wh; uint16_t* out; char* q;
  unsigned long long* cnt; uint32_t* sent; const uint4* xa; const uint4* xb; uint2* xe;
  int N, E, EPC; uint32_t magic; int force_slow; unsigned long long inv;
};
template<int V> struct IC { static constexpr int value = V; };

#define R32(d) "+f"(d[0]),"+f"(d[1]),"+f"(d[2]),"+f"(d[3]),"+f"(d[4]),"+f"(d[5]),"+f"(d[6]),"+f"(d[7]),"+f"(d[8]),"+f"(d[9]),"+f"(d[10]),"+f"(d[11]),"+f"(d[12]),"+f"(d[13]),"+f"(d[14]),"+f"(d[15]),"+f"(d[16]),"+f"(d[17]),"+f"(d[18]),"+f"(d[19]),"+f"(d[20]),"+f"(d[21]),"+f"(d[22]),"+f"(d[23]),"+f"(d[24]),"+f"(d[25]),"+f"(d[26]),"+f"(d[27]),"+f"(d[28]),"+f"(d[29]),"+f"(d[30]),"+f"(d[31])
#define S32 "{%0,%1,%2,%3,%4,%5,%6,%7,%8,%9,%10,%11,%12,%13,%14,%15,%16,%17,%18,%19,%20,%21,%22,%23,%24,%25,%26,%27,%28,%29,%30,%31}"
#define DI __device__ __forceinline__

constexpr uint64_t DHI = ((uint64_t)(1024 >> 4) << 32) | (1ull << 62);
template<int SD> DI void rs64b(float (&d)[32], uint32_t a0, uint32_t a1, uint32_t a2, uint32_t a3, uint64_t db) {
  asm volatile("wgmma.mma_async.sync.aligned.m64n64k16.f32.bf16.bf16 " S32 ", {%32,%33,%34,%35}, %36, %37, 1, 1, 1;" : R32(d) : "r"(a0), "r"(a1), "r"(a2), "r"(a3), "l"(db), "n"(SD)); }
template<int SD> DI void rs64h(float (&d)[32], uint32_t a0, uint32_t a1, uint32_t a2, uint32_t a3, uint64_t db) {
  asm volatile("wgmma.mma_async.sync.aligned.m64n64k16.f32.f16.f16 " S32 ", {%32,%33,%34,%35}, %36, %37, 1, 1, 1;" : R32(d) : "r"(a0), "r"(a1), "r"(a2), "r"(a3), "l"(db), "n"(SD)); }
template<int SD> DI void ss64(float (&d)[32], uint64_t da, uint64_t db) {
  asm volatile("wgmma.mma_async.sync.aligned.m64n64k16.f32.bf16.bf16 " S32 ", %32, %33, %34, 1, 1, 0, 1;" : R32(d) : "l"(da), "l"(db), "n"(SD)); }
DI void trap_if(bool c) { asm volatile("{.reg .pred p; setp.eq.u32 p, %0, 0; @p bra.uni LT_%=; trap; LT_%=:}" :: "r"((uint32_t)c)); }
DI void wg_fence() { asm volatile("wgmma.fence.sync.aligned;" ::: "memory"); }
DI void wg_commit() { asm volatile("wgmma.commit_group.sync.aligned;" ::: "memory"); }
DI void wg_wait0() { asm volatile("wgmma.wait_group.sync.aligned 0;" ::: "memory"); }
DI void fence_regs(float (&d)[32]) { asm volatile("" : R32(d) :: "memory"); }
DI void proxy_fence() { asm volatile("fence.proxy.async.shared::cta;" ::: "memory"); }
DI uint64_t pol_first() { uint64_t r; asm("createpolicy.fractional.L2::evict_first.b64 %0, 1.0;" : "=l"(r)); return r; }
DI float tanh_ap(float x) { float y; asm("tanh.approx.f32 %0, %1;" : "=f"(y) : "f"(x)); return y; }
DI float silu_h(float y) { return fmaf(y, tanh_ap(y), y); }
DI uint32_t pack_bf16(float lo, float hi) { uint32_t r; asm("cvt.rn.bf16x2.f32 %0, %1, %2;" : "=r"(r) : "f"(hi), "f"(lo)); return r; }
DI uint32_t pack_f16(float lo, float hi) { uint32_t r; asm("cvt.rn.f16x2.f32 %0, %1, %2;" : "=r"(r) : "f"(hi), "f"(lo)); return r; }
DI float bf_lo(uint32_t v) { return __uint_as_float(v << 16); }
DI float bf_hi(uint32_t v) { return __uint_as_float(v & 0xFFFF0000u); }
DI uint32_t b2h(uint32_t v, float s) { return pack_f16(s * bf_lo(v), s * bf_hi(v)); }
DI void mbar_wait(uint32_t bar, uint32_t parity = 0) {
  asm volatile("{.reg .pred p; .reg .u32 t0, t1;\n"
    "mbarrier.try_wait.parity.shared::cta.b64 p, [%0], %1;\n @p bra.uni LD_%=;\n mov.u32 t0, %%clock;\n"
    "LW_%=: mbarrier.try_wait.parity.shared::cta.b64 p, [%0], %1;\n"
    "@p bra.uni LD_%=;\n mov.u32 t1, %%clock; sub.u32 t1, t1, t0; setp.lt.u32 p, t1, 0x80000000;\n @p bra.uni LW_%=;\n trap;\n LD_%=:}" :: "r"(bar), "r"(parity) : "memory");
}
DI void mbar_arrive(uint32_t bar, int p = 1) { asm volatile("{.reg .pred p; setp.ne.b32 p, %1, 0; @p mbarrier.arrive.shared::cta.b64 _, [%0];}" :: "r"(bar), "r"(p) : "memory"); }
DI void bar_sync(int id, int n) { asm volatile("bar.sync %0, %1;" :: "r"(id), "r"(n) : "memory"); }
DI void bar_arrive(int id, int n) { asm volatile("bar.arrive %0, %1;" :: "r"(id), "r"(n) : "memory"); }
DI __nv_bfloat162 b2(uint32_t v) { return *(__nv_bfloat162*)&v; }
DI uint32_t u2(__nv_bfloat162 v) { return *(uint32_t*)&v; }
DI uint32_t hsq(uint32_t v) { return u2(__hmul2(b2(v), b2(v))); }
DI uint32_t hsub(uint32_t a, uint32_t b) { return u2(__hsub2(b2(a), b2(b))); }
DI uint32_t hhalf(uint32_t v) { return u2(__hmul2(b2(v), __floats2bfloat162_rn(0.5f, 0.5f))); }
DI uint32_t mag2(uint32_t m, uint32_t v) { return __vmaxu2(m, v & 0x7FFF7FFFu); }
DI uint32_t hmag(uint32_t m, uint32_t v) { const __half2 r = __hmax2(*(const __half2*)&m, __habs2(*(const __half2*)&v)); return *(const uint32_t*)&r; }
DI uint32_t magr(uint32_t m) { return max(m & 0xFFFF, m >> 16); }
DI void sts128(uint32_t a, uint32_t x, uint32_t y, uint32_t z, uint32_t w) { asm volatile("st.shared.v4.u32 [%0], {%1,%2,%3,%4};" :: "r"(a), "r"(x), "r"(y), "r"(z), "r"(w) : "memory"); }
DI void sts64(uint32_t a, uint32_t x, uint32_t y) { asm volatile("st.shared.v2.u32 [%0], {%1,%2};" :: "r"(a), "r"(x), "r"(y) : "memory"); }
DI void sts32(uint32_t a, uint32_t x) { asm volatile("st.shared.u32 [%0], %1;" :: "r"(a), "r"(x) : "memory"); }
DI void sts16(uint32_t a, uint32_t x) { asm volatile("st.shared.u16 [%0], %1;" :: "r"(a), "h"((uint16_t)x) : "memory"); }
DI void lds128(uint32_t* v, uint32_t a) { asm volatile("ld.shared.v4.u32 {%0, %1, %2, %3}, [%4];" : "=r"(v[0]), "=r"(v[1]), "=r"(v[2]), "=r"(v[3]) : "r"(a) : "memory"); }
DI void lds64(uint32_t& x, uint32_t& y, uint32_t a) { asm volatile("ld.shared.v2.u32 {%0, %1}, [%2];" : "=r"(x), "=r"(y) : "r"(a) : "memory"); }
DI uint32_t lds32(uint32_t a) { uint32_t x; asm volatile("ld.shared.u32 %0, [%1];" : "=r"(x) : "r"(a) : "memory"); return x; }
DI uint32_t lds16(uint32_t a) { uint32_t x; asm volatile("ld.shared.u16 %0, [%1];" : "=r"(x) : "r"(a) : "memory"); return x; }
DI uint32_t atoms_add(uint32_t a, uint32_t v) { uint32_t r; asm volatile("atom.shared.add.u32 %0, [%1], %2;" : "=r"(r) : "r"(a), "r"(v) : "memory"); return r; }
DI void bulk_load(uint32_t dst, const void* src, uint32_t bytes, uint32_t bar) {
  asm volatile("cp.async.bulk.shared::cluster.global.mbarrier::complete_tx::bytes.L2::cache_hint [%0], [%1], %2, [%3], %4;" :: "r"(dst), "l"(src), "r"(bytes), "r"(bar), "l"(pol_first()) : "memory"); }
DI void bulk_store(void* dst, uint32_t src, uint32_t bytes) { asm volatile("cp.async.bulk.global.shared::cta.bulk_group [%0], [%1], %2;" :: "l"(dst), "r"(src), "r"(bytes) : "memory"); }
DI void mbar_expect(uint32_t bar, uint32_t bytes) { asm volatile("mbarrier.arrive.expect_tx.shared::cta.b64 _, [%0], %1;" :: "r"(bar), "r"(bytes) : "memory"); }
DI void mbar_init(uint32_t bar, int n) { asm volatile("mbarrier.init.shared::cta.b64 [%0], %1;" :: "r"(bar), "r"(n) : "memory"); }
DI void tma_load(uint32_t dst, uint64_t tm, int row, uint32_t bar) {
  asm volatile("cp.async.bulk.tensor.2d.shared::cluster.global.mbarrier::complete_tx::bytes.L2::cache_hint [%0], [%1, {%3, %4}], [%2], %5;" :: "r"(dst), "l"(tm), "r"(bar), "r"(0), "r"(row), "l"(pol_first()) : "memory"); }
DI void tma_store(uint64_t tm, int col, int row, uint32_t src) {
  asm volatile("cp.async.bulk.tensor.2d.global.shared::cta.bulk_group [%0, {%2, %3}], [%1];" :: "l"(tm), "r"(src), "r"(col), "r"(row) : "memory"); }
DI void bulk_commit() { asm volatile("cp.async.bulk.commit_group;" ::: "memory"); }
DI void bulk_wait_read() { asm volatile("cp.async.bulk.wait_group.read 0;" ::: "memory"); }
DI uint2 ld_poll2(const void* a) { uint2 v; asm volatile("ld.relaxed.gpu.global.v2.u32 {%0, %1}, [%2];" : "=r"(v.x), "=r"(v.y) : "l"(a) : "memory"); return v; }
DI void st_ext(uint2* a, uint32_t v, uint32_t ep) { asm volatile("st.relaxed.gpu.global.v2.u32 [%0], {%1, %2};" :: "l"(a), "r"(v), "r"(ep) : "memory"); }
DI uint32_t ext_get(const uint2* a, uint32_t ep) { uint2 v; int spin = 0; do { v = ld_poll2(a); trap_if(++spin > 4000000); } while (__any_sync(~0u, v.y != ep)); return v.x; }
DI void bulk_wait() { asm volatile("cp.async.bulk.wait_group 0;" ::: "memory"); }
DI void grid_signal(unsigned long long* cnt, bool flag = false) {
  asm volatile("red.release.gpu.global.add.u64 [%0], %1;" :: "l"(cnt), "l"(flag ? (1ull << 44) + 1 : 1ull) : "memory"); }
DI bool grid_wait(unsigned long long* cnt, unsigned long long c0) {
  const unsigned long long M = (1ull << 44) - 1, target = ((c0 & M) / G + 1) * G;
  unsigned long long c; int spin = 0;
  do { asm volatile("ld.acquire.gpu.global.u64 %0, [%1];" : "=l"(c) : "l"(cnt) : "memory"); trap_if(++spin > 4000000); } while (__any_sync(~0u, (c & M) < target));
  return (c ^ c0) >> 44;
}
DI void hint_signal(uint32_t* c) { asm volatile("red.relaxed.gpu.global.add.u32 [%0], 1;" :: "l"(c) : "memory"); }
DI void hint_wait(const uint32_t* c, uint32_t target, uint32_t v) { int spin = 0;
  trap_if(target - __shfl_sync(~0u, v, 0) - 1 >= G);
  do { asm volatile("ld.relaxed.gpu.global.u32 %0, [%1];" : "=r"(v) : "l"(c) : "memory"); trap_if(++spin > 4000000); } while (__any_sync(~0u, (int)(v - target) < 0)); }
DI unsigned long long ld_cnt(const unsigned long long* cnt) { unsigned long long c; asm volatile("ld.relaxed.gpu.global.u64 %0, [%1];" : "=l"(c) : "l"(cnt)); return c; }
DI void stsm4(uint32_t a, uint32_t x, uint32_t y, uint32_t z, uint32_t w) { asm volatile("stmatrix.sync.aligned.m8n8.x4.shared.b16 [%0], {%1,%2,%3,%4};" :: "r"(a), "r"(x), "r"(y), "r"(z), "r"(w) : "memory"); }
DI void ldsm4(uint32_t* v, uint32_t a) { asm volatile("ldmatrix.sync.aligned.m8n8.x4.shared.b16 {%0,%1,%2,%3}, [%4];" : "=r"(v[0]), "=r"(v[1]), "=r"(v[2]), "=r"(v[3]) : "r"(a) : "memory"); }
DI void ldsm4t(uint32_t* v, uint32_t a) { asm volatile("ldmatrix.sync.aligned.m8n8.x4.trans.shared.b16 {%0,%1,%2,%3}, [%4];" : "=r"(v[0]), "=r"(v[1]), "=r"(v[2]), "=r"(v[3]) : "r"(a) : "memory"); }
DI uint32_t mad16(uint32_t x, uint32_t m, uint32_t c) { uint32_t r; asm("dp2a.lo.u32.u32 %0, %1, %2, %3;" : "=r"(r) : "r"(x), "r"(m), "r"(c)); return r; }
DI bool wbad(uint32_t m, uint32_t hi) { return m > hi || (m && m < 0x3980); }

__device__ __noinline__ void slow_path(const Params& p, int wid, int lane, int node0, int nloc) {
  const uint32_t ab = sb + OFF_P2 + wid * 8704;
  for (int i = lane; i < 32 * 68; i += 32) sts32(ab + i * 4, 0);
  __syncwarp();
  const uint32_t wdv = __ldg((const uint32_t*)(p.we + 128 * 64) + lane), wxv = __ldg((const uint32_t*)p.wx + lane);
  const int nb0 = node0 + wid * 32, cntn = max(0, min(32, nloc - wid * 32));
  auto dot = [&](uint32_t hv, const uint16_t* w, int K2, float& y0, float& y1) {
#pragma unroll 4
    for (int k = 0; k < K2; k++) {
      const uint32_t hk = __shfl_sync(~0u, hv, k), wa = __ldg((const uint32_t*)(w + 2 * k * 64) + lane), wb = __ldg((const uint32_t*)(w + (2 * k + 1) * 64) + lane);
      y0 = fmaf(bf_lo(hk), bf_lo(wa), fmaf(bf_hi(hk), bf_lo(wb), y0)); y1 = fmaf(bf_lo(hk), bf_hi(wa), fmaf(bf_hi(hk), bf_hi(wb), y1));
    }
  };
  auto silu = [](float x) { return x / (1.f + __expf(-x)); };
#pragma unroll 1
  for (int base = 0; base < p.E; base += 32) {
    const int e = base + lane;
    const uint32_t dl = e < p.E ? (uint32_t)(__ldg(p.dst + e) - nb0) : 0xFFFFFFFFu;
    uint32_t mk = __ballot_sync(~0u, dl < (uint32_t)cntn);
    while (mk) {
      const int l = __ffs(mk) - 1; mk &= mk - 1;
      const int ee = base + l, n = __shfl_sync(~0u, dl, l), s = __ldg(p.src + ee);
      const uint16_t *po = p.pos + (size_t)(nb0 + n) * 3, *pp = p.pos + (size_t)s * 3;
      const uint32_t dxy = hsub(__ldg(po) | (__ldg(po + 1) << 16), __ldg(pp) | (__ldg(pp + 1) << 16)), dz = hsub(__ldg(po + 2), __ldg(pp + 2));
      const uint32_t sq = hsq(dxy); const float d2 = bf_lo(sq) + bf_hi(sq) + bf_lo(hsq(dz));
      float y0 = d2 * bf_lo(wdv), y1 = d2 * bf_hi(wdv);
      dot(__ldg((const uint32_t*)(p.h + (size_t)(nb0 + n) * 8) + lane), p.we, 32, y0, y1);
      dot(__ldg((const uint32_t*)(p.h + (size_t)s * 8) + lane), p.we + 64 * 64, 32, y0, y1);
      dot(__ldg((const uint32_t*)(p.ea + (size_t)ee * 2) + (lane & 7)), p.we + 129 * 64, 8, y0, y1);
      const uint32_t mm = pack_bf16(silu(y0), silu(y1));
      float c = bf_lo(mm) * bf_lo(wxv) + bf_hi(mm) * bf_hi(wxv);
#pragma unroll
      for (int o = 16; o; o >>= 1) c += __shfl_xor_sync(~0u, c, o);
      const uint32_t a = ab + n * 272;
      uint32_t x0, x1; lds64(x0, x1, a + lane * 8);
      sts64(a + lane * 8, __float_as_uint(__uint_as_float(x0) + bf_lo(mm)), __float_as_uint(__uint_as_float(x1) + bf_hi(mm)));
      if (lane < 3) { const float df = lane == 0 ? bf_lo(dxy) : lane == 1 ? bf_hi(dxy) : bf_lo(dz); sts32(a + 256 + lane * 4, __float_as_uint(fmaf(c, df, __uint_as_float(lds32(a + 256 + lane * 4))))); }
    }
  }
  __syncwarp();
#pragma unroll 1
  for (int n = 0; n < cntn; n++) {
    uint32_t x0, x1; lds64(x0, x1, ab + n * 272 + lane * 8);
    const uint32_t hv = __ldg((const uint32_t*)(p.h + (size_t)(nb0 + n) * 8) + lane);
    float y0 = 0.f, y1 = 0.f;
    dot(hv, p.wh, 32, y0, y1); dot(pack_bf16(__uint_as_float(x0), __uint_as_float(x1)), p.wh + 64 * 64, 32, y0, y1);
    ((uint32_t*)p.out)[(size_t)(nb0 + n) * 32 + lane] = u2(__hadd2(b2(hv), b2(pack_bf16(silu(y0), silu(y1)))));
    if (lane < 3) p.out[(size_t)p.N * 64 + (size_t)(nb0 + n) * 3 + lane] = (uint16_t)pack_bf16(bf_lo(__ldg(p.pos + (size_t)(nb0 + n) * 3 + lane)) + __uint_as_float(lds32(ab + n * 272 + 256 + lane * 4)), 0.f);
  }
}

__global__ void __launch_bounds__(NTHR, 1) egnn_kernel(const __grid_constant__ Params p, const __grid_constant__ Maps maps) {
  const uint64_t tmb = (uint64_t)&maps;
  extern __shared__ __align__(1024) unsigned char smraw[];
  const int tid = threadIdx.x, cta = blockIdx.x;
  const int e0 = cta * p.EPC, n4 = max(0, min(p.EPC, p.E - e0)) >> 2;
  STAMP(0);
  unsigned long long c0 = 0;
  uint32_t s0_ = 0;
  asm volatile("{.reg .pred p, q; setp.eq.u32 p, %4, 384; setp.eq.u32 q, %5, 320; @p ld.relaxed.gpu.global.u64 %0, [%2]; @q ld.relaxed.gpu.global.u32 %1, [%3];}"
    : "+l"(c0), "+r"(s0_) : "l"(p.cnt), "l"(p.sent + (tid & 32)), "r"(tid & 415), "r"(tid & 479));
  if (tid == NWK) {
#pragma unroll
    for (int k = 0; k < NCH; k++) mbar_init(sb + BAR_DST + k * 8, 1);
    asm volatile("fence.mbarrier_init.release.cluster;" ::: "memory");
#pragma unroll 1
    for (int k = 0; k < NCH; k++) { const int nb = max(0, min(NWK, n4 - k * NWK)) * 16;
      mbar_expect(sb + BAR_DST + k * 8, nb);
      if (nb) bulk_load(sb + OFF_DST + k * NWK * 16, (const char*)(p.dst + e0) + k * NWK * 16, nb, sb + BAR_DST + k * 8); }
  }
  const int lane = tid & 31, wid = __shfl_sync(~0u, tid >> 5, 0), w = wid & 3;

  auto first_node = [&](int c) { return (int)((c * p.inv + 0xFFFFFFFFull) >> 32); };
  const int node0 = first_node(cta), nloc = min(first_node(cta + 1), p.N) - node0;
  const uint32_t ealo = (uint32_t)(uint64_t)p.ea;
  const int epad = min(e0, p.E - 1);
  if (wid >= 12) {
    const int t = tid - 384;
    auto prefetch_e = [&](int i) {
      const uint32_t nb = (p.E / G) & ~15u;
      if (nb && i < PFN) asm volatile("cp.async.bulk.prefetch.L2.global [%0], %1;" :: "l"((const char*)p.ea + (size_t)(i * G + cta) * nb), "r"(nb) : "memory");
    };
    auto load_h = [&](int b) { mbar_expect(sb + BAR_T + b * 8, 8192); tma_load(sb + OFF_H + b * 8192, tmb + TM_H, node0 + b * 64, sb + BAR_T + b * 8); };
    uint32_t pv[9], ev = 0;
#pragma unroll
    for (int i = 0; i < 3; i++) { const uint16_t* pp = p.pos + (size_t)(node0 + t + 128 * i) * 3;
      pv[3 * i] = pv[3 * i + 1] = pv[3 * i + 2] = 0;
      asm volatile("{.reg .pred p; setp.lt.s32 p, %4, %5;\n @p ld.global.nc.u16 %0, [%3];\n @p ld.global.nc.u16 %1, [%3+2];\n @p ld.global.nc.u16 %2, [%3+4];}"
        : "+r"(pv[3 * i]), "+r"(pv[3 * i + 1]), "+r"(pv[3 * i + 2]) : "l"(pp), "r"(t + 128 * i), "r"(p.N - node0)); }
    asm volatile("{.reg .pred p; setp.lt.u32 p, %3, 8; @p ld.global.nc.u32 %0, [%1]; @p st.global.v4.u32 [%2], {%4, %4, %4, %4};}"
      : "+r"(ev) : "l"((const uint32_t*)(p.ea + (size_t)epad * 2) + t), "l"(p.q + (size_t)(p.N + cta) * 128 + t * 16), "r"(t), "r"(0xF700F700u) : "memory");
    c0 = __shfl_sync(~0u, c0, 0);
    {
      const uint32_t e = (uint32_t)((c0 & ((1ull << 44) - 1)) / G) + 1, tg = (1 + e % 3) << 30, v = ((tg >> 16) + 512 + (lane & 7) * 4) * 0x10001u;
      if (t == 0) sts32(sb + OFF_MISC + 32, e);
#pragma unroll
      for (int i = 0; i < 9; i++) sts128(sb + OFF_SA + t * 16 + i * 2048, v, v + 0x10001u, v + 0x20002u, v + 0x30003u);
      bar_sync(6, NTHR);
      mbar_arrive(sb + BAR_EP, lane == 0);
#pragma unroll
      for (int i = 0; i < 17; i++) sts128(sb + OFF_SB + t * 16 + i * 2048, tg, tg, tg, tg); }
    uint32_t mp = 0;
#pragma unroll
    for (int i = 0; i < 3; i++) { sts64(sb + OFF_POS + (t + 128 * i) * 8, pv[3 * i] | (pv[3 * i + 1] << 16), pv[3 * i + 2]); mp = mag2(mag2(mp, pv[3 * i] | (pv[3 * i + 1] << 16)), pv[3 * i + 2]); }
    proxy_fence();
    __syncwarp();
    mbar_arrive(sb + BAR_PS, lane == 0);
    mbar_wait(sb + BAR_W);
#pragma unroll
    for (int i = 0; i < 8; i += 4) { uint32_t v[16];
#pragma unroll
      for (int k = 0; k < 4; k++) lds128(v + 4 * k, sb + OFF_W + t * 16 + (i + k) * 2048);
#pragma unroll
      for (int k = 0; k < 4; k++) sts128(sb + OFF_W + t * 16 + (i + k) * 2048, hhalf(v[4 * k]), hhalf(v[4 * k + 1]), hhalf(v[4 * k + 2]), hhalf(v[4 * k + 3])); }
    {
      uint32_t v[4], u[4]; const int r = t >> 3, c = t & 7;
      lds128(v, sb + OFF_WS + 128 + t * 16); lds128(u, sb + OFF_WS + c * 16);
      const uint32_t x = lds32(sb + OFF_WS + 2176 + lane * 4);
      sts128(sb + OFF_W3 + r * 128 + ((c ^ (r & 7)) << 4), b2h(v[0], .5f), b2h(v[1], .5f), b2h(v[2], .5f), b2h(v[3], .5f));
      const float s = ((r & 1) || r == 6) ? 0.f : .5f;
      if (t < 64) sts128(sb + OFF_WD + r * 128 + ((c ^ r) << 4), b2h(u[0], s), b2h(u[1], s), b2h(u[2], s), b2h(u[3], s));
      if (t < 32) sts32(sb + OFF_WX + (t & 3) * 32 + (t >> 2) * 4, b2h(x, 1.f));
      const uint32_t m3 = __reduce_max_sync(~0u, magr(mag2(mag2(mag2(mag2(0, v[0]), v[1]), v[2]), v[3]))), md = __reduce_max_sync(~0u, magr(mag2(mag2(mag2(mag2(0, u[0]), u[1]), u[2]), u[3])));
      if (wbad(m3, 0x4000) || wbad(md, 0x4000) || wbad(__reduce_max_sync(~0u, magr(mag2(0, x))), 0x4700) || magr(mp) >= 0x4200 || magr(mag2(0, ev)) >= 0x4380) sts32(sb + OFF_MISC + 8, 1);
    }
    proxy_fence();
    if (w == 1) STAMP(23);
    if (w == 1) {
#pragma unroll 1
      for (int b = 0; b < HW; b++) { mbar_wait(sb + BAR_SRC + max(0, H0 + b) * 8); if (lane == 0) load_h(b); }
    }
    bar_sync(3, 128);
    STAMP(24);
    const uint32_t frag = (w * 16 + (lane & 15)) * 128 + (((lane >> 4) ^ (lane & 7)) << 4);
    uint32_t mq = 0; mp = 0;
#pragma unroll 1
    for (int b = 0; b < 6; b++) {
      float acc[32], ac2[32];
      const uint64_t da = DHI | (((sb + OFF_H) >> 4) + b * 512), db = DHI | ((sb + OFF_W) >> 4);
      const uint32_t v0 = lds16(sb + OFF_POS + b * 512 + w * 128 + lane * 2), v1 = lds16(sb + OFF_POS + 64 + b * 512 + w * 128 + lane * 2);
      mbar_wait(sb + BAR_T + b * 8);
      if (b == 0) STAMP(25);
      if (b == 5) STAMP(26);
      wg_fence();
      ss64<0>(acc, da, db); ss64<1>(acc, da + 2, db + 128); ss64<1>(acc, da + 4, db + 256); ss64<1>(acc, da + 6, db + 384);
      wg_commit();
      ss64<0>(ac2, da, db + 512); ss64<1>(ac2, da + 2, db + 640); ss64<1>(ac2, da + 4, db + 768); ss64<1>(ac2, da + 6, db + 896);
      wg_commit();
      if (b == 0) mbar_wait(sb + BAR_AW);
      if (t == 32) { if (HALL) { if (b == 0) for (int k = HW; k < 6; k++) load_h(k); } else if (b + HW < 6) load_h(b + HW); }
      __syncwarp();
      uint32_t ff[6], fg[6];
#pragma unroll
      for (int j = 0; j < 6; j++) { ff[j] = (__byte_perm((j & 1) ? v1 : v0, 0, 0x4140) >> (3 * (j >> 1))) & 0x00070007u; fg[j] = __vsub2(0x00040004u, ff[j]);
        asm volatile("" : "+r"(ff[j]), "+r"(fg[j])); }
      asm volatile("wgmma.wait_group.sync.aligned 1;" ::: "memory"); fence_regs(acc);
      uint32_t o[16];
#pragma unroll
      for (int j = 0; j < 16; j++) o[j] = pack_f16(acc[2 * j], acc[2 * j + 1]);
#pragma unroll
      for (int j = 0; j < 6; j++) {
        const uint32_t m = o[j] & 0x7FFF7FFFu; mq = __vmaxu2(mq, m);
        o[j] = (__viaddmax_s16x2(m, fg[j], 0) & 0xFFF8FFF8u) | ff[j] | (o[j] & 0x80008000u); }
      const uint32_t qs = sb + (b < 2 ? OFF_P2 : OFF_SA - 16384) + b * 8192;
#pragma unroll
      for (int j = 0; j < 4; j++) stsm4((qs + frag) ^ (j << 5), o[4 * j], o[4 * j + 1], o[4 * j + 2], o[4 * j + 3]);
      proxy_fence();
      if (b == 5) { const uint32_t m = __reduce_max_sync(~0u, magr(mq)); if (lane == 0) sts32(sb + OFF_MISC + 16 + w * 4, m); }
      bar_sync(3, 128);
      if (t == 0) { if (b * 64 < nloc) tma_store(tmb + TM_Q, 0, node0 + b * 64, qs); if (b == 5) bulk_commit(); }
      __syncwarp();
      wg_wait0(); fence_regs(ac2);
#pragma unroll
      for (int j = 0; j < 16; j++) { o[j] = pack_f16(ac2[2 * j], ac2[2 * j + 1]); mp = hmag(mp, o[j]); }
      if (!(b & 5)) mbar_wait(sb + BAR_AX + b * 4);
      const uint32_t ps = sb + OFF_PT + b * 8192 + (b < 2 ? PTX : 0);
#pragma unroll
      for (int j = 0; j < 4; j++) stsm4((ps + frag) ^ (j << 5), o[4 * j], o[4 * j + 1], o[4 * j + 2], o[4 * j + 3]);
    }
    if (magr(mp) >= 0x7000) sts32(sb + OFF_MISC + 12, 1);
    __syncwarp();
    mbar_arrive(sb + BAR_BW, lane == 0);
    asm volatile("setmaxnreg.dec.sync.aligned.u32 32;");
    if (w == 0) {
      STAMP(18);
      uint32_t mv[4]; lds128(mv, sb + OFF_MISC + 16);
      const uint32_t mx = max(max(mv[0], mv[1]), max(mv[2], mv[3]));
      bulk_wait();
      mbar_arrive(sb + BAR_QR, lane == 0);
      mbar_wait(sb + BAR_XA);
      STAMP(19);
      if (lane == 0) grid_signal(p.cnt, nloc > 0 && (mx >= 0x7BF0 || mx < 0x1400));
      if (grid_wait(p.cnt, c0)) sts32(sb + OFF_MISC + 8, 1);
      STAMP(20);
      __syncwarp();
      mbar_arrive(sb + BAR_QP, lane == 0);
    }
    if (w == 1) {
      __nanosleep(PF0NS);
#pragma unroll 1
      for (int i = 0; i < PFN; i++) { if (lane == 0) prefetch_e(i); __nanosleep(PFNS); }
    }
    bar_sync(3, 128);
    if (t == 0) { mbar_expect(sb + BAR_U, 16384); tma_load(sb + OFF_W, tmb + TM_WH, 0, sb + BAR_U); tma_load(sb + OFF_W + 8192, tmb + TM_WH, 64, sb + BAR_U); }
    mbar_wait(sb + BAR_U);
    uint32_t mh = 0;
#pragma unroll 1
    for (int i = t; i < 512; i += 128) { uint32_t v[4]; const uint32_t a = sb + OFF_W + i * 16;
      lds128(v, a); sts128(a, hhalf(v[0]), hhalf(v[1]), hhalf(v[2]), hhalf(v[3]));
      lds128(v, a + 8192); sts128(a + 8192, b2h(v[0], .5f), b2h(v[1], .5f), b2h(v[2], .5f), b2h(v[3], .5f));
      mh = mag2(mag2(mag2(mag2(mh, v[0]), v[1]), v[2]), v[3]); }
    if (wbad(__reduce_max_sync(~0u, magr(mh)), 0x4700)) sts32(sb + OFF_MISC + 12, 1);
    proxy_fence();
    __syncwarp();
    mbar_arrive(sb + BAR_WH, lane == 0);
    return;
  }

  auto put = [&](uint32_t x, int hi, uint32_t bv, uint32_t eb) {
    asm volatile("{.reg .pred p; setp.eq.b32 p, %0, 0;\n @p st.shared.u32 [%1], %3;\n @p st.shared.u16 [%2], %4;}"
      :: "r"(x & (0x8000u << 16 * hi)), "r"(sb + OFF_TE + mad16(x, 2 << 8 * hi, 0)), "r"(sb + OFF_TS + (hi ? x >> 16 : x & 0xFFFF)), "r"(mad16(bv, 0x2000u, eb)), "h"((uint16_t)bv) : "memory");
  };
  if (tid == 320) {
    mbar_init(sb + BAR_W, 1);
    asm volatile("fence.mbarrier_init.release.cluster;" ::: "memory");
    mbar_expect(sb + BAR_W, 2 * 8192 + 2304);
    tma_load(sb + OFF_W, tmb + TM_WE, 64, sb + BAR_W); tma_load(sb + OFF_W + 8192, tmb + TM_WE, 0, sb + BAR_W);
    bulk_load(sb + OFF_WS, p.we + 128 * 64, 2176, sb + BAR_W); bulk_load(sb + OFF_WS + 2176, p.wx, 128, sb + BAR_W);
  }
  if (tid == 288) {
#pragma unroll
    for (int a = BAR_SRC; a < BAR_END; a += 8) if (a != BAR_W) mbar_init(sb + a, a == BAR_WH || a == BAR_PS || a == BAR_EP || a == BAR_BW ? 4 : a == BAR_XA ? 11 : 1);
    asm volatile("fence.mbarrier_init.release.cluster;" ::: "memory");
    asm volatile("prefetch.tensormap [%0];" :: "l"(tmb + TM_XA)); asm volatile("prefetch.tensormap [%0];" :: "l"(tmb + TM_H));
    asm volatile("prefetch.tensormap [%0];" :: "l"(tmb + TM_XB)); asm volatile("prefetch.tensormap [%0];" :: "l"(tmb + TM_Q));
  }
  {
    if (tid < 144) { const uint32_t z = (tid >> 3) == 16 ? 0x8000u : 0u; sts128(sb + OFF_CNT + tid * 16, z, z, z, z); }
    else if (tid <= 144 + G) sts32(sb + OFF_BC + (tid - 144) * 4, ((tid - 144) & 31) * 4);
    const uint32_t sp = (p.N + cta) * 0x10001u, em = first_node(G);
    if (wid < 7) {
#pragma unroll
      for (int i = 0; i < 4; i++) sts128(sb + OFF_TS + tid * 16 + i * 3584, sp, sp, sp, sp);
    }
    static_assert(SCAP * 32 == 4 * 3584, "fill");
#pragma unroll 1
    for (int i = n4 + tid; i < 1536; i += 384) sts128(sb + OFF_DST + i * 16, em, em, em, em);
    if (tid == 321) sts128(sb + OFF_MISC, 0, 0, p.force_slow, 0);
  }
  bar_arrive(6, NTHR);
  bar_sync(0, 384);
  uint32_t ep, tag, eb0, pk[12], r0[12], r1[12], cb, early = 1;
  uint2 vb[12];
  const uint2* xb = (const uint2*)(p.xb + (cta * G + wid) * 16) + ((lane + cta) & 31);
  auto bload_ = [&]() {
#pragma unroll
    for (int k = 0; k < 12; k++) { vb[k].x = vb[k].y = tag;
      asm volatile("{.reg .pred p; setp.eq.u32 p, %3, 0; @p ld.relaxed.gpu.global.v2.u32 {%0, %1}, [%2];}" : "+r"(vb[k].x), "+r"(vb[k].y) : "l"(xb + k * 352), "r"(pk[k] & 0x8000u) : "memory"); }
  };
  auto get_tag = [&]() { mbar_wait(sb + BAR_EP); ep = lds32(sb + OFF_MISC + 32); tag = (1 + ep % 3) << 30; eb0 = ealo - (tag >> 11); };
  if (wid == 11) {
    trap_if(sb != (uint32_t)__cvta_generic_to_shared(smraw));
#pragma unroll 1
    for (int k = 0; k < 3; k++) { const int nb = max(0, min(8192, n4 * 16 - k * 8192));
      mbar_wait(sb + BAR_DST + (k == 0 ? S0 : k == 1 ? S1 : S2) * 8);
      if (lane == 0) { mbar_expect(sb + BAR_SRC + k * 8, nb);
        if (nb) bulk_load(sb + OFF_SRCI + k * 8192, (const char*)(p.src + e0) + k * 8192, nb, sb + BAR_SRC + k * 8); } }
    get_tag();
    mbar_wait(sb + BAR_PS);
    bar_sync(12, 384);
    if (lane == 0) { tma_store(tmb + TM_XA, cta * 64, 0, sb + OFF_SA); bulk_commit(); }
    __syncwarp();
    uint32_t xm = 0;
#pragma unroll
    for (int k = 0; k < 5; k++) xm |= (lds32(sb + OFF_BC + min(lane + 32 * k, G - 1) * 4) >= (64 << 9) && lane + 32 * k < G) << k;
    auto ext_send = [&](int pl) {
      uint32_t x = xm;
      for (uint32_t m; (m = __ballot_sync(~0u, x));) {
        const uint32_t l = __ffs(m) - 1, j = l + 32 * (__ffs(__shfl_sync(~0u, x, l)) - 1);
        if (lane == l) x &= x - 1;
        const uint32_t e = min(lds16(sb + OFF_AX + j * 128 + ((4 * l + 2 * lane) & 126)), 6143u);
        st_ext(p.xe + (j * G + cta) * 64 + pl * 32 + lane, pl ? lds32(sb + OFF_SRCI + e * 4) + tag + (e << 16) : (lds32(sb + OFF_DST + e * 4) & 511) | (lds32(sb + OFF_BC + j * 4) & ~511u), ep);
      }
    };
    if (lane == 0) { bulk_wait(); hint_signal(p.sent); STAMP(16); }
    __syncwarp();
    ext_send(0);
    proxy_fence();
    __syncwarp();
    mbar_arrive(sb + BAR_AW, lane == 0);
    bar_sync(13, 384);
    if (!B_HOLD && lane == 0) { tma_store(tmb + TM_XB, cta * 64, 0, sb + OFF_SB); bulk_commit(); }
    __syncwarp();
    ext_send(1);
    mbar_arrive(sb + BAR_AX, lane == 0);
    if (B_HOLD) mbar_wait(sb + (B_HOLD == 1 ? BAR_HA : BAR_XA));
    if (lane == 0) {
      bulk_wait();
#pragma unroll 1
      for (int r = B_HOLD ? 0 : BROWS; r < G; r += BROWS) { tma_store(tmb + TM_XB, cta * 64, r, sb + OFF_SB + r * 256); bulk_commit(); bulk_wait(); }
      hint_signal(p.sent + 32);
      mbar_arrive(sb + BAR_BS);
      STAMP(17);
    }
    __syncwarp();
    hint_wait(p.sent + 32, ep * G, s0_);
    mbar_arrive(sb + BAR_HB, lane == 0);
    STAMP(21);
  } else {
    STAMP(15);
    {
      uint32_t d[4 * NCH], jj[4 * NCH], rr[4 * NCH];
      auto count = [&](int k) {
        mbar_wait(sb + BAR_DST + k * 8);
        lds128(d + 4 * k, sb + OFF_DST + (tid + NWK * k) * 16);
#pragma unroll
        for (int i = 4 * k; i < 4 * k + 4; i++) { jj[i] = d[i] * p.magic; rr[i] = atoms_add(__dp4a(jj[i], 0x04000000u, sb + OFF_BC), 0x202u); }
      };
      auto place = [&](int k) {
#pragma unroll
        for (int i = 4 * k; i < 4 * k + 4; i++) {
          const uint32_t o = __dp4a(jj[i], 0x80000000u, rr[i] & 0x807Eu);
          d[i] = (d[i] & 511) | (tag >> 16);
          asm("{.reg .pred p; setp.ge.u32 p, %1, 0x8000; @p add.u32 %0, %2, %3;}" : "+r"(d[i]) : "r"(o), "r"(tid * 4), "r"(NWK * k * 4 + (i & 3)));
          sts16(sb + OFF_SA + o, d[i]); jj[i] = __viaddmin_u32(o, o, G * 256);
        }
      };
      count(0); STAMP(1); count(1); get_tag(); place(0); count(2); place(1); count(3); place(2);
      if (wid < 4) { count(4); place(3); place(4); } else place(3);
      proxy_fence();
      bar_arrive(12, 384);
      STAMP(2);
      mbar_wait(sb + BAR_PS);
      mbar_wait(sb + BAR_SRC); mbar_wait(sb + BAR_SRC + 8); mbar_wait(sb + BAR_SRC + 16);
      STAMP(12);
#pragma unroll
      for (int k = 0; k < NCH; k++) lds128(d + 4 * k, sb + OFF_SRCI + (tid + NWK * k) * 16);
      const uint32_t tb = tag + (tid << 18);
#pragma unroll
      for (int i = 0; i < 4 * NCH; i++) if (i < 4 * NCH - 4 || wid < 4) sts32(sb + OFF_SB + jj[i], d[i] + tb + ((NWK * (i >> 2) * 4 + (i & 3)) << 16));
      proxy_fence();
      bar_arrive(13, 384);
      STAMP(3);
    }
    const uint32_t rot = (lane + cta) & 31;
    cb = sb + OFF_CNT - (tag >> 14);
    {
      const uint32_t* xa = (const uint32_t*)(p.xa + (cta * G + wid) * 8) + rot;
      if (wid < 8) { const uint32_t e_ = ealo + epad * 32;
        mbar_wait(sb + BAR_AX);
#pragma unroll
        for (int i = 0; i < 7; i++) sts128(sb + OFF_TE + tid * 16 + i * 4096, e_, e_, e_, e_); }
      static_assert(SCAP * 64 == 7 * 4096, "fill");
      if (wid == 10) { hint_wait(p.sent, ep * G, s0_); mbar_arrive(sb + BAR_HA, lane == 0); }
      mbar_wait(sb + BAR_HA);
      STAMP(14);
      uint32_t all;
#pragma unroll 1
      for (int spin = 0;; spin++) {
        uint32_t st = 0; all = ~0u;
#pragma unroll
        for (int k = 0; k < 12; k++) asm volatile("ld.relaxed.gpu.global.u32 %0, [%1];" : "=r"(pk[k]) : "l"(xa + k * 352) : "memory");
#pragma unroll
        for (int k = 0; k < 12; k++) { st |= pk[k] ^ (tag | (tag >> 16)); all &= pk[k]; }
        if (!__any_sync(~0u, st & 0xC000C000u)) break;
        trap_if(spin > 2000000);
      }
      if (wid == 0) STAMP(22);
      uint32_t xm = 0; uint2 xv;
      auto xadr = [&]() { return p.xe + (cta * G + wid + 11 * (__ffs(xm) - 1)) * 64 + lane; };
      if (!(__shfl_sync(~0u, all, 31) & 0x2000000u)) {
#pragma unroll
        for (int k = 0; k < 12; k++) xm |= (~pk[k] >> 25 & 1) << k;
        xm = __shfl_sync(~0u, xm, 31);
        xv = ld_poll2(xadr());
      }
#pragma unroll
      for (int k = 0; k < 12; k++) { r0[k] = mad16(pk[k], 0x0004u, cb); r1[k] = mad16(pk[k], 0x0400u, cb); vb[k].x = atoms_add(r0[k], 16); vb[k].y = atoms_add(r1[k], 16); }
      mbar_arrive(sb + BAR_XA, lane == 0);
#pragma unroll
      for (int k = 0; k < 12; k++) pk[k] = __byte_perm(vb[k].x, vb[k].y, 0x5410);
      for (; xm; xm &= xm - 1) {
        if (__any_sync(~0u, xv.y != ep)) xv.x = ext_get(xadr(), ep);
        const uint32_t cn = xv.x >> 9, n = xv.x & 511;
        if (cn > 96) sts32(sb + OFF_MISC + 8, 1);
        else if (lane < cn - 64) {
          const uint32_t r = atoms_add(sb + OFF_CNT + n * 4, 16), idx = atoms_add(sb + OFF_MISC + 4, 1);
          if (idx < 256) sts32(sb + OFF_EXT + idx * 4, n | ((wid + 11 * (__ffs(xm) - 1)) << 9) | (lane << 17) | (min(r >> 4, 255u) << 22));
          else sts32(sb + OFF_MISC + 8, 1);
        }
        xv.y = ~ep;
        __syncwarp();
      }
    }
    STAMP(4);
    if (wid >= 6) { bar_arrive(11, NWK); mbar_wait(sb + BAR_HB); }
    else asm volatile("{.reg .pred p; mbarrier.test_wait.parity.shared::cta.b64 p, [%1], 0; vote.sync.all.pred p, p, -1; selp.u32 %0, 1, 0, p;}" : "=r"(early) : "r"(sb + BAR_HB) : "memory");
    if (early) bload_();
    if (wid < 6) {
      uint32_t ca[2], ky[2], dr[2], sq[2], ps[4];
#pragma unroll
      for (int i = 0; i < 2; i++) { ca[i] = sb + OFF_CNT + ((node0 + tid + 192 * i) & 511) * 4; lds64(ps[2 * i], ps[2 * i + 1], sb + OFF_POS + (tid + 192 * i) * 8); ps[2 * i + 1] |= (tid + 192 * i) << 16; }
      bar_sync(11, NWK);
      STAMP(5);
#pragma unroll
      for (int i = 0; i < 2; i++) ky[i] = (lds32(ca[i]) + 16) >> 5;
      if (max(ky[0], ky[1]) > 31) sts32(sb + OFF_MISC + 8, 1);
#pragma unroll
      for (int i = 0; i < 2; i++) { ky[i] = min(ky[i], 31u); dr[i] = atoms_add(sb + OFF_DH + ky[i] * 4, 1); }
      bar_sync(10, 192);
      const uint32_t hv = lds32(sb + OFF_DH + lane * 4);
      uint32_t inc = hv;
#pragma unroll
      for (int o = 1; o < 32; o <<= 1) asm("{.reg .pred p; .reg .b32 y; shfl.sync.down.b32 y|p, %0, %1, 31, -1; @p add.u32 %0, %0, y;}" : "+r"(inc) : "r"(o));
#pragma unroll
      for (int i = 0; i < 2; i++) {
        const uint32_t pos = __shfl_sync(~0u, inc - hv, ky[i]) + dr[i];
        const uint32_t ak = (uint32_t)(0x1453AB297860ull >> ((pos >> 5) * 4)) & 15, l = (pos >> 3) & 3;
        sq[i] = (ak >> 2) * 16 + ((ak & 1) ? 3 - l : l) * 4 + (ak & 3);
        dr[i] = pos & 7;
        asm volatile("{.reg .pred p; setp.eq.u32 p, %2, 0; @p st.shared.u8 [%0], %1;}" :: "r"(sb + OFF_LEN + sq[i]), "r"(max(ky[i], 1u)), "r"(dr[i]) : "memory");
        sts64(sb + OFF_GP + sq[i] * 64 + dr[i] * 8, ps[2 * i], ps[2 * i + 1]);
      }
      bar_sync(10, 192);
      const uint32_t ln = lds32(sb + OFF_LEN + min(lane, 11) * 4), tot = __dp4a(ln, 0x01010101u, 0u);
      inc = tot;
#pragma unroll
      for (int o = 1; o < 16; o <<= 1) asm("{.reg .pred p; .reg .b32 y; shfl.sync.up.b32 y|p, %0, %1, 0, -1; @p add.u32 %0, %0, y;}" : "+r"(inc) : "r"(o));
      if (wid == 1) sts32(sb + OFF_CNT + 2048 + lane * 4, 0);
      if (tid < 12) { sts32(sb + OFF_LEN + 64 + tid * 4, inc - tot); if (inc > SCAP) sts32(sb + OFF_MISC + 8, 1); }
#pragma unroll
      for (int i = 0; i < 2; i++) sts32(ca[i], __dp4a(__shfl_sync(~0u, ln, sq[i] >> 2), 0x00010101u >> (24 - 8 * (sq[i] & 3)), __shfl_sync(~0u, inc - tot, sq[i] >> 2)) * 32 + dr[i] * 2);
    }
  }
  bar_sync(1, 384);
  STAMP(6);
  if (wid != 11) {
    if (!early) bload_();
#pragma unroll
    for (int k = 0; k < 12; k++) { r0[k] = lds32(r0[k]); r1[k] = lds32(r1[k]); }
#pragma unroll
    for (int k = 0; k < 12; k++) pk[k] += __byte_perm(r0[k], r1[k], 0x5410);
  }
  mbar_wait(sb + BAR_QR);
  asm volatile("setmaxnreg.inc.sync.aligned.u32 160;");
  uint32_t bad;
  {
    const uint32_t ring = sb + OFF_RING + wid * (NST * STG), p2 = sb + OFF_P2 + wid * 2048;
    uint32_t lens = __shfl_sync(~0u, lds32(sb + OFF_LEN + wid * 4), 0);
    uint32_t rem = __dp4a(lens, 0x20202020u, 0u);
    const uint32_t base = min(lds32(sb + OFF_LEN + 64 + wid * 4), SCAP);
    uint32_t a_s = sb + OFF_TS + base * 32 + (lane >> 3) * 8, a_e = sb + OFF_TE + base * 64 + (lane >> 1) * 4;
    uint32_t k0 = (uint32_t)(uint64_t)p.q + (((lane & 7) ^ ((lane >> 1) & 4)) << 4), k1 = k0 ^ 16, k2 = k0 ^ 32, k3 = k0 ^ 48, ke = ((lane ^ (lane >> 3)) & 1) << 4;
    uint32_t dst0 = ring + (lane >> 3) * 640 + (lane & 7) * 16;
    const uint32_t qhi = (uint32_t)((uint64_t)p.q >> 32), ehi = (uint32_t)((uint64_t)p.ea >> 32);
    uint32_t s0, s1, ev, to = 0, so = 0;
    auto tl_ = [&]() { lds64(s0, s1, a_s + to); asm volatile("ld.shared.u32 %0, [%1]; add.u32 %1, %1, 64;" : "=&r"(ev), "+r"(a_e) :: "memory"); to += 32; };
#define CPQ(LH, x, k, off) "dp2a." LH ".u32.u32 lo, " x ", 0x80000080, " k "; mov.b64 a, {lo, %7}; @p cp.async.cg.shared.global [%0+" #off "], [a], 16;\n"
#define CPE "or.b32 lo, %10, %11; mov.b64 a, {lo, %12}; @p cp.async.cg.shared.global [%0+512], [a], 16;\n"
#define CPA(BODY) asm volatile("{.reg .b32 lo; .reg .b64 a; .reg .pred p; setp.le.u32 p, %8, %9;\n" BODY "}" \
      :: "r"(dst0 + so), "r"(s0), "r"(s1), "r"(k0), "r"(k1), "r"(k2), "r"(k3), "r"(qhi), "r"(to), "r"(rem), "r"(ev), "r"(ke), "r"(ehi) : "memory")
#define CPQ4 CPQ("lo", "%1", "%3", 0) CPQ("hi", "%1", "%4", 128) CPQ("lo", "%2", "%5", 256) CPQ("hi", "%2", "%6", 384) "cp.async.commit_group;"
    auto issue = [&]() { CPA(CPE CPQ4); so = so == (NST - 1) * STG ? 0 : so + STG; };
    const int g = lane >> 2, qd = lane & 3;
    const uint32_t sw = ((lane >> 4) ^ (lane & 7)) << 4, fr = (lane & 15) * 128 + sw;
    uint32_t qa0 = ring + (g & 3) * 640 + qd * 128 + sw, qa1 = qa0 ^ 32, qa2 = qa0 ^ 64, qa3 = qa0 ^ 96;
    uint32_t eadr = ring + 512 + (g & 3) * 640 + qd * 32 + ((((lane >> 4) ^ g) & 1) << 4);
    uint32_t oh0 = g == 2 * qd ? 0x3C00u : g == 2 * qd + 1 ? 0x3C000000u : 0u, oh1 = oh0;
    uint32_t a_g = sb + OFF_GP + wid * 256 + lane * 2;
    uint32_t a_n = sb + OFF_GP + wid * 256 + (lane & 15) * 8 + 6;
    uint32_t a_p = ((lane & 8) ? p2 : sb + OFF_WD) + (lane & 7) * 128 + ((((lane >> 4) ^ lane) & 7) << 4);
    uint32_t a_w = sb + OFF_W3 + fr;
#define OPQ4(A, B, C, D, o) asm volatile("{st.volatile.shared.v4.b32 [%4], {%0,%1,%2,%3}; ld.volatile.shared.v4.b32 {%0,%1,%2,%3}, [%4];}" : "+r"(A), "+r"(B), "+r"(C), "+r"(D) : "r"(sb + OFF_SA + wid * 2048 + lane * 16 + o) : "memory")
    if (OPQ) { OPQ4(a_w, oh0, oh1, dst0, 0); OPQ4(qa0, qa1, qa2, qa3, 512); OPQ4(k0, k1, k2, k3, 1024); OPQ4(a_g, a_n, a_p, eadr, 1536); }
    uint32_t w3[16], wv[8], bp[16], sp[8], pq[16], sum[8], Y[16], M[16], own, ownp, dpk; uint16_t tl[16], th[16];
    float pacc = 0.f, chk = 0.f;
    auto wload = [&]() {
#pragma unroll
      for (int j = 0; j < 4; j++) ldsm4t(w3 + 4 * j, a_w ^ (j << 5));
      lds128(wv, sb + OFF_WX + (a_g & 6) * 16); lds128(wv + 4, sb + OFF_WX + 16 + (a_g & 6) * 16);
    };
    auto hload = [&](uint32_t (&hf)[16], uint32_t nd) {
      const uint32_t hrow = sb + OFF_H + nd * 128 + (((nd & 7) << 4) ^ ((a_g >> 1) & 16));
#pragma unroll
      for (int j = 0; j < 4; j++) ldsm4(hf + 4 * j, hrow ^ (j << 5));
      return hrow;
    };
    auto bload = [&](uint32_t o) {
#pragma unroll
      for (int j = 0; j < 4; j++) ldsm4t(bp + 4 * j, (a_p ^ (j << 5)) + o);
    };
    {
      const uint32_t an = sb + OFF_GP + wid * 256 + (lane & 7) * 8 + 6, n0 = lds16(an), n1 = lds16(an + 64), n2 = lds16(a_n + 128);
      auto prow = [&](uint32_t n, uint32_t c) { return sb + OFF_PT + n * 128 + (n < 128 ? PTX : 0) + (((n ^ c) & 7) << 4); };
      const uint32_t r0 = (lane & 8) ? prow(n0, lane >> 4) : a_p, r1 = prow(n1, lane >> 3), r2 = prow(n2, lane >> 4);
      mbar_wait(sb + BAR_BW);
#pragma unroll
      for (int j = 0; j < 4; j++) { ldsm4t(bp + 4 * j, r0 ^ (j << 5)); ldsm4(pq + 4 * j, r2 ^ (j << 5)); }
      ldsm4t(sp, r1); ldsm4t(sp + 4, r1 ^ 64);
    }
    if (wid == 0) STAMP(27);
    if (__shfl_sync(~0u, lds32(sb + OFF_MISC + 8), 0)) rem = 0;
    else if (wid == 11) {
      const uint32_t nx = __shfl_sync(~0u, lds32(sb + OFF_MISC + 4), 0);
      for (uint32_t k = 0; k < nx; k += 32) {
        const uint32_t x = lds32(sb + OFF_EXT + min(k + lane, nx - 1) * 4), y = ext_get(p.xe + (cta * G + ((x >> 9) & 255)) * 64 + 32 + ((x >> 17) & 31), ep);
        put(lds32(sb + OFF_CNT + (x & 511) * 4) + (x >> 22) * 16, 0, y, eb0 + ((x >> 9) & 255) * p.EPC * 32);
      }
    } else {
#pragma unroll 1
      for (int spin = 0;; spin++) {
        uint32_t st = 0;
#pragma unroll
        for (int k = 0; k < 12; k++) st |= (vb[k].x ^ tag) | (vb[k].y ^ tag);
        if (!__any_sync(~0u, st >> 30)) break;
        trap_if(spin > 2000000);
#pragma unroll
        for (int k = 0; k < 12; k++) vb[k] = ld_poll2(xb + k * 352);
      }
#pragma unroll
      for (int k = 0; k < 12; k++) { const uint32_t eb = eb0 + (wid + 11 * k) * p.EPC * 32; put(pk[k], 0, vb[k].x, eb); put(pk[k], 1, vb[k].y, eb); }
    }
    STAMP(7);
    wload();
    own = lds16(a_g) * 0x10001u;
    bar_sync(2, 384);
    uint32_t sv[3 * NST];
#pragma unroll
    for (int i = 0; i < NST; i++) { tl_(); sv[3 * i] = s0; sv[3 * i + 1] = s1; sv[3 * i + 2] = ev; }
#pragma unroll
    for (int j = 0; j < 4; j++) stsm4((p2 + fr) ^ (j << 5), pq[4 * j], pq[4 * j + 1], pq[4 * j + 2], pq[4 * j + 3]);
#pragma unroll
    for (int i = 0; i < NST; i++) { to = 32 * i + 32; so = i * STG; ev = sv[3 * i + 2]; CPA(CPE); }
    mbar_wait(sb + BAR_QP);
    STAMP(13);
    bad = __shfl_sync(~0u, lds32(sb + OFF_MISC + 8), 0);
   if (!bad) {
#pragma unroll
    for (int i = 0; i < NST; i++) { to = 32 * i + 32; so = i * STG; s0 = sv[3 * i]; s1 = sv[3 * i + 1]; CPA(CPQ4); }
    so = 0;
    auto body = [&](auto MODE) {
      constexpr int mode = decltype(MODE)::value;
      uint32_t T[16], ef[4], q0, q1, x0, x1, x2; float e0_, e1_, cs[4];
      auto mu = [&](int j) {
#pragma unroll
        for (int i = 2 * j; i < 2 * j + 2; i++) asm volatile("{.reg .b16 l, h; mov.b32 {l, h}, %2; tanh.approx.f16 %0, l; tanh.approx.f16 %1, h;}" : "=h"(tl[i]), "=h"(th[i]) : "r"(Y[i])); };
      auto fi = [&](int j) {
#pragma unroll
        for (int i = 2 * j; i < 2 * j + 2; i++) asm volatile("{.reg .b32 t; mov.b32 t, {%2, %3}; fma.rn.f16x2 %0, %1, t, %1;}" : "=r"(M[i]) : "r"(Y[i]), "h"(tl[i]), "h"(th[i])); };
      auto ad = [&](int j) { asm volatile("add.rn.f16x2 %0, %0, %1; add.rn.f16x2 %0, %0, %2;" : "+r"(sum[j]) : "r"(M[2 * j]), "r"(M[2 * j + 1])); };
      auto he = [&](int j) { asm volatile("mma.sync.aligned.m16n8k16.row.col.f16.f16.f16.f16 {%0,%1}, {%2,%3,%4,%5}, {%6,%7}, {%0,%1};" : "+r"(T[2 * j]), "+r"(T[2 * j + 1]) : "r"(ef[0]), "r"(ef[1]), "r"(ef[2]), "r"(ef[3]), "r"(w3[2 * j]), "r"(w3[2 * j + 1])); };
      auto hs = [&](int j) { asm volatile("mma.sync.aligned.m16n8k16.row.col.f16.f16.f16.f16 {%0,%1}, {%2,%3,%4,%5}, {%6,%7}, {%8,%9};" : "=r"(Y[2 * j]), "=r"(Y[2 * j + 1]) : "r"(q0), "r"(q1), "r"(oh0), "r"(oh1), "r"(bp[2 * j]), "r"(bp[2 * j + 1]), "r"(T[2 * j]), "r"(T[2 * j + 1])); };
      auto hc = [&](int j) {
        if (j) asm volatile("mma.sync.aligned.m16n8k16.row.col.f32.f16.f16.f32 {%0,%1,%2,%3}, {%4,%5,%6,%7}, {%8,%9}, {%0,%1,%2,%3};" : "+f"(cs[0]), "+f"(cs[1]), "+f"(cs[2]), "+f"(cs[3]) : "r"(M[4 * j]), "r"(M[4 * j + 1]), "r"(M[4 * j + 2]), "r"(M[4 * j + 3]), "r"(wv[2 * j]), "r"(wv[2 * j + 1]));
        else asm volatile("mma.sync.aligned.m16n8k16.row.col.f32.f16.f16.f32 {%0,%1,%2,%3}, {%4,%5,%6,%7}, {%8,%9}, {%10,%10,%10,%10};" : "=f"(cs[0]), "=f"(cs[1]), "=f"(cs[2]), "=f"(cs[3]) : "r"(M[0]), "r"(M[1]), "r"(M[2]), "r"(M[3]), "r"(wv[0]), "r"(wv[1]), "f"(0.f)); };
      auto cv = [&](int i) { asm volatile("{.reg .b32 a, b; shl.b32 a, %0, 16; and.b32 b, %0, 0xFFFF0000; cvt.rn.f16x2.f32 %0, b, a;}" : "+r"(ef[i])); };
      auto un = [&]() { asm volatile("shl.b32 %0, %2, 16; and.b32 %1, %2, 0xFFFF0000;" : "=&f"(e0_), "=&f"(e1_) : "r"(dpk)); };
      auto ex0 = [&]() { asm volatile("prmt.b32 %0, %3, %4, 0x6420; prmt.b32 %1, %5, %6, 0x6420; prmt.b32 %2, %7, %8, 0x6420;" : "=&r"(x0), "=&r"(x1), "=&r"(x2) : "r"(T[0]), "r"(T[1]), "r"(T[2]), "r"(T[3]), "r"(T[4]), "r"(T[5])); };
      auto ex1 = [&]() { asm volatile("{.reg .b32 a, b; shl.b32 a, %2, 3; shl.b32 b, %3, 6; lop3.b32 a, %1, a, 0x38383838, 0xD8; lop3.b32 a, a, b, 0xC0C0C0C0, 0xD8; sub.rn.bf16x2 %0, %4, a;}" : "=r"(dpk) : "r"(x0), "r"(x1), "r"(x2), "r"(own)); };
      auto ex2 = [&]() { asm volatile("{.reg .b32 a, b, d, u; .reg .b16 l, h; shl.b32 a, %2, 16; and.b32 b, %2, 0xFFFF0000; cvt.rn.f16x2.f32 d, b, a; mul.rn.f16x2 %0, d, d; mov.b32 {l, h}, d; mov.b32 u, {h, h}; mul.rn.f16x2 %1, u, u;}" : "=&r"(q0), "=&r"(q1) : "r"(dpk)); };
      auto pf = [&]() { asm volatile("fma.rn.f32 %0, %1, %2, %0; fma.rn.f32 %0, %3, %4, %0;" : "+f"(pacc) : "f"(cs[0]), "f"(e0_), "f"(cs[2]), "f"(e1_)); };
#define FX(k) if (FM >> k & 1) asm volatile("pmevent 1;" ::: "memory")
      if (mode == 2) {
        hc(0); mu(3); fi(2); un(); ad(0); ad(1); mu(4); fi(3); hc(1); mu(5); fi(4); ad(2); mu(6); fi(5); ad(3); hc(2); mu(7); fi(6); fi(7); ad(4); ad(5); hc(3); ad(6); ad(7); pf();
        return;
      }
      asm volatile("cp.async.wait_group %0;" :: "n"(NST - 1) : "memory");
      __syncwarp();
      if (mode == 1) STAMP(8);
      ldsm4(ef, eadr + so); ldsm4(T, qa0 + so); ldsm4(T + 4, qa1 + so); ldsm4(T + 8, qa2 + so); ldsm4(T + 12, qa3 + so);
      tl_();
      if (mode == 1) {
        issue();
        cv(0); cv(1); cv(2); cv(3); ex0(); ex1(); ex2();
#pragma unroll
        for (int j = 0; j < 8; j++) { he(j); hs(j); }
        mu(0); mu(1); fi(0); mu(2); fi(1);
        return;
      }
      hc(0); mu(3); fi(2); un(); ad(0); ad(1);
      FX(0);
      mu(4); fi(3); cv(0); cv(1); cv(2); cv(3); ex0(); ex1();
      FX(1);
      he(0); he(1); hc(1); mu(5); fi(4); ex2(); ad(2);
      FX(2);
      hs(0); he(2); mu(6); fi(5); issue(); ad(3);
      FX(3);
      hs(1); he(3); hc(2); mu(7); fi(6);
      FX(4);
      hs(2); hs(3); he(4); he(5); mu(0); fi(7); ad(4); ad(5);
      FX(5);
      hc(3); hs(4); he(6); he(7); mu(1); fi(0); ad(6);
      FX(6);
      hs(5); hs(6); hs(7); mu(2); fi(1); ad(7); pf();
      FX(7);
    };
#pragma unroll
    for (int j = 0; j < 8; j++) sum[j] = 0;
    body(IC<1>());
    int cnt = (lens & 255) - 1;
#pragma unroll 1
    for (int t = 0; t < 8; t++) {
#pragma unroll 1
      for (; cnt > 0; cnt--) body(IC<0>());
      if (!(t & 1)) {
        ownp = own;
        if (t < 6) {
          a_g += 64; own = lds16(a_g) * 0x10001u;
          if (t == 0) {
#pragma unroll
            for (int j = 0; j < 8; j++) bp[2 * j + 1] = sp[j];
          } else bload((a_g & 16) ? (t & 4) * 256 : 0);
          lens >>= 8; cnt = 1;
          continue;
        }
        body(IC<2>()); t++;
        STAMP(9);
      }
      cnt = (lens & 255) - 1;
      { const uint32_t ng = __shfl_sync(~0u, ownp, (a_g >> 1) | 3) >> 16, c3 = (a_g >> 1) & 3;
        asm volatile("{.reg .pred p; setp.lt.u32 p, %2, %3; @p st.global.u16 [%0], %1;}" :: "l"(p.out + (size_t)p.N * 64 + (size_t)node0 * 3 + (ng * 3 + c3)), "h"((uint16_t)pack_bf16(bf_hi(ownp) + pacc, 0.f)), "r"(ng), "r"(c3 < 3 ? nloc : 0) : "memory"); }
      chk = fmaf(pacc, 0.f, chk); pacc = 0.f;
      if (t & 2) {
        uint32_t hf[16]; float acc[32];
        const uint32_t nd = lds16(a_n); a_n += 128;
        const uint32_t hrow = hload(hf, nd);
        const uint64_t b1 = DHI | ((sb + OFF_W) >> 4), b2_ = b1 + 512;
        mbar_wait(sb + BAR_WH);
        wg_fence();
        rs64h<0>(acc, sp[0], sum[0], sp[1], sum[1], b2_); rs64h<1>(acc, sp[2], sum[2], sp[3], sum[3], b2_ + 128); rs64h<1>(acc, sp[4], sum[4], sp[5], sum[5], b2_ + 256); rs64h<1>(acc, sp[6], sum[6], sp[7], sum[7], b2_ + 384);
        rs64b<1>(acc, hf[0], hf[1], hf[2], hf[3], b1); rs64b<1>(acc, hf[4], hf[5], hf[6], hf[7], b1 + 128); rs64b<1>(acc, hf[8], hf[9], hf[10], hf[11], b1 + 256); rs64b<1>(acc, hf[12], hf[13], hf[14], hf[15], b1 + 384);
        wg_commit(); wg_wait0(); fence_regs(acc);
        if (t == 7) STAMP(10);
        chk = fmaf(acc[0], 0.f, fmaf(acc[2], 0.f, chk));
        auto fin = [&](uint32_t x, float y0, float y1) { return u2(__hadd2(b2(x), b2(pack_bf16(silu_h(y0), silu_h(y1))))); };
#pragma unroll
        for (int j = 0; j < 4; j++) stsm4(hrow ^ (j << 5), fin(hf[4 * j], acc[8 * j], acc[8 * j + 1]), fin(hf[4 * j + 1], acc[8 * j + 2], acc[8 * j + 3]), fin(hf[4 * j + 2], acc[8 * j + 4], acc[8 * j + 5]), fin(hf[4 * j + 3], acc[8 * j + 6], acc[8 * j + 7]));
        __syncwarp();
        const uint32_t c8 = (a_g << 3) & 0x70;
#pragma unroll
        for (int j = 0; j < 4; j++) { uint32_t v[4]; const uint32_t n = __shfl_sync(~0u, nd, 4 * j + ((a_g >> 4) & 3)); lds128(v, sb + OFF_H + n * 128 + (((n << 4) ^ c8) & 0x70));
          asm volatile("{.reg .pred p; setp.lt.u32 p, %5, %6; @p st.global.v4.b32 [%0], {%1,%2,%3,%4};}" :: "l"((const char*)p.out + (size_t)node0 * 128 + (n * 128 + c8)), "r"(v[0]), "r"(v[1]), "r"(v[2]), "r"(v[3]), "r"(n), "r"(nloc) : "memory"); }
        wload();
      }
#pragma unroll
      for (int j = 0; j < 8; j++) { sp[j] = sum[j]; asm volatile("mov.b32 %0, 0;" : "=r"(sum[j])); }
    }
    asm volatile("{.reg .pred p, q; setp.neu.f32 p, %1, 0f00000000; setp.ne.or.u32 p, %2, 0, p; bar.red.or.pred q, 5, 384, p; selp.u32 %0, 1, 0, q;}" : "=r"(bad) : "f"(chk), "r"(lds32(sb + OFF_MISC + 12)) : "memory");
    STAMP(11);
   } else { asm volatile("cp.async.wait_all;" ::: "memory"); bar_sync(5, 384); }
  }
  if (bad) slow_path(p, wid, lane, node0, nloc);
}

}

typedef CUresult (*EncodeFn)(CUtensorMap*, CUtensorMapDataType, cuuint32_t, void*, const cuuint64_t*, const cuuint64_t*, const cuuint32_t*, const cuuint32_t*,
                             CUtensorMapInterleave, CUtensorMapSwizzle, CUtensorMapL2promotion, CUtensorMapFloatOOBfill);

extern "C" void kernel_launch(void* const* d_in, const int* in_sizes, int n_in, void* d_out, int out_size) {
  Params p; Maps maps;
  p.h = (const uint4*)d_in[0]; p.pos = (const uint16_t*)d_in[1]; p.ea = (const uint4*)d_in[2];
  p.src = (const int*)d_in[3]; p.dst = (const int*)d_in[4];
  p.we = (const uint16_t*)d_in[5]; p.wx = (const uint16_t*)d_in[6]; p.wh = (const uint16_t*)d_in[7];
  p.out = (uint16_t*)d_out;
  p.N = in_sizes[0] / 64; p.E = in_sizes[3];
  p.EPC = ((p.E + G * 4 - 1) / (G * 4)) * 4;
  p.magic = (uint32_t)(((uint64_t)G << 24) / (uint64_t)p.N);
  p.inv = (1ull << 56) / p.magic;
  const uint64_t ea0 = (uint64_t)d_in[2], ea1 = ea0 + (uint64_t)p.E * 32 - 1;
  p.force_slow = ((ea0 >> 32) != (ea1 >> 32)) || (ea0 & 31) || (p.E & 3);
  void* qp = nullptr;
  cudaGetSymbolAddress(&qp, g_q);
  p.q = (char*)qp;
  if (((uint64_t)p.q >> 32) != (((uint64_t)p.q + QBYTES) >> 32)) p.q += QBYTES;
  cudaGetSymbolAddress((void**)&p.cnt, g_cnt); cudaGetSymbolAddress((void**)&p.sent, g_sent); cudaGetSymbolAddress((void**)&p.xe, g_xe);
  cudaGetSymbolAddress((void**)&p.xa, g_xa); cudaGetSymbolAddress((void**)&p.xb, g_xb);
  void* fn = nullptr; cudaDriverEntryPointQueryResult qr;
  cudaGetDriverEntryPoint("cuTensorMapEncodeTiled", &fn, cudaEnableDefault, &qr);
  auto mk = [&](CUtensorMap* tm, void* base, int rows) {
    const cuuint64_t dim[2] = {64, (cuuint64_t)rows}, str[1] = {128}; const cuuint32_t bx[2] = {64, 64}, es[2] = {1, 1};
    ((EncodeFn)fn)(tm, CU_TENSOR_MAP_DATA_TYPE_BFLOAT16, 2, base, dim, str, bx, es, CU_TENSOR_MAP_INTERLEAVE_NONE, CU_TENSOR_MAP_SWIZZLE_128B,
                   CU_TENSOR_MAP_L2_PROMOTION_NONE, CU_TENSOR_MAP_FLOAT_OOB_FILL_NONE);
  };
  mk(&maps.m[TM_H / 128], d_in[0], p.N); mk(&maps.m[TM_WE / 128], d_in[5], 145); mk(&maps.m[TM_WH / 128], d_in[7], 128); mk(&maps.m[TM_Q / 128], p.q, p.N);
  for (int k = 0; k < 2; k++) {
    void* xp = (void*)(k ? p.xb : p.xa);
    const cuuint64_t dim[2] = {(cuuint64_t)G * 64, (cuuint64_t)G}, str[1] = {(cuuint64_t)G * (128 << k)}; const cuuint32_t bx[2] = {64, (cuuint32_t)(k ? BROWS : G)}, es[2] = {1, 1};
    ((EncodeFn)fn)(&maps.m[TM_XA / 128 + k], k ? CU_TENSOR_MAP_DATA_TYPE_UINT32 : CU_TENSOR_MAP_DATA_TYPE_UINT16, 2, xp, dim, str, bx, es, CU_TENSOR_MAP_INTERLEAVE_NONE,
                   CU_TENSOR_MAP_SWIZZLE_NONE, CU_TENSOR_MAP_L2_PROMOTION_NONE, CU_TENSOR_MAP_FLOAT_OOB_FILL_NONE);
  }
  cudaFuncSetAttribute(egnn_kernel, cudaFuncAttributeMaxDynamicSharedMemorySize, SMEM);
  egnn_kernel<<<G, NTHR, SMEM>>>(p, maps);
}
```

```cpp
#include <cuda_runtime.h>
#include <cuda_bf16.h>
#include <cuda_fp16.h>
#include <cuda.h>
#include <stdint.h>
#pragma nv_diag_suppress 549

#define PFN 8
#define PFNS 250
#define FM 0
#define OPQ 15
#define H0 0
#define HALL 0
#define PF0NS 500
#define HW 3
#define BROWS 132
#define B_HOLD 0
#define LSEQ 0x231200ull
#define HE 0
namespace {

constexpr int G = 132;
constexpr int NTHR = 512, NWK = 352, NCH = 5;
constexpr int NST = 3, STG = 2560;
constexpr int SCAP = 448;

constexpr int OFF_H = 0;
constexpr int OFF_W = 49152;
constexpr int OFF_WD = OFF_W + 16384;
constexpr int OFF_W3 = OFF_WD + 1024;
constexpr int OFF_P2 = OFF_W3 + 2048;
constexpr int OFF_RING = OFF_P2 + 24576;
constexpr int OFF_TE = OFF_RING + 12 * NST * STG;
constexpr int OFF_TS = OFF_TE + SCAP * 64;
constexpr int OFF_GP = OFF_TS + SCAP * 32;
constexpr int OFF_WX = OFF_GP + 3072;
constexpr int OFF_LEN = OFF_WX + 128;
constexpr int OFF_MISC = OFF_LEN + 128;
constexpr int OFF_BAR = OFF_MISC + 48;
constexpr int SMEM = OFF_BAR + 256;
static_assert(SMEM <= 232448, "smem");
constexpr uint32_t sb = 1024;
constexpr int OFF_SRCI = OFF_TE;
constexpr int OFF_SB = OFF_RING, OFF_SA = OFF_SB + 34816, OFF_AX = OFF_SA + 32768, OFF_DST = OFF_H + 24576;
constexpr int OFF_PT = OFF_SB - 16384, PTX = OFF_AX - OFF_PT;
constexpr int OFF_XB = OFF_SA - 1024;
constexpr int OFF_WS = OFF_AX + 17408;
constexpr int OFF_BC = OFF_WS + 2304;
constexpr int OFF_CNT = OFF_P2 + 16384;
constexpr int OFF_DH = OFF_CNT + 2176;
constexpr int OFF_POS = OFF_DH + 128;
constexpr int OFF_EXT = OFF_POS + 3072;
static_assert(OFF_XB + G * 256 <= OFF_AX && OFF_EXT + 1024 <= OFF_RING && OFF_BC + 544 <= OFF_TE && OFF_P2 % 1024 == 0 && OFF_SA % 1024 == 0 && SCAP * 64 >= 24576, "staging");
constexpr int BAR_DST = OFF_BAR, BAR_SRC = BAR_DST + 40, BAR_T = BAR_SRC + 24, BAR_W = BAR_T + 48, BAR_XA = BAR_W + 8, BAR_PS = BAR_XA + 8, BAR_AW = BAR_PS + 8,
              BAR_BW = BAR_AW + 8, BAR_QP = BAR_BW + 8, BAR_QR = BAR_QP + 8, BAR_HA = BAR_QR + 8, BAR_EP = BAR_HA + 8, BAR_AX = BAR_EP + 8, BAR_BS = BAR_AX + 8, BAR_HB = BAR_BS + 8, BAR_U = BAR_HB + 8, BAR_WH = BAR_U + 8, BAR_END = BAR_WH + 8;
constexpr uint32_t QBYTES = 8u << 20;

__device__ __align__(256) uint4 g_xa[G * G * 8];
__device__ __align__(256) uint4 g_xb[G * G * 16];
__device__ __align__(256) uint2 g_xe[G * G * 64];
__device__ __align__(256) uint4 g_q[2 * QBYTES / 16];
__device__ __align__(256) unsigned long long g_cnt;
__device__ __align__(256) uint32_t g_sent[64];
#define STAMP(k)

struct Maps { CUtensorMap m[6]; };
constexpr int TM_H = 0, TM_WE = 128, TM_WH = 256, TM_Q = 384, TM_XA = 512, TM_XB = 640;
struct Params {
  const uint4* h; const uint16_t* pos; const uint4* ea; const int* src; const int* dst;
  const uint16_t* we; const uint16_t* wx; const uint16_t* wh; uint16_t* out; char* q;
  unsigned long long* cnt; uint32_t* sent; const uint4* xa; const uint4* xb; uint2* xe;
  int N, E, EPC; uint32_t magic; int force_slow; unsigned long long inv;
};
template<int V> struct IC { static constexpr int value = V; };

#define R32(d) "+f"(d[0]),"+f"(d[1]),"+f"(d[2]),"+f"(d[3]),"+f"(d[4]),"+f"(d[5]),"+f"(d[6]),"+f"(d[7]),"+f"(d[8]),"+f"(d[9]),"+f"(d[10]),"+f"(d[11]),"+f"(d[12]),"+f"(d[13]),"+f"(d[14]),"+f"(d[15]),"+f"(d[16]),"+f"(d[17]),"+f"(d[18]),"+f"(d[19]),"+f"(d[20]),"+f"(d[21]),"+f"(d[22]),"+f"(d[23]),"+f"(d[24]),"+f"(d[25]),"+f"(d[26]),"+f"(d[27]),"+f"(d[28]),"+f"(d[29]),"+f"(d[30]),"+f"(d[31])
#define S32 "{%0,%1,%2,%3,%4,%5,%6,%7,%8,%9,%10,%11,%12,%13,%14,%15,%16,%17,%18,%19,%20,%21,%22,%23,%24,%25,%26,%27,%28,%29,%30,%31}"
#define DI __device__ __forceinline__

constexpr uint64_t DHI = ((uint64_t)(1024 >> 4) << 32) | (1ull << 62);
template<int SD> DI void rs64b(float (&d)[32], uint32_t a0, uint32_t a1, uint32_t a2, uint32_t a3, uint64_t db) {
  asm volatile("wgmma.mma_async.sync.aligned.m64n64k16.f32.bf16.bf16 " S32 ", {%32,%33,%34,%35}, %36, %37, 1, 1, 1;" : R32(d) : "r"(a0), "r"(a1), "r"(a2), "r"(a3), "l"(db), "n"(SD)); }
template<int SD> DI void rs64h(float (&d)[32], uint32_t a0, uint32_t a1, uint32_t a2, uint32_t a3, uint64_t db) {
  asm volatile("wgmma.mma_async.sync.aligned.m64n64k16.f32.f16.f16 " S32 ", {%32,%33,%34,%35}, %36, %37, 1, 1, 1;" : R32(d) : "r"(a0), "r"(a1), "r"(a2), "r"(a3), "l"(db), "n"(SD)); }
template<int SD> DI void ss64(float (&d)[32], uint64_t da, uint64_t db) {
  asm volatile("wgmma.mma_async.sync.aligned.m64n64k16.f32.bf16.bf16 " S32 ", %32, %33, %34, 1, 1, 0, 1;" : R32(d) : "l"(da), "l"(db), "n"(SD)); }
DI void trap_if(bool c) { asm volatile("{.reg .pred p; setp.eq.u32 p, %0, 0; @p bra.uni LT_%=; trap; LT_%=:}" :: "r"((uint32_t)c)); }
DI void wg_fence() { asm volatile("wgmma.fence.sync.aligned;" ::: "memory"); }
DI void wg_commit() { asm volatile("wgmma.commit_group.sync.aligned;" ::: "memory"); }
DI void wg_wait0() { asm volatile("wgmma.wait_group.sync.aligned 0;" ::: "memory"); }
DI void fence_regs(float (&d)[32]) { asm volatile("" : R32(d) :: "memory"); }
DI void proxy_fence() { asm volatile("fence.proxy.async.shared::cta;" ::: "memory"); }
DI uint64_t pol_first() { uint64_t r; asm("createpolicy.fractional.L2::evict_first.b64 %0, 1.0;" : "=l"(r)); return r; }
DI float tanh_ap(float x) { float y; asm("tanh.approx.f32 %0, %1;" : "=f"(y) : "f"(x)); return y; }
DI float silu_h(float y) { return fmaf(y, tanh_ap(y), y); }
DI uint32_t pack_bf16(float lo, float hi) { uint32_t r; asm("cvt.rn.bf16x2.f32 %0, %1, %2;" : "=r"(r) : "f"(hi), "f"(lo)); return r; }
DI uint32_t pack_f16(float lo, float hi) { uint32_t r; asm("cvt.rn.f16x2.f32 %0, %1, %2;" : "=r"(r) : "f"(hi), "f"(lo)); return r; }
DI float bf_lo(uint32_t v) { return __uint_as_float(v << 16); }
DI float bf_hi(uint32_t v) { return __uint_as_float(v & 0xFFFF0000u); }
DI uint32_t b2h(uint32_t v, float s) { return pack_f16(s * bf_lo(v), s * bf_hi(v)); }
DI void mbar_wait(uint32_t bar, uint32_t parity = 0) {
  asm volatile("{.reg .pred p; .reg .u32 t0, t1;\n"
    "mbarrier.try_wait.parity.shared::cta.b64 p, [%0], %1;\n @p bra.uni LD_%=;\n mov.u32 t0, %%clock;\n"
    "LW_%=: mbarrier.try_wait.parity.shared::cta.b64 p, [%0], %1;\n"
    "@p bra.uni LD_%=;\n mov.u32 t1, %%clock; sub.u32 t1, t1, t0; setp.lt.u32 p, t1, 0x80000000;\n @p bra.uni LW_%=;\n trap;\n LD_%=:}" :: "r"(bar), "r"(parity) : "memory");
}
DI void mbar_arrive(uint32_t bar, int p = 1) { asm volatile("{.reg .pred p; setp.ne.b32 p, %1, 0; @p mbarrier.arrive.shared::cta.b64 _, [%0];}" :: "r"(bar), "r"(p) : "memory"); }
DI void bar_sync(int id, int n) { asm volatile("bar.sync %0, %1;" :: "r"(id), "r"(n) : "memory"); }
DI void bar_arrive(int id, int n) { asm volatile("bar.arrive %0, %1;" :: "r"(id), "r"(n) : "memory"); }
DI __nv_bfloat162 b2(uint32_t v) { return *(__nv_bfloat162*)&v; }
DI uint32_t u2(__nv_bfloat162 v) { return *(uint32_t*)&v; }
DI uint32_t hsq(uint32_t v) { return u2(__hmul2(b2(v), b2(v))); }
DI uint32_t hsub(uint32_t a, uint32_t b) { return u2(__hsub2(b2(a), b2(b))); }
DI uint32_t hhalf(uint32_t v) { return u2(__hmul2(b2(v), __floats2bfloat162_rn(0.5f, 0.5f))); }
DI uint32_t mag2(uint32_t m, uint32_t v) { return __vmaxu2(m, v & 0x7FFF7FFFu); }
DI uint32_t hmag(uint32_t m, uint32_t v) { const __half2 r = __hmax2(*(const __half2*)&m, __habs2(*(const __half2*)&v)); return *(const uint32_t*)&r; }
DI uint32_t magr(uint32_t m) { return max(m & 0xFFFF, m >> 16); }
DI void sts128(uint32_t a, uint32_t x, uint32_t y, uint32_t z, uint32_t w) { asm volatile("st.shared.v4.u32 [%0], {%1,%2,%3,%4};" :: "r"(a), "r"(x), "r"(y), "r"(z), "r"(w) : "memory"); }
DI void sts64(uint32_t a, uint32_t x, uint32_t y) { asm volatile("st.shared.v2.u32 [%0], {%1,%2};" :: "r"(a), "r"(x), "r"(y) : "memory"); }
DI void sts32(uint32_t a, uint32_t x) { asm volatile("st.shared.u32 [%0], %1;" :: "r"(a), "r"(x) : "memory"); }
DI void sts16(uint32_t a, uint32_t x) { asm volatile("st.shared.u16 [%0], %1;" :: "r"(a), "h"((uint16_t)x) : "memory"); }
DI void lds128(uint32_t* v, uint32_t a) { asm volatile("ld.shared.v4.u32 {%0, %1, %2, %3}, [%4];" : "=r"(v[0]), "=r"(v[1]), "=r"(v[2]), "=r"(v[3]) : "r"(a) : "memory"); }
DI void lds64(uint32_t& x, uint32_t& y, uint32_t a) { asm volatile("ld.shared.v2.u32 {%0, %1}, [%2];" : "=r"(x), "=r"(y) : "r"(a) : "memory"); }
DI uint32_t lds32(uint32_t a) { uint32_t x; asm volatile("ld.shared.u32 %0, [%1];" : "=r"(x) : "r"(a) : "memory"); return x; }
DI uint32_t lds16(uint32_t a) { uint32_t x; asm volatile("ld.shared.u16 %0, [%1];" : "=r"(x) : "r"(a) : "memory"); return x; }
DI uint32_t atoms_add(uint32_t a, uint32_t v) { uint32_t r; asm volatile("atom.shared.add.u32 %0, [%1], %2;" : "=r"(r) : "r"(a), "r"(v) : "memory"); return r; }
DI void bulk_load(uint32_t dst, const void* src, uint32_t bytes, uint32_t bar) {
  asm volatile("cp.async.bulk.shared::cluster.global.mbarrier::complete_tx::bytes.L2::cache_hint [%0], [%1], %2, [%3], %4;" :: "r"(dst), "l"(src), "r"(bytes), "r"(bar), "l"(pol_first()) : "memory"); }
DI void bulk_store(void* dst, uint32_t src, uint32_t bytes) { asm volatile("cp.async.bulk.global.shared::cta.bulk_group [%0], [%1], %2;" :: "l"(dst), "r"(src), "r"(bytes) : "memory"); }
DI void mbar_expect(uint32_t bar, uint32_t bytes) { asm volatile("mbarrier.arrive.expect_tx.shared::cta.b64 _, [%0], %1;" :: "r"(bar), "r"(bytes) : "memory"); }
DI void mbar_init(uint32_t bar, int n) { asm volatile("mbarrier.init.shared::cta.b64 [%0], %1;" :: "r"(bar), "r"(n) : "memory"); }
DI void tma_load(uint32_t dst, uint64_t tm, int row, uint32_t bar) {
  asm volatile("cp.async.bulk.tensor.2d.shared::cluster.global.mbarrier::complete_tx::bytes.L2::cache_hint [%0], [%1, {%3, %4}], [%2], %5;" :: "r"(dst), "l"(tm), "r"(bar), "r"(0), "r"(row), "l"(pol_first()) : "memory"); }
DI void tma_store(uint64_t tm, int col, int row, uint32_t src) {
  asm volatile("cp.async.bulk.tensor.2d.global.shared::cta.bulk_group [%0, {%2, %3}], [%1];" :: "l"(tm), "r"(src), "r"(col), "r"(row) : "memory"); }
DI void bulk_commit() { asm volatile("cp.async.bulk.commit_group;" ::: "memory"); }
DI void bulk_wait_read() { asm volatile("cp.async.bulk.wait_group.read 0;" ::: "memory"); }
DI uint2 ld_poll2(const void* a) { uint2 v; asm volatile("ld.relaxed.gpu.global.v2.u32 {%0, %1}, [%2];" : "=r"(v.x), "=r"(v.y) : "l"(a) : "memory"); return v; }
DI void st_ext(uint2* a, uint32_t v, uint32_t ep) { asm volatile("st.relaxed.gpu.global.v2.u32 [%0], {%1, %2};" :: "l"(a), "r"(v), "r"(ep) : "memory"); }
DI uint32_t ext_get(const uint2* a, uint32_t ep) { uint2 v; int spin = 0; do { v = ld_poll2(a); trap_if(++spin > 4000000); } while (__any_sync(~0u, v.y != ep)); return v.x; }
DI void bulk_wait() { asm volatile("cp.async.bulk.wait_group 0;" ::: "memory"); }
DI void grid_signal(unsigned long long* cnt, bool flag = false) {
  asm volatile("red.release.gpu.global.add.u64 [%0], %1;" :: "l"(cnt), "l"(flag ? (1ull << 44) + 1 : 1ull) : "memory"); }
DI bool grid_wait(unsigned long long* cnt, unsigned long long c0) {
  const unsigned long long M = (1ull << 44) - 1, target = ((c0 & M) / G + 1) * G;
  unsigned long long c; int spin = 0;
  do { asm volatile("ld.acquire.gpu.global.u64 %0, [%1];" : "=l"(c) : "l"(cnt) : "memory"); trap_if(++spin > 4000000); } while (__any_sync(~0u, (c & M) < target));
  return (c ^ c0) >> 44;
}
DI void hint_signal(uint32_t* c) { asm volatile("red.relaxed.gpu.global.add.u32 [%0], 1;" :: "l"(c) : "memory"); }
DI void hint_wait(const uint32_t* c, uint32_t target, uint32_t v) { int spin = 0;
  trap_if(target - __shfl_sync(~0u, v, 0) - 1 >= G);
  do { asm volatile("ld.relaxed.gpu.global.u32 %0, [%1];" : "=r"(v) : "l"(c) : "memory"); trap_if(++spin > 4000000); } while (__any_sync(~0u, (int)(v - target) < 0)); }
DI unsigned long long ld_cnt(const unsigned long long* cnt) { unsigned long long c; asm volatile("ld.relaxed.gpu.global.u64 %0, [%1];" : "=l"(c) : "l"(cnt)); return c; }
DI void stsm4(uint32_t a, uint32_t x, uint32_t y, uint32_t z, uint32_t w) { asm volatile("stmatrix.sync.aligned.m8n8.x4.shared.b16 [%0], {%1,%2,%3,%4};" :: "r"(a), "r"(x), "r"(y), "r"(z), "r"(w) : "memory"); }
DI void ldsm4(uint32_t* v, uint32_t a) { asm volatile("ldmatrix.sync.aligned.m8n8.x4.shared.b16 {%0,%1,%2,%3}, [%4];" : "=r"(v[0]), "=r"(v[1]), "=r"(v[2]), "=r"(v[3]) : "r"(a) : "memory"); }
DI void ldsm4t(uint32_t* v, uint32_t a) { asm volatile("ldmatrix.sync.aligned.m8n8.x4.trans.shared.b16 {%0,%1,%2,%3}, [%4];" : "=r"(v[0]), "=r"(v[1]), "=r"(v[2]), "=r"(v[3]) : "r"(a) : "memory"); }
DI uint32_t mad16(uint32_t x, uint32_t m, uint32_t c) { uint32_t r; asm("dp2a.lo.u32.u32 %0, %1, %2, %3;" : "=r"(r) : "r"(x), "r"(m), "r"(c)); return r; }
DI bool wbad(uint32_t m, uint32_t hi) { return m > hi || (m && m < 0x3980); }

__device__ __noinline__ void slow_path(const Params& p, int wid, int lane, int node0, int nloc) {
  const uint32_t ab = sb + OFF_P2 + wid * 8704;
  for (int i = lane; i < 32 * 68; i += 32) sts32(ab + i * 4, 0);
  __syncwarp();
  const uint32_t wdv = __ldg((const uint32_t*)(p.we + 128 * 64) + lane), wxv = __ldg((const uint32_t*)p.wx + lane);
  const int nb0 = node0 + wid * 32, cntn = max(0, min(32, nloc - wid * 32));
  auto dot = [&](uint32_t hv, const uint16_t* w, int K2, float& y0, float& y1) {
#pragma unroll 4
    for (int k = 0; k < K2; k++) {
      const uint32_t hk = __shfl_sync(~0u, hv, k), wa = __ldg((const uint32_t*)(w + 2 * k * 64) + lane), wb = __ldg((const uint32_t*)(w + (2 * k + 1) * 64) + lane);
      y0 = fmaf(bf_lo(hk), bf_lo(wa), fmaf(bf_hi(hk), bf_lo(wb), y0)); y1 = fmaf(bf_lo(hk), bf_hi(wa), fmaf(bf_hi(hk), bf_hi(wb), y1));
    }
  };
  auto silu = [](float x) { return x / (1.f + __expf(-x)); };
#pragma unroll 1
  for (int base = 0; base < p.E; base += 32) {
    const int e = base + lane;
    const uint32_t dl = e < p.E ? (uint32_t)(__ldg(p.dst + e) - nb0) : 0xFFFFFFFFu;
    uint32_t mk = __ballot_sync(~0u, dl < (uint32_t)cntn);
    while (mk) {
      const int l = __ffs(mk) - 1; mk &= mk - 1;
      const int ee = base + l, n = __shfl_sync(~0u, dl, l), s = __ldg(p.src + ee);
      const uint16_t *po = p.pos + (size_t)(nb0 + n) * 3, *pp = p.pos + (size_t)s * 3;
      const uint32_t dxy = hsub(__ldg(po) | (__ldg(po + 1) << 16), __ldg(pp) | (__ldg(pp + 1) << 16)), dz = hsub(__ldg(po + 2), __ldg(pp + 2));
      const uint32_t sq = hsq(dxy); const float d2 = bf_lo(sq) + bf_hi(sq) + bf_lo(hsq(dz));
      float y0 = d2 * bf_lo(wdv), y1 = d2 * bf_hi(wdv);
      dot(__ldg((const uint32_t*)(p.h + (size_t)(nb0 + n) * 8) + lane), p.we, 32, y0, y1);
      dot(__ldg((const uint32_t*)(p.h + (size_t)s * 8) + lane), p.we + 64 * 64, 32, y0, y1);
      dot(__ldg((const uint32_t*)(p.ea + (size_t)ee * 2) + (lane & 7)), p.we + 129 * 64, 8, y0, y1);
      const uint32_t mm = pack_bf16(silu(y0), silu(y1));
      float c = bf_lo(mm) * bf_lo(wxv) + bf_hi(mm) * bf_hi(wxv);
#pragma unroll
      for (int o = 16; o; o >>= 1) c += __shfl_xor_sync(~0u, c, o);
      const uint32_t a = ab + n * 272;
      uint32_t x0, x1; lds64(x0, x1, a + lane * 8);
      sts64(a + lane * 8, __float_as_uint(__uint_as_float(x0) + bf_lo(mm)), __float_as_uint(__uint_as_float(x1) + bf_hi(mm)));
      if (lane < 3) { const float df = lane == 0 ? bf_lo(dxy) : lane == 1 ? bf_hi(dxy) : bf_lo(dz); sts32(a + 256 + lane * 4, __float_as_uint(fmaf(c, df, __uint_as_float(lds32(a + 256 + lane * 4))))); }
    }
  }
  __syncwarp();
#pragma unroll 1
  for (int n = 0; n < cntn; n++) {
    uint32_t x0, x1; lds64(x0, x1, ab + n * 272 + lane * 8);
    const uint32_t hv = __ldg((const uint32_t*)(p.h + (size_t)(nb0 + n) * 8) + lane);
    float y0 = 0.f, y1 = 0.f;
    dot(hv, p.wh, 32, y0, y1); dot(pack_bf16(__uint_as_float(x0), __uint_as_float(x1)), p.wh + 64 * 64, 32, y0, y1);
    ((uint32_t*)p.out)[(size_t)(nb0 + n) * 32 + lane] = u2(__hadd2(b2(hv), b2(pack_bf16(silu(y0), silu(y1)))));
    if (lane < 3) p.out[(size_t)p.N * 64 + (size_t)(nb0 + n) * 3 + lane] = (uint16_t)pack_bf16(bf_lo(__ldg(p.pos + (size_t)(nb0 + n) * 3 + lane)) + __uint_as_float(lds32(ab + n * 272 + 256 + lane * 4)), 0.f);
  }
}

__global__ void __launch_bounds__(NTHR, 1) egnn_kernel(const __grid_constant__ Params p, const __grid_constant__ Maps maps) {
  const uint64_t tmb = (uint64_t)&maps;
  extern __shared__ __align__(1024) unsigned char smraw[];
  const int tid = threadIdx.x, cta = blockIdx.x;
  const int e0 = cta * p.EPC, n4 = max(0, min(p.EPC, p.E - e0)) >> 2;
  STAMP(0);
  unsigned long long c0 = 0;
  uint32_t s0_ = 0;
  asm volatile("{.reg .pred p, q; setp.eq.u32 p, %4, 384; setp.eq.u32 q, %5, 320; @p ld.relaxed.gpu.global.u64 %0, [%2]; @q ld.relaxed.gpu.global.u32 %1, [%3];}"
    : "+l"(c0), "+r"(s0_) : "l"(p.cnt), "l"(p.sent + (tid & 32)), "r"(tid & 415), "r"(tid & 479));
  if (tid == NWK) {
#pragma unroll
    for (int k = 0; k < NCH; k++) mbar_init(sb + BAR_DST + k * 8, 1);
    asm volatile("fence.mbarrier_init.release.cluster;" ::: "memory");
#pragma unroll 1
    for (int k = 0; k < NCH; k++) { const int nb = max(0, min(NWK, n4 - k * NWK)) * 16;
      mbar_expect(sb + BAR_DST + k * 8, nb);
      if (nb) bulk_load(sb + OFF_DST + k * NWK * 16, (const char*)(p.dst + e0) + k * NWK * 16, nb, sb + BAR_DST + k * 8); }
  }
  const int lane = tid & 31, wid = __shfl_sync(~0u, tid >> 5, 0), w = wid & 3;

  auto first_node = [&](int c) { return (int)((c * p.inv + 0xFFFFFFFFull) >> 32); };
  const int node0 = first_node(cta), nloc = min(first_node(cta + 1), p.N) - node0;
  const uint32_t ealo = (uint32_t)(uint64_t)p.ea;
  const int epad = min(e0, p.E - 1);
  auto load_h = [&](int b) { mbar_expect(sb + BAR_T + b * 8, 8192); tma_load(sb + OFF_H + b * 8192, tmb + TM_H, node0 + b * 64, sb + BAR_T + b * 8); };
  if (wid >= 12) {
    const int t = tid - 384;
    auto prefetch_e = [&](int i) {
      const uint32_t nb = (p.E / G) & ~15u;
      if (nb && i < PFN) asm volatile("cp.async.bulk.prefetch.L2.global [%0], %1;" :: "l"((const char*)p.ea + (size_t)(i * G + cta) * nb), "r"(nb) : "memory");
    };
    uint32_t pv[9], ev = 0;
#pragma unroll
    for (int i = 0; i < 3; i++) { const uint16_t* pp = p.pos + (size_t)(node0 + t + 128 * i) * 3;
      pv[3 * i] = pv[3 * i + 1] = pv[3 * i + 2] = 0;
      asm volatile("{.reg .pred p; setp.lt.s32 p, %4, %5;\n @p ld.global.nc.u16 %0, [%3];\n @p ld.global.nc.u16 %1, [%3+2];\n @p ld.global.nc.u16 %2, [%3+4];}"
        : "+r"(pv[3 * i]), "+r"(pv[3 * i + 1]), "+r"(pv[3 * i + 2]) : "l"(pp), "r"(t + 128 * i), "r"(p.N - node0)); }
    asm volatile("{.reg .pred p; setp.lt.u32 p, %3, 8; @p ld.global.nc.u32 %0, [%1]; @p st.global.v4.u32 [%2], {%4, %4, %4, %4};}"
      : "+r"(ev) : "l"((const uint32_t*)(p.ea + (size_t)epad * 2) + t), "l"(p.q + (size_t)(p.N + cta) * 128 + t * 16), "r"(t), "r"(0xF700F700u) : "memory");
    c0 = __shfl_sync(~0u, c0, 0);
    {
      const uint32_t e = (uint32_t)((c0 & ((1ull << 44) - 1)) / G) + 1, tg = (1 + e % 3) << 30, v = ((tg >> 16) + 512 + (lane & 7) * 4) * 0x10001u;
      if (t == 0) sts32(sb + OFF_MISC + 32, e);
#pragma unroll
      for (int i = 0; i < 9; i++) sts128(sb + OFF_SA + t * 16 + i * 2048, v, v + 0x10001u, v + 0x20002u, v + 0x30003u);
      bar_sync(6, NTHR);
      mbar_arrive(sb + BAR_EP, lane == 0);
#pragma unroll
      for (int i = 0; i < 17; i++) sts128(sb + OFF_SB + t * 16 + i * 2048, tg, tg, tg, tg); }
    uint32_t mp = 0;
#pragma unroll
    for (int i = 0; i < 3; i++) { sts64(sb + OFF_POS + (t + 128 * i) * 8, pv[3 * i] | (pv[3 * i + 1] << 16), pv[3 * i + 2]); mp = mag2(mag2(mp, pv[3 * i] | (pv[3 * i + 1] << 16)), pv[3 * i + 2]); }
    proxy_fence();
    __syncwarp();
    mbar_arrive(sb + BAR_PS, lane == 0);
    mbar_wait(sb + BAR_W);
#pragma unroll
    for (int i = 0; i < 8; i += 4) { uint32_t v[16];
#pragma unroll
      for (int k = 0; k < 4; k++) lds128(v + 4 * k, sb + OFF_W + t * 16 + (i + k) * 2048);
#pragma unroll
      for (int k = 0; k < 4; k++) sts128(sb + OFF_W + t * 16 + (i + k) * 2048, hhalf(v[4 * k]), hhalf(v[4 * k + 1]), hhalf(v[4 * k + 2]), hhalf(v[4 * k + 3])); }
    {
      uint32_t v[4], u[4]; const int r = t >> 3, c = t & 7;
      lds128(v, sb + OFF_WS + 128 + t * 16); lds128(u, sb + OFF_WS + c * 16);
      const uint32_t x = lds32(sb + OFF_WS + 2176 + lane * 4);
      sts128(sb + OFF_W3 + r * 128 + ((c ^ (r & 7)) << 4), b2h(v[0], .5f), b2h(v[1], .5f), b2h(v[2], .5f), b2h(v[3], .5f));
      const float s = ((r & 1) || r == 6) ? 0.f : .5f;
      if (t < 64) sts128(sb + OFF_WD + r * 128 + ((c ^ r) << 4), b2h(u[0], s), b2h(u[1], s), b2h(u[2], s), b2h(u[3], s));
      if (t < 32) sts32(sb + OFF_WX + (t & 3) * 32 + (t >> 2) * 4, b2h(x, 1.f));
      const uint32_t m3 = __reduce_max_sync(~0u, magr(mag2(mag2(mag2(mag2(0, v[0]), v[1]), v[2]), v[3]))), md = __reduce_max_sync(~0u, magr(mag2(mag2(mag2(mag2(0, u[0]), u[1]), u[2]), u[3])));
      if (wbad(m3, 0x4000) || wbad(md, 0x4000) || wbad(__reduce_max_sync(~0u, magr(mag2(0, x))), 0x4700) || magr(mp) >= 0x4200 || magr(mag2(0, ev)) >= 0x4380) sts32(sb + OFF_MISC + 8, 1);
    }
    proxy_fence();
    if (w == 1) STAMP(23);
    if (w == 1) {
#pragma unroll 1
      for (int b = HE; b < HW; b++) { mbar_wait(sb + BAR_SRC + max(0, H0 + b) * 8); if (lane == 0) load_h(b); }
    }
    bar_sync(3, 128);
    STAMP(24);
    const uint32_t frag = (w * 16 + (lane & 15)) * 128 + (((lane >> 4) ^ (lane & 7)) << 4);
    uint32_t mq = 0; mp = 0;
#pragma unroll 1
    for (int b = 0; b < 6; b++) {
      float acc[32], ac2[32];
      const uint64_t da = DHI | (((sb + OFF_H) >> 4) + b * 512), db = DHI | ((sb + OFF_W) >> 4);
      const uint32_t v0 = lds16(sb + OFF_POS + b * 512 + w * 128 + lane * 2), v1 = lds16(sb + OFF_POS + 64 + b * 512 + w * 128 + lane * 2);
      mbar_wait(sb + BAR_T + b * 8);
      if (b == 0) STAMP(25);
      if (b == 5) STAMP(26);
      wg_fence();
      ss64<0>(acc, da, db); ss64<1>(acc, da + 2, db + 128); ss64<1>(acc, da + 4, db + 256); ss64<1>(acc, da + 6, db + 384);
      wg_commit();
      ss64<0>(ac2, da, db + 512); ss64<1>(ac2, da + 2, db + 640); ss64<1>(ac2, da + 4, db + 768); ss64<1>(ac2, da + 6, db + 896);
      wg_commit();
      if (b == 0) mbar_wait(sb + BAR_AW);
      if (t == 32) { if (HALL) { if (b == 0) for (int k = HW; k < 6; k++) load_h(k); } else if (b + HW < 6) load_h(b + HW); }
      __syncwarp();
      uint32_t ff[6], fg[6];
#pragma unroll
      for (int j = 0; j < 6; j++) { ff[j] = (__byte_perm((j & 1) ? v1 : v0, 0, 0x4140) >> (3 * (j >> 1))) & 0x00070007u; fg[j] = __vsub2(0x00040004u, ff[j]);
        asm volatile("" : "+r"(ff[j]), "+r"(fg[j])); }
      asm volatile("wgmma.wait_group.sync.aligned 1;" ::: "memory"); fence_regs(acc);
      uint32_t o[16];
#pragma unroll
      for (int j = 0; j < 16; j++) o[j] = pack_f16(acc[2 * j], acc[2 * j + 1]);
#pragma unroll
      for (int j = 0; j < 6; j++) {
        const uint32_t m = o[j] & 0x7FFF7FFFu; mq = __vmaxu2(mq, m);
        o[j] = (__viaddmax_s16x2(m, fg[j], 0) & 0xFFF8FFF8u) | ff[j] | (o[j] & 0x80008000u); }
      const uint32_t qs = sb + OFF_P2 + (b & 1) * 8192;
#pragma unroll
      for (int j = 0; j < 4; j++) stsm4((qs + frag) ^ (j << 5), o[4 * j], o[4 * j + 1], o[4 * j + 2], o[4 * j + 3]);
      proxy_fence();
      if (b == 5) { const uint32_t m = __reduce_max_sync(~0u, magr(mq)); if (lane == 0) sts32(sb + OFF_MISC + 16 + w * 4, m); }
      bulk_wait_read();
      bar_sync(3, 128);
      if (t == 0) { if (b * 64 < nloc) tma_store(tmb + TM_Q, 0, node0 + b * 64, qs); bulk_commit(); }
      __syncwarp();
      wg_wait0(); fence_regs(ac2);
#pragma unroll
      for (int j = 0; j < 16; j++) { o[j] = pack_f16(ac2[2 * j], ac2[2 * j + 1]); mp = hmag(mp, o[j]); }
      if (!(b & 5)) mbar_wait(sb + BAR_AX + b * 4);
      const uint32_t ps = sb + OFF_PT + b * 8192 + (b < 2 ? PTX : 0);
#pragma unroll
      for (int j = 0; j < 4; j++) stsm4((ps + frag) ^ (j << 5), o[4 * j], o[4 * j + 1], o[4 * j + 2], o[4 * j + 3]);
    }
    if (magr(mp) >= 0x7000) sts32(sb + OFF_MISC + 12, 1);
    __syncwarp();
    mbar_arrive(sb + BAR_BW, lane == 0);
    asm volatile("setmaxnreg.dec.sync.aligned.u32 32;");
    if (w == 0) {
      STAMP(18);
      uint32_t mv[4]; lds128(mv, sb + OFF_MISC + 16);
      const uint32_t mx = max(max(mv[0], mv[1]), max(mv[2], mv[3]));
      bulk_wait();
      mbar_arrive(sb + BAR_QR, lane == 0);
      mbar_wait(sb + BAR_XA);
      STAMP(19);
      if (lane == 0) grid_signal(p.cnt, nloc > 0 && (mx >= 0x7BF0 || mx < 0x1400));
      if (grid_wait(p.cnt, c0)) sts32(sb + OFF_MISC + 8, 1);
      STAMP(20);
      __syncwarp();
      mbar_arrive(sb + BAR_QP, lane == 0);
    }
    if (w == 1) {
      __nanosleep(PF0NS);
#pragma unroll 1
      for (int i = 0; i < PFN; i++) { if (lane == 0) prefetch_e(i); __nanosleep(PFNS); }
    }
    bar_sync(3, 128);
    if (t == 0) { mbar_expect(sb + BAR_U, 16384); tma_load(sb + OFF_W, tmb + TM_WH, 0, sb + BAR_U); tma_load(sb + OFF_W + 8192, tmb + TM_WH, 64, sb + BAR_U); }
    mbar_wait(sb + BAR_U);
    uint32_t mh = 0;
#pragma unroll 1
    for (int i = t; i < 512; i += 128) { uint32_t v[4]; const uint32_t a = sb + OFF_W + i * 16;
      lds128(v, a); sts128(a, hhalf(v[0]), hhalf(v[1]), hhalf(v[2]), hhalf(v[3]));
      lds128(v, a + 8192); sts128(a + 8192, b2h(v[0], .5f), b2h(v[1], .5f), b2h(v[2], .5f), b2h(v[3], .5f));
      mh = mag2(mag2(mag2(mag2(mh, v[0]), v[1]), v[2]), v[3]); }
    if (wbad(__reduce_max_sync(~0u, magr(mh)), 0x4700)) sts32(sb + OFF_MISC + 12, 1);
    proxy_fence();
    __syncwarp();
    mbar_arrive(sb + BAR_WH, lane == 0);
    return;
  }

  auto put = [&](uint32_t x, int hi, uint32_t bv, uint32_t eb) {
    asm volatile("{.reg .pred p; setp.eq.b32 p, %0, 0;\n @p st.shared.u32 [%1], %3;\n @p st.shared.u16 [%2], %4;}"
      :: "r"(x & (0x8000u << 16 * hi)), "r"(sb + OFF_TE + mad16(x, 2 << 8 * hi, 0)), "r"(sb + OFF_TS + (hi ? x >> 16 : x & 0xFFFF)), "r"(mad16(bv, 0x2000u, eb)), "h"((uint16_t)bv) : "memory");
  };
  if (tid == 320) {
    mbar_init(sb + BAR_W, 1);
    asm volatile("fence.mbarrier_init.release.cluster;" ::: "memory");
    mbar_expect(sb + BAR_W, 2 * 8192 + 2304);
    tma_load(sb + OFF_W, tmb + TM_WE, 64, sb + BAR_W); tma_load(sb + OFF_W + 8192, tmb + TM_WE, 0, sb + BAR_W);
    bulk_load(sb + OFF_WS, p.we + 128 * 64, 2176, sb + BAR_W); bulk_load(sb + OFF_WS + 2176, p.wx, 128, sb + BAR_W);
  }
  if (tid == 288) {
#pragma unroll
    for (int a = BAR_SRC; a < BAR_END; a += 8) if (a != BAR_W) mbar_init(sb + a, a == BAR_WH || a == BAR_PS || a == BAR_EP || a == BAR_BW ? 4 : a == BAR_XA ? 11 : 1);
    asm volatile("fence.mbarrier_init.release.cluster;" ::: "memory");
    asm volatile("prefetch.tensormap [%0];" :: "l"(tmb + TM_XA)); asm volatile("prefetch.tensormap [%0];" :: "l"(tmb + TM_H));
    asm volatile("prefetch.tensormap [%0];" :: "l"(tmb + TM_XB)); asm volatile("prefetch.tensormap [%0];" :: "l"(tmb + TM_Q));
  }
  {
    if (tid < 144) { const uint32_t z = (tid >> 3) == 16 ? 0x8000u : 0u; sts128(sb + OFF_CNT + tid * 16, z, z, z, z); }
    else if (tid <= 144 + G) sts32(sb + OFF_BC + (tid - 144) * 4, ((tid - 144) & 31) * 4);
    const uint32_t sp = (p.N + cta) * 0x10001u, em = first_node(G);
    if (wid < 7) {
#pragma unroll
      for (int i = 0; i < 4; i++) sts128(sb + OFF_TS + tid * 16 + i * 3584, sp, sp, sp, sp);
    }
    static_assert(SCAP * 32 == 4 * 3584, "fill");
#pragma unroll 1
    for (int i = n4 + tid; i < 1536; i += 384) sts128(sb + OFF_DST + i * 16, em, em, em, em);
    if (tid == 321) sts128(sb + OFF_MISC, 0, 0, p.force_slow, 0);
  }
  bar_arrive(6, NTHR);
  bar_sync(0, 384);
  uint32_t ep, tag, eb0, pk[12], r0[12], r1[12], cb;
  uint2 vb[12];
  const uint2* xb = (const uint2*)(p.xb + (cta * G + wid) * 16) + ((lane + cta) & 31);
  auto get_tag = [&]() { mbar_wait(sb + BAR_EP); ep = lds32(sb + OFF_MISC + 32); tag = (1 + ep % 3) << 30; eb0 = ealo - (tag >> 11); };
  if (wid == 11) {
    trap_if(sb != (uint32_t)__cvta_generic_to_shared(smraw));
#pragma unroll 1
    for (unsigned long long q = LSEQ; q; q >>= 8) { const int k = (q >> 4) & 7, nb = max(0, min(8192, n4 * 16 - k * 8192));
      mbar_wait(sb + BAR_DST + ((uint32_t)q & 7) * 8);
      if (lane == 0) {
        if (k >= 3) load_h(k - 3);
        else { mbar_expect(sb + BAR_SRC + k * 8, nb);
          if (nb) bulk_load(sb + OFF_SRCI + k * 8192, (const char*)(p.src + e0) + k * 8192, nb, sb + BAR_SRC + k * 8); } } }
    get_tag();
    mbar_wait(sb + BAR_PS);
    bar_sync(12, 384);
    if (lane == 0) { tma_store(tmb + TM_XA, cta * 64, 0, sb + OFF_SA); bulk_commit(); }
    __syncwarp();
    uint32_t xm = 0;
#pragma unroll
    for (int k = 0; k < 5; k++) xm |= (lds32(sb + OFF_BC + min(lane + 32 * k, G - 1) * 4) >= (64 << 9) && lane + 32 * k < G) << k;
    auto ext_send = [&](int pl) {
      uint32_t x = xm;
      for (uint32_t m; (m = __ballot_sync(~0u, x));) {
        const uint32_t l = __ffs(m) - 1, j = l + 32 * (__ffs(__shfl_sync(~0u, x, l)) - 1);
        if (lane == l) x &= x - 1;
        const uint32_t e = min(lds16(sb + OFF_AX + j * 128 + ((4 * l + 2 * lane) & 126)), 6143u);
        st_ext(p.xe + (j * G + cta) * 64 + pl * 32 + lane, pl ? lds32(sb + OFF_SRCI + e * 4) + tag + (e << 16) : (lds32(sb + OFF_DST + e * 4) & 511) | (lds32(sb + OFF_BC + j * 4) & ~511u), ep);
      }
    };
    if (lane == 0) { bulk_wait(); hint_signal(p.sent); STAMP(16); }
    __syncwarp();
    ext_send(0);
    proxy_fence();
    __syncwarp();
    mbar_arrive(sb + BAR_AW, lane == 0);
    bar_sync(13, 384);
    if (!B_HOLD && lane == 0) { tma_store(tmb + TM_XB, cta * 64, 0, sb + OFF_SB); bulk_commit(); }
    __syncwarp();
    ext_send(1);
    mbar_arrive(sb + BAR_AX, lane == 0);
    if (B_HOLD) mbar_wait(sb + (B_HOLD == 1 ? BAR_HA : BAR_XA));
    if (lane == 0) {
      bulk_wait();
#pragma unroll 1
      for (int r = B_HOLD ? 0 : BROWS; r < G; r += BROWS) { tma_store(tmb + TM_XB, cta * 64, r, sb + OFF_SB + r * 256); bulk_commit(); bulk_wait(); }
      hint_signal(p.sent + 32);
      mbar_arrive(sb + BAR_BS);
      STAMP(17);
    }
    __syncwarp();
    hint_wait(p.sent + 32, ep * G, s0_);
    if (lane == 0) { mbar_expect(sb + BAR_HB, G * 256);
#pragma unroll 1
      for (int o = 0; o < 4; o++) bulk_load(sb + OFF_XB + o * (G * 64), (const char*)p.xb + (size_t)(cta * 4 + o) * (G * 64), G * 64, sb + BAR_HB); }
    __syncwarp();
    STAMP(21);
  } else {
    STAMP(15);
    {
      uint32_t d[4 * NCH], jj[4 * NCH], rr[4 * NCH];
      auto count = [&](int k) {
        mbar_wait(sb + BAR_DST + k * 8);
        lds128(d + 4 * k, sb + OFF_DST + (tid + NWK * k) * 16);
#pragma unroll
        for (int i = 4 * k; i < 4 * k + 4; i++) { jj[i] = d[i] * p.magic; rr[i] = atoms_add(__dp4a(jj[i], 0x04000000u, sb + OFF_BC), 0x202u); }
      };
      auto place = [&](int k) {
#pragma unroll
        for (int i = 4 * k; i < 4 * k + 4; i++) {
          const uint32_t o = __dp4a(jj[i], 0x80000000u, rr[i] & 0x807Eu);
          d[i] = (d[i] & 511) | (tag >> 16);
          asm("{.reg .pred p; setp.ge.u32 p, %1, 0x8000; @p add.u32 %0, %2, %3;}" : "+r"(d[i]) : "r"(o), "r"(tid * 4), "r"(NWK * k * 4 + (i & 3)));
          sts16(sb + OFF_SA + o, d[i]); jj[i] = __viaddmin_u32(o, o, G * 256);
        }
      };
      count(0); STAMP(1); count(1); get_tag(); place(0); count(2); place(1); count(3); place(2);
      if (wid < 4) { count(4); place(3); place(4); } else place(3);
      proxy_fence();
      bar_arrive(12, 384);
      STAMP(2);
      mbar_wait(sb + BAR_PS);
      mbar_wait(sb + BAR_SRC); mbar_wait(sb + BAR_SRC + 8); mbar_wait(sb + BAR_SRC + 16);
      STAMP(12);
#pragma unroll
      for (int k = 0; k < NCH; k++) lds128(d + 4 * k, sb + OFF_SRCI + (tid + NWK * k) * 16);
      const uint32_t tb = tag + (tid << 18);
#pragma unroll
      for (int i = 0; i < 4 * NCH; i++) if (i < 4 * NCH - 4 || wid < 4) sts32(sb + OFF_SB + jj[i], d[i] + tb + ((NWK * (i >> 2) * 4 + (i & 3)) << 16));
      proxy_fence();
      bar_arrive(13, 384);
      STAMP(3);
    }
    const uint32_t rot = (lane + cta) & 31;
    cb = sb + OFF_CNT - (tag >> 14);
    {
      const uint32_t* xa = (const uint32_t*)(p.xa + (cta * G + wid) * 8) + rot;
      if (wid < 8) { const uint32_t e_ = ealo + epad * 32;
        mbar_wait(sb + BAR_AX);
#pragma unroll
        for (int i = 0; i < 7; i++) sts128(sb + OFF_TE + tid * 16 + i * 4096, e_, e_, e_, e_); }
      static_assert(SCAP * 64 == 7 * 4096, "fill");
      if (wid == 10) { hint_wait(p.sent, ep * G, s0_); mbar_arrive(sb + BAR_HA, lane == 0); }
      mbar_wait(sb + BAR_HA);
      STAMP(14);
      uint32_t all;
#pragma unroll 1
      for (int spin = 0;; spin++) {
        uint32_t st = 0; all = ~0u;
#pragma unroll
        for (int k = 0; k < 12; k++) asm volatile("ld.relaxed.gpu.global.u32 %0, [%1];" : "=r"(pk[k]) : "l"(xa + k * 352) : "memory");
#pragma unroll
        for (int k = 0; k < 12; k++) { st |= pk[k] ^ (tag | (tag >> 16)); all &= pk[k]; }
        if (!__any_sync(~0u, st & 0xC000C000u)) break;
        trap_if(spin > 2000000);
      }
      if (wid == 0) STAMP(22);
      uint32_t xm = 0; uint2 xv;
      auto xadr = [&]() { return p.xe + (cta * G + wid + 11 * (__ffs(xm) - 1)) * 64 + lane; };
      if (!(__shfl_sync(~0u, all, 31) & 0x2000000u)) {
#pragma unroll
        for (int k = 0; k < 12; k++) xm |= (~pk[k] >> 25 & 1) << k;
        xm = __shfl_sync(~0u, xm, 31);
        xv = ld_poll2(xadr());
      }
#pragma unroll
      for (int k = 0; k < 12; k++) { r0[k] = mad16(pk[k], 0x0004u, cb); r1[k] = mad16(pk[k], 0x0400u, cb); vb[k].x = atoms_add(r0[k], 16); vb[k].y = atoms_add(r1[k], 16); }
      mbar_arrive(sb + BAR_XA, lane == 0);
#pragma unroll
      for (int k = 0; k < 12; k++) pk[k] = __byte_perm(vb[k].x, vb[k].y, 0x5410);
      for (; xm; xm &= xm - 1) {
        if (__any_sync(~0u, xv.y != ep)) xv.x = ext_get(xadr(), ep);
        const uint32_t cn = xv.x >> 9, n = xv.x & 511;
        if (cn > 96) sts32(sb + OFF_MISC + 8, 1);
        else if (lane < cn - 64) {
          const uint32_t r = atoms_add(sb + OFF_CNT + n * 4, 16), idx = atoms_add(sb + OFF_MISC + 4, 1);
          if (idx < 256) sts32(sb + OFF_EXT + idx * 4, n | ((wid + 11 * (__ffs(xm) - 1)) << 9) | (lane << 17) | (min(r >> 4, 255u) << 22));
          else sts32(sb + OFF_MISC + 8, 1);
        }
        xv.y = ~ep;
        __syncwarp();
      }
    }
    STAMP(4);
    if (wid >= 6) bar_arrive(11, NWK);
    if (wid < 6) {
      uint32_t ca[2], ky[2], dr[2], sq[2], ps[4];
#pragma unroll
      for (int i = 0; i < 2; i++) { ca[i] = sb + OFF_CNT + ((node0 + tid + 192 * i) & 511) * 4; lds64(ps[2 * i], ps[2 * i + 1], sb + OFF_POS + (tid + 192 * i) * 8); ps[2 * i + 1] |= (tid + 192 * i) << 16; }
      bar_sync(11, NWK);
      STAMP(5);
#pragma unroll
      for (int i = 0; i < 2; i++) ky[i] = (lds32(ca[i]) + 16) >> 5;
      if (max(ky[0], ky[1]) > 31) sts32(sb + OFF_MISC + 8, 1);
#pragma unroll
      for (int i = 0; i < 2; i++) { ky[i] = min(ky[i], 31u); dr[i] = atoms_add(sb + OFF_DH + ky[i] * 4, 1); }
      bar_sync(10, 192);
      const uint32_t hv = lds32(sb + OFF_DH + lane * 4);
      uint32_t inc = hv;
#pragma unroll
      for (int o = 1; o < 32; o <<= 1) asm("{.reg .pred p; .reg .b32 y; shfl.sync.down.b32 y|p, %0, %1, 31, -1; @p add.u32 %0, %0, y;}" : "+r"(inc) : "r"(o));
#pragma unroll
      for (int i = 0; i < 2; i++) {
        const uint32_t pos = __shfl_sync(~0u, inc - hv, ky[i]) + dr[i];
        const uint32_t ak = (uint32_t)(0x1453AB297860ull >> ((pos >> 5) * 4)) & 15, l = (pos >> 3) & 3;
        sq[i] = (ak >> 2) * 16 + ((ak & 1) ? 3 - l : l) * 4 + (ak & 3);
        dr[i] = pos & 7;
        asm volatile("{.reg .pred p; setp.eq.u32 p, %2, 0; @p st.shared.u8 [%0], %1;}" :: "r"(sb + OFF_LEN + sq[i]), "r"(max(ky[i], 1u)), "r"(dr[i]) : "memory");
        sts64(sb + OFF_GP + sq[i] * 64 + dr[i] * 8, ps[2 * i], ps[2 * i + 1]);
      }
      bar_sync(10, 192);
      const uint32_t ln = lds32(sb + OFF_LEN + min(lane, 11) * 4), tot = __dp4a(ln, 0x01010101u, 0u);
      inc = tot;
#pragma unroll
      for (int o = 1; o < 16; o <<= 1) asm("{.reg .pred p; .reg .b32 y; shfl.sync.up.b32 y|p, %0, %1, 0, -1; @p add.u32 %0, %0, y;}" : "+r"(inc) : "r"(o));
      if (wid == 1) sts32(sb + OFF_CNT + 2048 + lane * 4, 0);
      if (tid < 12) { sts32(sb + OFF_LEN + 64 + tid * 4, inc - tot); if (inc > SCAP) sts32(sb + OFF_MISC + 8, 1); }
#pragma unroll
      for (int i = 0; i < 2; i++) sts32(ca[i], __dp4a(__shfl_sync(~0u, ln, sq[i] >> 2), 0x00010101u >> (24 - 8 * (sq[i] & 3)), __shfl_sync(~0u, inc - tot, sq[i] >> 2)) * 32 + dr[i] * 2);
    }
    bar_arrive(7, 384);
  }
  if (wid == 11) bar_sync(7, 384); else bar_sync(1, NWK);
  STAMP(6);
  if (wid != 11) {
#pragma unroll
    for (int k = 0; k < 12; k++) { r0[k] = lds32(r0[k]); r1[k] = lds32(r1[k]); }
#pragma unroll
    for (int k = 0; k < 12; k++) pk[k] += __byte_perm(r0[k], r1[k], 0x5410);
  }
  mbar_wait(sb + BAR_QR);
  asm volatile("setmaxnreg.inc.sync.aligned.u32 160;");
  uint32_t bad;
  {
    const uint32_t ring = sb + OFF_RING + wid * (NST * STG), p2 = sb + OFF_P2 + wid * 2048;
    uint32_t lens = __shfl_sync(~0u, lds32(sb + OFF_LEN + wid * 4), 0);
    uint32_t rem = __dp4a(lens, 0x20202020u, 0u);
    const uint32_t base = min(lds32(sb + OFF_LEN + 64 + wid * 4), SCAP);
    uint32_t a_s = sb + OFF_TS + base * 32 + (lane >> 3) * 8, a_e = sb + OFF_TE + base * 64 + (lane >> 1) * 4;
    uint32_t k0 = (uint32_t)(uint64_t)p.q + (((lane & 7) ^ ((lane >> 1) & 4)) << 4), k1 = k0 ^ 16, k2 = k0 ^ 32, k3 = k0 ^ 48, ke = ((lane ^ (lane >> 3)) & 1) << 4;
    uint32_t dst0 = ring + (lane >> 3) * 640 + (lane & 7) * 16;
    const uint32_t qhi = (uint32_t)((uint64_t)p.q >> 32), ehi = (uint32_t)((uint64_t)p.ea >> 32);
    uint32_t s0, s1, ev, to = 0, so = 0;
    auto tl_ = [&]() { lds64(s0, s1, a_s + to); asm volatile("ld.shared.u32 %0, [%1]; add.u32 %1, %1, 64;" : "=&r"(ev), "+r"(a_e) :: "memory"); to += 32; };
#define CPQ(LH, x, k, off) "dp2a." LH ".u32.u32 lo, " x ", 0x80000080, " k "; mov.b64 a, {lo, %7}; @p cp.async.cg.shared.global [%0+" #off "], [a], 16;\n"
#define CPE "or.b32 lo, %10, %11; mov.b64 a, {lo, %12}; @p cp.async.cg.shared.global [%0+512], [a], 16;\n"
#define CPA(BODY) asm volatile("{.reg .b32 lo; .reg .b64 a; .reg .pred p; setp.le.u32 p, %8, %9;\n" BODY "}" \
      :: "r"(dst0 + so), "r"(s0), "r"(s1), "r"(k0), "r"(k1), "r"(k2), "r"(k3), "r"(qhi), "r"(to), "r"(rem), "r"(ev), "r"(ke), "r"(ehi) : "memory")
#define CPQ4 CPQ("lo", "%1", "%3", 0) CPQ("hi", "%1", "%4", 128) CPQ("lo", "%2", "%5", 256) CPQ("hi", "%2", "%6", 384) "cp.async.commit_group;"
    auto issue = [&]() { CPA(CPE CPQ4); so = so == (NST - 1) * STG ? 0 : so + STG; };
    const int g = lane >> 2, qd = lane & 3;
    const uint32_t sw = ((lane >> 4) ^ (lane & 7)) << 4, fr = (lane & 15) * 128 + sw;
    uint32_t qa0 = ring + (g & 3) * 640 + qd * 128 + sw, qa1 = qa0 ^ 32, qa2 = qa0 ^ 64, qa3 = qa0 ^ 96;
    uint32_t eadr = ring + 512 + (g & 3) * 640 + qd * 32 + ((((lane >> 4) ^ g) & 1) << 4);
    uint32_t oh0 = g == 2 * qd ? 0x3C00u : g == 2 * qd + 1 ? 0x3C000000u : 0u, oh1 = oh0;
    uint32_t a_g = sb + OFF_GP + wid * 256 + lane * 2;
    uint32_t a_n = sb + OFF_GP + wid * 256 + (lane & 15) * 8 + 6;
    uint32_t a_p = ((lane & 8) ? p2 : sb + OFF_WD) + (lane & 7) * 128 + ((((lane >> 4) ^ lane) & 7) << 4);
    uint32_t a_w = sb + OFF_W3 + fr;
#define OPQ4(A, B, C, D) asm volatile("shfl.sync.bfly.b32 %0, %0, 0, 31, -1; shfl.sync.bfly.b32 %1, %1, 0, 31, -1; shfl.sync.bfly.b32 %2, %2, 0, 31, -1; shfl.sync.bfly.b32 %3, %3, 0, 31, -1;" : "+r"(A), "+r"(B), "+r"(C), "+r"(D))
    asm volatile("shfl.sync.idx.b32 %0, %0, %1, 31, -1;" : "+r"(oh1) : "r"(lane));
    if (OPQ & 1) OPQ4(a_w, oh0, ke, dst0);
    if (OPQ & 2) OPQ4(qa0, qa1, qa2, qa3);
    if (OPQ & 4) OPQ4(k0, k1, k2, k3);
    if (OPQ & 8) OPQ4(a_g, a_n, a_p, eadr);
    uint32_t w3[16], wv[8], bp[16], sp[8], pq[16], sum[8], Y[16], M[16], own, ownp, dpk; uint16_t tl[16], th[16];
    float pacc = 0.f, chk = 0.f;
    auto wload = [&]() {
#pragma unroll
      for (int j = 0; j < 4; j++) ldsm4t(w3 + 4 * j, a_w ^ (j << 5));
      lds128(wv, sb + OFF_WX + (a_g & 6) * 16); lds128(wv + 4, sb + OFF_WX + 16 + (a_g & 6) * 16);
    };
    auto hload = [&](uint32_t (&hf)[16], uint32_t nd) {
      const uint32_t hrow = sb + OFF_H + nd * 128 + (((nd & 7) << 4) ^ ((a_g >> 1) & 16));
#pragma unroll
      for (int j = 0; j < 4; j++) ldsm4(hf + 4 * j, hrow ^ (j << 5));
      return hrow;
    };
    auto bload = [&](uint32_t o) {
#pragma unroll
      for (int j = 0; j < 4; j++) ldsm4t(bp + 4 * j, (a_p ^ (j << 5)) + o);
    };
    {
      const uint32_t an = sb + OFF_GP + wid * 256 + (lane & 7) * 8 + 6, n0 = lds16(an), n1 = lds16(an + 64);
      auto prow = [&](uint32_t n, uint32_t c) { return sb + OFF_PT + n * 128 + (n < 128 ? PTX : 0) + (((n ^ c) & 7) << 4); };
      const uint32_t r0 = (lane & 8) ? prow(n0, lane >> 4) : a_p, r1 = prow(n1, lane >> 3);
      uint32_t r2[4];
#pragma unroll
      for (int j = 0; j < 4; j++) r2[j] = prow(lds16(sb + OFF_GP + wid * 256 + 134 + (lane >> 3) * 8 + j * 32), lane ^ (lane >> 3) ^ (4 * j));
      mbar_wait(sb + BAR_BW);
#pragma unroll
      for (int j = 0; j < 4; j++) { ldsm4t(bp + 4 * j, r0 ^ (j << 5)); lds128(pq + 4 * j, r2[j]); }
      ldsm4t(sp, r1); ldsm4t(sp + 4, r1 ^ 64);
    }
    own = lds16(a_g) * 0x10001u;
    if (wid == 0) STAMP(27);
    mbar_wait(sb + BAR_HB);
    if (__shfl_sync(~0u, lds32(sb + OFF_MISC + 8), 0)) rem = 0;
    else if (wid == 11) {
      const uint32_t nx = __shfl_sync(~0u, lds32(sb + OFF_MISC + 4), 0);
      for (uint32_t k = 0; k < nx; k += 32) {
        const uint32_t x = lds32(sb + OFF_EXT + min(k + lane, nx - 1) * 4), y = ext_get(p.xe + (cta * G + ((x >> 9) & 255)) * 64 + 32 + ((x >> 17) & 31), ep);
        put(lds32(sb + OFF_CNT + (x & 511) * 4) + (x >> 22) * 16, 0, y, eb0 + ((x >> 9) & 255) * p.EPC * 32);
      }
    } else {
#pragma unroll
      for (int k = 0; k < 12; k++) lds64(vb[k].x, vb[k].y, sb + OFF_XB + (wid + 11 * k) * 256 + ((lane + cta) & 31) * 8);
#pragma unroll 1
      for (int spin = 0;; spin++) {
        uint32_t st = 0;
#pragma unroll
        for (int k = 0; k < 12; k++) st |= (vb[k].x ^ tag) | (vb[k].y ^ tag);
        if (!__any_sync(~0u, st >> 30)) break;
        trap_if(spin > 2000000);
#pragma unroll
        for (int k = 0; k < 12; k++) vb[k] = ld_poll2(xb + k * 352);
      }
#pragma unroll
      for (int k = 0; k < 12; k++) { const uint32_t eb = eb0 + (wid + 11 * k) * p.EPC * 32; put(pk[k], 0, vb[k].x, eb); put(pk[k], 1, vb[k].y, eb); }
    }
    STAMP(7);
    wload();
    bar_sync(2, 384);
    uint32_t sv[3 * NST];
#pragma unroll
    for (int i = 0; i < NST; i++) { tl_(); sv[3 * i] = s0; sv[3 * i + 1] = s1; sv[3 * i + 2] = ev; }
#pragma unroll
    for (int j = 0; j < 4; j++) sts128(p2 + lane * 16 + j * 512, pq[4 * j], pq[4 * j + 1], pq[4 * j + 2], pq[4 * j + 3]);
#pragma unroll
    for (int i = 0; i < NST; i++) { to = 32 * i + 32; so = i * STG; ev = sv[3 * i + 2]; CPA(CPE); }
    mbar_wait(sb + BAR_QP);
    STAMP(13);
    bad = __shfl_sync(~0u, lds32(sb + OFF_MISC + 8), 0);
   if (!bad) {
#pragma unroll
    for (int i = 0; i < NST; i++) { to = 32 * i + 32; so = i * STG; s0 = sv[3 * i]; s1 = sv[3 * i + 1]; CPA(CPQ4); }
    so = 0;
    auto body = [&](auto MODE) {
      constexpr int mode = decltype(MODE)::value;
      uint32_t T[16], ef[4], q0, q1, x0, x1, x2; float e0_, e1_, cs[4];
      auto mu = [&](int j) {
#pragma unroll
        for (int i = 2 * j; i < 2 * j + 2; i++) asm volatile("{.reg .b16 l, h; mov.b32 {l, h}, %2; tanh.approx.f16 %0, l; tanh.approx.f16 %1, h;}" : "=h"(tl[i]), "=h"(th[i]) : "r"(Y[i])); };
      auto fi = [&](int j) {
#pragma unroll
        for (int i = 2 * j; i < 2 * j + 2; i++) asm volatile("{.reg .b32 t; mov.b32 t, {%2, %3}; fma.rn.f16x2 %0, %1, t, %1;}" : "=r"(M[i]) : "r"(Y[i]), "h"(tl[i]), "h"(th[i])); };
      auto ad = [&](int j) { asm volatile("add.rn.f16x2 %0, %0, %1; add.rn.f16x2 %0, %0, %2;" : "+r"(sum[j]) : "r"(M[2 * j]), "r"(M[2 * j + 1])); };
      auto he = [&](int j) { asm volatile("mma.sync.aligned.m16n8k16.row.col.f16.f16.f16.f16 {%0,%1}, {%2,%3,%4,%5}, {%6,%7}, {%0,%1};" : "+r"(T[2 * j]), "+r"(T[2 * j + 1]) : "r"(ef[0]), "r"(ef[1]), "r"(ef[2]), "r"(ef[3]), "r"(w3[2 * j]), "r"(w3[2 * j + 1])); };
      auto hs = [&](int j) { asm volatile("mma.sync.aligned.m16n8k16.row.col.f16.f16.f16.f16 {%0,%1}, {%2,%3,%4,%5}, {%6,%7}, {%8,%9};" : "=r"(Y[2 * j]), "=r"(Y[2 * j + 1]) : "r"(q0), "r"(q1), "r"(oh0), "r"(oh1), "r"(bp[2 * j]), "r"(bp[2 * j + 1]), "r"(T[2 * j]), "r"(T[2 * j + 1])); };
      auto hc = [&](int j) {
        if (j) asm volatile("mma.sync.aligned.m16n8k16.row.col.f32.f16.f16.f32 {%0,%1,%2,%3}, {%4,%5,%6,%7}, {%8,%9}, {%0,%1,%2,%3};" : "+f"(cs[0]), "+f"(cs[1]), "+f"(cs[2]), "+f"(cs[3]) : "r"(M[4 * j]), "r"(M[4 * j + 1]), "r"(M[4 * j + 2]), "r"(M[4 * j + 3]), "r"(wv[2 * j]), "r"(wv[2 * j + 1]));
        else asm volatile("mma.sync.aligned.m16n8k16.row.col.f32.f16.f16.f32 {%0,%1,%2,%3}, {%4,%5,%6,%7}, {%8,%9}, {%10,%10,%10,%10};" : "=f"(cs[0]), "=f"(cs[1]), "=f"(cs[2]), "=f"(cs[3]) : "r"(M[0]), "r"(M[1]), "r"(M[2]), "r"(M[3]), "r"(wv[0]), "r"(wv[1]), "f"(0.f)); };
      auto cv = [&](int i) { asm volatile("{.reg .b32 a, b; shl.b32 a, %0, 16; and.b32 b, %0, 0xFFFF0000; cvt.rn.f16x2.f32 %0, b, a;}" : "+r"(ef[i])); };
      auto un = [&]() { asm volatile("shl.b32 %0, %2, 16; and.b32 %1, %2, 0xFFFF0000;" : "=&f"(e0_), "=&f"(e1_) : "r"(dpk)); };
      auto ex0 = [&]() { asm volatile("prmt.b32 %0, %3, %4, 0x6420; prmt.b32 %1, %5, %6, 0x6420; prmt.b32 %2, %7, %8, 0x6420;" : "=&r"(x0), "=&r"(x1), "=&r"(x2) : "r"(T[0]), "r"(T[1]), "r"(T[2]), "r"(T[3]), "r"(T[4]), "r"(T[5])); };
      auto ex1 = [&]() { asm volatile("{.reg .b32 a, b; shl.b32 a, %2, 3; shl.b32 b, %3, 6; lop3.b32 a, %1, a, 0x38383838, 0xD8; lop3.b32 a, a, b, 0xC0C0C0C0, 0xD8; sub.rn.bf16x2 %0, %4, a;}" : "=r"(dpk) : "r"(x0), "r"(x1), "r"(x2), "r"(own)); };
      auto ex2 = [&]() { asm volatile("{.reg .b32 a, b, d, u; .reg .b16 l, h; shl.b32 a, %2, 16; and.b32 b, %2, 0xFFFF0000; cvt.rn.f16x2.f32 d, b, a; mul.rn.f16x2 %0, d, d; mov.b32 {l, h}, d; mov.b32 u, {h, h}; mul.rn.f16x2 %1, u, u;}" : "=&r"(q0), "=&r"(q1) : "r"(dpk)); };
      auto pf = [&]() { asm volatile("fma.rn.f32 %0, %1, %2, %0; fma.rn.f32 %0, %3, %4, %0;" : "+f"(pacc) : "f"(cs[0]), "f"(e0_), "f"(cs[2]), "f"(e1_)); };
#define FX(k) if (FM >> k & 1) asm volatile("pmevent 1;" ::: "memory")
      if (mode == 2) {
        hc(0); mu(3); fi(2); un(); ad(0); ad(1); mu(4); fi(3); hc(1); mu(5); fi(4); ad(2); mu(6); fi(5); ad(3); hc(2); mu(7); fi(6); fi(7); ad(4); ad(5); hc(3); ad(6); ad(7); pf();
        return;
      }
      asm volatile("cp.async.wait_group %0;" :: "n"(NST - 1) : "memory");
      __syncwarp();
      if (mode == 1) STAMP(8);
      ldsm4(ef, eadr + so); ldsm4(T, qa0 + so); ldsm4(T + 4, qa1 + so); ldsm4(T + 8, qa2 + so); ldsm4(T + 12, qa3 + so);
      tl_();
      if (mode == 1) {
        issue();
        cv(0); cv(1); cv(2); cv(3); ex0(); ex1(); ex2();
#pragma unroll
        for (int j = 0; j < 8; j++) { he(j); hs(j); }
        mu(0); mu(1); fi(0); mu(2); fi(1);
        return;
      }
      hc(0); mu(3); fi(2); un(); ad(0); ad(1);
      FX(0);
      mu(4); fi(3); cv(0); cv(1); cv(2); cv(3); ex0(); ex1();
      FX(1);
      he(0); he(1); hc(1); mu(5); fi(4); ex2(); ad(2);
      FX(2);
      hs(0); he(2); mu(6); fi(5); issue(); ad(3);
      FX(3);
      hs(1); he(3); hc(2); mu(7); fi(6);
      FX(4);
      hs(2); hs(3); he(4); he(5); mu(0); fi(7); ad(4); ad(5);
      FX(5);
      hc(3); hs(4); he(6); he(7); mu(1); fi(0); ad(6);
      FX(6);
      hs(5); hs(6); hs(7); mu(2); fi(1); ad(7); pf();
      FX(7);
    };
#pragma unroll
    for (int j = 0; j < 8; j++) sum[j] = 0;
    body(IC<1>());
    int cnt = (lens & 255) - 1;
#pragma unroll 1
    for (int t = 0; t < 8; t++) {
#pragma unroll 1
      for (; cnt > 0; cnt--) body(IC<0>());
      if (!(t & 1)) {
        ownp = own;
        if (t < 6) {
          a_g += 64; own = lds16(a_g) * 0x10001u;
          if (t == 0) {
#pragma unroll
            for (int j = 0; j < 8; j++) bp[2 * j + 1] = sp[j];
          } else bload((a_g & 16) ? (t & 4) * 256 : 0);
          lens >>= 8; cnt = 1;
          continue;
        }
        body(IC<2>()); t++;
        STAMP(9);
      }
      cnt = (lens & 255) - 1;
      { const uint32_t ng = __shfl_sync(~0u, ownp, (a_g >> 1) | 3) >> 16, c3 = (a_g >> 1) & 3;
        asm volatile("{.reg .pred p; setp.lt.u32 p, %2, %3; @p st.global.u16 [%0], %1;}" :: "l"(p.out + (size_t)p.N * 64 + (size_t)node0 * 3 + (ng * 3 + c3)), "h"((uint16_t)pack_bf16(bf_hi(ownp) + pacc, 0.f)), "r"(ng), "r"(c3 < 3 ? nloc : 0) : "memory"); }
      chk = fmaf(pacc, 0.f, chk); pacc = 0.f;
      if (t & 2) {
        uint32_t hf[16]; float acc[32];
        const uint32_t nd = lds16(a_n); a_n += 128;
        const uint32_t hrow = hload(hf, nd);
        const uint64_t b1 = DHI | ((sb + OFF_W) >> 4), b2_ = b1 + 512;
        mbar_wait(sb + BAR_WH);
        wg_fence();
        rs64h<0>(acc, sp[0], sum[0], sp[1], sum[1], b2_); rs64h<1>(acc, sp[2], sum[2], sp[3], sum[3], b2_ + 128); rs64h<1>(acc, sp[4], sum[4], sp[5], sum[5], b2_ + 256); rs64h<1>(acc, sp[6], sum[6], sp[7], sum[7], b2_ + 384);
        rs64b<1>(acc, hf[0], hf[1], hf[2], hf[3], b1); rs64b<1>(acc, hf[4], hf[5], hf[6], hf[7], b1 + 128); rs64b<1>(acc, hf[8], hf[9], hf[10], hf[11], b1 + 256); rs64b<1>(acc, hf[12], hf[13], hf[14], hf[15], b1 + 384);
        wg_commit(); wg_wait0(); fence_regs(acc);
        if (t == 7) STAMP(10);
        chk = fmaf(acc[0], 0.f, fmaf(acc[2], 0.f, chk));
        auto fin = [&](uint32_t x, float y0, float y1) { return u2(__hadd2(b2(x), b2(pack_bf16(silu_h(y0), silu_h(y1))))); };
#pragma unroll
        for (int j = 0; j < 4; j++) stsm4(hrow ^ (j << 5), fin(hf[4 * j], acc[8 * j], acc[8 * j + 1]), fin(hf[4 * j + 1], acc[8 * j + 2], acc[8 * j + 3]), fin(hf[4 * j + 2], acc[8 * j + 4], acc[8 * j + 5]), fin(hf[4 * j + 3], acc[8 * j + 6], acc[8 * j + 7]));
        __syncwarp();
        const uint32_t c8 = (a_g << 3) & 0x70;
#pragma unroll
        for (int j = 0; j < 4; j++) { uint32_t v[4]; const uint32_t n = __shfl_sync(~0u, nd, 4 * j + ((a_g >> 4) & 3)); lds128(v, sb + OFF_H + n * 128 + (((n << 4) ^ c8) & 0x70));
          asm volatile("{.reg .pred p; setp.lt.u32 p, %5, %6; @p st.global.v4.b32 [%0], {%1,%2,%3,%4};}" :: "l"((const char*)p.out + (size_t)node0 * 128 + (n * 128 + c8)), "r"(v[0]), "r"(v[1]), "r"(v[2]), "r"(v[3]), "r"(n), "r"(nloc) : "memory"); }
        wload();
      }
#pragma unroll
      for (int j = 0; j < 8; j++) { sp[j] = sum[j]; asm volatile("mov.b32 %0, 0;" : "=r"(sum[j])); }
    }
    asm volatile("{.reg .pred p, q; setp.neu.f32 p, %1, 0f00000000; setp.ne.or.u32 p, %2, 0, p; bar.red.or.pred q, 5, 384, p; selp.u32 %0, 1, 0, q;}" : "=r"(bad) : "f"(chk), "r"(lds32(sb + OFF_MISC + 12)) : "memory");
    STAMP(11);
   } else { asm volatile("cp.async.wait_all;" ::: "memory"); bar_sync(5, 384); }
  }
  if (bad) slow_path(p, wid, lane, node0, nloc);
}

}

typedef CUresult (*EncodeFn)(CUtensorMap*, CUtensorMapDataType, cuuint32_t, void*, const cuuint64_t*, const cuuint64_t*, const cuuint32_t*, const cuuint32_t*,
                             CUtensorMapInterleave, CUtensorMapSwizzle, CUtensorMapL2promotion, CUtensorMapFloatOOBfill);

extern "C" void kernel_launch(void* const* d_in, const int* in_sizes, int n_in, void* d_out, int out_size) {
  Params p; Maps maps;
  p.h = (const uint4*)d_in[0]; p.pos = (const uint16_t*)d_in[1]; p.ea = (const uint4*)d_in[2];
  p.src = (const int*)d_in[3]; p.dst = (const int*)d_in[4];
  p.we = (const uint16_t*)d_in[5]; p.wx = (const uint16_t*)d_in[6]; p.wh = (const uint16_t*)d_in[7];
  p.out = (uint16_t*)d_out;
  p.N = in_sizes[0] / 64; p.E = in_sizes[3];
  p.EPC = ((p.E + G * 4 - 1) / (G * 4)) * 4;
  p.magic = (uint32_t)(((uint64_t)G << 24) / (uint64_t)p.N);
  p.inv = (1ull << 56) / p.magic;
  const uint64_t ea0 = (uint64_t)d_in[2], ea1 = ea0 + (uint64_t)p.E * 32 - 1;
  p.force_slow = ((ea0 >> 32) != (ea1 >> 32)) || (ea0 & 31) || (p.E & 3);
  void* qp = nullptr;
  cudaGetSymbolAddress(&qp, g_q);
  p.q = (char*)qp;
  if (((uint64_t)p.q >> 32) != (((uint64_t)p.q + QBYTES) >> 32)) p.q += QBYTES;
  cudaGetSymbolAddress((void**)&p.cnt, g_cnt); cudaGetSymbolAddress((void**)&p.sent, g_sent); cudaGetSymbolAddress((void**)&p.xe, g_xe);
  cudaGetSymbolAddress((void**)&p.xa, g_xa); cudaGetSymbolAddress((void**)&p.xb, g_xb);
  void* fn = nullptr; cudaDriverEntryPointQueryResult qr;
  cudaGetDriverEntryPoint("cuTensorMapEncodeTiled", &fn, cudaEnableDefault, &qr);
  auto mk = [&](CUtensorMap* tm, void* base, int rows) {
    const cuuint64_t dim[2] = {64, (cuuint64_t)rows}, str[1] = {128}; const cuuint32_t bx[2] = {64, 64}, es[2] = {1, 1};
    ((EncodeFn)fn)(tm, CU_TENSOR_MAP_DATA_TYPE_BFLOAT16, 2, base, dim, str, bx, es, CU_TENSOR_MAP_INTERLEAVE_NONE, CU_TENSOR_MAP_SWIZZLE_128B,
                   CU_TENSOR_MAP_L2_PROMOTION_NONE, CU_TENSOR_MAP_FLOAT_OOB_FILL_NONE);
  };
  mk(&maps.m[TM_H / 128], d_in[0], p.N); mk(&maps.m[TM_WE / 128], d_in[5], 145); mk(&maps.m[TM_WH / 128], d_in[7], 128); mk(&maps.m[TM_Q / 128], p.q, p.N);
  for (int k = 0; k < 2; k++) {
    void* xp = (void*)(k ? p.xb : p.xa);
    const cuuint64_t dim[2] = {(cuuint64_t)G * 64, (cuuint64_t)G}, str[1] = {(cuuint64_t)G * (128 << k)}; const cuuint32_t bx[2] = {64, (cuuint32_t)(k ? BROWS : G)}, es[2] = {1, 1};
    ((EncodeFn)fn)(&maps.m[TM_XA / 128 + k], k ? CU_TENSOR_MAP_DATA_TYPE_UINT32 : CU_TENSOR_MAP_DATA_TYPE_UINT16, 2, xp, dim, str, bx, es, CU_TENSOR_MAP_INTERLEAVE_NONE,
                   CU_TENSOR_MAP_SWIZZLE_NONE, CU_TENSOR_MAP_L2_PROMOTION_NONE, CU_TENSOR_MAP_FLOAT_OOB_FILL_NONE);
  }
  cudaFuncSetAttribute(egnn_kernel, cudaFuncAttributeMaxDynamicSharedMemorySize, SMEM);
  egnn_kernel<<<G, NTHR, SMEM>>>(p, maps);
}
```

```cpp
#include <cuda_runtime.h>
#include <cuda_bf16.h>
#include <cuda_fp16.h>
#include <cuda.h>
#include <stdint.h>
#pragma nv_diag_suppress 549

#define PFN 16
#define PFNS 250
#define FM 0
#define OPQ 0
#define H0 0
#define HALL 0
#define PF0NS 0
#define PFW 0
#define QCODE 0x254a109b7863ull
#define QREV 0x605
#define PFS 1
#define ESZ ""
#define XEF 0
#define OCS ""
#define HW 3
#define BROWS 132
#define B_HOLD 1
#define LSEQ 0x231200ull
#define HE 0
namespace {

constexpr int G = 132;
constexpr int NTHR = 512, NWK = 352, NCH = 5;
constexpr int NST = 3, STG = 2560;
constexpr int SCAP = 448;

constexpr int OFF_H = 0;
constexpr int OFF_W = 49152;
constexpr int OFF_WD = OFF_W + 16384;
constexpr int OFF_W3 = OFF_WD + 1024;
constexpr int OFF_P2 = OFF_W3 + 2048;
constexpr int OFF_RING = OFF_P2 + 24576;
constexpr int OFF_TE = OFF_RING + 12 * NST * STG;
constexpr int OFF_TS = OFF_TE + SCAP * 64;
constexpr int OFF_GP = OFF_TS + SCAP * 32;
constexpr int OFF_WX = OFF_GP + 3072;
constexpr int OFF_LEN = OFF_WX + 128;
constexpr int OFF_MISC = OFF_LEN + 128;
constexpr int OFF_BAR = OFF_MISC + 48;
constexpr int SMEM = OFF_BAR + 256;
static_assert(SMEM <= 232448, "smem");
constexpr uint32_t sb = 1024;
constexpr int OFF_SRCI = OFF_TE;
constexpr int OFF_SB = OFF_RING, OFF_SA = OFF_SB + 34816, OFF_AX = OFF_SA + 32768, OFF_DST = OFF_H + 24576;
constexpr int OFF_XB = OFF_SB;
constexpr int OFF_WS = OFF_AX + 17408;
constexpr int OFF_BC = OFF_WS + 2304;
constexpr int OFF_CNT = OFF_P2 + 16384;
constexpr int OFF_DH = OFF_CNT + 2176;
constexpr int OFF_POS = OFF_DH + 128;
constexpr int OFF_EXT = OFF_POS + 3072;
static_assert(OFF_XB + G * 256 <= OFF_AX && OFF_EXT + 1024 <= OFF_RING && OFF_BC + 544 <= OFF_TE && OFF_P2 % 1024 == 0 && OFF_SA % 1024 == 0 && SCAP * 64 >= 24576, "staging");
constexpr int BAR_DST = OFF_BAR, BAR_SRC = BAR_DST + 40, BAR_T = BAR_SRC + 24, BAR_W = BAR_T + 48, BAR_XA = BAR_W + 8, BAR_PS = BAR_XA + 8, BAR_AW = BAR_PS + 8,
              BAR_QP = BAR_AW + 8, BAR_QR = BAR_QP + 8, BAR_HA = BAR_QR + 8, BAR_EP = BAR_HA + 8, BAR_AX = BAR_EP + 8, BAR_HB = BAR_AX + 8, BAR_U = BAR_HB + 8, BAR_WH = BAR_U + 8, BAR_END = BAR_WH + 8;
constexpr uint32_t QBYTES = 8u << 20;

__device__ __align__(256) uint4 g_xa[G * G * 8];
__device__ __align__(256) uint4 g_xb[G * G * 16];
__device__ __align__(256) uint2 g_xe[G * G * 64];
__device__ __align__(256) uint4 g_q[2 * QBYTES / 16];
__device__ __align__(256) uint32_t g_sync[8];
#define STAMP(k)

struct Maps { CUtensorMap m[6]; };
constexpr int TM_H = 0, TM_WE = 128, TM_WH = 256, TM_Q = 384, TM_XA = 512, TM_XB = 640;
struct Params {
  const uint4* h; const uint16_t* pos; const uint4* ea; const int* src; const int* dst;
  const uint16_t* we; const uint16_t* wx; const uint16_t* wh; uint16_t* out; char* q;
  uint32_t* sync; const uint4* xa; const uint4* xb; uint2* xe;
  int N, E, EPC; uint32_t magic; int force_slow; unsigned long long inv;
};
template<int V> struct IC { static constexpr int value = V; };

#define R32(d) "+f"(d[0]),"+f"(d[1]),"+f"(d[2]),"+f"(d[3]),"+f"(d[4]),"+f"(d[5]),"+f"(d[6]),"+f"(d[7]),"+f"(d[8]),"+f"(d[9]),"+f"(d[10]),"+f"(d[11]),"+f"(d[12]),"+f"(d[13]),"+f"(d[14]),"+f"(d[15]),"+f"(d[16]),"+f"(d[17]),"+f"(d[18]),"+f"(d[19]),"+f"(d[20]),"+f"(d[21]),"+f"(d[22]),"+f"(d[23]),"+f"(d[24]),"+f"(d[25]),"+f"(d[26]),"+f"(d[27]),"+f"(d[28]),"+f"(d[29]),"+f"(d[30]),"+f"(d[31])
#define S32 "{%0,%1,%2,%3,%4,%5,%6,%7,%8,%9,%10,%11,%12,%13,%14,%15,%16,%17,%18,%19,%20,%21,%22,%23,%24,%25,%26,%27,%28,%29,%30,%31}"
#define DI __device__ __forceinline__

constexpr uint64_t DHI = ((uint64_t)(1024 >> 4) << 32) | (1ull << 62);
template<int SD> DI void rs64b(float (&d)[32], uint32_t a0, uint32_t a1, uint32_t a2, uint32_t a3, uint64_t db) {
  asm volatile("wgmma.mma_async.sync.aligned.m64n64k16.f32.bf16.bf16 " S32 ", {%32,%33,%34,%35}, %36, %37, 1, 1, 1;" : R32(d) : "r"(a0), "r"(a1), "r"(a2), "r"(a3), "l"(db), "n"(SD)); }
template<int SD> DI void rs64h(float (&d)[32], uint32_t a0, uint32_t a1, uint32_t a2, uint32_t a3, uint64_t db) {
  asm volatile("wgmma.mma_async.sync.aligned.m64n64k16.f32.f16.f16 " S32 ", {%32,%33,%34,%35}, %36, %37, 1, 1, 1;" : R32(d) : "r"(a0), "r"(a1), "r"(a2), "r"(a3), "l"(db), "n"(SD)); }
template<int SD> DI void ss64(float (&d)[32], uint64_t da, uint64_t db) {
  asm volatile("wgmma.mma_async.sync.aligned.m64n64k16.f32.bf16.bf16 " S32 ", %32, %33, %34, 1, 1, 0, 1;" : R32(d) : "l"(da), "l"(db), "n"(SD)); }
DI void trap_if(bool c) { asm volatile("{.reg .pred p; setp.eq.u32 p, %0, 0; @p bra.uni LT_%=; trap; LT_%=:}" :: "r"((uint32_t)c)); }
DI void wg_fence() { asm volatile("wgmma.fence.sync.aligned;" ::: "memory"); }
DI void wg_commit() { asm volatile("wgmma.commit_group.sync.aligned;" ::: "memory"); }
DI void wg_wait0() { asm volatile("wgmma.wait_group.sync.aligned 0;" ::: "memory"); }
DI void fence_regs(float (&d)[32]) { asm volatile("" : R32(d) :: "memory"); }
DI void proxy_fence() { asm volatile("fence.proxy.async.shared::cta;" ::: "memory"); }
DI uint64_t pol_first() { uint64_t r; asm("createpolicy.fractional.L2::evict_first.b64 %0, 1.0;" : "=l"(r)); return r; }
DI float tanh_ap(float x) { float y; asm("tanh.approx.f32 %0, %1;" : "=f"(y) : "f"(x)); return y; }
DI float silu_h(float y) { return fmaf(y, tanh_ap(y), y); }
DI uint32_t pack_bf16(float lo, float hi) { uint32_t r; asm("cvt.rn.bf16x2.f32 %0, %1, %2;" : "=r"(r) : "f"(hi), "f"(lo)); return r; }
DI uint32_t pack_f16(float lo, float hi) { uint32_t r; asm("cvt.rn.f16x2.f32 %0, %1, %2;" : "=r"(r) : "f"(hi), "f"(lo)); return r; }
DI float bf_lo(uint32_t v) { return __uint_as_float(v << 16); }
DI float bf_hi(uint32_t v) { return __uint_as_float(v & 0xFFFF0000u); }
DI uint32_t b2h(uint32_t v, float s) { return pack_f16(s * bf_lo(v), s * bf_hi(v)); }
DI void mbar_wait(uint32_t bar, uint32_t parity = 0) {
  asm volatile("{.reg .pred p; .reg .u32 t0, t1;\n"
    "mbarrier.try_wait.parity.shared::cta.b64 p, [%0], %1;\n @p bra.uni LD_%=;\n mov.u32 t0, %%clock;\n"
    "LW_%=: mbarrier.try_wait.parity.shared::cta.b64 p, [%0], %1;\n"
    "@p bra.uni LD_%=;\n mov.u32 t1, %%clock; sub.u32 t1, t1, t0; setp.lt.u32 p, t1, 0x80000000;\n @p bra.uni LW_%=;\n trap;\n LD_%=:}" :: "r"(bar), "r"(parity) : "memory");
}
DI void mbar_arrive(uint32_t bar, int p = 1) { asm volatile("{.reg .pred p; setp.ne.b32 p, %1, 0; @p mbarrier.arrive.shared::cta.b64 _, [%0];}" :: "r"(bar), "r"(p) : "memory"); }
DI void bar_sync(int id, int n) { asm volatile("bar.sync %0, %1;" :: "r"(id), "r"(n) : "memory"); }
DI void bar_arrive(int id, int n) { asm volatile("bar.arrive %0, %1;" :: "r"(id), "r"(n) : "memory"); }
DI __nv_bfloat162 b2(uint32_t v) { return *(__nv_bfloat162*)&v; }
DI uint32_t u2(__nv_bfloat162 v) { return *(uint32_t*)&v; }
DI uint32_t hsq(uint32_t v) { return u2(__hmul2(b2(v), b2(v))); }
DI uint32_t hsub(uint32_t a, uint32_t b) { return u2(__hsub2(b2(a), b2(b))); }
DI uint32_t hhalf(uint32_t v) { return u2(__hmul2(b2(v), __floats2bfloat162_rn(0.5f, 0.5f))); }
DI uint32_t mag2(uint32_t m, uint32_t v) { return __vmaxu2(m, v & 0x7FFF7FFFu); }
DI uint32_t hmag(uint32_t m, uint32_t v) { const __half2 r = __hmax2(*(const __half2*)&m, __habs2(*(const __half2*)&v)); return *(const uint32_t*)&r; }
DI uint32_t magr(uint32_t m) { return max(m & 0xFFFF, m >> 16); }
DI void sts128(uint32_t a, uint32_t x, uint32_t y, uint32_t z, uint32_t w) { asm volatile("st.shared.v4.u32 [%0], {%1,%2,%3,%4};" :: "r"(a), "r"(x), "r"(y), "r"(z), "r"(w) : "memory"); }
DI void sts64(uint32_t a, uint32_t x, uint32_t y) { asm volatile("st.shared.v2.u32 [%0], {%1,%2};" :: "r"(a), "r"(x), "r"(y) : "memory"); }
DI void sts32(uint32_t a, uint32_t x) { asm volatile("st.shared.u32 [%0], %1;" :: "r"(a), "r"(x) : "memory"); }
DI void sts16(uint32_t a, uint32_t x) { asm volatile("st.shared.u16 [%0], %1;" :: "r"(a), "h"((uint16_t)x) : "memory"); }
DI void lds128(uint32_t* v, uint32_t a) { asm volatile("ld.shared.v4.u32 {%0, %1, %2, %3}, [%4];" : "=r"(v[0]), "=r"(v[1]), "=r"(v[2]), "=r"(v[3]) : "r"(a) : "memory"); }
DI void lds64(uint32_t& x, uint32_t& y, uint32_t a) { asm volatile("ld.shared.v2.u32 {%0, %1}, [%2];" : "=r"(x), "=r"(y) : "r"(a) : "memory"); }
DI uint32_t lds32(uint32_t a) { uint32_t x; asm volatile("ld.shared.u32 %0, [%1];" : "=r"(x) : "r"(a) : "memory"); return x; }
DI uint32_t lds16(uint32_t a) { uint32_t x; asm volatile("ld.shared.u16 %0, [%1];" : "=r"(x) : "r"(a) : "memory"); return x; }
DI uint32_t atoms_add(uint32_t a, uint32_t v) { uint32_t r; asm volatile("atom.shared.add.u32 %0, [%1], %2;" : "=r"(r) : "r"(a), "r"(v) : "memory"); return r; }
DI void bulk_load(uint32_t dst, const void* src, uint32_t bytes, uint32_t bar) {
  asm volatile("cp.async.bulk.shared::cluster.global.mbarrier::complete_tx::bytes.L2::cache_hint [%0], [%1], %2, [%3], %4;" :: "r"(dst), "l"(src), "r"(bytes), "r"(bar), "l"(pol_first()) : "memory"); }
DI void bulk_store(void* dst, uint32_t src, uint32_t bytes) { asm volatile("cp.async.bulk.global.shared::cta.bulk_group [%0], [%1], %2;" :: "l"(dst), "r"(src), "r"(bytes) : "memory"); }
DI void mbar_expect(uint32_t bar, uint32_t bytes) { asm volatile("mbarrier.arrive.expect_tx.shared::cta.b64 _, [%0], %1;" :: "r"(bar), "r"(bytes) : "memory"); }
DI void mbar_init(uint32_t bar, int n) { asm volatile("mbarrier.init.shared::cta.b64 [%0], %1;" :: "r"(bar), "r"(n) : "memory"); }
DI void tma_load(uint32_t dst, uint64_t tm, int row, uint32_t bar) {
  asm volatile("cp.async.bulk.tensor.2d.shared::cluster.global.mbarrier::complete_tx::bytes.L2::cache_hint [%0], [%1, {%3, %4}], [%2], %5;" :: "r"(dst), "l"(tm), "r"(bar), "r"(0), "r"(row), "l"(pol_first()) : "memory"); }
DI void tma_store(uint64_t tm, int col, int row, uint32_t src) {
  asm volatile("cp.async.bulk.tensor.2d.global.shared::cta.bulk_group [%0, {%2, %3}], [%1];" :: "l"(tm), "r"(src), "r"(col), "r"(row) : "memory"); }
DI void tma_store_ef(uint64_t tm, int col, int row, uint32_t src) {
  if (XEF) asm volatile("cp.async.bulk.tensor.2d.global.shared::cta.bulk_group.L2::cache_hint [%0, {%2, %3}], [%1], %4;" :: "l"(tm), "r"(src), "r"(col), "r"(row), "l"(pol_first()) : "memory");
  else tma_store(tm, col, row, src); }
DI void bulk_commit() { asm volatile("cp.async.bulk.commit_group;" ::: "memory"); }
DI void bulk_wait_read() { asm volatile("cp.async.bulk.wait_group.read 0;" ::: "memory"); }
DI uint2 ld_poll2(const void* a) { uint2 v; asm volatile("ld.relaxed.gpu.global.v2.u32 {%0, %1}, [%2];" : "=r"(v.x), "=r"(v.y) : "l"(a) : "memory"); return v; }
DI void st_ext(uint2* a, uint32_t v, uint32_t ep) { asm volatile("st.relaxed.gpu.global.v2.u32 [%0], {%1, %2};" :: "l"(a), "r"(v), "r"(ep) : "memory"); }
DI uint32_t ext_get(const uint2* a, uint32_t ep) { uint2 v; int spin = 0; do { v = ld_poll2(a); trap_if(++spin > 4000000); } while (__any_sync(~0u, v.y != ep)); return v.x; }
DI void bulk_wait() { asm volatile("cp.async.bulk.wait_group 0;" ::: "memory"); }
DI void hint_signal(uint32_t* c) { asm volatile("red.relaxed.gpu.global.add.u32 [%0], 1;" :: "l"(c) : "memory"); }
DI void hint_wait(const uint32_t* c, uint32_t target) { uint32_t v; int spin = 0;
  do { asm volatile("ld.relaxed.gpu.global.u32 %0, [%1];" : "=r"(v) : "l"(c) : "memory"); trap_if(++spin > 4000000); } while (__any_sync(~0u, (int)(v - target) < 0)); }
DI void stsm4(uint32_t a, uint32_t x, uint32_t y, uint32_t z, uint32_t w) { asm volatile("stmatrix.sync.aligned.m8n8.x4.shared.b16 [%0], {%1,%2,%3,%4};" :: "r"(a), "r"(x), "r"(y), "r"(z), "r"(w) : "memory"); }
DI void ldsm4(uint32_t* v, uint32_t a) { asm volatile("ldmatrix.sync.aligned.m8n8.x4.shared.b16 {%0,%1,%2,%3}, [%4];" : "=r"(v[0]), "=r"(v[1]), "=r"(v[2]), "=r"(v[3]) : "r"(a) : "memory"); }
DI void ldsm4t(uint32_t* v, uint32_t a) { asm volatile("ldmatrix.sync.aligned.m8n8.x4.trans.shared.b16 {%0,%1,%2,%3}, [%4];" : "=r"(v[0]), "=r"(v[1]), "=r"(v[2]), "=r"(v[3]) : "r"(a) : "memory"); }
DI uint32_t mad16(uint32_t x, uint32_t m, uint32_t c) { uint32_t r; asm("dp2a.lo.u32.u32 %0, %1, %2, %3;" : "=r"(r) : "r"(x), "r"(m), "r"(c)); return r; }
DI bool wbad(uint32_t m, uint32_t hi) { return m > hi || (m && m < 0x3980); }

__device__ __noinline__ void slow_path(const Params& p, int wid, int lane, int node0, int nloc) {
  const uint32_t ab = sb + OFF_P2 + wid * 8704;
  for (int i = lane; i < 32 * 68; i += 32) sts32(ab + i * 4, 0);
  __syncwarp();
  const uint32_t wdv = __ldg((const uint32_t*)(p.we + 128 * 64) + lane), wxv = __ldg((const uint32_t*)p.wx + lane);
  const int nb0 = node0 + wid * 32, cntn = max(0, min(32, nloc - wid * 32));
  auto dot = [&](uint32_t hv, const uint16_t* w, int K2, float& y0, float& y1) {
#pragma unroll 4
    for (int k = 0; k < K2; k++) {
      const uint32_t hk = __shfl_sync(~0u, hv, k), wa = __ldg((const uint32_t*)(w + 2 * k * 64) + lane), wb = __ldg((const uint32_t*)(w + (2 * k + 1) * 64) + lane);
      y0 = fmaf(bf_lo(hk), bf_lo(wa), fmaf(bf_hi(hk), bf_lo(wb), y0)); y1 = fmaf(bf_lo(hk), bf_hi(wa), fmaf(bf_hi(hk), bf_hi(wb), y1));
    }
  };
  auto silu = [](float x) { return x / (1.f + __expf(-x)); };
#pragma unroll 1
  for (int base = 0; base < p.E; base += 32) {
    const int e = base + lane;
    const uint32_t dl = e < p.E ? (uint32_t)(__ldg(p.dst + e) - nb0) : 0xFFFFFFFFu;
    uint32_t mk = __ballot_sync(~0u, dl < (uint32_t)cntn);
    while (mk) {
      const int l = __ffs(mk) - 1; mk &= mk - 1;
      const int ee = base + l, n = __shfl_sync(~0u, dl, l), s = __ldg(p.src + ee);
      const uint16_t *po = p.pos + (size_t)(nb0 + n) * 3, *pp = p.pos + (size_t)s * 3;
      const uint32_t dxy = hsub(__ldg(po) | (__ldg(po + 1) << 16), __ldg(pp) | (__ldg(pp + 1) << 16)), dz = hsub(__ldg(po + 2), __ldg(pp + 2));
      const uint32_t sq = hsq(dxy); const float d2 = bf_lo(sq) + bf_hi(sq) + bf_lo(hsq(dz));
      float y0 = d2 * bf_lo(wdv), y1 = d2 * bf_hi(wdv);
      dot(__ldg((const uint32_t*)(p.h + (size_t)(nb0 + n) * 8) + lane), p.we, 32, y0, y1);
      dot(__ldg((const uint32_t*)(p.h + (size_t)s * 8) + lane), p.we + 64 * 64, 32, y0, y1);
      dot(__ldg((const uint32_t*)(p.ea + (size_t)ee * 2) + (lane & 7)), p.we + 129 * 64, 8, y0, y1);
      const uint32_t mm = pack_bf16(silu(y0), silu(y1));
      float c = bf_lo(mm) * bf_lo(wxv) + bf_hi(mm) * bf_hi(wxv);
#pragma unroll
      for (int o = 16; o; o >>= 1) c += __shfl_xor_sync(~0u, c, o);
      const uint32_t a = ab + n * 272;
      uint32_t x0, x1; lds64(x0, x1, a + lane * 8);
      sts64(a + lane * 8, __float_as_uint(__uint_as_float(x0) + bf_lo(mm)), __float_as_uint(__uint_as_float(x1) + bf_hi(mm)));
      if (lane < 3) { const float df = lane == 0 ? bf_lo(dxy) : lane == 1 ? bf_hi(dxy) : bf_lo(dz); sts32(a + 256 + lane * 4, __float_as_uint(fmaf(c, df, __uint_as_float(lds32(a + 256 + lane * 4))))); }
    }
  }
  __syncwarp();
#pragma unroll 1
  for (int n = 0; n < cntn; n++) {
    uint32_t x0, x1; lds64(x0, x1, ab + n * 272 + lane * 8);
    const uint32_t hv = __ldg((const uint32_t*)(p.h + (size_t)(nb0 + n) * 8) + lane);
    float y0 = 0.f, y1 = 0.f;
    dot(hv, p.wh, 32, y0, y1); dot(pack_bf16(__uint_as_float(x0), __uint_as_float(x1)), p.wh + 64 * 64, 32, y0, y1);
    ((uint32_t*)p.out)[(size_t)(nb0 + n) * 32 + lane] = u2(__hadd2(b2(hv), b2(pack_bf16(silu(y0), silu(y1)))));
    if (lane < 3) p.out[(size_t)p.N * 64 + (size_t)(nb0 + n) * 3 + lane] = (uint16_t)pack_bf16(bf_lo(__ldg(p.pos + (size_t)(nb0 + n) * 3 + lane)) + __uint_as_float(lds32(ab + n * 272 + 256 + lane * 4)), 0.f);
  }
}

__global__ void __launch_bounds__(NTHR, 1) egnn_kernel(const __grid_constant__ Params p, const __grid_constant__ Maps maps) {
  const uint64_t tmb = (uint64_t)&maps;
  extern __shared__ __align__(1024) unsigned char smraw[];
  const int tid = threadIdx.x, cta = blockIdx.x;
  const int e0 = cta * p.EPC, n4 = max(0, min(p.EPC, p.E - e0)) >> 2;
  STAMP(0);
  uint32_t c0 = 0;
  asm volatile("{.reg .pred p; setp.eq.u32 p, %2, 384; @p ld.relaxed.gpu.global.u32 %0, [%1+8];}" : "+r"(c0) : "l"(p.sync), "r"(tid & 415));
  if (tid == NWK) {
#pragma unroll
    for (int k = 0; k < NCH; k++) mbar_init(sb + BAR_DST + k * 8, 1);
    asm volatile("fence.mbarrier_init.release.cluster;" ::: "memory");
#pragma unroll 1
    for (int k = 0; k < NCH; k++) { const int nb = max(0, min(NWK, n4 - k * NWK)) * 16;
      mbar_expect(sb + BAR_DST + k * 8, nb);
      if (nb) bulk_load(sb + OFF_DST + k * NWK * 16, (const char*)(p.dst + e0) + k * NWK * 16, nb, sb + BAR_DST + k * 8); }
  }
  const int lane = tid & 31, wid = __shfl_sync(~0u, tid >> 5, 0), w = wid & 3;

  auto first_node = [&](int c) { return (int)((c * p.inv + 0xFFFFFFFFull) >> 32); };
  const int node0 = first_node(cta), nloc = min(first_node(cta + 1), p.N) - node0;
  const uint32_t ealo = (uint32_t)(uint64_t)p.ea;
  const int epad = min(e0, p.E - 1);
  auto load_h = [&](int b) { mbar_expect(sb + BAR_T + b * 8, 8192); tma_load(sb + OFF_H + b * 8192, tmb + TM_H, node0 + b * 64, sb + BAR_T + b * 8); };
  if (wid >= 12) {
    const int t = tid - 384;
    auto prefetch_e = [&](int i) {
      const uint32_t nb = (p.E / G) & ~15u;
      if (nb && i < PFN) asm volatile("cp.async.bulk.prefetch.L2.global [%0], %1;" :: "l"((const char*)p.ea + (size_t)(((i * PFS + i * PFS / 32 * (~PFS & 1)) & 31) * G + cta) * nb), "r"(nb) : "memory");
    };
    uint32_t pv[9], ev = 0;
#pragma unroll
    for (int i = 0; i < 3; i++) { const uint16_t* pp = p.pos + (size_t)(node0 + t + 128 * i) * 3;
      pv[3 * i] = pv[3 * i + 1] = pv[3 * i + 2] = 0;
      asm volatile("{.reg .pred p; setp.lt.s32 p, %4, %5;\n @p ld.global.nc.u16 %0, [%3];\n @p ld.global.nc.u16 %1, [%3+2];\n @p ld.global.nc.u16 %2, [%3+4];}"
        : "+r"(pv[3 * i]), "+r"(pv[3 * i + 1]), "+r"(pv[3 * i + 2]) : "l"(pp), "r"(t + 128 * i), "r"(p.N - node0)); }
    asm volatile("{.reg .pred p; setp.lt.u32 p, %3, 8; @p ld.global.nc.u32 %0, [%1]; @p st.global.v4.u32 [%2], {%4, %4, %4, %4};}"
      : "+r"(ev) : "l"((const uint32_t*)(p.ea + (size_t)epad * 2) + t), "l"(p.q + (size_t)(p.N + cta) * 128 + t * 16), "r"(t), "r"(0xF700F700u) : "memory");
    const uint32_t e = __shfl_sync(~0u, c0, 0) + 1;
    {
      const uint32_t tg = (1 + e % 3) << 30, v = ((tg >> 16) + 512 + (lane & 7) * 4) * 0x10001u;
      if (t == 0) sts32(sb + OFF_MISC + 32, e);
#pragma unroll
      for (int i = 0; i < 9; i++) sts128(sb + OFF_SA + t * 16 + i * 2048, v, v + 0x10001u, v + 0x20002u, v + 0x30003u);
      bar_sync(6, NTHR);
      mbar_arrive(sb + BAR_EP, lane == 0);
#pragma unroll
      for (int i = 0; i < 17; i++) sts128(sb + OFF_SB + t * 16 + i * 2048, tg, tg, tg, tg); }
    uint32_t mp = 0;
#pragma unroll
    for (int i = 0; i < 3; i++) { sts64(sb + OFF_POS + (t + 128 * i) * 8, pv[3 * i] | (pv[3 * i + 1] << 16), pv[3 * i + 2]); mp = mag2(mag2(mp, pv[3 * i] | (pv[3 * i + 1] << 16)), pv[3 * i + 2]); }
    proxy_fence();
    __syncwarp();
    mbar_arrive(sb + BAR_PS, lane == 0);
    mbar_wait(sb + BAR_W);
#pragma unroll
    for (int i = 0; i < 8; i += 4) { uint32_t v[16];
#pragma unroll
      for (int k = 0; k < 4; k++) lds128(v + 4 * k, sb + OFF_W + t * 16 + (i + k) * 2048);
#pragma unroll
      for (int k = 0; k < 4; k++) sts128(sb + OFF_W + t * 16 + (i + k) * 2048, hhalf(v[4 * k]), hhalf(v[4 * k + 1]), hhalf(v[4 * k + 2]), hhalf(v[4 * k + 3])); }
    {
      uint32_t v[4], u[4]; const int r = t >> 3, c = t & 7;
      lds128(v, sb + OFF_WS + 128 + t * 16); lds128(u, sb + OFF_WS + c * 16);
      const uint32_t x = lds32(sb + OFF_WS + 2176 + lane * 4);
      sts128(sb + OFF_W3 + r * 128 + ((c ^ (r & 7)) << 4), b2h(v[0], .5f), b2h(v[1], .5f), b2h(v[2], .5f), b2h(v[3], .5f));
      const float s = ((r & 1) || r == 6) ? 0.f : .5f;
      if (t < 64) sts128(sb + OFF_WD + r * 128 + ((c ^ r) << 4), b2h(u[0], s), b2h(u[1], s), b2h(u[2], s), b2h(u[3], s));
      if (t < 32) sts32(sb + OFF_WX + (t & 3) * 32 + (t >> 2) * 4, b2h(x, 1.f));
      const uint32_t m3 = __reduce_max_sync(~0u, magr(mag2(mag2(mag2(mag2(0, v[0]), v[1]), v[2]), v[3]))), md = __reduce_max_sync(~0u, magr(mag2(mag2(mag2(mag2(0, u[0]), u[1]), u[2]), u[3])));
      if (wbad(m3, 0x4000) || wbad(md, 0x4000) || wbad(__reduce_max_sync(~0u, magr(mag2(0, x))), 0x4700) || magr(mp) >= 0x4200 || magr(mag2(0, ev)) >= 0x4380) sts32(sb + OFF_MISC + 8, 1);
    }
    proxy_fence();
    if (w == 1) {
#pragma unroll 1
      for (int b = HE; b < HW; b++) { mbar_wait(sb + BAR_SRC + max(0, H0 + b) * 8); if (lane == 0) load_h(b); }
    }
    bar_sync(3, 128);
    STAMP(24);
    const uint32_t frag = (w * 16 + (lane & 15)) * 128 + (((lane >> 4) ^ (lane & 7)) << 4);
    uint32_t mq = 0;
#pragma unroll 1
    for (int b = 0; b < 6; b++) {
      float acc[32];
      const uint64_t da = DHI | (((sb + OFF_H) >> 4) + b * 512), db = DHI | ((sb + OFF_W) >> 4);
      const uint32_t v0 = lds16(sb + OFF_POS + b * 512 + w * 128 + lane * 2), v1 = lds16(sb + OFF_POS + 64 + b * 512 + w * 128 + lane * 2);
      mbar_wait(sb + BAR_T + b * 8);
      if (b == 0) STAMP(25);
      if (b == 5) STAMP(26);
      wg_fence();
      ss64<0>(acc, da, db); ss64<1>(acc, da + 2, db + 128); ss64<1>(acc, da + 4, db + 256); ss64<1>(acc, da + 6, db + 384);
      wg_commit();
      if (b == 0) mbar_wait(sb + BAR_AW);
      if (t == 32) { if (HALL) { if (b == 0) for (int k = HW; k < 6; k++) load_h(k); } else if (b + HW < 6) load_h(b + HW); }
      __syncwarp();
      uint32_t ff[6], fg[6];
#pragma unroll
      for (int j = 0; j < 6; j++) { ff[j] = (__byte_perm((j & 1) ? v1 : v0, 0, 0x4140) >> (3 * (j >> 1))) & 0x00070007u; fg[j] = __vsub2(0x00040004u, ff[j]);
        asm volatile("" : "+r"(ff[j]), "+r"(fg[j])); }
      wg_wait0(); fence_regs(acc);
      uint32_t o[16];
#pragma unroll
      for (int j = 0; j < 16; j++) o[j] = pack_f16(acc[2 * j], acc[2 * j + 1]);
#pragma unroll
      for (int j = 0; j < 6; j++) {
        const uint32_t m = o[j] & 0x7FFF7FFFu; mq = __vmaxu2(mq, m);
        o[j] = (__viaddmax_s16x2(m, fg[j], 0) & 0xFFF8FFF8u) | ff[j] | (o[j] & 0x80008000u); }
      const uint32_t qs = sb + (b < 2 ? OFF_P2 : OFF_SA - 16384) + b * 8192;
#pragma unroll
      for (int j = 0; j < 4; j++) stsm4((qs + frag) ^ (j << 5), o[4 * j], o[4 * j + 1], o[4 * j + 2], o[4 * j + 3]);
      proxy_fence();
      if (b == 5) { const uint32_t m = __reduce_max_sync(~0u, magr(mq)); if (lane == 0) sts32(sb + OFF_MISC + 16 + w * 4, m); }
      bar_sync(3, 128);
      if (t == 0) { if (b * 64 < nloc) tma_store(tmb + TM_Q, 0, node0 + b * 64, qs); if (b == 5) bulk_commit(); }
      __syncwarp();
    }
    asm volatile("setmaxnreg.dec.sync.aligned.u32 32;");
    if (w == 0) {
      STAMP(18);
      uint32_t mv[4]; lds128(mv, sb + OFF_MISC + 16);
      const uint32_t mx = max(max(mv[0], mv[1]), max(mv[2], mv[3]));
      bulk_wait();
      mbar_arrive(sb + BAR_QR, lane == 0);
      STAMP(19);
      if (lane == 0) {
        if (nloc > 0 && (mx >= 0x7BF0 || mx < 0x1400)) asm volatile("st.relaxed.gpu.global.u32 [%0+4], %1;" :: "l"(p.sync), "r"(e) : "memory");
        asm volatile("red.release.gpu.global.add.u32 [%0], 1;" :: "l"(p.sync) : "memory");
      }
      __syncwarp();
      uint32_t c, f; int spin = 0;
      do { asm volatile("ld.acquire.gpu.global.v2.u32 {%0, %1}, [%2];" : "=r"(c), "=r"(f) : "l"(p.sync) : "memory"); trap_if(++spin > 4000000); } while (__any_sync(~0u, (int)(c - e * G) < 0));
      if (f == e) sts32(sb + OFF_MISC + 8, 1);
      if (cta == 0 && lane == 0) asm volatile("st.relaxed.gpu.global.u32 [%0+8], %1;" :: "l"(p.sync), "r"(e) : "memory");
      STAMP(20);
      __syncwarp();
      mbar_arrive(sb + BAR_QP, lane == 0);
    }
    if (w == 1) {
      if (PFW) mbar_wait(sb + PFW);
      __nanosleep(PF0NS);
#pragma unroll 1
      for (int i = 0; i < PFN; i++) { if (lane == 0) prefetch_e(i); __nanosleep(PFNS); }
    }
    bar_sync(4, NTHR);
    if (t == 0) { mbar_expect(sb + BAR_U, 16384); tma_load(sb + OFF_W, tmb + TM_WH, 0, sb + BAR_U); tma_load(sb + OFF_W + 8192, tmb + TM_WH, 64, sb + BAR_U); }
    mbar_wait(sb + BAR_U);
    uint32_t mh = 0;
#pragma unroll 1
    for (int i = t; i < 512; i += 128) { uint32_t v[4]; const uint32_t a = sb + OFF_W + i * 16;
      lds128(v, a); sts128(a, hhalf(v[0]), hhalf(v[1]), hhalf(v[2]), hhalf(v[3]));
      lds128(v, a + 8192); sts128(a + 8192, b2h(v[0], .5f), b2h(v[1], .5f), b2h(v[2], .5f), b2h(v[3], .5f));
      mh = mag2(mag2(mag2(mag2(mh, v[0]), v[1]), v[2]), v[3]); }
    if (wbad(__reduce_max_sync(~0u, magr(mh)), 0x4700)) sts32(sb + OFF_MISC + 12, 1);
    proxy_fence();
    __syncwarp();
    mbar_arrive(sb + BAR_WH, lane == 0);
    return;
  }

  auto put = [&](uint32_t x, int hi, uint32_t bv, uint32_t eb) {
    asm volatile("{.reg .pred p; setp.eq.b32 p, %0, 0;\n @p st.shared.u32 [%1], %3;\n @p st.shared.u16 [%2], %4;}"
      :: "r"(x & (0x8000u << 16 * hi)), "r"(sb + OFF_TE + mad16(x, 2 << 8 * hi, 0)), "r"(sb + OFF_TS + (hi ? x >> 16 : x & 0xFFFF)), "r"(mad16(bv, 0x2000u, eb)), "h"((uint16_t)bv) : "memory");
  };
  if (tid == 320) {
    mbar_init(sb + BAR_W, 1);
    asm volatile("fence.mbarrier_init.release.cluster;" ::: "memory");
    mbar_expect(sb + BAR_W, 2 * 8192 + 2304);
    tma_load(sb + OFF_W, tmb + TM_WE, 64, sb + BAR_W); tma_load(sb + OFF_W + 8192, tmb + TM_WE, 0, sb + BAR_W);
    bulk_load(sb + OFF_WS, p.we + 128 * 64, 2176, sb + BAR_W); bulk_load(sb + OFF_WS + 2176, p.wx, 128, sb + BAR_W);
  }
  if (tid == 288) {
#pragma unroll
    for (int a = BAR_SRC; a < BAR_END; a += 8) if (a != BAR_W) mbar_init(sb + a, a == BAR_WH || a == BAR_PS || a == BAR_EP ? 4 : a == BAR_XA ? 11 : 1);
    asm volatile("fence.mbarrier_init.release.cluster;" ::: "memory");
    asm volatile("prefetch.tensormap [%0];" :: "l"(tmb + TM_XA)); asm volatile("prefetch.tensormap [%0];" :: "l"(tmb + TM_H));
    asm volatile("prefetch.tensormap [%0];" :: "l"(tmb + TM_XB)); asm volatile("prefetch.tensormap [%0];" :: "l"(tmb + TM_Q));
  }
  {
    if (tid < 144) { const uint32_t z = (tid >> 3) == 16 ? 0x8000u : 0u; sts128(sb + OFF_CNT + tid * 16, z, z, z, z); }
    else if (tid <= 144 + G) sts32(sb + OFF_BC + (tid - 144) * 4, ((tid - 144) & 31) * 4);
    const uint32_t sp = (p.N + cta) * 0x10001u, em = first_node(G);
    if (wid < 7) {
#pragma unroll
      for (int i = 0; i < 4; i++) sts128(sb + OFF_TS + tid * 16 + i * 3584, sp, sp, sp, sp);
    }
    static_assert(SCAP * 32 == 4 * 3584, "fill");
#pragma unroll 1
    for (int i = n4 + tid; i < 1536; i += 384) sts128(sb + OFF_DST + i * 16, em, em, em, em);
    if (tid == 321) sts128(sb + OFF_MISC, 0, 0, p.force_slow, 0);
  }
  bar_arrive(6, NTHR);
  bar_sync(0, 384);
  uint32_t ep, tag, eb0, pk[12], r0[12], r1[12], cb;
  uint2 vb[12];
  const uint2* xb = (const uint2*)(p.xb + (cta * G + wid) * 16) + ((lane + cta) & 31);
  auto get_tag = [&]() { mbar_wait(sb + BAR_EP); ep = lds32(sb + OFF_MISC + 32); tag = (1 + ep % 3) << 30; eb0 = ealo - (tag >> 11); };
  if (wid == 11) {
    trap_if(sb != (uint32_t)__cvta_generic_to_shared(smraw));
#pragma unroll 1
    for (unsigned long long q = LSEQ; q; q >>= 8) { const int k = (q >> 4) & 7, nb = max(0, min(8192, n4 * 16 - k * 8192));
      mbar_wait(sb + BAR_DST + ((uint32_t)q & 7) * 8);
      if (lane == 0) {
        if (k >= 3) load_h(k - 3);
        else { mbar_expect(sb + BAR_SRC + k * 8, nb);
          if (nb) bulk_load(sb + OFF_SRCI + k * 8192, (const char*)(p.src + e0) + k * 8192, nb, sb + BAR_SRC + k * 8); } } }
    get_tag();
    mbar_wait(sb + BAR_PS);
    bar_sync(12, 384);
    if (lane == 0) { tma_store_ef(tmb + TM_XA, cta * 64, 0, sb + OFF_SA); bulk_commit(); }
    __syncwarp();
    uint32_t xm = 0;
#pragma unroll
    for (int k = 0; k < 5; k++) xm |= (lds32(sb + OFF_BC + min(lane + 32 * k, G - 1) * 4) >= (64 << 9) && lane + 32 * k < G) << k;
    auto ext_send = [&](int pl) {
      uint32_t x = xm;
      for (uint32_t m; (m = __ballot_sync(~0u, x));) {
        const uint32_t l = __ffs(m) - 1, j = l + 32 * (__ffs(__shfl_sync(~0u, x, l)) - 1);
        if (lane == l) x &= x - 1;
        const uint32_t e = min(lds16(sb + OFF_AX + j * 128 + ((4 * l + 2 * lane) & 126)), 6143u);
        st_ext(p.xe + (j * G + cta) * 64 + pl * 32 + lane, pl ? lds32(sb + OFF_SRCI + e * 4) + tag + (e << 16) : (lds32(sb + OFF_DST + e * 4) & 511) | (lds32(sb + OFF_BC + j * 4) & ~511u), ep);
      }
    };
    if (lane == 0) { bulk_wait(); hint_signal(p.sync + 4); STAMP(16); }
    __syncwarp();
    ext_send(0);
    proxy_fence();
    __syncwarp();
    mbar_arrive(sb + BAR_AW, lane == 0);
    bar_sync(13, 384);
    if (!B_HOLD && lane == 0) { tma_store_ef(tmb + TM_XB, cta * 64, 0, sb + OFF_SB); bulk_commit(); }
    __syncwarp();
    ext_send(1);
    mbar_arrive(sb + BAR_AX, lane == 0);
    if (B_HOLD) mbar_wait(sb + (B_HOLD == 1 ? BAR_HA : BAR_XA));
    if (lane == 0) {
      bulk_wait();
#pragma unroll 1
      for (int r = B_HOLD ? 0 : BROWS; r < G; r += BROWS) { tma_store_ef(tmb + TM_XB, cta * 64, r, sb + OFF_SB + r * 256); bulk_commit(); bulk_wait(); }
      hint_signal(p.sync + 5);
      STAMP(17);
    }
    __syncwarp();
    hint_wait(p.sync + 5, ep * G);
    if (lane == 0) { mbar_expect(sb + BAR_HB, G * 256);
#pragma unroll 1
      for (int o = 0; o < 4; o++) bulk_load(sb + OFF_XB + o * (G * 64), (const char*)p.xb + (size_t)(cta * 4 + o) * (G * 64), G * 64, sb + BAR_HB); }
    __syncwarp();
    STAMP(21);
  } else {
    STAMP(15);
    {
      uint32_t d[4 * NCH], jj[4 * NCH], rr[4 * NCH];
      auto count = [&](int k) {
        mbar_wait(sb + BAR_DST + k * 8);
        lds128(d + 4 * k, sb + OFF_DST + (tid + NWK * k) * 16);
#pragma unroll
        for (int i = 4 * k; i < 4 * k + 4; i++) { jj[i] = d[i] * p.magic; rr[i] = atoms_add(__dp4a(jj[i], 0x04000000u, sb + OFF_BC), 0x202u); }
      };
      auto place = [&](int k) {
#pragma unroll
        for (int i = 4 * k; i < 4 * k + 4; i++) {
          const uint32_t o = __dp4a(jj[i], 0x80000000u, rr[i] & 0x807Eu);
          d[i] = (d[i] & 511) | (tag >> 16);
          asm("{.reg .pred p; setp.ge.u32 p, %1, 0x8000; @p add.u32 %0, %2, %3;}" : "+r"(d[i]) : "r"(o), "r"(tid * 4), "r"(NWK * k * 4 + (i & 3)));
          sts16(sb + OFF_SA + o, d[i]); jj[i] = __viaddmin_u32(o, o, G * 256);
        }
      };
      count(0); STAMP(1); count(1); get_tag(); place(0); count(2); place(1); count(3); place(2);
      if (wid < 4) { count(4); place(3); place(4); } else place(3);
      proxy_fence();
      bar_arrive(12, 384);
      STAMP(2);
      mbar_wait(sb + BAR_PS);
      mbar_wait(sb + BAR_SRC); mbar_wait(sb + BAR_SRC + 8); mbar_wait(sb + BAR_SRC + 16);
      STAMP(12);
#pragma unroll
      for (int k = 0; k < NCH; k++) lds128(d + 4 * k, sb + OFF_SRCI + (tid + NWK * k) * 16);
      const uint32_t tb = tag + (tid << 18);
#pragma unroll
      for (int i = 0; i < 4 * NCH; i++) if (i < 4 * NCH - 4 || wid < 4) sts32(sb + OFF_SB + jj[i], d[i] + tb + ((NWK * (i >> 2) * 4 + (i & 3)) << 16));
      proxy_fence();
      bar_arrive(13, 384);
      STAMP(3);
    }
    const uint32_t rot = (lane + cta) & 31;
    cb = sb + OFF_CNT - (tag >> 14);
    {
      const uint32_t* xa = (const uint32_t*)(p.xa + (cta * G + wid) * 8) + rot;
      if (wid < 8) { const uint32_t e_ = ealo + epad * 32;
        mbar_wait(sb + BAR_AX);
#pragma unroll
        for (int i = 0; i < 7; i++) sts128(sb + OFF_TE + tid * 16 + i * 4096, e_, e_, e_, e_); }
      static_assert(SCAP * 64 == 7 * 4096, "fill");
      if (wid == 10) { hint_wait(p.sync + 4, ep * G); mbar_arrive(sb + BAR_HA, lane == 0); }
      mbar_wait(sb + BAR_HA);
      STAMP(14);
      uint32_t all;
#pragma unroll 1
      for (int spin = 0;; spin++) {
        uint32_t st = 0; all = ~0u;
#pragma unroll
        for (int k = 0; k < 12; k++) asm volatile("ld.relaxed.gpu.global.u32 %0, [%1];" : "=r"(pk[k]) : "l"(xa + k * 352) : "memory");
#pragma unroll
        for (int k = 0; k < 12; k++) { st |= pk[k] ^ (tag | (tag >> 16)); all &= pk[k]; }
        if (!__any_sync(~0u, st & 0xC000C000u)) break;
        trap_if(spin > 2000000);
      }
      if (wid == 0) STAMP(22);
      uint32_t xm = 0; uint2 xv;
      auto xadr = [&]() { return p.xe + (cta * G + wid + 11 * (__ffs(xm) - 1)) * 64 + lane; };
      if (!(__shfl_sync(~0u, all, 31) & 0x2000000u)) {
#pragma unroll
        for (int k = 0; k < 12; k++) xm |= (~pk[k] >> 25 & 1) << k;
        xm = __shfl_sync(~0u, xm, 31);
        xv = ld_poll2(xadr());
      }
#pragma unroll
      for (int k = 0; k < 12; k++) { r0[k] = mad16(pk[k], 0x0004u, cb); r1[k] = mad16(pk[k], 0x0400u, cb); vb[k].x = atoms_add(r0[k], 16); vb[k].y = atoms_add(r1[k], 16); }
      if (B_HOLD == 2) mbar_arrive(sb + BAR_XA, lane == 0);
#pragma unroll
      for (int k = 0; k < 12; k++) pk[k] = __byte_perm(vb[k].x, vb[k].y, 0x5410);
      for (; xm; xm &= xm - 1) {
        if (__any_sync(~0u, xv.y != ep)) xv.x = ext_get(xadr(), ep);
        const uint32_t cn = xv.x >> 9, n = xv.x & 511;
        if (cn > 96) sts32(sb + OFF_MISC + 8, 1);
        else if (lane < cn - 64) {
          const uint32_t r = atoms_add(sb + OFF_CNT + n * 4, 16), idx = atoms_add(sb + OFF_MISC + 4, 1);
          if (idx < 256) sts32(sb + OFF_EXT + idx * 4, n | ((wid + 11 * (__ffs(xm) - 1)) << 9) | (lane << 17) | (min(r >> 4, 255u) << 22));
          else sts32(sb + OFF_MISC + 8, 1);
        }
        xv.y = ~ep;
        __syncwarp();
      }
    }
    STAMP(4);
    if (wid >= 6) bar_arrive(11, NWK);
    if (wid < 6) {
      uint32_t ca[2], ky[2], dr[2], sq[2], ps[4];
#pragma unroll
      for (int i = 0; i < 2; i++) { ca[i] = sb + OFF_CNT + ((node0 + tid + 192 * i) & 511) * 4; lds64(ps[2 * i], ps[2 * i + 1], sb + OFF_POS + (tid + 192 * i) * 8); ps[2 * i + 1] |= (tid + 192 * i) << 16; }
      bar_sync(11, NWK);
      STAMP(5);
#pragma unroll
      for (int i = 0; i < 2; i++) ky[i] = (lds32(ca[i]) + 16) >> 5;
      if (max(ky[0], ky[1]) > 31) sts32(sb + OFF_MISC + 8, 1);
#pragma unroll
      for (int i = 0; i < 2; i++) { ky[i] = min(ky[i], 31u); dr[i] = atoms_add(sb + OFF_DH + ky[i] * 4, 1); }
      bar_sync(10, 192);
      const uint32_t hv = lds32(sb + OFF_DH + lane * 4);
      uint32_t inc = hv;
#pragma unroll
      for (int o = 1; o < 32; o <<= 1) asm("{.reg .pred p; .reg .b32 y; shfl.sync.down.b32 y|p, %0, %1, 31, -1; @p add.u32 %0, %0, y;}" : "+r"(inc) : "r"(o));
#pragma unroll
      for (int i = 0; i < 2; i++) {
        const uint32_t pos = __shfl_sync(~0u, inc - hv, ky[i]) + dr[i];
        const uint32_t ak = (uint32_t)(QCODE >> ((pos >> 5) * 4)) & 15, l = (pos >> 3) & 3;
        sq[i] = (ak >> 2) * 16 + ((QREV >> (pos >> 5) & 1) ? 3 - l : l) * 4 + (ak & 3);
        dr[i] = pos & 7;
        asm volatile("{.reg .pred p; setp.eq.u32 p, %2, 0; @p st.shared.u8 [%0], %1;}" :: "r"(sb + OFF_LEN + sq[i]), "r"(max(ky[i], 1u)), "r"(dr[i]) : "memory");
        sts64(sb + OFF_GP + sq[i] * 64 + dr[i] * 8, ps[2 * i], ps[2 * i + 1]);
      }
      bar_sync(10, 192);
      const uint32_t ln = lds32(sb + OFF_LEN + min(lane, 11) * 4), tot = __dp4a(ln, 0x01010101u, 0u);
      inc = tot;
#pragma unroll
      for (int o = 1; o < 16; o <<= 1) asm("{.reg .pred p; .reg .b32 y; shfl.sync.up.b32 y|p, %0, %1, 0, -1; @p add.u32 %0, %0, y;}" : "+r"(inc) : "r"(o));
      if (wid == 1) sts32(sb + OFF_CNT + 2048 + lane * 4, 0);
      if (tid < 12) { sts32(sb + OFF_LEN + 64 + tid * 4, inc - tot); if (inc > SCAP) sts32(sb + OFF_MISC + 8, 1); }
#pragma unroll
      for (int i = 0; i < 2; i++) sts32(ca[i], __dp4a(__shfl_sync(~0u, ln, sq[i] >> 2), 0x00010101u >> (24 - 8 * (sq[i] & 3)), __shfl_sync(~0u, inc - tot, sq[i] >> 2)) * 32 + dr[i] * 2);
    }
    bar_arrive(7, 384);
  }
  if (wid == 11) bar_sync(7, 384); else bar_sync(1, NWK);
  STAMP(6);
  if (wid != 11) {
#pragma unroll
    for (int k = 0; k < 12; k++) { r0[k] = lds32(r0[k]); r1[k] = lds32(r1[k]); }
  }
  mbar_wait(sb + BAR_QR);
  asm volatile("setmaxnreg.inc.sync.aligned.u32 160;");
#pragma unroll
  for (int k = 0; k < 12; k++) asm volatile("{.reg .b32 t; prmt.b32 t, %1, %2, 0x5410; add.u32 %0, %0, t;}" : "+r"(pk[k]) : "r"(r0[k]), "r"(r1[k]));
  uint32_t pa[8], sp[8], pq[16]; float chk = 0.f;
  {
    uint32_t hf[32], mp = 0; float a0[32], a1[32];
    const uint32_t an = sb + OFF_GP + wid * 256 + (lane & 15) * 8 + 6, n0 = lds16(an), n1 = lds16(an + 128);
#pragma unroll
    for (int j = 0; j < 8; j++) { const uint32_t nd = j < 4 ? n0 : n1; ldsm4(hf + 4 * j, (sb + OFF_H + nd * 128 + (((nd & 7) << 4) ^ (lane & 16))) ^ ((j & 3) << 5)); }
    const uint64_t db = DHI | ((sb + OFF_W + 8192) >> 4);
    wg_fence();
    rs64b<0>(a0, hf[0], hf[1], hf[2], hf[3], db); rs64b<1>(a0, hf[4], hf[5], hf[6], hf[7], db + 128); rs64b<1>(a0, hf[8], hf[9], hf[10], hf[11], db + 256); rs64b<1>(a0, hf[12], hf[13], hf[14], hf[15], db + 384);
    wg_commit();
    rs64b<0>(a1, hf[16], hf[17], hf[18], hf[19], db); rs64b<1>(a1, hf[20], hf[21], hf[22], hf[23], db + 128); rs64b<1>(a1, hf[24], hf[25], hf[26], hf[27], db + 256); rs64b<1>(a1, hf[28], hf[29], hf[30], hf[31], db + 384);
    wg_commit();
    asm volatile("wgmma.wait_group.sync.aligned 1;" ::: "memory"); fence_regs(a0);
#pragma unroll
    for (int j = 0; j < 8; j++) { const uint32_t x = pack_f16(a0[4 * j], a0[4 * j + 1]), y = pack_f16(a0[4 * j + 2], a0[4 * j + 3]); mp = hmag(hmag(mp, x), y);
      asm volatile("movmatrix.sync.aligned.m8n8.trans.b16 %0, %1;" : "=r"(pa[j]) : "r"(x)); asm volatile("movmatrix.sync.aligned.m8n8.trans.b16 %0, %1;" : "=r"(sp[j]) : "r"(y)); }
    wg_wait0(); fence_regs(a1);
    bar_arrive(4, NTHR);
#pragma unroll
    for (int j = 0; j < 16; j++) { pq[j] = pack_f16(a1[2 * j], a1[2 * j + 1]); mp = hmag(mp, pq[j]); }
    if (magr(mp) >= 0x7000) chk = __int_as_float(0x7FC00000);
  }
  if (wid == 0) STAMP(23);
  uint32_t bad;
  {
    const uint32_t ring = sb + OFF_RING + wid * (NST * STG), p2 = sb + OFF_P2 + wid * 2048;
    uint32_t lens = __shfl_sync(~0u, lds32(sb + OFF_LEN + wid * 4), 0);
    uint32_t rem = __dp4a(lens, 0x20202020u, 0u);
    const uint32_t base = min(lds32(sb + OFF_LEN + 64 + wid * 4), SCAP);
    uint32_t a_s = sb + OFF_TS + base * 32 + (lane >> 3) * 8, a_e = sb + OFF_TE + base * 64 + (lane >> 1) * 4;
    uint32_t k0 = (uint32_t)(uint64_t)p.q + (((lane & 7) ^ ((lane >> 1) & 4)) << 4), k1 = k0 ^ 16, k2 = k0 ^ 32, k3 = k0 ^ 48, ke = ((lane ^ (lane >> 3)) & 1) << 4;
    uint32_t dst0 = ring + (lane >> 3) * 640 + (lane & 7) * 16;
    const uint32_t qhi = (uint32_t)((uint64_t)p.q >> 32), ehi = (uint32_t)((uint64_t)p.ea >> 32);
    uint32_t s0, s1, ev, to = 0, so = 0;
    auto tl_ = [&]() { lds64(s0, s1, a_s + to); asm volatile("ld.shared.u32 %0, [%1]; add.u32 %1, %1, 64;" : "=&r"(ev), "+r"(a_e) :: "memory"); to += 32; };
#define CPQ(LH, x, k, off) "dp2a." LH ".u32.u32 lo, " x ", 0x80000080, " k "; mov.b64 a, {lo, %7}; @p cp.async.cg.shared.global [%0+" #off "], [a], 16;\n"
#define CPE "or.b32 lo, %10, %11; mov.b64 a, {lo, %12}; @p cp.async.cg.shared.global" ESZ " [%0+512], [a], 16;\n"
#define CPA(BODY) asm volatile("{.reg .b32 lo; .reg .b64 a; .reg .pred p; setp.le.u32 p, %8, %9;\n" BODY "}" \
      :: "r"(dst0 + so), "r"(s0), "r"(s1), "r"(k0), "r"(k1), "r"(k2), "r"(k3), "r"(qhi), "r"(to), "r"(rem), "r"(ev), "r"(ke), "r"(ehi) : "memory")
#define CPQ4 CPQ("lo", "%1", "%3", 0) CPQ("hi", "%1", "%4", 128) CPQ("lo", "%2", "%5", 256) CPQ("hi", "%2", "%6", 384) "cp.async.commit_group;"
    auto issue = [&]() { CPA(CPE CPQ4); so = so == (NST - 1) * STG ? 0 : so + STG; };
    const int g = lane >> 2, qd = lane & 3;
    const uint32_t sw = ((lane >> 4) ^ (lane & 7)) << 4, fr = (lane & 15) * 128 + sw;
    uint32_t qa0 = ring + (g & 3) * 640 + qd * 128 + sw, qa1 = qa0 ^ 32, qa2 = qa0 ^ 64, qa3 = qa0 ^ 96;
    uint32_t eadr = ring + 512 + (g & 3) * 640 + qd * 32 + ((((lane >> 4) ^ g) & 1) << 4);
    uint32_t oh0 = g == 2 * qd ? 0x3C00u : g == 2 * qd + 1 ? 0x3C000000u : 0u, oh1 = oh0;
    uint32_t a_g = sb + OFF_GP + wid * 256 + lane * 2;
    uint32_t a_n = sb + OFF_GP + wid * 256 + (lane & 15) * 8 + 6;
    uint32_t a_p = ((lane & 8) ? p2 : sb + OFF_WD) + (lane & 7) * 128 + ((((lane >> 4) ^ lane) & 7) << 4);
    uint32_t a_w = sb + OFF_W3 + fr;
#define OPQ4(A, B, C, D) asm volatile("shfl.sync.bfly.b32 %0, %0, 0, 31, -1; shfl.sync.bfly.b32 %1, %1, 0, 31, -1; shfl.sync.bfly.b32 %2, %2, 0, 31, -1; shfl.sync.bfly.b32 %3, %3, 0, 31, -1;" : "+r"(A), "+r"(B), "+r"(C), "+r"(D))
    asm volatile("shfl.sync.idx.b32 %0, %0, %1, 31, -1;" : "+r"(oh1) : "r"(lane));
    if (OPQ & 1) OPQ4(a_w, oh0, ke, dst0);
    if (OPQ & 2) OPQ4(qa0, qa1, qa2, qa3);
    if (OPQ & 4) OPQ4(k0, k1, k2, k3);
    if (OPQ & 8) OPQ4(a_g, a_n, a_p, eadr);
    uint32_t w3[16], wv[8], bp[16], sum[8], Y[16], M[16], own, ownp, dpk; uint16_t tl[16], th[16];
    float pacc = 0.f;
    auto wload = [&]() {
#pragma unroll
      for (int j = 0; j < 4; j++) ldsm4t(w3 + 4 * j, a_w ^ (j << 5));
      lds128(wv, sb + OFF_WX + (a_g & 6) * 16); lds128(wv + 4, sb + OFF_WX + 16 + (a_g & 6) * 16);
    };
    auto hload = [&](uint32_t (&hf)[16], uint32_t nd) {
      const uint32_t hrow = sb + OFF_H + nd * 128 + (((nd & 7) << 4) ^ ((a_g >> 1) & 16));
#pragma unroll
      for (int j = 0; j < 4; j++) ldsm4(hf + 4 * j, hrow ^ (j << 5));
      return hrow;
    };
    auto bload = [&](uint32_t o) {
#pragma unroll
      for (int j = 0; j < 4; j++) ldsm4t(bp + 4 * j, (a_p ^ (j << 5)) + o);
    };
    { uint32_t wd[8]; const uint32_t a = sb + OFF_WD + (lane & 7) * 128 + ((((lane >> 3) ^ lane) & 7) << 4);
      ldsm4t(wd, a); ldsm4t(wd + 4, a ^ 64);
#pragma unroll
      for (int j = 0; j < 8; j++) { bp[2 * j] = wd[j]; bp[2 * j + 1] = pa[j]; } }
    own = lds16(a_g) * 0x10001u;
    if (wid == 0) STAMP(27);
    mbar_wait(sb + BAR_HB);
    if (__shfl_sync(~0u, lds32(sb + OFF_MISC + 8), 0)) rem = 0;
    else if (wid == 11) {
      const uint32_t nx = __shfl_sync(~0u, lds32(sb + OFF_MISC + 4), 0);
      for (uint32_t k = 0; k < nx; k += 32) {
        const uint32_t x = lds32(sb + OFF_EXT + min(k + lane, nx - 1) * 4), y = ext_get(p.xe + (cta * G + ((x >> 9) & 255)) * 64 + 32 + ((x >> 17) & 31), ep);
        put(lds32(sb + OFF_CNT + (x & 511) * 4) + (x >> 22) * 16, 0, y, eb0 + ((x >> 9) & 255) * p.EPC * 32);
      }
    } else {
#pragma unroll
      for (int k = 0; k < 12; k++) lds64(vb[k].x, vb[k].y, sb + OFF_XB + (wid + 11 * k) * 256 + ((lane + cta) & 31) * 8);
#pragma unroll 1
      for (int spin = 0;; spin++) {
        uint32_t st = 0;
#pragma unroll
        for (int k = 0; k < 12; k++) st |= (vb[k].x ^ tag) | (vb[k].y ^ tag);
        if (!__any_sync(~0u, st >> 30)) break;
        trap_if(spin > 2000000);
#pragma unroll
        for (int k = 0; k < 12; k++) vb[k] = ld_poll2(xb + k * 352);
      }
#pragma unroll
      for (int k = 0; k < 12; k++) { const uint32_t eb = eb0 + (wid + 11 * k) * p.EPC * 32; put(pk[k], 0, vb[k].x, eb); put(pk[k], 1, vb[k].y, eb); }
    }
    STAMP(7);
    wload();
    bar_sync(2, 384);
    uint32_t sv[3 * NST];
#pragma unroll
    for (int i = 0; i < NST; i++) { tl_(); sv[3 * i] = s0; sv[3 * i + 1] = s1; sv[3 * i + 2] = ev; }
#pragma unroll
    for (int j = 0; j < 4; j++) stsm4((p2 + fr) ^ (j << 5), pq[4 * j], pq[4 * j + 1], pq[4 * j + 2], pq[4 * j + 3]);
#pragma unroll
    for (int i = 0; i < NST; i++) { to = 32 * i + 32; so = i * STG; ev = sv[3 * i + 2]; CPA(CPE); }
    mbar_wait(sb + BAR_QP);
    STAMP(13);
    bad = __shfl_sync(~0u, lds32(sb + OFF_MISC + 8), 0);
   if (!bad) {
#pragma unroll
    for (int i = 0; i < NST; i++) { to = 32 * i + 32; so = i * STG; s0 = sv[3 * i]; s1 = sv[3 * i + 1]; CPA(CPQ4); }
    so = 0;
    auto body = [&](auto MODE) {
      constexpr int mode = decltype(MODE)::value;
      uint32_t T[16], ef[4], q0, q1, x0, x1, x2; float e0_, e1_, cs[4];
      auto mu = [&](int j) {
#pragma unroll
        for (int i = 2 * j; i < 2 * j + 2; i++) asm volatile("{.reg .b16 l, h; mov.b32 {l, h}, %2; tanh.approx.f16 %0, l; tanh.approx.f16 %1, h;}" : "=h"(tl[i]), "=h"(th[i]) : "r"(Y[i])); };
      auto fi = [&](int j) {
#pragma unroll
        for (int i = 2 * j; i < 2 * j + 2; i++) asm volatile("{.reg .b32 t; mov.b32 t, {%2, %3}; fma.rn.f16x2 %0, %1, t, %1;}" : "=r"(M[i]) : "r"(Y[i]), "h"(tl[i]), "h"(th[i])); };
      auto ad = [&](int j) { asm volatile("add.rn.f16x2 %0, %0, %1; add.rn.f16x2 %0, %0, %2;" : "+r"(sum[j]) : "r"(M[2 * j]), "r"(M[2 * j + 1])); };
      auto he = [&](int j) { asm volatile("mma.sync.aligned.m16n8k16.row.col.f16.f16.f16.f16 {%0,%1}, {%2,%3,%4,%5}, {%6,%7}, {%0,%1};" : "+r"(T[2 * j]), "+r"(T[2 * j + 1]) : "r"(ef[0]), "r"(ef[1]), "r"(ef[2]), "r"(ef[3]), "r"(w3[2 * j]), "r"(w3[2 * j + 1])); };
      auto hs = [&](int j) { asm volatile("mma.sync.aligned.m16n8k16.row.col.f16.f16.f16.f16 {%0,%1}, {%2,%3,%4,%5}, {%6,%7}, {%8,%9};" : "=r"(Y[2 * j]), "=r"(Y[2 * j + 1]) : "r"(q0), "r"(q1), "r"(oh0), "r"(oh1), "r"(bp[2 * j]), "r"(bp[2 * j + 1]), "r"(T[2 * j]), "r"(T[2 * j + 1])); };
      auto hc = [&](int j) {
        if (j) asm volatile("mma.sync.aligned.m16n8k16.row.col.f32.f16.f16.f32 {%0,%1,%2,%3}, {%4,%5,%6,%7}, {%8,%9}, {%0,%1,%2,%3};" : "+f"(cs[0]), "+f"(cs[1]), "+f"(cs[2]), "+f"(cs[3]) : "r"(M[4 * j]), "r"(M[4 * j + 1]), "r"(M[4 * j + 2]), "r"(M[4 * j + 3]), "r"(wv[2 * j]), "r"(wv[2 * j + 1]));
        else asm volatile("mma.sync.aligned.m16n8k16.row.col.f32.f16.f16.f32 {%0,%1,%2,%3}, {%4,%5,%6,%7}, {%8,%9}, {%10,%10,%10,%10};" : "=f"(cs[0]), "=f"(cs[1]), "=f"(cs[2]), "=f"(cs[3]) : "r"(M[0]), "r"(M[1]), "r"(M[2]), "r"(M[3]), "r"(wv[0]), "r"(wv[1]), "f"(0.f)); };
      auto cv = [&](int i) { asm volatile("{.reg .b32 a, b; shl.b32 a, %0, 16; and.b32 b, %0, 0xFFFF0000; cvt.rn.f16x2.f32 %0, b, a;}" : "+r"(ef[i])); };
      auto un = [&]() { asm volatile("shl.b32 %0, %2, 16; and.b32 %1, %2, 0xFFFF0000;" : "=&f"(e0_), "=&f"(e1_) : "r"(dpk)); };
      auto ex0 = [&]() { asm volatile("prmt.b32 %0, %3, %4, 0x6420; prmt.b32 %1, %5, %6, 0x6420; prmt.b32 %2, %7, %8, 0x6420;" : "=&r"(x0), "=&r"(x1), "=&r"(x2) : "r"(T[0]), "r"(T[1]), "r"(T[2]), "r"(T[3]), "r"(T[4]), "r"(T[5])); };
      auto ex1 = [&]() { asm volatile("{.reg .b32 a, b; shl.b32 a, %2, 3; shl.b32 b, %3, 6; lop3.b32 a, %1, a, 0x38383838, 0xD8; lop3.b32 a, a, b, 0xC0C0C0C0, 0xD8; sub.rn.bf16x2 %0, %4, a;}" : "=r"(dpk) : "r"(x0), "r"(x1), "r"(x2), "r"(own)); };
      auto ex2 = [&]() { asm volatile("{.reg .b32 a, b, d, u; .reg .b16 l, h; shl.b32 a, %2, 16; and.b32 b, %2, 0xFFFF0000; cvt.rn.f16x2.f32 d, b, a; mul.rn.f16x2 %0, d, d; mov.b32 {l, h}, d; mov.b32 u, {h, h}; mul.rn.f16x2 %1, u, u;}" : "=&r"(q0), "=&r"(q1) : "r"(dpk)); };
      auto pf = [&]() { asm volatile("fma.rn.f32 %0, %1, %2, %0; fma.rn.f32 %0, %3, %4, %0;" : "+f"(pacc) : "f"(cs[0]), "f"(e0_), "f"(cs[2]), "f"(e1_)); };
#define FX(k) if (FM >> k & 1) asm volatile("pmevent 1;" ::: "memory")
      if (mode == 2) {
        hc(0); mu(3); fi(2); un(); ad(0); ad(1); mu(4); fi(3); hc(1); mu(5); fi(4); ad(2); mu(6); fi(5); ad(3); hc(2); mu(7); fi(6); fi(7); ad(4); ad(5); hc(3); ad(6); ad(7); pf();
        return;
      }
      asm volatile("cp.async.wait_group %0;" :: "n"(NST - 1) : "memory");
      __syncwarp();
      if (mode == 1) STAMP(8);
      ldsm4(ef, eadr + so); ldsm4(T, qa0 + so); ldsm4(T + 4, qa1 + so); ldsm4(T + 8, qa2 + so); ldsm4(T + 12, qa3 + so);
      tl_();
      if (mode == 1) {
        issue();
        cv(0); cv(1); cv(2); cv(3); ex0(); ex1(); ex2();
#pragma unroll
        for (int j = 0; j < 8; j++) { he(j); hs(j); }
        mu(0); mu(1); fi(0); mu(2); fi(1);
        return;
      }
      hc(0); mu(3); fi(2); un(); ad(0); ad(1);
      FX(0);
      mu(4); fi(3); cv(0); cv(1); cv(2); cv(3); ex0(); ex1();
      FX(1);
      he(0); he(1); hc(1); mu(5); fi(4); ex2(); ad(2);
      FX(2);
      hs(0); he(2); mu(6); fi(5); issue(); ad(3);
      FX(3);
      hs(1); he(3); hc(2); mu(7); fi(6);
      FX(4);
      hs(2); hs(3); he(4); he(5); mu(0); fi(7); ad(4); ad(5);
      FX(5);
      hc(3); hs(4); he(6); he(7); mu(1); fi(0); ad(6);
      FX(6);
      hs(5); hs(6); hs(7); mu(2); fi(1); ad(7); pf();
      FX(7);
    };
#pragma unroll
    for (int j = 0; j < 8; j++) sum[j] = 0;
    body(IC<1>());
    int cnt = (lens & 255) - 1;
#pragma unroll 1
    for (int t = 0; t < 8; t++) {
#pragma unroll 1
      for (; cnt > 0; cnt--) { body(IC<0>());
      }
      if (!(t & 1)) {
        ownp = own;
        if (t < 6) {
          a_g += 64; own = lds16(a_g) * 0x10001u;
          if (t == 0) {
#pragma unroll
            for (int j = 0; j < 8; j++) bp[2 * j + 1] = sp[j];
          } else bload((a_g & 16) ? (t & 4) * 256 : 0);
          lens >>= 8; cnt = 1;
          continue;
        }
        body(IC<2>()); t++;
        STAMP(9);
      }
      cnt = (lens & 255) - 1;
      { const uint32_t ng = __shfl_sync(~0u, ownp, (a_g >> 1) | 3) >> 16, c3 = (a_g >> 1) & 3;
        asm volatile("{.reg .pred p; setp.lt.u32 p, %2, %3; @p st.global.u16 [%0], %1;}" :: "l"(p.out + (size_t)p.N * 64 + (size_t)node0 * 3 + (ng * 3 + c3)), "h"((uint16_t)pack_bf16(bf_hi(ownp) + pacc, 0.f)), "r"(ng), "r"(c3 < 3 ? nloc : 0) : "memory"); }
      chk = fmaf(pacc, 0.f, chk); pacc = 0.f;
      if (t & 2) {
        uint32_t hf[16]; float acc[32];
        const uint32_t nd = lds16(a_n); a_n += 128;
        const uint32_t hrow = hload(hf, nd);
        const uint64_t b1 = DHI | ((sb + OFF_W) >> 4), b2_ = b1 + 512;
        mbar_wait(sb + BAR_WH);
        wg_fence();
        rs64h<0>(acc, sp[0], sum[0], sp[1], sum[1], b2_); rs64h<1>(acc, sp[2], sum[2], sp[3], sum[3], b2_ + 128); rs64h<1>(acc, sp[4], sum[4], sp[5], sum[5], b2_ + 256); rs64h<1>(acc, sp[6], sum[6], sp[7], sum[7], b2_ + 384);
        rs64b<1>(acc, hf[0], hf[1], hf[2], hf[3], b1); rs64b<1>(acc, hf[4], hf[5], hf[6], hf[7], b1 + 128); rs64b<1>(acc, hf[8], hf[9], hf[10], hf[11], b1 + 256); rs64b<1>(acc, hf[12], hf[13], hf[14], hf[15], b1 + 384);
        wg_commit(); wg_wait0(); fence_regs(acc);
        if (t == 7) STAMP(10);
        chk = fmaf(acc[0], 0.f, fmaf(acc[2], 0.f, chk));
        auto fin = [&](uint32_t x, float y0, float y1) { return u2(__hadd2(b2(x), b2(pack_bf16(silu_h(y0), silu_h(y1))))); };
#pragma unroll
        for (int j = 0; j < 4; j++) stsm4(hrow ^ (j << 5), fin(hf[4 * j], acc[8 * j], acc[8 * j + 1]), fin(hf[4 * j + 1], acc[8 * j + 2], acc[8 * j + 3]), fin(hf[4 * j + 2], acc[8 * j + 4], acc[8 * j + 5]), fin(hf[4 * j + 3], acc[8 * j + 6], acc[8 * j + 7]));
        __syncwarp();
        const uint32_t c8 = (a_g << 3) & 0x70;
#pragma unroll
        for (int j = 0; j < 4; j++) { uint32_t v[4]; const uint32_t n = __shfl_sync(~0u, nd, 4 * j + ((a_g >> 4) & 3)); lds128(v, sb + OFF_H + n * 128 + (((n << 4) ^ c8) & 0x70));
          asm volatile("{.reg .pred p; setp.lt.u32 p, %5, %6; @p st.global" OCS ".v4.b32 [%0], {%1,%2,%3,%4};}" :: "l"((const char*)p.out + (size_t)node0 * 128 + (n * 128 + c8)), "r"(v[0]), "r"(v[1]), "r"(v[2]), "r"(v[3]), "r"(n), "r"(nloc) : "memory"); }
        wload();
      }
#pragma unroll
      for (int j = 0; j < 8; j++) { sp[j] = sum[j]; asm volatile("mov.b32 %0, 0;" : "=r"(sum[j])); }
    }
    asm volatile("{.reg .pred p, q; setp.neu.f32 p, %1, 0f00000000; setp.ne.or.u32 p, %2, 0, p; bar.red.or.pred q, 5, 384, p; selp.u32 %0, 1, 0, q;}" : "=r"(bad) : "f"(chk), "r"(lds32(sb + OFF_MISC + 12)) : "memory");
    STAMP(11);
   } else { asm volatile("cp.async.wait_all;" ::: "memory"); bar_sync(5, 384); }
  }
  if (bad) slow_path(p, wid, lane, node0, nloc);
}

}

typedef CUresult (*EncodeFn)(CUtensorMap*, CUtensorMapDataType, cuuint32_t, void*, const cuuint64_t*, const cuuint64_t*, const cuuint32_t*, const cuuint32_t*,
                             CUtensorMapInterleave, CUtensorMapSwizzle, CUtensorMapL2promotion, CUtensorMapFloatOOBfill);

extern "C" void kernel_launch(void* const* d_in, const int* in_sizes, int n_in, void* d_out, int out_size) {
  Params p; Maps maps;
  p.h = (const uint4*)d_in[0]; p.pos = (const uint16_t*)d_in[1]; p.ea = (const uint4*)d_in[2];
  p.src = (const int*)d_in[3]; p.dst = (const int*)d_in[4];
  p.we = (const uint16_t*)d_in[5]; p.wx = (const uint16_t*)d_in[6]; p.wh = (const uint16_t*)d_in[7];
  p.out = (uint16_t*)d_out;
  p.N = in_sizes[0] / 64; p.E = in_sizes[3];
  p.EPC = ((p.E + G * 4 - 1) / (G * 4)) * 4;
  p.magic = (uint32_t)(((uint64_t)G << 24) / (uint64_t)p.N);
  p.inv = (1ull << 56) / p.magic;
  const uint64_t ea0 = (uint64_t)d_in[2], ea1 = ea0 + (uint64_t)p.E * 32 - 1;
  p.force_slow = ((ea0 >> 32) != (ea1 >> 32)) || (ea0 & 31) || (p.E & 3);
  void* qp = nullptr;
  cudaGetSymbolAddress(&qp, g_q);
  p.q = (char*)qp;
  if (((uint64_t)p.q >> 32) != (((uint64_t)p.q + QBYTES) >> 32)) p.q += QBYTES;
  cudaGetSymbolAddress((void**)&p.sync, g_sync); cudaGetSymbolAddress((void**)&p.xe, g_xe);
  cudaGetSymbolAddress((void**)&p.xa, g_xa); cudaGetSymbolAddress((void**)&p.xb, g_xb);
  void* fn = nullptr; cudaDriverEntryPointQueryResult qr;
  cudaGetDriverEntryPoint("cuTensorMapEncodeTiled", &fn, cudaEnableDefault, &qr);
  auto mk = [&](CUtensorMap* tm, void* base, int rows) {
    const cuuint64_t dim[2] = {64, (cuuint64_t)rows}, str[1] = {128}; const cuuint32_t bx[2] = {64, 64}, es[2] = {1, 1};
    ((EncodeFn)fn)(tm, CU_TENSOR_MAP_DATA_TYPE_BFLOAT16, 2, base, dim, str, bx, es, CU_TENSOR_MAP_INTERLEAVE_NONE, CU_TENSOR_MAP_SWIZZLE_128B,
                   CU_TENSOR_MAP_L2_PROMOTION_NONE, CU_TENSOR_MAP_FLOAT_OOB_FILL_NONE);
  };
  mk(&maps.m[TM_H / 128], d_in[0], p.N); mk(&maps.m[TM_WE / 128], d_in[5], 145); mk(&maps.m[TM_WH / 128], d_in[7], 128); mk(&maps.m[TM_Q / 128], p.q, p.N);
  for (int k = 0; k < 2; k++) {
    void* xp = (void*)(k ? p.xb : p.xa);
    const cuuint64_t dim[2] = {(cuuint64_t)G * 64, (cuuint64_t)G}, str[1] = {(cuuint64_t)G * (128 << k)}; const cuuint32_t bx[2] = {64, (cuuint32_t)(k ? BROWS : G)}, es[2] = {1, 1};
    ((EncodeFn)fn)(&maps.m[TM_XA / 128 + k], k ? CU_TENSOR_MAP_DATA_TYPE_UINT32 : CU_TENSOR_MAP_DATA_TYPE_UINT16, 2, xp, dim, str, bx, es, CU_TENSOR_MAP_INTERLEAVE_NONE,
                   CU_TENSOR_MAP_SWIZZLE_NONE, CU_TENSOR_MAP_L2_PROMOTION_NONE, CU_TENSOR_MAP_FLOAT_OOB_FILL_NONE);
  }
  cudaFuncSetAttribute(egnn_kernel, cudaFuncAttributeMaxDynamicSharedMemorySize, SMEM);
  egnn_kernel<<<G, NTHR, SMEM>>>(p, maps);
}
```

```cpp
#include <cuda_runtime.h>
#include <cuda_bf16.h>
#include <cuda_fp16.h>
#include <cuda.h>
#include <stdint.h>
#pragma nv_diag_suppress 549

#define PFN 16
#define PFNS 250
#define FM 0
#define OPQ 0
#define H0 0
#define HALL 0
#define PF0NS 0
#define PFW 0
#define QCODE 0x254a109b7863ull
#define QREV 0x605
#define PFS 1
#define ESZ ""
#define XEF 0
#define OCS ""
#define HW 3
#define BROWS 132
#define B_HOLD 1
#define LSEQ 0x231200ull
#define HE 0
namespace {

constexpr int G = 132;
constexpr int NTHR = 512, NWK = 352, NCH = 5;
constexpr int NST = 3, STG = 2560;
constexpr int SCAP = 448;

constexpr int OFF_H = 0;
constexpr int OFF_W = 49152;
constexpr int OFF_WD = OFF_W + 16384;
constexpr int OFF_W3 = OFF_WD + 1024;
constexpr int OFF_P2 = OFF_W3 + 2048;
constexpr int OFF_RING = OFF_P2 + 24576;
constexpr int OFF_TE = OFF_RING + 12 * NST * STG;
constexpr int OFF_TS = OFF_TE + SCAP * 64;
constexpr int OFF_GP = OFF_TS + SCAP * 32;
constexpr int OFF_WX = OFF_GP + 3072;
constexpr int OFF_LEN = OFF_WX + 128;
constexpr int OFF_MISC = OFF_LEN + 128;
constexpr int OFF_BAR = OFF_MISC + 48;
constexpr int SMEM = OFF_BAR + 256;
static_assert(SMEM <= 232448, "smem");
constexpr uint32_t sb = 1024;
constexpr int OFF_SRCI = OFF_TE;
constexpr int OFF_SB = OFF_RING, OFF_SA = OFF_SB + 34816, OFF_AX = OFF_SA + 32768, OFF_DST = OFF_H + 24576;
constexpr int OFF_XB = OFF_SB;
constexpr int OFF_WS = OFF_AX + 17408;
constexpr int OFF_BC = OFF_WS + 2304;
constexpr int OFF_CNT = OFF_P2 + 16384;
constexpr int OFF_DH = OFF_CNT + 2176;
constexpr int OFF_POS = OFF_DH + 128;
constexpr int OFF_EXT = OFF_POS + 3072;
static_assert(OFF_XB + G * 256 <= OFF_AX && OFF_EXT + 1024 <= OFF_RING && OFF_BC + 544 <= OFF_TE && OFF_P2 % 1024 == 0 && OFF_SA % 1024 == 0 && SCAP * 64 >= 24576, "staging");
constexpr int BAR_DST = OFF_BAR, BAR_SRC = BAR_DST + 40, BAR_T = BAR_SRC + 24, BAR_W = BAR_T + 48, BAR_XA = BAR_W + 8, BAR_PS = BAR_XA + 8, BAR_AW = BAR_PS + 8,
              BAR_QP = BAR_AW + 8, BAR_QR = BAR_QP + 8, BAR_HA = BAR_QR + 8, BAR_EP = BAR_HA + 8, BAR_AX = BAR_EP + 8, BAR_AI = BAR_AX + 8, BAR_HB = BAR_AI + 8, BAR_U = BAR_HB + 8, BAR_WH = BAR_U + 8, BAR_END = BAR_WH + 8;
constexpr uint32_t QBYTES = 8u << 20;

__device__ __align__(256) uint4 g_xa[G * G * 8];
__device__ __align__(256) uint4 g_xb[G * G * 16];
__device__ __align__(256) uint2 g_xe[G * G * 32];
__device__ __align__(256) uint4 g_q[2 * QBYTES / 16];
__device__ __align__(256) uint32_t g_sync[8];
#define STAMP(k)

struct Maps { CUtensorMap m[6]; };
constexpr int TM_H = 0, TM_WE = 128, TM_WH = 256, TM_Q = 384, TM_XA = 512, TM_XB = 640;
struct Params {
  const uint4* h; const uint16_t* pos; const uint4* ea; const int* src; const int* dst;
  const uint16_t* we; const uint16_t* wx; const uint16_t* wh; uint16_t* out; char* q;
  uint32_t* sync; const uint4* xa; const uint4* xb; uint2* xe;
  int N, E, EPC; uint32_t magic; int force_slow; unsigned long long inv;
};
template<int V> struct IC { static constexpr int value = V; };

#define R32(d) "+f"(d[0]),"+f"(d[1]),"+f"(d[2]),"+f"(d[3]),"+f"(d[4]),"+f"(d[5]),"+f"(d[6]),"+f"(d[7]),"+f"(d[8]),"+f"(d[9]),"+f"(d[10]),"+f"(d[11]),"+f"(d[12]),"+f"(d[13]),"+f"(d[14]),"+f"(d[15]),"+f"(d[16]),"+f"(d[17]),"+f"(d[18]),"+f"(d[19]),"+f"(d[20]),"+f"(d[21]),"+f"(d[22]),"+f"(d[23]),"+f"(d[24]),"+f"(d[25]),"+f"(d[26]),"+f"(d[27]),"+f"(d[28]),"+f"(d[29]),"+f"(d[30]),"+f"(d[31])
#define S32 "{%0,%1,%2,%3,%4,%5,%6,%7,%8,%9,%10,%11,%12,%13,%14,%15,%16,%17,%18,%19,%20,%21,%22,%23,%24,%25,%26,%27,%28,%29,%30,%31}"
#define DI __device__ __forceinline__

constexpr uint64_t DHI = ((uint64_t)(1024 >> 4) << 32) | (1ull << 62);
template<int SD> DI void rs64b(float (&d)[32], uint32_t a0, uint32_t a1, uint32_t a2, uint32_t a3, uint64_t db) {
  asm volatile("wgmma.mma_async.sync.aligned.m64n64k16.f32.bf16.bf16 " S32 ", {%32,%33,%34,%35}, %36, %37, 1, 1, 1;" : R32(d) : "r"(a0), "r"(a1), "r"(a2), "r"(a3), "l"(db), "n"(SD)); }
template<int SD> DI void rs64h(float (&d)[32], uint32_t a0, uint32_t a1, uint32_t a2, uint32_t a3, uint64_t db) {
  asm volatile("wgmma.mma_async.sync.aligned.m64n64k16.f32.f16.f16 " S32 ", {%32,%33,%34,%35}, %36, %37, 1, 1, 1;" : R32(d) : "r"(a0), "r"(a1), "r"(a2), "r"(a3), "l"(db), "n"(SD)); }
template<int SD> DI void ss64(float (&d)[32], uint64_t da, uint64_t db) {
  asm volatile("wgmma.mma_async.sync.aligned.m64n64k16.f32.bf16.bf16 " S32 ", %32, %33, %34, 1, 1, 0, 1;" : R32(d) : "l"(da), "l"(db), "n"(SD)); }
DI void trap_if(bool c) { asm volatile("{.reg .pred p; setp.eq.u32 p, %0, 0; @p bra.uni LT_%=; trap; LT_%=:}" :: "r"((uint32_t)c)); }
DI void wg_fence() { asm volatile("wgmma.fence.sync.aligned;" ::: "memory"); }
DI void wg_commit() { asm volatile("wgmma.commit_group.sync.aligned;" ::: "memory"); }
DI void wg_wait0() { asm volatile("wgmma.wait_group.sync.aligned 0;" ::: "memory"); }
DI void fence_regs(float (&d)[32]) { asm volatile("" : R32(d) :: "memory"); }
DI void proxy_fence() { asm volatile("fence.proxy.async.shared::cta;" ::: "memory"); }
DI uint64_t pol_first() { uint64_t r; asm("createpolicy.fractional.L2::evict_first.b64 %0, 1.0;" : "=l"(r)); return r; }
DI float tanh_ap(float x) { float y; asm("tanh.approx.f32 %0, %1;" : "=f"(y) : "f"(x)); return y; }
DI float silu_h(float y) { return fmaf(y, tanh_ap(y), y); }
DI uint32_t pack_bf16(float lo, float hi) { uint32_t r; asm("cvt.rn.bf16x2.f32 %0, %1, %2;" : "=r"(r) : "f"(hi), "f"(lo)); return r; }
DI uint32_t pack_f16(float lo, float hi) { uint32_t r; asm("cvt.rn.f16x2.f32 %0, %1, %2;" : "=r"(r) : "f"(hi), "f"(lo)); return r; }
DI float bf_lo(uint32_t v) { return __uint_as_float(v << 16); }
DI float bf_hi(uint32_t v) { return __uint_as_float(v & 0xFFFF0000u); }
DI uint32_t b2h(uint32_t v, float s) { return pack_f16(s * bf_lo(v), s * bf_hi(v)); }
DI void mbar_wait(uint32_t bar, uint32_t parity = 0) {
  asm volatile("{.reg .pred p; .reg .u32 t0, t1;\n"
    "mbarrier.try_wait.parity.shared::cta.b64 p, [%0], %1;\n @p bra.uni LD_%=;\n mov.u32 t0, %%clock;\n"
    "LW_%=: mbarrier.try_wait.parity.shared::cta.b64 p, [%0], %1;\n"
    "@p bra.uni LD_%=;\n mov.u32 t1, %%clock; sub.u32 t1, t1, t0; setp.lt.u32 p, t1, 0x80000000;\n @p bra.uni LW_%=;\n trap;\n LD_%=:}" :: "r"(bar), "r"(parity) : "memory");
}
DI void mbar_arrive(uint32_t bar, int p = 1) { asm volatile("{.reg .pred p; setp.ne.b32 p, %1, 0; @p mbarrier.arrive.shared::cta.b64 _, [%0];}" :: "r"(bar), "r"(p) : "memory"); }
DI void bar_sync(int id, int n) { asm volatile("bar.sync %0, %1;" :: "r"(id), "r"(n) : "memory"); }
DI void bar_arrive(int id, int n) { asm volatile("bar.arrive %0, %1;" :: "r"(id), "r"(n) : "memory"); }
DI __nv_bfloat162 b2(uint32_t v) { return *(__nv_bfloat162*)&v; }
DI uint32_t u2(__nv_bfloat162 v) { return *(uint32_t*)&v; }
DI uint32_t hsq(uint32_t v) { return u2(__hmul2(b2(v), b2(v))); }
DI uint32_t hsub(uint32_t a, uint32_t b) { return u2(__hsub2(b2(a), b2(b))); }
DI uint32_t hhalf(uint32_t v) { return u2(__hmul2(b2(v), __floats2bfloat162_rn(0.5f, 0.5f))); }
DI uint32_t mag2(uint32_t m, uint32_t v) { return __vmaxu2(m, v & 0x7FFF7FFFu); }
DI uint32_t hmag(uint32_t m, uint32_t v) { const __half2 r = __hmax2(*(const __half2*)&m, __habs2(*(const __half2*)&v)); return *(const uint32_t*)&r; }
DI uint32_t magr(uint32_t m) { return max(m & 0xFFFF, m >> 16); }
DI void sts128(uint32_t a, uint32_t x, uint32_t y, uint32_t z, uint32_t w) { asm volatile("st.shared.v4.u32 [%0], {%1,%2,%3,%4};" :: "r"(a), "r"(x), "r"(y), "r"(z), "r"(w) : "memory"); }
DI void sts64(uint32_t a, uint32_t x, uint32_t y) { asm volatile("st.shared.v2.u32 [%0], {%1,%2};" :: "r"(a), "r"(x), "r"(y) : "memory"); }
DI void sts32(uint32_t a, uint32_t x) { asm volatile("st.shared.u32 [%0], %1;" :: "r"(a), "r"(x) : "memory"); }
DI void sts16(uint32_t a, uint32_t x) { asm volatile("st.shared.u16 [%0], %1;" :: "r"(a), "h"((uint16_t)x) : "memory"); }
DI void lds128(uint32_t* v, uint32_t a) { asm volatile("ld.shared.v4.u32 {%0, %1, %2, %3}, [%4];" : "=r"(v[0]), "=r"(v[1]), "=r"(v[2]), "=r"(v[3]) : "r"(a) : "memory"); }
DI void lds64(uint32_t& x, uint32_t& y, uint32_t a) { asm volatile("ld.shared.v2.u32 {%0, %1}, [%2];" : "=r"(x), "=r"(y) : "r"(a) : "memory"); }
DI uint32_t lds32(uint32_t a) { uint32_t x; asm volatile("ld.shared.u32 %0, [%1];" : "=r"(x) : "r"(a) : "memory"); return x; }
DI uint32_t lds16(uint32_t a) { uint32_t x; asm volatile("ld.shared.u16 %0, [%1];" : "=r"(x) : "r"(a) : "memory"); return x; }
DI uint32_t atoms_add(uint32_t a, uint32_t v) { uint32_t r; asm volatile("atom.shared.add.u32 %0, [%1], %2;" : "=r"(r) : "r"(a), "r"(v) : "memory"); return r; }
DI void bulk_load(uint32_t dst, const void* src, uint32_t bytes, uint32_t bar) {
  asm volatile("cp.async.bulk.shared::cluster.global.mbarrier::complete_tx::bytes.L2::cache_hint [%0], [%1], %2, [%3], %4;" :: "r"(dst), "l"(src), "r"(bytes), "r"(bar), "l"(pol_first()) : "memory"); }
DI void bulk_store(void* dst, uint32_t src, uint32_t bytes) { asm volatile("cp.async.bulk.global.shared::cta.bulk_group [%0], [%1], %2;" :: "l"(dst), "r"(src), "r"(bytes) : "memory"); }
DI void mbar_expect(uint32_t bar, uint32_t bytes) { asm volatile("mbarrier.arrive.expect_tx.shared::cta.b64 _, [%0], %1;" :: "r"(bar), "r"(bytes) : "memory"); }
DI void mbar_init(uint32_t bar, int n) { asm volatile("mbarrier.init.shared::cta.b64 [%0], %1;" :: "r"(bar), "r"(n) : "memory"); }
DI void tma_load(uint32_t dst, uint64_t tm, int row, uint32_t bar) {
  asm volatile("cp.async.bulk.tensor.2d.shared::cluster.global.mbarrier::complete_tx::bytes.L2::cache_hint [%0], [%1, {%3, %4}], [%2], %5;" :: "r"(dst), "l"(tm), "r"(bar), "r"(0), "r"(row), "l"(pol_first()) : "memory"); }
DI void tma_store(uint64_t tm, int col, int row, uint32_t src) {
  asm volatile("cp.async.bulk.tensor.2d.global.shared::cta.bulk_group [%0, {%2, %3}], [%1];" :: "l"(tm), "r"(src), "r"(col), "r"(row) : "memory"); }
DI void tma_store_ef(uint64_t tm, int col, int row, uint32_t src) {
  if (XEF) asm volatile("cp.async.bulk.tensor.2d.global.shared::cta.bulk_group.L2::cache_hint [%0, {%2, %3}], [%1], %4;" :: "l"(tm), "r"(src), "r"(col), "r"(row), "l"(pol_first()) : "memory");
  else tma_store(tm, col, row, src); }
DI void bulk_commit() { asm volatile("cp.async.bulk.commit_group;" ::: "memory"); }
DI void bulk_wait_read() { asm volatile("cp.async.bulk.wait_group.read 0;" ::: "memory"); }
DI uint2 ld_poll2(const void* a) { uint2 v; asm volatile("ld.relaxed.gpu.global.v2.u32 {%0, %1}, [%2];" : "=r"(v.x), "=r"(v.y) : "l"(a) : "memory"); return v; }
DI void st_ext(uint2* a, uint32_t v, uint32_t ep) { asm volatile("st.relaxed.gpu.global.v2.u32 [%0], {%1, %2};" :: "l"(a), "r"(v), "r"(ep) : "memory"); }
DI uint32_t ext_get(const uint2* a, uint32_t ep) { uint2 v; int spin = 0; do { v = ld_poll2(a); trap_if(++spin > 4000000); } while (__any_sync(~0u, v.y != ep)); return v.x; }
DI void bulk_wait() { asm volatile("cp.async.bulk.wait_group 0;" ::: "memory"); }
DI void hint_signal(uint32_t* c) { asm volatile("red.relaxed.gpu.global.add.u32 [%0], 1;" :: "l"(c) : "memory"); }
DI void hint_wait(const uint32_t* c, uint32_t target) { uint32_t v; int spin = 0;
  do { asm volatile("ld.relaxed.gpu.global.u32 %0, [%1];" : "=r"(v) : "l"(c) : "memory"); trap_if(++spin > 4000000); } while (__any_sync(~0u, (int)(v - target) < 0)); }
DI void stsm4(uint32_t a, uint32_t x, uint32_t y, uint32_t z, uint32_t w) { asm volatile("stmatrix.sync.aligned.m8n8.x4.shared.b16 [%0], {%1,%2,%3,%4};" :: "r"(a), "r"(x), "r"(y), "r"(z), "r"(w) : "memory"); }
DI void ldsm4(uint32_t* v, uint32_t a) { asm volatile("ldmatrix.sync.aligned.m8n8.x4.shared.b16 {%0,%1,%2,%3}, [%4];" : "=r"(v[0]), "=r"(v[1]), "=r"(v[2]), "=r"(v[3]) : "r"(a) : "memory"); }
DI void ldsm4t(uint32_t* v, uint32_t a) { asm volatile("ldmatrix.sync.aligned.m8n8.x4.trans.shared.b16 {%0,%1,%2,%3}, [%4];" : "=r"(v[0]), "=r"(v[1]), "=r"(v[2]), "=r"(v[3]) : "r"(a) : "memory"); }
DI uint32_t mad16(uint32_t x, uint32_t m, uint32_t c) { uint32_t r; asm("dp2a.lo.u32.u32 %0, %1, %2, %3;" : "=r"(r) : "r"(x), "r"(m), "r"(c)); return r; }
DI bool wbad(uint32_t m, uint32_t hi) { return m > hi || (m && m < 0x3980); }

__device__ __noinline__ void slow_path(const Params& p, int wid, int lane, int node0, int nloc) {
  const uint32_t ab = sb + OFF_P2 + wid * 8704;
  for (int i = lane; i < 32 * 68; i += 32) sts32(ab + i * 4, 0);
  __syncwarp();
  const uint32_t wdv = __ldg((const uint32_t*)(p.we + 128 * 64) + lane), wxv = __ldg((const uint32_t*)p.wx + lane);
  const int nb0 = node0 + wid * 32, cntn = max(0, min(32, nloc - wid * 32));
  auto dot = [&](uint32_t hv, const uint16_t* w, int K2, float& y0, float& y1) {
#pragma unroll 4
    for (int k = 0; k < K2; k++) {
      const uint32_t hk = __shfl_sync(~0u, hv, k), wa = __ldg((const uint32_t*)(w + 2 * k * 64) + lane), wb = __ldg((const uint32_t*)(w + (2 * k + 1) * 64) + lane);
      y0 = fmaf(bf_lo(hk), bf_lo(wa), fmaf(bf_hi(hk), bf_lo(wb), y0)); y1 = fmaf(bf_lo(hk), bf_hi(wa), fmaf(bf_hi(hk), bf_hi(wb), y1));
    }
  };
  auto silu = [](float x) { return x / (1.f + __expf(-x)); };
#pragma unroll 1
  for (int base = 0; base < p.E; base += 32) {
    const int e = base + lane;
    const uint32_t dl = e < p.E ? (uint32_t)(__ldg(p.dst + e) - nb0) : 0xFFFFFFFFu;
    uint32_t mk = __ballot_sync(~0u, dl < (uint32_t)cntn);
    while (mk) {
      const int l = __ffs(mk) - 1; mk &= mk - 1;
      const int ee = base + l, n = __shfl_sync(~0u, dl, l), s = __ldg(p.src + ee);
      const uint16_t *po = p.pos + (size_t)(nb0 + n) * 3, *pp = p.pos + (size_t)s * 3;
      const uint32_t dxy = hsub(__ldg(po) | (__ldg(po + 1) << 16), __ldg(pp) | (__ldg(pp + 1) << 16)), dz = hsub(__ldg(po + 2), __ldg(pp + 2));
      const uint32_t sq = hsq(dxy); const float d2 = bf_lo(sq) + bf_hi(sq) + bf_lo(hsq(dz));
      float y0 = d2 * bf_lo(wdv), y1 = d2 * bf_hi(wdv);
      dot(__ldg((const uint32_t*)(p.h + (size_t)(nb0 + n) * 8) + lane), p.we, 32, y0, y1);
      dot(__ldg((const uint32_t*)(p.h + (size_t)s * 8) + lane), p.we + 64 * 64, 32, y0, y1);
      dot(__ldg((const uint32_t*)(p.ea + (size_t)ee * 2) + (lane & 7)), p.we + 129 * 64, 8, y0, y1);
      const uint32_t mm = pack_bf16(silu(y0), silu(y1));
      float c = bf_lo(mm) * bf_lo(wxv) + bf_hi(mm) * bf_hi(wxv);
#pragma unroll
      for (int o = 16; o; o >>= 1) c += __shfl_xor_sync(~0u, c, o);
      const uint32_t a = ab + n * 272;
      uint32_t x0, x1; lds64(x0, x1, a + lane * 8);
      sts64(a + lane * 8, __float_as_uint(__uint_as_float(x0) + bf_lo(mm)), __float_as_uint(__uint_as_float(x1) + bf_hi(mm)));
      if (lane < 3) { const float df = lane == 0 ? bf_lo(dxy) : lane == 1 ? bf_hi(dxy) : bf_lo(dz); sts32(a + 256 + lane * 4, __float_as_uint(fmaf(c, df, __uint_as_float(lds32(a + 256 + lane * 4))))); }
    }
  }
  __syncwarp();
#pragma unroll 1
  for (int n = 0; n < cntn; n++) {
    uint32_t x0, x1; lds64(x0, x1, ab + n * 272 + lane * 8);
    const uint32_t hv = __ldg((const uint32_t*)(p.h + (size_t)(nb0 + n) * 8) + lane);
    float y0 = 0.f, y1 = 0.f;
    dot(hv, p.wh, 32, y0, y1); dot(pack_bf16(__uint_as_float(x0), __uint_as_float(x1)), p.wh + 64 * 64, 32, y0, y1);
    ((uint32_t*)p.out)[(size_t)(nb0 + n) * 32 + lane] = u2(__hadd2(b2(hv), b2(pack_bf16(silu(y0), silu(y1)))));
    if (lane < 3) p.out[(size_t)p.N * 64 + (size_t)(nb0 + n) * 3 + lane] = (uint16_t)pack_bf16(bf_lo(__ldg(p.pos + (size_t)(nb0 + n) * 3 + lane)) + __uint_as_float(lds32(ab + n * 272 + 256 + lane * 4)), 0.f);
  }
}

__global__ void __launch_bounds__(NTHR, 1) egnn_kernel(const __grid_constant__ Params p, const __grid_constant__ Maps maps) {
  const uint64_t tmb = (uint64_t)&maps;
  extern __shared__ __align__(1024) unsigned char smraw[];
  const int tid = threadIdx.x, cta = blockIdx.x;
  const int e0 = cta * p.EPC, n4 = max(0, min(p.EPC, p.E - e0)) >> 2;
  STAMP(0);
  asm volatile("{.reg .pred p; setp.eq.u32 p, %2, 384; @p cp.async.cg.shared.global [%0], [%1], 16;}" :: "r"(sb + OFF_LEN - 192 + (tid >> 1)), "l"(p.sync), "r"(tid & 415) : "memory");
  if (tid == NWK) {
#pragma unroll
    for (int k = 0; k < NCH; k++) mbar_init(sb + BAR_DST + k * 8, 1);
    asm volatile("fence.mbarrier_init.release.cluster;" ::: "memory");
#pragma unroll 1
    for (int k = 0; k < NCH; k++) { const int nb = max(0, min(NWK, n4 - k * NWK)) * 16;
      mbar_expect(sb + BAR_DST + k * 8, nb);
      if (nb) bulk_load(sb + OFF_DST + k * NWK * 16, (const char*)(p.dst + e0) + k * NWK * 16, nb, sb + BAR_DST + k * 8); }
  }
  const int lane = tid & 31, wid = __shfl_sync(~0u, tid >> 5, 0), w = wid & 3;

  auto first_node = [&](int c) { return (int)((c * p.inv + 0xFFFFFFFFull) >> 32); };
  const int node0 = first_node(cta), nloc = min(first_node(cta + 1), p.N) - node0;
  const uint32_t ealo = (uint32_t)(uint64_t)p.ea;
  const int epad = min(e0, p.E - 1);
  auto load_h = [&](int b) { mbar_expect(sb + BAR_T + b * 8, 8192); tma_load(sb + OFF_H + b * 8192, tmb + TM_H, node0 + b * 64, sb + BAR_T + b * 8); };
  if (wid >= 12) {
    const int t = tid - 384;
    auto prefetch_e = [&](int i) {
      const uint32_t nb = (p.E / G) & ~15u;
      if (nb && i < PFN) asm volatile("cp.async.bulk.prefetch.L2.global [%0], %1;" :: "l"((const char*)p.ea + (size_t)(((i * PFS + i * PFS / 32 * (~PFS & 1)) & 31) * G + cta) * nb), "r"(nb) : "memory");
    };
    uint32_t pv[9], ev = 0;
#pragma unroll
    for (int i = 0; i < 3; i++) { const uint16_t* pp = p.pos + (size_t)(node0 + t + 128 * i) * 3;
      pv[3 * i] = pv[3 * i + 1] = pv[3 * i + 2] = 0;
      asm volatile("{.reg .pred p; setp.lt.s32 p, %4, %5;\n @p ld.global.nc.u16 %0, [%3];\n @p ld.global.nc.u16 %1, [%3+2];\n @p ld.global.nc.u16 %2, [%3+4];}"
        : "+r"(pv[3 * i]), "+r"(pv[3 * i + 1]), "+r"(pv[3 * i + 2]) : "l"(pp), "r"(t + 128 * i), "r"(p.N - node0)); }
    asm volatile("{.reg .pred p; setp.lt.u32 p, %3, 8; @p ld.global.nc.u32 %0, [%1]; @p st.global.v4.u32 [%2], {%4, %4, %4, %4};}"
      : "+r"(ev) : "l"((const uint32_t*)(p.ea + (size_t)epad * 2) + t), "l"(p.q + (size_t)(p.N + cta) * 128 + t * 16), "r"(t), "r"(0xF700F700u) : "memory");
    asm volatile("cp.async.wait_all;" ::: "memory");
    __syncwarp();
    const uint32_t e = lds32(sb + OFF_LEN + 8 + w * 16) + 1;
    {
      const uint32_t tg = (1 + e % 3) << 30, v = ((tg >> 16) + 512 + (lane & 7) * 4) * 0x10001u;
      if (t == 0) sts32(sb + OFF_MISC + 32, e);
#pragma unroll
      for (int i = 0; i < 9; i++) sts128(sb + OFF_SA + t * 16 + i * 2048, v, v + 0x10001u, v + 0x20002u, v + 0x30003u);
      bar_sync(6, NTHR);
      mbar_arrive(sb + BAR_EP, lane == 0);
#pragma unroll
      for (int i = 0; i < 17; i++) sts128(sb + OFF_SB + t * 16 + i * 2048, tg, tg, tg, tg); }
    uint32_t mp = 0;
#pragma unroll
    for (int i = 0; i < 3; i++) { sts64(sb + OFF_POS + (t + 128 * i) * 8, pv[3 * i] | (pv[3 * i + 1] << 16), pv[3 * i + 2]); mp = mag2(mag2(mp, pv[3 * i] | (pv[3 * i + 1] << 16)), pv[3 * i + 2]); }
    proxy_fence();
    __syncwarp();
    mbar_arrive(sb + BAR_PS, lane == 0);
    mbar_wait(sb + BAR_W);
#pragma unroll
    for (int i = 0; i < 8; i += 4) { uint32_t v[16];
#pragma unroll
      for (int k = 0; k < 4; k++) lds128(v + 4 * k, sb + OFF_W + t * 16 + (i + k) * 2048);
#pragma unroll
      for (int k = 0; k < 4; k++) sts128(sb + OFF_W + t * 16 + (i + k) * 2048, hhalf(v[4 * k]), hhalf(v[4 * k + 1]), hhalf(v[4 * k + 2]), hhalf(v[4 * k + 3])); }
    {
      uint32_t v[4], u[4]; const int r = t >> 3, c = t & 7;
      lds128(v, sb + OFF_WS + 128 + t * 16); lds128(u, sb + OFF_WS + c * 16);
      const uint32_t x = lds32(sb + OFF_WS + 2176 + lane * 4);
      sts128(sb + OFF_W3 + r * 128 + ((c ^ (r & 7)) << 4), b2h(v[0], .5f), b2h(v[1], .5f), b2h(v[2], .5f), b2h(v[3], .5f));
      const float s = ((r & 1) || r == 6) ? 0.f : .5f;
      if (t < 64) sts128(sb + OFF_WD + r * 128 + ((c ^ r) << 4), b2h(u[0], s), b2h(u[1], s), b2h(u[2], s), b2h(u[3], s));
      if (t < 32) sts32(sb + OFF_WX + (t & 3) * 32 + (t >> 2) * 4, b2h(x, 1.f));
      const uint32_t m3 = __reduce_max_sync(~0u, magr(mag2(mag2(mag2(mag2(0, v[0]), v[1]), v[2]), v[3]))), md = __reduce_max_sync(~0u, magr(mag2(mag2(mag2(mag2(0, u[0]), u[1]), u[2]), u[3])));
      if (wbad(m3, 0x4000) || wbad(md, 0x4000) || wbad(__reduce_max_sync(~0u, magr(mag2(0, x))), 0x4700) || magr(mp) >= 0x4200 || magr(mag2(0, ev)) >= 0x4380) sts32(sb + OFF_MISC + 8, 1);
    }
    proxy_fence();
    if (w == 1) {
#pragma unroll 1
      for (int b = HE; b < HW; b++) { mbar_wait(sb + BAR_SRC + max(0, H0 + b) * 8); if (lane == 0) load_h(b); }
    }
    bar_sync(3, 128);
    STAMP(24);
    const uint32_t frag = (w * 16 + (lane & 15)) * 128 + (((lane >> 4) ^ (lane & 7)) << 4);
    uint32_t mq = 0;
#pragma unroll 1
    for (int b = 0; b < 6; b++) {
      float acc[32];
      const uint64_t da = DHI | (((sb + OFF_H) >> 4) + b * 512), db = DHI | ((sb + OFF_W) >> 4);
      const uint32_t v0 = lds16(sb + OFF_POS + b * 512 + w * 128 + lane * 2), v1 = lds16(sb + OFF_POS + 64 + b * 512 + w * 128 + lane * 2);
      mbar_wait(sb + BAR_T + b * 8);
      if (b == 0) STAMP(25);
      if (b == 5) STAMP(26);
      wg_fence();
      ss64<0>(acc, da, db); ss64<1>(acc, da + 2, db + 128); ss64<1>(acc, da + 4, db + 256); ss64<1>(acc, da + 6, db + 384);
      wg_commit();
      if (b == 0) mbar_wait(sb + BAR_AW);
      if (t == 32) { if (HALL) { if (b == 0) for (int k = HW; k < 6; k++) load_h(k); } else if (b + HW < 6) load_h(b + HW); }
      __syncwarp();
      uint32_t ff[6], fg[6];
#pragma unroll
      for (int j = 0; j < 6; j++) { ff[j] = (__byte_perm((j & 1) ? v1 : v0, 0, 0x4140) >> (3 * (j >> 1))) & 0x00070007u; fg[j] = __vsub2(0x00040004u, ff[j]);
        asm volatile("" : "+r"(ff[j]), "+r"(fg[j])); }
      wg_wait0(); fence_regs(acc);
      uint32_t o[16];
#pragma unroll
      for (int j = 0; j < 16; j++) o[j] = pack_f16(acc[2 * j], acc[2 * j + 1]);
#pragma unroll
      for (int j = 0; j < 6; j++) {
        const uint32_t m = o[j] & 0x7FFF7FFFu; mq = __vmaxu2(mq, m);
        o[j] = (__viaddmax_s16x2(m, fg[j], 0) & 0xFFF8FFF8u) | ff[j] | (o[j] & 0x80008000u); }
      const uint32_t qs = sb + (b < 2 ? OFF_P2 : OFF_SA - 16384) + b * 8192;
#pragma unroll
      for (int j = 0; j < 4; j++) stsm4((qs + frag) ^ (j << 5), o[4 * j], o[4 * j + 1], o[4 * j + 2], o[4 * j + 3]);
      proxy_fence();
      if (b == 5) { const uint32_t m = __reduce_max_sync(~0u, magr(mq)); if (lane == 0) sts32(sb + OFF_MISC + 16 + w * 4, m); }
      bar_sync(3, 128);
      if (t == 0) { if (b * 64 < nloc) tma_store(tmb + TM_Q, 0, node0 + b * 64, qs); if (b == 5) bulk_commit(); }
      __syncwarp();
    }
    asm volatile("setmaxnreg.dec.sync.aligned.u32 32;");
    if (w == 0) {
      STAMP(18);
      uint32_t mv[4]; lds128(mv, sb + OFF_MISC + 16);
      const uint32_t mx = max(max(mv[0], mv[1]), max(mv[2], mv[3]));
      bulk_wait();
      mbar_arrive(sb + BAR_QR, lane == 0);
      STAMP(19);
      if (lane == 0) {
        if (nloc > 0 && (mx >= 0x7BF0 || mx < 0x1400)) asm volatile("st.relaxed.gpu.global.u32 [%0+4], %1;" :: "l"(p.sync), "r"(e) : "memory");
        asm volatile("red.release.gpu.global.add.u32 [%0], 1;" :: "l"(p.sync) : "memory");
      }
      __syncwarp();
      uint32_t c, f; int spin = 0;
      do { asm volatile("ld.acquire.gpu.global.v2.u32 {%0, %1}, [%2];" : "=r"(c), "=r"(f) : "l"(p.sync) : "memory"); trap_if(++spin > 4000000); } while (__any_sync(~0u, (int)(c - e * G) < 0));
      if (f == e) sts32(sb + OFF_MISC + 8, 1);
      if (cta == 0 && lane == 0) asm volatile("st.relaxed.gpu.global.u32 [%0+8], %1;" :: "l"(p.sync), "r"(e) : "memory");
      STAMP(20);
      __syncwarp();
      mbar_arrive(sb + BAR_QP, lane == 0);
    }
    if (w == 1) {
      if (PFW) mbar_wait(sb + PFW);
      __nanosleep(PF0NS);
#pragma unroll 1
      for (int i = 0; i < PFN; i++) { if (lane == 0) prefetch_e(i); __nanosleep(PFNS); }
    }
    bar_sync(4, NTHR);
    if (t == 0) { mbar_expect(sb + BAR_U, 16384); tma_load(sb + OFF_W, tmb + TM_WH, 0, sb + BAR_U); tma_load(sb + OFF_W + 8192, tmb + TM_WH, 64, sb + BAR_U); }
    mbar_wait(sb + BAR_U);
    uint32_t mh = 0;
#pragma unroll 1
    for (int i = t; i < 512; i += 128) { uint32_t v[4]; const uint32_t a = sb + OFF_W + i * 16;
      lds128(v, a); sts128(a, hhalf(v[0]), hhalf(v[1]), hhalf(v[2]), hhalf(v[3]));
      lds128(v, a + 8192); sts128(a + 8192, b2h(v[0], .5f), b2h(v[1], .5f), b2h(v[2], .5f), b2h(v[3], .5f));
      mh = mag2(mag2(mag2(mag2(mh, v[0]), v[1]), v[2]), v[3]); }
    if (wbad(__reduce_max_sync(~0u, magr(mh)), 0x4700)) sts32(sb + OFF_MISC + 12, 1);
    proxy_fence();
    __syncwarp();
    mbar_arrive(sb + BAR_WH, lane == 0);
    return;
  }

  auto put = [&](uint32_t x, int hi, uint32_t bv, uint32_t eb) {
    asm volatile("{.reg .pred p; setp.eq.b32 p, %0, 0;\n @p st.shared.u32 [%1], %3;\n @p st.shared.u16 [%2], %4;}"
      :: "r"(x & (0x8000u << 16 * hi)), "r"(sb + OFF_TE + mad16(x, 2 << 8 * hi, 0)), "r"(sb + OFF_TS + (hi ? x >> 16 : x & 0xFFFF)), "r"(mad16(bv, 0x2000u, eb)), "h"((uint16_t)bv) : "memory");
  };
  if (tid == 320) {
    mbar_init(sb + BAR_W, 1);
    asm volatile("fence.mbarrier_init.release.cluster;" ::: "memory");
    mbar_expect(sb + BAR_W, 2 * 8192 + 2304);
    tma_load(sb + OFF_W, tmb + TM_WE, 64, sb + BAR_W); tma_load(sb + OFF_W + 8192, tmb + TM_WE, 0, sb + BAR_W);
    bulk_load(sb + OFF_WS, p.we + 128 * 64, 2176, sb + BAR_W); bulk_load(sb + OFF_WS + 2176, p.wx, 128, sb + BAR_W);
  }
  if (tid == 288) {
#pragma unroll
    for (int a = BAR_SRC; a < BAR_END; a += 8) if (a != BAR_W) mbar_init(sb + a, a == BAR_WH || a == BAR_PS || a == BAR_EP ? 4 : a == BAR_XA ? 11 : 1);
    asm volatile("fence.mbarrier_init.release.cluster;" ::: "memory");
    asm volatile("prefetch.tensormap [%0];" :: "l"(tmb + TM_XA)); asm volatile("prefetch.tensormap [%0];" :: "l"(tmb + TM_H));
    asm volatile("prefetch.tensormap [%0];" :: "l"(tmb + TM_XB)); asm volatile("prefetch.tensormap [%0];" :: "l"(tmb + TM_Q));
  }
  {
    if (tid < 144) { const uint32_t z = (tid >> 3) == 16 ? 0x8000u : 0u; sts128(sb + OFF_CNT + tid * 16, z, z, z, z); }
    else if (tid <= 144 + G) sts32(sb + OFF_BC + (tid - 144) * 4, ((tid - 144) & 31) * 4);
    const uint32_t sp = (p.N + cta) * 0x10001u, em = first_node(G);
    if (wid < 7) {
#pragma unroll
      for (int i = 0; i < 4; i++) sts128(sb + OFF_TS + tid * 16 + i * 3584, sp, sp, sp, sp);
    }
    static_assert(SCAP * 32 == 4 * 3584, "fill");
#pragma unroll 1
    for (int i = n4 + tid; i < 1536; i += 384) sts128(sb + OFF_DST + i * 16, em, em, em, em);
    if (tid == 321) sts128(sb + OFF_MISC, 0, 0, p.force_slow, 0);
  }
  bar_arrive(6, NTHR);
  bar_sync(0, 384);
  uint32_t ep, tag, eb0, pk[12], r0[12], r1[12], cb;
  uint2 vb[12];
  const uint2* xb = (const uint2*)(p.xb + (cta * G + wid) * 16) + ((lane + cta) & 31);
  auto get_tag = [&]() { mbar_wait(sb + BAR_EP); ep = lds32(sb + OFF_MISC + 32); tag = (1 + ep % 3) << 30; eb0 = ealo - (tag >> 11); };
  if (wid == 11) {
    trap_if(sb != (uint32_t)__cvta_generic_to_shared(smraw));
#pragma unroll 1
    for (unsigned long long q = LSEQ; q; q >>= 8) { const int k = (q >> 4) & 7, nb = max(0, min(8192, n4 * 16 - k * 8192));
      mbar_wait(sb + BAR_DST + ((uint32_t)q & 7) * 8);
      if (lane == 0) {
        if (k >= 3) load_h(k - 3);
        else { mbar_expect(sb + BAR_SRC + k * 8, nb);
          if (nb) bulk_load(sb + OFF_SRCI + k * 8192, (const char*)(p.src + e0) + k * 8192, nb, sb + BAR_SRC + k * 8); } } }
    get_tag();
    mbar_wait(sb + BAR_PS);
    bar_sync(12, 384);
    uint32_t xm = 0;
#pragma unroll
    for (int k = 0; k < 5; k++) xm |= (lds32(sb + OFF_BC + min(lane + 32 * k, G - 1) * 4) >= (65 << 9) && lane + 32 * k < G) << k;
    auto ext_send = [&](int pl) {
      uint32_t x = xm;
      for (uint32_t m; (m = __ballot_sync(~0u, x));) {
        const uint32_t l = __ffs(m) - 1, j = l + 32 * (__ffs(__shfl_sync(~0u, x, l)) - 1);
        if (lane == l) x &= x - 1;
        const uint32_t e = min(lds16(sb + OFF_AX + j * 128 + ((4 * l + 2 * lane) & 126)), 6143u);
        if (pl) st_ext(p.xe + (j * G + cta) * 32 + lane, lds32(sb + OFF_SRCI + e * 4) + tag + (e << 16), ep);
        else { const uint32_t cn = lds32(sb + OFF_BC + j * 4) >> 9, v = cn > 96 ? 1 : lane + 64 < cn ? 512 | (lds32(sb + OFF_DST + e * 4) & 511) : 0;
          asm volatile("red.shared.xor.b32 [%0], %1;" :: "r"(sb + OFF_SA + j * 128 + ((l + lane) & 31) * 4), "r"(((v & 63) << 10) | ((v >> 6) << 26)) : "memory"); }
      }
    };
    if (__any_sync(~0u, xm)) { ext_send(0); proxy_fence(); __syncwarp(); }
    if (lane == 0) { tma_store_ef(tmb + TM_XA, cta * 64, 0, sb + OFF_SA); bulk_commit(); mbar_arrive(sb + BAR_AI); bulk_wait(); hint_signal(p.sync + 4); mbar_arrive(sb + BAR_AW); STAMP(16); }
    __syncwarp();
    bar_sync(13, 384);
    if (!B_HOLD && lane == 0) { tma_store_ef(tmb + TM_XB, cta * 64, 0, sb + OFF_SB); bulk_commit(); }
    __syncwarp();
    ext_send(1);
    mbar_arrive(sb + BAR_AX, lane == 0);
    if (B_HOLD) mbar_wait(sb + (B_HOLD == 1 ? BAR_HA : BAR_XA));
    if (lane == 0) {
      bulk_wait();
#pragma unroll 1
      for (int r = B_HOLD ? 0 : BROWS; r < G; r += BROWS) { tma_store_ef(tmb + TM_XB, cta * 64, r, sb + OFF_SB + r * 256); bulk_commit(); bulk_wait(); }
      hint_signal(p.sync + 5);
      STAMP(17);
    }
    __syncwarp();
    hint_wait(p.sync + 5, ep * G);
    if (lane == 0) { mbar_expect(sb + BAR_HB, G * 256);
#pragma unroll 1
      for (int o = 0; o < 4; o++) bulk_load(sb + OFF_XB + o * (G * 64), (const char*)p.xb + (size_t)(cta * 4 + o) * (G * 64), G * 64, sb + BAR_HB); }
    __syncwarp();
    STAMP(21);
  } else {
    STAMP(15);
    {
      uint32_t d[4 * NCH], jj[4 * NCH], rr[4 * NCH];
      auto count = [&](int k) {
        mbar_wait(sb + BAR_DST + k * 8);
        lds128(d + 4 * k, sb + OFF_DST + (tid + NWK * k) * 16);
#pragma unroll
        for (int i = 4 * k; i < 4 * k + 4; i++) { jj[i] = d[i] * p.magic; rr[i] = atoms_add(__dp4a(jj[i], 0x04000000u, sb + OFF_BC), 0x202u); }
      };
      auto place = [&](int k) {
#pragma unroll
        for (int i = 4 * k; i < 4 * k + 4; i++) {
          const uint32_t o = __dp4a(jj[i], 0x80000000u, rr[i] & 0x807Eu);
          d[i] = (d[i] & 511) | (tag >> 16);
          asm("{.reg .pred p; setp.ge.u32 p, %1, 0x8000; @p add.u32 %0, %2, %3;}" : "+r"(d[i]) : "r"(o), "r"(tid * 4), "r"(NWK * k * 4 + (i & 3)));
          sts16(sb + OFF_SA + o, d[i]); jj[i] = __viaddmin_u32(o, o, G * 256);
        }
      };
      count(0); STAMP(1); count(1); get_tag(); place(0); count(2); place(1); count(3); place(2);
      if (wid < 4) { count(4); place(3); place(4); } else place(3);
      proxy_fence();
      bar_arrive(12, 384);
      STAMP(2);
      mbar_wait(sb + BAR_AI);
      mbar_wait(sb + BAR_SRC); mbar_wait(sb + BAR_SRC + 8); mbar_wait(sb + BAR_SRC + 16);
      STAMP(12);
#pragma unroll
      for (int k = 0; k < NCH; k++) lds128(d + 4 * k, sb + OFF_SRCI + (tid + NWK * k) * 16);
      const uint32_t tb = tag + (tid << 18);
#pragma unroll
      for (int i = 0; i < 4 * NCH; i++) if (i < 4 * NCH - 4 || wid < 4) sts32(sb + OFF_SB + jj[i], d[i] + tb + ((NWK * (i >> 2) * 4 + (i & 3)) << 16));
      proxy_fence();
      bar_arrive(13, 384);
      STAMP(3);
    }
    const uint32_t rot = (lane + cta) & 31;
    cb = sb + OFF_CNT - (tag >> 14);
    {
      const uint32_t* xa = (const uint32_t*)(p.xa + (cta * G + wid) * 8) + rot;
      if (wid < 8) { const uint32_t e_ = ealo + epad * 32;
        mbar_wait(sb + BAR_AX);
#pragma unroll
        for (int i = 0; i < 7; i++) sts128(sb + OFF_TE + tid * 16 + i * 4096, e_, e_, e_, e_); }
      static_assert(SCAP * 64 == 7 * 4096, "fill");
      if (wid == 10) { hint_wait(p.sync + 4, ep * G); mbar_arrive(sb + BAR_HA, lane == 0); }
      mbar_wait(sb + BAR_HA);
      STAMP(14);
      const uint32_t tp = tag | (tag >> 16);
      uint32_t st;
#pragma unroll 1
      for (int spin = 0;; spin++) {
        st = 0;
#pragma unroll
        for (int k = 0; k < 12; k++) asm volatile("ld.relaxed.gpu.global.u32 %0, [%1];" : "=r"(pk[k]) : "l"(xa + k * 352) : "memory");
#pragma unroll
        for (int k = 0; k < 12; k++) st |= pk[k] ^ tp;
        st = __reduce_or_sync(~0u, st);
        if (!(st >> 30)) break;
        trap_if(spin > 2000000);
      }
      if (wid == 0) STAMP(22);
      if (st & 0x3C00FC00u) {
#pragma unroll 1
        for (;;) {
          uint32_t x = 0, row = 0;
#pragma unroll
          for (int k = 0; k < 12; k++) { const uint32_t y = (pk[k] ^ tp) & 0x3C00FC00u; if (!x && y) { x = y; row = wid + 11 * k; pk[k] ^= y; } }
          if (!__any_sync(~0u, x)) break;
          const uint32_t n = ((x >> 10) & 63) | ((x >> 20) & 0x1C0);
          if (x >> 29) {
            const uint32_t r = atoms_add(sb + OFF_CNT + n * 4, 16), idx = atoms_add(sb + OFF_MISC + 4, 1);
            if (idx < 256) sts32(sb + OFF_EXT + idx * 4, n | (row << 9) | (lane << 17) | (min(r >> 4, 255u) << 22));
            else x = 1;
          }
          if (x && !(x >> 29)) sts32(sb + OFF_MISC + 8, 1);
          __syncwarp();
        }
      }
#pragma unroll
      for (int k = 0; k < 12; k++) { r0[k] = mad16(pk[k], 0x0004u, cb); r1[k] = mad16(pk[k], 0x0400u, cb); vb[k].x = atoms_add(r0[k], 16); vb[k].y = atoms_add(r1[k], 16); }
      if (B_HOLD == 2) mbar_arrive(sb + BAR_XA, lane == 0);
#pragma unroll
      for (int k = 0; k < 12; k++) pk[k] = __byte_perm(vb[k].x, vb[k].y, 0x5410);
    }
    STAMP(4);
    if (wid >= 6) bar_arrive(11, NWK);
    if (wid < 6) {
      uint32_t ca[2], ky[2], dr[2], sq[2], ps[4];
#pragma unroll
      for (int i = 0; i < 2; i++) { ca[i] = sb + OFF_CNT + ((node0 + tid + 192 * i) & 511) * 4; lds64(ps[2 * i], ps[2 * i + 1], sb + OFF_POS + (tid + 192 * i) * 8); ps[2 * i + 1] |= (tid + 192 * i) << 16; }
      bar_sync(11, NWK);
      STAMP(5);
#pragma unroll
      for (int i = 0; i < 2; i++) ky[i] = (lds32(ca[i]) + 16) >> 5;
      if (max(ky[0], ky[1]) > 31) sts32(sb + OFF_MISC + 8, 1);
#pragma unroll
      for (int i = 0; i < 2; i++) { ky[i] = min(ky[i], 31u); dr[i] = atoms_add(sb + OFF_DH + ky[i] * 4, 1); }
      bar_sync(10, 192);
      const uint32_t hv = lds32(sb + OFF_DH + lane * 4);
      uint32_t inc = hv;
#pragma unroll
      for (int o = 1; o < 32; o <<= 1) asm("{.reg .pred p; .reg .b32 y; shfl.sync.down.b32 y|p, %0, %1, 31, -1; @p add.u32 %0, %0, y;}" : "+r"(inc) : "r"(o));
#pragma unroll
      for (int i = 0; i < 2; i++) {
        const uint32_t pos = __shfl_sync(~0u, inc - hv, ky[i]) + dr[i];
        const uint32_t ak = (uint32_t)(QCODE >> ((pos >> 5) * 4)) & 15, l = (pos >> 3) & 3;
        sq[i] = (ak >> 2) * 16 + ((QREV >> (pos >> 5) & 1) ? 3 - l : l) * 4 + (ak & 3);
        dr[i] = pos & 7;
        asm volatile("{.reg .pred p; setp.eq.u32 p, %2, 0; @p st.shared.u8 [%0], %1;}" :: "r"(sb + OFF_LEN + sq[i]), "r"(max(ky[i], 1u)), "r"(dr[i]) : "memory");
        sts64(sb + OFF_GP + sq[i] * 64 + dr[i] * 8, ps[2 * i], ps[2 * i + 1]);
      }
      bar_sync(10, 192);
      const uint32_t ln = lds32(sb + OFF_LEN + min(lane, 11) * 4), tot = __dp4a(ln, 0x01010101u, 0u);
      inc = tot;
#pragma unroll
      for (int o = 1; o < 16; o <<= 1) asm("{.reg .pred p; .reg .b32 y; shfl.sync.up.b32 y|p, %0, %1, 0, -1; @p add.u32 %0, %0, y;}" : "+r"(inc) : "r"(o));
      if (wid == 1) sts32(sb + OFF_CNT + 2048 + lane * 4, 0);
      if (tid < 12) { sts32(sb + OFF_LEN + 64 + tid * 4, inc - tot); if (inc > SCAP) sts32(sb + OFF_MISC + 8, 1); }
#pragma unroll
      for (int i = 0; i < 2; i++) sts32(ca[i], __dp4a(__shfl_sync(~0u, ln, sq[i] >> 2), 0x00010101u >> (24 - 8 * (sq[i] & 3)), __shfl_sync(~0u, inc - tot, sq[i] >> 2)) * 32 + dr[i] * 2);
    }
    bar_arrive(7, 384);
  }
  if (wid == 11) bar_sync(7, 384); else bar_sync(1, NWK);
  STAMP(6);
  if (wid != 11) {
#pragma unroll
    for (int k = 0; k < 12; k++) { r0[k] = lds32(r0[k]); r1[k] = lds32(r1[k]); }
  }

  mbar_wait(sb + BAR_QR);
  asm volatile("setmaxnreg.inc.sync.aligned.u32 160;");
#pragma unroll
  for (int k = 0; k < 12; k++) asm volatile("{.reg .b32 t; prmt.b32 t, %1, %2, 0x5410; add.u32 %0, %0, t;}" : "+r"(pk[k]) : "r"(r0[k]), "r"(r1[k]));
  uint32_t nx = 0, xr = 0; uint2 xv = make_uint2(0, 0);
  auto xadr = [&]() { return p.xe + (cta * G + ((xr >> 9) & 255)) * 32 + ((xr >> 17) & 31); };
  if (wid == 11) { nx = min(__shfl_sync(~0u, lds32(sb + OFF_MISC + 4), 0), 256u);
    if (nx) { xr = lds32(sb + OFF_EXT + min(lane, nx - 1) * 4); xv = ld_poll2(xadr()); } }
  uint32_t pa[8], sp[8], pq[16]; float chk = 0.f;
  {
    uint32_t hf[32], mp = 0; float a0[32], a1[32];
    const uint32_t an = sb + OFF_GP + wid * 256 + (lane & 15) * 8 + 6, n0 = lds16(an), n1 = lds16(an + 128);
#pragma unroll
    for (int j = 0; j < 8; j++) { const uint32_t nd = j < 4 ? n0 : n1; ldsm4(hf + 4 * j, (sb + OFF_H + nd * 128 + (((nd & 7) << 4) ^ (lane & 16))) ^ ((j & 3) << 5)); }
    const uint64_t db = DHI | ((sb + OFF_W + 8192) >> 4);
    wg_fence();
    rs64b<0>(a0, hf[0], hf[1], hf[2], hf[3], db); rs64b<1>(a0, hf[4], hf[5], hf[6], hf[7], db + 128); rs64b<1>(a0, hf[8], hf[9], hf[10], hf[11], db + 256); rs64b<1>(a0, hf[12], hf[13], hf[14], hf[15], db + 384);
    wg_commit();
    rs64b<0>(a1, hf[16], hf[17], hf[18], hf[19], db); rs64b<1>(a1, hf[20], hf[21], hf[22], hf[23], db + 128); rs64b<1>(a1, hf[24], hf[25], hf[26], hf[27], db + 256); rs64b<1>(a1, hf[28], hf[29], hf[30], hf[31], db + 384);
    wg_commit();
    asm volatile("wgmma.wait_group.sync.aligned 1;" ::: "memory"); fence_regs(a0);
#pragma unroll
    for (int j = 0; j < 8; j++) { const uint32_t x = pack_f16(a0[4 * j], a0[4 * j + 1]), y = pack_f16(a0[4 * j + 2], a0[4 * j + 3]); mp = hmag(hmag(mp, x), y);
      asm volatile("movmatrix.sync.aligned.m8n8.trans.b16 %0, %1;" : "=r"(pa[j]) : "r"(x)); asm volatile("movmatrix.sync.aligned.m8n8.trans.b16 %0, %1;" : "=r"(sp[j]) : "r"(y)); }
    wg_wait0(); fence_regs(a1);
    bar_arrive(4, NTHR);
#pragma unroll
    for (int j = 0; j < 16; j++) { pq[j] = pack_f16(a1[2 * j], a1[2 * j + 1]); mp = hmag(mp, pq[j]); }
    if (magr(mp) >= 0x7000) chk = __int_as_float(0x7FC00000);
  }
  if (wid == 0) STAMP(23);
  uint32_t bad;
  {
    const uint32_t ring = sb + OFF_RING + wid * (NST * STG), p2 = sb + OFF_P2 + wid * 2048;
    uint32_t lens = __shfl_sync(~0u, lds32(sb + OFF_LEN + wid * 4), 0);
    uint32_t rem = __dp4a(lens, 0x20202020u, 0u);
    const uint32_t base = min(lds32(sb + OFF_LEN + 64 + wid * 4), SCAP);
    uint32_t a_s = sb + OFF_TS + base * 32 + (lane >> 3) * 8, a_e = sb + OFF_TE + base * 64 + (lane >> 1) * 4;
    uint32_t k0 = (uint32_t)(uint64_t)p.q + (((lane & 7) ^ ((lane >> 1) & 4)) << 4), k1 = k0 ^ 16, k2 = k0 ^ 32, k3 = k0 ^ 48, ke = ((lane ^ (lane >> 3)) & 1) << 4;
    uint32_t dst0 = ring + (lane >> 3) * 640 + (lane & 7) * 16;
    const uint32_t qhi = (uint32_t)((uint64_t)p.q >> 32), ehi = (uint32_t)((uint64_t)p.ea >> 32);
    uint32_t s0, s1, ev, to = 0, so = 0;
    auto tl_ = [&]() { lds64(s0, s1, a_s + to); asm volatile("ld.shared.u32 %0, [%1]; add.u32 %1, %1, 64;" : "=&r"(ev), "+r"(a_e) :: "memory"); to += 32; };
#define CPQ(LH, x, k, off) "dp2a." LH ".u32.u32 lo, " x ", 0x80000080, " k "; mov.b64 a, {lo, %7}; @p cp.async.cg.shared.global [%0+" #off "], [a], 16;\n"
#define CPE "or.b32 lo, %10, %11; mov.b64 a, {lo, %12}; @p cp.async.cg.shared.global" ESZ " [%0+512], [a], 16;\n"
#define CPA(BODY) asm volatile("{.reg .b32 lo; .reg .b64 a; .reg .pred p; setp.le.u32 p, %8, %9;\n" BODY "}" \
      :: "r"(dst0 + so), "r"(s0), "r"(s1), "r"(k0), "r"(k1), "r"(k2), "r"(k3), "r"(qhi), "r"(to), "r"(rem), "r"(ev), "r"(ke), "r"(ehi) : "memory")
#define CPQ4 CPQ("lo", "%1", "%3", 0) CPQ("hi", "%1", "%4", 128) CPQ("lo", "%2", "%5", 256) CPQ("hi", "%2", "%6", 384) "cp.async.commit_group;"
    auto issue = [&]() { CPA(CPE CPQ4); so = so == (NST - 1) * STG ? 0 : so + STG; };
    const int g = lane >> 2, qd = lane & 3;
    const uint32_t sw = ((lane >> 4) ^ (lane & 7)) << 4, fr = (lane & 15) * 128 + sw;
    uint32_t qa0 = ring + (g & 3) * 640 + qd * 128 + sw, qa1 = qa0 ^ 32, qa2 = qa0 ^ 64, qa3 = qa0 ^ 96;
    uint32_t eadr = ring + 512 + (g & 3) * 640 + qd * 32 + ((((lane >> 4) ^ g) & 1) << 4);
    uint32_t oh0 = g == 2 * qd ? 0x3C00u : g == 2 * qd + 1 ? 0x3C000000u : 0u, oh1 = oh0;
    uint32_t a_g = sb + OFF_GP + wid * 256 + lane * 2;
    uint32_t a_n = sb + OFF_GP + wid * 256 + (lane & 15) * 8 + 6;
    uint32_t a_p = ((lane & 8) ? p2 : sb + OFF_WD) + (lane & 7) * 128 + ((((lane >> 4) ^ lane) & 7) << 4);
    uint32_t a_w = sb + OFF_W3 + fr;
#define OPQ4(A, B, C, D) asm volatile("shfl.sync.bfly.b32 %0, %0, 0, 31, -1; shfl.sync.bfly.b32 %1, %1, 0, 31, -1; shfl.sync.bfly.b32 %2, %2, 0, 31, -1; shfl.sync.bfly.b32 %3, %3, 0, 31, -1;" : "+r"(A), "+r"(B), "+r"(C), "+r"(D))
    asm volatile("shfl.sync.idx.b32 %0, %0, %1, 31, -1;" : "+r"(oh1) : "r"(lane));
    if (OPQ & 1) OPQ4(a_w, oh0, ke, dst0);
    if (OPQ & 2) OPQ4(qa0, qa1, qa2, qa3);
    if (OPQ & 4) OPQ4(k0, k1, k2, k3);
    if (OPQ & 8) OPQ4(a_g, a_n, a_p, eadr);
    uint32_t w3[16], wv[8], bp[16], sum[8], Y[16], M[16], own, ownp, dpk; uint16_t tl[16], th[16];
    float pacc = 0.f;
    auto wload = [&]() {
#pragma unroll
      for (int j = 0; j < 4; j++) ldsm4t(w3 + 4 * j, a_w ^ (j << 5));
      lds128(wv, sb + OFF_WX + (a_g & 6) * 16); lds128(wv + 4, sb + OFF_WX + 16 + (a_g & 6) * 16);
    };
    auto hload = [&](uint32_t (&hf)[16], uint32_t nd) {
      const uint32_t hrow = sb + OFF_H + nd * 128 + (((nd & 7) << 4) ^ ((a_g >> 1) & 16));
#pragma unroll
      for (int j = 0; j < 4; j++) ldsm4(hf + 4 * j, hrow ^ (j << 5));
      return hrow;
    };
    auto bload = [&](uint32_t o) {
#pragma unroll
      for (int j = 0; j < 4; j++) ldsm4t(bp + 4 * j, (a_p ^ (j << 5)) + o);
    };
    { uint32_t wd[8]; const uint32_t a = sb + OFF_WD + (lane & 7) * 128 + ((((lane >> 3) ^ lane) & 7) << 4);
      ldsm4t(wd, a); ldsm4t(wd + 4, a ^ 64);
#pragma unroll
      for (int j = 0; j < 8; j++) { bp[2 * j] = wd[j]; bp[2 * j + 1] = pa[j]; } }
    own = lds16(a_g) * 0x10001u;
    if (wid == 0) STAMP(27);
    mbar_wait(sb + BAR_HB);
    if (__shfl_sync(~0u, lds32(sb + OFF_MISC + 8), 0)) rem = 0;
    else if (wid == 11) {
      for (uint32_t k = 0; k < nx; k += 32) {
        xr = lds32(sb + OFF_EXT + min(k + lane, nx - 1) * 4);
        if (k || __any_sync(~0u, xv.y != ep)) xv.x = ext_get(xadr(), ep);
        put(lds32(sb + OFF_CNT + (xr & 511) * 4) + (xr >> 22) * 16, 0, xv.x, eb0 + ((xr >> 9) & 255) * p.EPC * 32);
      }
    } else {
#pragma unroll
      for (int k = 0; k < 12; k++) lds64(vb[k].x, vb[k].y, sb + OFF_XB + (wid + 11 * k) * 256 + ((lane + cta) & 31) * 8);
#pragma unroll 1
      for (int spin = 0;; spin++) {
        uint32_t st = 0;
#pragma unroll
        for (int k = 0; k < 12; k++) st |= (vb[k].x ^ tag) | (vb[k].y ^ tag);
        if (!__any_sync(~0u, st >> 30)) break;
        trap_if(spin > 2000000);
#pragma unroll
        for (int k = 0; k < 12; k++) vb[k] = ld_poll2(xb + k * 352);
      }
#pragma unroll
      for (int k = 0; k < 12; k++) { const uint32_t eb = eb0 + (wid + 11 * k) * p.EPC * 32; put(pk[k], 0, vb[k].x, eb); put(pk[k], 1, vb[k].y, eb); }
    }
    STAMP(7);
    wload();
    bar_sync(2, 384);
    uint32_t sv[3 * NST];
#pragma unroll
    for (int i = 0; i < NST; i++) { tl_(); sv[3 * i] = s0; sv[3 * i + 1] = s1; sv[3 * i + 2] = ev; }
#pragma unroll
    for (int j = 0; j < 4; j++) stsm4((p2 + fr) ^ (j << 5), pq[4 * j], pq[4 * j + 1], pq[4 * j + 2], pq[4 * j + 3]);
#pragma unroll
    for (int i = 0; i < NST; i++) { to = 32 * i + 32; so = i * STG; ev = sv[3 * i + 2]; CPA(CPE); }
    mbar_wait(sb + BAR_QP);
    STAMP(13);
    bad = __shfl_sync(~0u, lds32(sb + OFF_MISC + 8), 0);
   if (!bad) {
#pragma unroll
    for (int i = 0; i < NST; i++) { to = 32 * i + 32; so = i * STG; s0 = sv[3 * i]; s1 = sv[3 * i + 1]; CPA(CPQ4); }
    so = 0;
    auto body = [&](auto MODE) {
      constexpr int mode = decltype(MODE)::value;
      uint32_t T[16], ef[4], q0, q1, x0, x1, x2; float e0_, e1_, cs[4];
      auto mu = [&](int j) {
#pragma unroll
        for (int i = 2 * j; i < 2 * j + 2; i++) asm volatile("{.reg .b16 l, h; mov.b32 {l, h}, %2; tanh.approx.f16 %0, l; tanh.approx.f16 %1, h;}" : "=h"(tl[i]), "=h"(th[i]) : "r"(Y[i])); };
      auto fi = [&](int j) {
#pragma unroll
        for (int i = 2 * j; i < 2 * j + 2; i++) asm volatile("{.reg .b32 t; mov.b32 t, {%2, %3}; fma.rn.f16x2 %0, %1, t, %1;}" : "=r"(M[i]) : "r"(Y[i]), "h"(tl[i]), "h"(th[i])); };
      auto ad = [&](int j) { asm volatile("add.rn.f16x2 %0, %0, %1; add.rn.f16x2 %0, %0, %2;" : "+r"(sum[j]) : "r"(M[2 * j]), "r"(M[2 * j + 1])); };
      auto he = [&](int j) { asm volatile("mma.sync.aligned.m16n8k16.row.col.f16.f16.f16.f16 {%0,%1}, {%2,%3,%4,%5}, {%6,%7}, {%0,%1};" : "+r"(T[2 * j]), "+r"(T[2 * j + 1]) : "r"(ef[0]), "r"(ef[1]), "r"(ef[2]), "r"(ef[3]), "r"(w3[2 * j]), "r"(w3[2 * j + 1])); };
      auto hs = [&](int j) { asm volatile("mma.sync.aligned.m16n8k16.row.col.f16.f16.f16.f16 {%0,%1}, {%2,%3,%4,%5}, {%6,%7}, {%8,%9};" : "=r"(Y[2 * j]), "=r"(Y[2 * j + 1]) : "r"(q0), "r"(q1), "r"(oh0), "r"(oh1), "r"(bp[2 * j]), "r"(bp[2 * j + 1]), "r"(T[2 * j]), "r"(T[2 * j + 1])); };
      auto hc = [&](int j) {
        if (j) asm volatile("mma.sync.aligned.m16n8k16.row.col.f32.f16.f16.f32 {%0,%1,%2,%3}, {%4,%5,%6,%7}, {%8,%9}, {%0,%1,%2,%3};" : "+f"(cs[0]), "+f"(cs[1]), "+f"(cs[2]), "+f"(cs[3]) : "r"(M[4 * j]), "r"(M[4 * j + 1]), "r"(M[4 * j + 2]), "r"(M[4 * j + 3]), "r"(wv[2 * j]), "r"(wv[2 * j + 1]));
        else asm volatile("mma.sync.aligned.m16n8k16.row.col.f32.f16.f16.f32 {%0,%1,%2,%3}, {%4,%5,%6,%7}, {%8,%9}, {%10,%10,%10,%10};" : "=f"(cs[0]), "=f"(cs[1]), "=f"(cs[2]), "=f"(cs[3]) : "r"(M[0]), "r"(M[1]), "r"(M[2]), "r"(M[3]), "r"(wv[0]), "r"(wv[1]), "f"(0.f)); };
      auto cv = [&](int i) { asm volatile("{.reg .b32 a, b; shl.b32 a, %0, 16; and.b32 b, %0, 0xFFFF0000; cvt.rn.f16x2.f32 %0, b, a;}" : "+r"(ef[i])); };
      auto un = [&]() { asm volatile("shl.b32 %0, %2, 16; and.b32 %1, %2, 0xFFFF0000;" : "=&f"(e0_), "=&f"(e1_) : "r"(dpk)); };
      auto ex0 = [&]() { asm volatile("prmt.b32 %0, %3, %4, 0x6420; prmt.b32 %1, %5, %6, 0x6420; prmt.b32 %2, %7, %8, 0x6420;" : "=&r"(x0), "=&r"(x1), "=&r"(x2) : "r"(T[0]), "r"(T[1]), "r"(T[2]), "r"(T[3]), "r"(T[4]), "r"(T[5])); };
      auto ex1 = [&]() { asm volatile("{.reg .b32 a, b; shl.b32 a, %2, 3; shl.b32 b, %3, 6; lop3.b32 a, %1, a, 0x38383838, 0xD8; lop3.b32 a, a, b, 0xC0C0C0C0, 0xD8; sub.rn.bf16x2 %0, %4, a;}" : "=r"(dpk) : "r"(x0), "r"(x1), "r"(x2), "r"(own)); };
      auto ex2 = [&]() { asm volatile("{.reg .b32 a, b, d, u; .reg .b16 l, h; shl.b32 a, %2, 16; and.b32 b, %2, 0xFFFF0000; cvt.rn.f16x2.f32 d, b, a; mul.rn.f16x2 %0, d, d; mov.b32 {l, h}, d; mov.b32 u, {h, h}; mul.rn.f16x2 %1, u, u;}" : "=&r"(q0), "=&r"(q1) : "r"(dpk)); };
      auto pf = [&]() { asm volatile("fma.rn.f32 %0, %1, %2, %0; fma.rn.f32 %0, %3, %4, %0;" : "+f"(pacc) : "f"(cs[0]), "f"(e0_), "f"(cs[2]), "f"(e1_)); };
#define FX(k) if (FM >> k & 1) asm volatile("pmevent 1;" ::: "memory")
      if (mode == 2) {
        hc(0); mu(3); fi(2); un(); ad(0); ad(1); mu(4); fi(3); hc(1); mu(5); fi(4); ad(2); mu(6); fi(5); ad(3); hc(2); mu(7); fi(6); fi(7); ad(4); ad(5); hc(3); ad(6); ad(7); pf();
        return;
      }
      asm volatile("cp.async.wait_group %0;" :: "n"(NST - 1) : "memory");
      __syncwarp();
      if (mode == 1) STAMP(8);
      ldsm4(ef, eadr + so); ldsm4(T, qa0 + so); ldsm4(T + 4, qa1 + so); ldsm4(T + 8, qa2 + so); ldsm4(T + 12, qa3 + so);
      tl_();
      if (mode == 1) {
        issue();
        cv(0); cv(1); cv(2); cv(3); ex0(); ex1(); ex2();
#pragma unroll
        for (int j = 0; j < 8; j++) { he(j); hs(j); }
        mu(0); mu(1); fi(0); mu(2); fi(1);
        return;
      }
      hc(0); mu(3); fi(2); un(); ad(0); ad(1);
      FX(0);
      mu(4); fi(3); cv(0); cv(1); cv(2); cv(3); ex0(); ex1();
      FX(1);
      he(0); he(1); hc(1); mu(5); fi(4); ex2(); ad(2);
      FX(2);
      hs(0); he(2); mu(6); fi(5); issue(); ad(3);
      FX(3);
      hs(1); he(3); hc(2); mu(7); fi(6);
      FX(4);
      hs(2); hs(3); he(4); he(5); mu(0); fi(7); ad(4); ad(5);
      FX(5);
      hc(3); hs(4); he(6); he(7); mu(1); fi(0); ad(6);
      FX(6);
      hs(5); hs(6); hs(7); mu(2); fi(1); ad(7); pf();
      FX(7);
    };
#pragma unroll
    for (int j = 0; j < 8; j++) sum[j] = 0;
    body(IC<1>());
    int cnt = (lens & 255) - 1;
#pragma unroll 1
    for (int t = 0; t < 8; t++) {
#pragma unroll 1
      for (; cnt > 0; cnt--) { body(IC<0>());
      }
      if (!(t & 1)) {
        ownp = own;
        if (t < 6) {
          a_g += 64; own = lds16(a_g) * 0x10001u;
          if (t == 0) {
#pragma unroll
            for (int j = 0; j < 8; j++) bp[2 * j + 1] = sp[j];
          } else bload((a_g & 16) ? (t & 4) * 256 : 0);
          lens >>= 8; cnt = 1;
          continue;
        }
        body(IC<2>()); t++;
        STAMP(9);
      }
      cnt = (lens & 255) - 1;
      { const uint32_t ng = __shfl_sync(~0u, ownp, (a_g >> 1) | 3) >> 16, c3 = (a_g >> 1) & 3;
        asm volatile("{.reg .pred p; setp.lt.u32 p, %2, %3; @p st.global.u16 [%0], %1;}" :: "l"(p.out + (size_t)p.N * 64 + (size_t)node0 * 3 + (ng * 3 + c3)), "h"((uint16_t)pack_bf16(bf_hi(ownp) + pacc, 0.f)), "r"(ng), "r"(c3 < 3 ? nloc : 0) : "memory"); }
      chk = fmaf(pacc, 0.f, chk); pacc = 0.f;
      if (t & 2) {
        uint32_t hf[16]; float acc[32];
        const uint32_t nd = lds16(a_n); a_n += 128;
        const uint32_t hrow = hload(hf, nd);
        const uint64_t b1 = DHI | ((sb + OFF_W) >> 4), b2_ = b1 + 512;
        mbar_wait(sb + BAR_WH);
        wg_fence();
        rs64h<0>(acc, sp[0], sum[0], sp[1], sum[1], b2_); rs64h<1>(acc, sp[2], sum[2], sp[3], sum[3], b2_ + 128); rs64h<1>(acc, sp[4], sum[4], sp[5], sum[5], b2_ + 256); rs64h<1>(acc, sp[6], sum[6], sp[7], sum[7], b2_ + 384);
        rs64b<1>(acc, hf[0], hf[1], hf[2], hf[3], b1); rs64b<1>(acc, hf[4], hf[5], hf[6], hf[7], b1 + 128); rs64b<1>(acc, hf[8], hf[9], hf[10], hf[11], b1 + 256); rs64b<1>(acc, hf[12], hf[13], hf[14], hf[15], b1 + 384);
        wg_commit(); wg_wait0(); fence_regs(acc);
        if (t == 7) STAMP(10);
        chk = fmaf(acc[0], 0.f, fmaf(acc[2], 0.f, chk));
        auto fin = [&](uint32_t x, float y0, float y1) { return u2(__hadd2(b2(x), b2(pack_bf16(silu_h(y0), silu_h(y1))))); };
#pragma unroll
        for (int j = 0; j < 4; j++) stsm4(hrow ^ (j << 5), fin(hf[4 * j], acc[8 * j], acc[8 * j + 1]), fin(hf[4 * j + 1], acc[8 * j + 2], acc[8 * j + 3]), fin(hf[4 * j + 2], acc[8 * j + 4], acc[8 * j + 5]), fin(hf[4 * j + 3], acc[8 * j + 6], acc[8 * j + 7]));
        __syncwarp();
        const uint32_t c8 = (a_g << 3) & 0x70;
#pragma unroll
        for (int j = 0; j < 4; j++) { uint32_t v[4]; const uint32_t n = __shfl_sync(~0u, nd, 4 * j + ((a_g >> 4) & 3)); lds128(v, sb + OFF_H + n * 128 + (((n << 4) ^ c8) & 0x70));
          asm volatile("{.reg .pred p; setp.lt.u32 p, %5, %6; @p st.global" OCS ".v4.b32 [%0], {%1,%2,%3,%4};}" :: "l"((const char*)p.out + (size_t)node0 * 128 + (n * 128 + c8)), "r"(v[0]), "r"(v[1]), "r"(v[2]), "r"(v[3]), "r"(n), "r"(nloc) : "memory"); }
        wload();
      }
#pragma unroll
      for (int j = 0; j < 8; j++) { sp[j] = sum[j]; asm volatile("mov.b32 %0, 0;" : "=r"(sum[j])); }
    }
    asm volatile("{.reg .pred p, q; setp.neu.f32 p, %1, 0f00000000; setp.ne.or.u32 p, %2, 0, p; bar.red.or.pred q, 5, 384, p; selp.u32 %0, 1, 0, q;}" : "=r"(bad) : "f"(chk), "r"(lds32(sb + OFF_MISC + 12)) : "memory");
    STAMP(11);
   } else { asm volatile("cp.async.wait_all;" ::: "memory"); bar_sync(5, 384); }
  }
  if (bad) slow_path(p, wid, lane, node0, nloc);
}

}

typedef CUresult (*EncodeFn)(CUtensorMap*, CUtensorMapDataType, cuuint32_t, void*, const cuuint64_t*, const cuuint64_t*, const cuuint32_t*, const cuuint32_t*,
                             CUtensorMapInterleave, CUtensorMapSwizzle, CUtensorMapL2promotion, CUtensorMapFloatOOBfill);

extern "C" void kernel_launch(void* const* d_in, const int* in_sizes, int n_in, void* d_out, int out_size) {
  Params p; Maps maps;
  p.h = (const uint4*)d_in[0]; p.pos = (const uint16_t*)d_in[1]; p.ea = (const uint4*)d_in[2];
  p.src = (const int*)d_in[3]; p.dst = (const int*)d_in[4];
  p.we = (const uint16_t*)d_in[5]; p.wx = (const uint16_t*)d_in[6]; p.wh = (const uint16_t*)d_in[7];
  p.out = (uint16_t*)d_out;
  p.N = in_sizes[0] / 64; p.E = in_sizes[3];
  p.EPC = ((p.E + G * 4 - 1) / (G * 4)) * 4;
  p.magic = (uint32_t)(((uint64_t)G << 24) / (uint64_t)p.N);
  p.inv = (1ull << 56) / p.magic;
  const uint64_t ea0 = (uint64_t)d_in[2], ea1 = ea0 + (uint64_t)p.E * 32 - 1;
  p.force_slow = ((ea0 >> 32) != (ea1 >> 32)) || (ea0 & 31) || (p.E & 3);
  void* qp = nullptr;
  cudaGetSymbolAddress(&qp, g_q);
  p.q = (char*)qp;
  if (((uint64_t)p.q >> 32) != (((uint64_t)p.q + QBYTES) >> 32)) p.q += QBYTES;
  cudaGetSymbolAddress((void**)&p.sync, g_sync); cudaGetSymbolAddress((void**)&p.xe, g_xe);
  cudaGetSymbolAddress((void**)&p.xa, g_xa); cudaGetSymbolAddress((void**)&p.xb, g_xb);
  void* fn = nullptr; cudaDriverEntryPointQueryResult qr;
  cudaGetDriverEntryPoint("cuTensorMapEncodeTiled", &fn, cudaEnableDefault, &qr);
  auto mk = [&](CUtensorMap* tm, void* base, int rows) {
    const cuuint64_t dim[2] = {64, (cuuint64_t)rows}, str[1] = {128}; const cuuint32_t bx[2] = {64, 64}, es[2] = {1, 1};
    ((EncodeFn)fn)(tm, CU_TENSOR_MAP_DATA_TYPE_BFLOAT16, 2, base, dim, str, bx, es, CU_TENSOR_MAP_INTERLEAVE_NONE, CU_TENSOR_MAP_SWIZZLE_128B,
                   CU_TENSOR_MAP_L2_PROMOTION_NONE, CU_TENSOR_MAP_FLOAT_OOB_FILL_NONE);
  };
  mk(&maps.m[TM_H / 128], d_in[0], p.N); mk(&maps.m[TM_WE / 128], d_in[5], 145); mk(&maps.m[TM_WH / 128], d_in[7], 128); mk(&maps.m[TM_Q / 128], p.q, p.N);
  for (int k = 0; k < 2; k++) {
    void* xp = (void*)(k ? p.xb : p.xa);
    const cuuint64_t dim[2] = {(cuuint64_t)G * 64, (cuuint64_t)G}, str[1] = {(cuuint64_t)G * (128 << k)}; const cuuint32_t bx[2] = {64, (cuuint32_t)(k ? BROWS : G)}, es[2] = {1, 1};
    ((EncodeFn)fn)(&maps.m[TM_XA / 128 + k], k ? CU_TENSOR_MAP_DATA_TYPE_UINT32 : CU_TENSOR_MAP_DATA_TYPE_UINT16, 2, xp, dim, str, bx, es, CU_TENSOR_MAP_INTERLEAVE_NONE,
                   CU_TENSOR_MAP_SWIZZLE_NONE, CU_TENSOR_MAP_L2_PROMOTION_NONE, CU_TENSOR_MAP_FLOAT_OOB_FILL_NONE);
  }
  cudaFuncSetAttribute(egnn_kernel, cudaFuncAttributeMaxDynamicSharedMemorySize, SMEM);
  egnn_kernel<<<G, NTHR, SMEM>>>(p, maps);
}
```

```cpp
#include <cuda_runtime.h>
#include <cuda_bf16.h>
#include <cuda_fp16.h>
#include <cuda.h>
#include <stdint.h>
#pragma nv_diag_suppress 549

#define PFN 16
#define PFNS 250
#define FM 0
#define OPQ 0
#define H0 0
#define HALL 0
#define PF0NS 0
#define PFW 0
#define QCODE 0x254a109b7863ull
#define QREV 0x605
#define PFS 1
#define ESZ ""
#define XEF 0
#define OCS ""
#define RNB 4
#define HW 3
#define BROWS 132
#define B_HOLD 1
#define LSEQ 0x231200ull
#define HE 0
namespace {

constexpr int G = 132;
constexpr int NTHR = 512, NWK = 352, NCH = 5;
constexpr int NST = 3, STG = 2560;
constexpr int SCAP = 448;

constexpr int OFF_H = 0;
constexpr int OFF_W = 49152;
constexpr int OFF_WD = OFF_W + 16384;
constexpr int OFF_W3 = OFF_WD + 1024;
constexpr int OFF_P2 = OFF_W3 + 2048;
constexpr int OFF_RING = OFF_P2 + 24576;
constexpr int OFF_TE = OFF_RING + 12 * NST * STG;
constexpr int OFF_TS = OFF_TE + SCAP * 64;
constexpr int OFF_GP = OFF_TS + SCAP * 32;
constexpr int OFF_WX = OFF_GP + 3072;
constexpr int OFF_LEN = OFF_WX + 128;
constexpr int OFF_MISC = OFF_LEN + 128;
constexpr int OFF_BAR = OFF_MISC + 48;
constexpr int SMEM = OFF_BAR + 256;
static_assert(SMEM <= 232448, "smem");
constexpr uint32_t sb = 1024;
constexpr int OFF_SRCI = OFF_TE;
constexpr int OFF_SB = OFF_RING, OFF_SA = OFF_SB + 34816, OFF_AX = OFF_SA + 32768, OFF_DST = OFF_H + 24576;
constexpr int OFF_WS = OFF_AX + 17408;
constexpr int OFF_BC = OFF_WS + 2304;
constexpr int OFF_CNT = OFF_P2;
constexpr int OFF_DH = OFF_CNT + 2176;
constexpr int OFF_POS = OFF_DH + 128;
constexpr int OFF_EXT = OFF_POS + 3072;
constexpr int OFF_XB = OFF_EXT + 1024, XPAD = G * 256;
static_assert(OFF_XB + XPAD + 1028 <= OFF_RING + 12 * STG && OFF_XB % 128 == 0 && OFF_BC + 544 <= OFF_TE && OFF_P2 % 1024 == 0 && OFF_SA % 1024 == 0 && SCAP * 64 >= 24576, "staging");
constexpr int BAR_DST = OFF_BAR, BAR_SRC = BAR_DST + 40, BAR_T = BAR_SRC + 24, BAR_W = BAR_T + 48, BAR_XA = BAR_W + 8, BAR_PS = BAR_XA + 8, BAR_AW = BAR_PS + 8,
              BAR_QP = BAR_AW + 8, BAR_QR = BAR_QP + 8, BAR_HA = BAR_QR + 8, BAR_EP = BAR_HA + 8, BAR_AX = BAR_EP + 8, BAR_AI = BAR_AX + 8, BAR_HB = BAR_AI + 8, BAR_U = BAR_HB + 8, BAR_WH = BAR_U + 8, BAR_END = BAR_WH + 8;
constexpr uint32_t QBYTES = 8u << 20;

__device__ __align__(256) uint4 g_xa[G * G * 8];
__device__ __align__(256) uint4 g_xb[G * G * 16];
__device__ __align__(256) uint2 g_xe[G * G * 32];
__device__ __align__(256) uint4 g_q[2 * QBYTES / 16];
__device__ __align__(256) uint32_t g_sync[8];
#define STAMP(k)

struct Maps { CUtensorMap m[6]; };
constexpr int TM_H = 0, TM_WE = 128, TM_WH = 256, TM_Q = 384, TM_XA = 512, TM_XB = 640;
struct Params {
  const uint4* h; const uint16_t* pos; const uint4* ea; const int* src; const int* dst;
  const uint16_t* we; const uint16_t* wx; const uint16_t* wh; uint16_t* out; char* q;
  uint32_t* sync; const uint4* xa; const uint4* xb; uint2* xe;
  int N, E, EPC; uint32_t magic; int force_slow; unsigned long long inv;
};
template<int V> struct IC { static constexpr int value = V; };

#define R32(d) "+f"(d[0]),"+f"(d[1]),"+f"(d[2]),"+f"(d[3]),"+f"(d[4]),"+f"(d[5]),"+f"(d[6]),"+f"(d[7]),"+f"(d[8]),"+f"(d[9]),"+f"(d[10]),"+f"(d[11]),"+f"(d[12]),"+f"(d[13]),"+f"(d[14]),"+f"(d[15]),"+f"(d[16]),"+f"(d[17]),"+f"(d[18]),"+f"(d[19]),"+f"(d[20]),"+f"(d[21]),"+f"(d[22]),"+f"(d[23]),"+f"(d[24]),"+f"(d[25]),"+f"(d[26]),"+f"(d[27]),"+f"(d[28]),"+f"(d[29]),"+f"(d[30]),"+f"(d[31])
#define S32 "{%0,%1,%2,%3,%4,%5,%6,%7,%8,%9,%10,%11,%12,%13,%14,%15,%16,%17,%18,%19,%20,%21,%22,%23,%24,%25,%26,%27,%28,%29,%30,%31}"
#define DI __device__ __forceinline__

constexpr uint64_t DHI = ((uint64_t)(1024 >> 4) << 32) | (1ull << 62);
template<int SD> DI void rs64b(float (&d)[32], uint32_t a0, uint32_t a1, uint32_t a2, uint32_t a3, uint64_t db) {
  asm volatile("wgmma.mma_async.sync.aligned.m64n64k16.f32.bf16.bf16 " S32 ", {%32,%33,%34,%35}, %36, %37, 1, 1, 1;" : R32(d) : "r"(a0), "r"(a1), "r"(a2), "r"(a3), "l"(db), "n"(SD)); }
template<int SD> DI void rs64h(float (&d)[32], uint32_t a0, uint32_t a1, uint32_t a2, uint32_t a3, uint64_t db) {
  asm volatile("wgmma.mma_async.sync.aligned.m64n64k16.f32.f16.f16 " S32 ", {%32,%33,%34,%35}, %36, %37, 1, 1, 1;" : R32(d) : "r"(a0), "r"(a1), "r"(a2), "r"(a3), "l"(db), "n"(SD)); }
template<int SD> DI void ss64(float (&d)[32], uint64_t da, uint64_t db) {
  asm volatile("wgmma.mma_async.sync.aligned.m64n64k16.f32.bf16.bf16 " S32 ", %32, %33, %34, 1, 1, 0, 1;" : R32(d) : "l"(da), "l"(db), "n"(SD)); }
DI void trap_if(bool c) { asm volatile("{.reg .pred p; setp.eq.u32 p, %0, 0; @p bra.uni LT_%=; trap; LT_%=:}" :: "r"((uint32_t)c)); }
DI void wg_fence() { asm volatile("wgmma.fence.sync.aligned;" ::: "memory"); }
DI void wg_commit() { asm volatile("wgmma.commit_group.sync.aligned;" ::: "memory"); }
DI void wg_wait0() { asm volatile("wgmma.wait_group.sync.aligned 0;" ::: "memory"); }
DI void fence_regs(float (&d)[32]) { asm volatile("" : R32(d) :: "memory"); }
DI void proxy_fence() { asm volatile("fence.proxy.async.shared::cta;" ::: "memory"); }
DI uint64_t pol_first() { uint64_t r; asm("createpolicy.fractional.L2::evict_first.b64 %0, 1.0;" : "=l"(r)); return r; }
DI float tanh_ap(float x) { float y; asm("tanh.approx.f32 %0, %1;" : "=f"(y) : "f"(x)); return y; }
DI float silu_h(float y) { return fmaf(y, tanh_ap(y), y); }
DI uint32_t pack_bf16(float lo, float hi) { uint32_t r; asm("cvt.rn.bf16x2.f32 %0, %1, %2;" : "=r"(r) : "f"(hi), "f"(lo)); return r; }
DI uint32_t pack_f16(float lo, float hi) { uint32_t r; asm("cvt.rn.f16x2.f32 %0, %1, %2;" : "=r"(r) : "f"(hi), "f"(lo)); return r; }
DI float bf_lo(uint32_t v) { return __uint_as_float(v << 16); }
DI float bf_hi(uint32_t v) { return __uint_as_float(v & 0xFFFF0000u); }
DI uint32_t b2h(uint32_t v, float s) { return pack_f16(s * bf_lo(v), s * bf_hi(v)); }
DI void mbar_wait(uint32_t bar, uint32_t parity = 0) {
  asm volatile("{.reg .pred p; .reg .u32 t0, t1;\n"
    "mbarrier.try_wait.parity.shared::cta.b64 p, [%0], %1;\n @p bra.uni LD_%=;\n mov.u32 t0, %%clock;\n"
    "LW_%=: mbarrier.try_wait.parity.shared::cta.b64 p, [%0], %1;\n"
    "@p bra.uni LD_%=;\n mov.u32 t1, %%clock; sub.u32 t1, t1, t0; setp.lt.u32 p, t1, 0x80000000;\n @p bra.uni LW_%=;\n trap;\n LD_%=:}" :: "r"(bar), "r"(parity) : "memory");
}
DI void mbar_arrive(uint32_t bar, int p = 1) { asm volatile("{.reg .pred p; setp.ne.b32 p, %1, 0; @p mbarrier.arrive.shared::cta.b64 _, [%0];}" :: "r"(bar), "r"(p) : "memory"); }
DI void bar_sync(int id, int n) { asm volatile("bar.sync %0, %1;" :: "r"(id), "r"(n) : "memory"); }
DI void bar_arrive(int id, int n) { asm volatile("bar.arrive %0, %1;" :: "r"(id), "r"(n) : "memory"); }
DI __nv_bfloat162 b2(uint32_t v) { return *(__nv_bfloat162*)&v; }
DI uint32_t u2(__nv_bfloat162 v) { return *(uint32_t*)&v; }
DI uint32_t hsq(uint32_t v) { return u2(__hmul2(b2(v), b2(v))); }
DI uint32_t hsub(uint32_t a, uint32_t b) { return u2(__hsub2(b2(a), b2(b))); }
DI uint32_t hhalf(uint32_t v) { return u2(__hmul2(b2(v), __floats2bfloat162_rn(0.5f, 0.5f))); }
DI uint32_t mag2(uint32_t m, uint32_t v) { return __vmaxu2(m, v & 0x7FFF7FFFu); }
DI uint32_t hmag(uint32_t m, uint32_t v) { const __half2 r = __hmax2(*(const __half2*)&m, __habs2(*(const __half2*)&v)); return *(const uint32_t*)&r; }
DI uint32_t magr(uint32_t m) { return max(m & 0xFFFF, m >> 16); }
DI void sts128(uint32_t a, uint32_t x, uint32_t y, uint32_t z, uint32_t w) { asm volatile("st.shared.v4.u32 [%0], {%1,%2,%3,%4};" :: "r"(a), "r"(x), "r"(y), "r"(z), "r"(w) : "memory"); }
DI void sts64(uint32_t a, uint32_t x, uint32_t y) { asm volatile("st.shared.v2.u32 [%0], {%1,%2};" :: "r"(a), "r"(x), "r"(y) : "memory"); }
DI void sts32(uint32_t a, uint32_t x) { asm volatile("st.shared.u32 [%0], %1;" :: "r"(a), "r"(x) : "memory"); }
DI void sts16(uint32_t a, uint32_t x) { asm volatile("st.shared.u16 [%0], %1;" :: "r"(a), "h"((uint16_t)x) : "memory"); }
DI void lds128(uint32_t* v, uint32_t a) { asm volatile("ld.shared.v4.u32 {%0, %1, %2, %3}, [%4];" : "=r"(v[0]), "=r"(v[1]), "=r"(v[2]), "=r"(v[3]) : "r"(a) : "memory"); }
DI void lds64(uint32_t& x, uint32_t& y, uint32_t a) { asm volatile("ld.shared.v2.u32 {%0, %1}, [%2];" : "=r"(x), "=r"(y) : "r"(a) : "memory"); }
DI uint32_t lds32(uint32_t a) { uint32_t x; asm volatile("ld.shared.u32 %0, [%1];" : "=r"(x) : "r"(a) : "memory"); return x; }
DI uint32_t lds16(uint32_t a) { uint32_t x; asm volatile("ld.shared.u16 %0, [%1];" : "=r"(x) : "r"(a) : "memory"); return x; }
DI uint32_t atoms_add(uint32_t a, uint32_t v) { uint32_t r; asm volatile("atom.shared.add.u32 %0, [%1], %2;" : "=r"(r) : "r"(a), "r"(v) : "memory"); return r; }
DI void bulk_load(uint32_t dst, const void* src, uint32_t bytes, uint32_t bar) {
  asm volatile("cp.async.bulk.shared::cluster.global.mbarrier::complete_tx::bytes.L2::cache_hint [%0], [%1], %2, [%3], %4;" :: "r"(dst), "l"(src), "r"(bytes), "r"(bar), "l"(pol_first()) : "memory"); }
DI void bulk_store(void* dst, uint32_t src, uint32_t bytes) { asm volatile("cp.async.bulk.global.shared::cta.bulk_group [%0], [%1], %2;" :: "l"(dst), "r"(src), "r"(bytes) : "memory"); }
DI void mbar_expect(uint32_t bar, uint32_t bytes) { asm volatile("mbarrier.arrive.expect_tx.shared::cta.b64 _, [%0], %1;" :: "r"(bar), "r"(bytes) : "memory"); }
DI void mbar_init(uint32_t bar, int n) { asm volatile("mbarrier.init.shared::cta.b64 [%0], %1;" :: "r"(bar), "r"(n) : "memory"); }
DI void tma_load(uint32_t dst, uint64_t tm, int row, uint32_t bar) {
  asm volatile("cp.async.bulk.tensor.2d.shared::cluster.global.mbarrier::complete_tx::bytes.L2::cache_hint [%0], [%1, {%3, %4}], [%2], %5;" :: "r"(dst), "l"(tm), "r"(bar), "r"(0), "r"(row), "l"(pol_first()) : "memory"); }
DI void tma_store(uint64_t tm, int col, int row, uint32_t src) {
  asm volatile("cp.async.bulk.tensor.2d.global.shared::cta.bulk_group [%0, {%2, %3}], [%1];" :: "l"(tm), "r"(src), "r"(col), "r"(row) : "memory"); }
DI void tma_store_ef(uint64_t tm, int col, int row, uint32_t src) {
  if (XEF) asm volatile("cp.async.bulk.tensor.2d.global.shared::cta.bulk_group.L2::cache_hint [%0, {%2, %3}], [%1], %4;" :: "l"(tm), "r"(src), "r"(col), "r"(row), "l"(pol_first()) : "memory");
  else tma_store(tm, col, row, src); }
DI void bulk_commit() { asm volatile("cp.async.bulk.commit_group;" ::: "memory"); }
DI void bulk_wait_read() { asm volatile("cp.async.bulk.wait_group.read 0;" ::: "memory"); }
DI uint2 ld_poll2(const void* a) { uint2 v; asm volatile("ld.relaxed.gpu.global.v2.u32 {%0, %1}, [%2];" : "=r"(v.x), "=r"(v.y) : "l"(a) : "memory"); return v; }
DI void st_ext(uint2* a, uint32_t v, uint32_t ep) { asm volatile("st.relaxed.gpu.global.v2.u32 [%0], {%1, %2};" :: "l"(a), "r"(v), "r"(ep) : "memory"); }
DI uint32_t ext_get(const uint2* a, uint32_t ep) { uint2 v; int spin = 0; do { v = ld_poll2(a); trap_if(++spin > 4000000); } while (__any_sync(~0u, v.y != ep)); return v.x; }
DI void bulk_wait() { asm volatile("cp.async.bulk.wait_group 0;" ::: "memory"); }
DI void hint_signal(uint32_t* c) { asm volatile("red.relaxed.gpu.global.add.u32 [%0], 1;" :: "l"(c) : "memory"); }
DI void hint_wait(const uint32_t* c, uint32_t target) { uint32_t v; int spin = 0;
  do { asm volatile("ld.relaxed.gpu.global.u32 %0, [%1];" : "=r"(v) : "l"(c) : "memory"); trap_if(++spin > 4000000); } while (__any_sync(~0u, (int)(v - target) < 0)); }
DI void stsm4(uint32_t a, uint32_t x, uint32_t y, uint32_t z, uint32_t w) { asm volatile("stmatrix.sync.aligned.m8n8.x4.shared.b16 [%0], {%1,%2,%3,%4};" :: "r"(a), "r"(x), "r"(y), "r"(z), "r"(w) : "memory"); }
DI void ldsm4(uint32_t* v, uint32_t a) { asm volatile("ldmatrix.sync.aligned.m8n8.x4.shared.b16 {%0,%1,%2,%3}, [%4];" : "=r"(v[0]), "=r"(v[1]), "=r"(v[2]), "=r"(v[3]) : "r"(a) : "memory"); }
DI void ldsm4t(uint32_t* v, uint32_t a) { asm volatile("ldmatrix.sync.aligned.m8n8.x4.trans.shared.b16 {%0,%1,%2,%3}, [%4];" : "=r"(v[0]), "=r"(v[1]), "=r"(v[2]), "=r"(v[3]) : "r"(a) : "memory"); }
DI uint32_t mad16(uint32_t x, uint32_t m, uint32_t c) { uint32_t r; asm("dp2a.lo.u32.u32 %0, %1, %2, %3;" : "=r"(r) : "r"(x), "r"(m), "r"(c)); return r; }
DI bool wbad(uint32_t m, uint32_t hi) { return m > hi || (m && m < 0x3980); }

__device__ __noinline__ void slow_path(const Params& p, int wid, int lane, int node0, int nloc) {
  const uint32_t ab = sb + OFF_P2 + wid * 8704;
  for (int i = lane; i < 32 * 68; i += 32) sts32(ab + i * 4, 0);
  __syncwarp();
  const uint32_t wdv = __ldg((const uint32_t*)(p.we + 128 * 64) + lane), wxv = __ldg((const uint32_t*)p.wx + lane);
  const int nb0 = node0 + wid * 32, cntn = max(0, min(32, nloc - wid * 32));
  auto dot = [&](uint32_t hv, const uint16_t* w, int K2, float& y0, float& y1) {
#pragma unroll 4
    for (int k = 0; k < K2; k++) {
      const uint32_t hk = __shfl_sync(~0u, hv, k), wa = __ldg((const uint32_t*)(w + 2 * k * 64) + lane), wb = __ldg((const uint32_t*)(w + (2 * k + 1) * 64) + lane);
      y0 = fmaf(bf_lo(hk), bf_lo(wa), fmaf(bf_hi(hk), bf_lo(wb), y0)); y1 = fmaf(bf_lo(hk), bf_hi(wa), fmaf(bf_hi(hk), bf_hi(wb), y1));
    }
  };
  auto silu = [](float x) { return x / (1.f + __expf(-x)); };
#pragma unroll 1
  for (int base = 0; base < p.E; base += 32) {
    const int e = base + lane;
    const uint32_t dl = e < p.E ? (uint32_t)(__ldg(p.dst + e) - nb0) : 0xFFFFFFFFu;
    uint32_t mk = __ballot_sync(~0u, dl < (uint32_t)cntn);
    while (mk) {
      const int l = __ffs(mk) - 1; mk &= mk - 1;
      const int ee = base + l, n = __shfl_sync(~0u, dl, l), s = __ldg(p.src + ee);
      const uint16_t *po = p.pos + (size_t)(nb0 + n) * 3, *pp = p.pos + (size_t)s * 3;
      const uint32_t dxy = hsub(__ldg(po) | (__ldg(po + 1) << 16), __ldg(pp) | (__ldg(pp + 1) << 16)), dz = hsub(__ldg(po + 2), __ldg(pp + 2));
      const uint32_t sq = hsq(dxy); const float d2 = bf_lo(sq) + bf_hi(sq) + bf_lo(hsq(dz));
      float y0 = d2 * bf_lo(wdv), y1 = d2 * bf_hi(wdv);
      dot(__ldg((const uint32_t*)(p.h + (size_t)(nb0 + n) * 8) + lane), p.we, 32, y0, y1);
      dot(__ldg((const uint32_t*)(p.h + (size_t)s * 8) + lane), p.we + 64 * 64, 32, y0, y1);
      dot(__ldg((const uint32_t*)(p.ea + (size_t)ee * 2) + (lane & 7)), p.we + 129 * 64, 8, y0, y1);
      const uint32_t mm = pack_bf16(silu(y0), silu(y1));
      float c = bf_lo(mm) * bf_lo(wxv) + bf_hi(mm) * bf_hi(wxv);
#pragma unroll
      for (int o = 16; o; o >>= 1) c += __shfl_xor_sync(~0u, c, o);
      const uint32_t a = ab + n * 272;
      uint32_t x0, x1; lds64(x0, x1, a + lane * 8);
      sts64(a + lane * 8, __float_as_uint(__uint_as_float(x0) + bf_lo(mm)), __float_as_uint(__uint_as_float(x1) + bf_hi(mm)));
      if (lane < 3) { const float df = lane == 0 ? bf_lo(dxy) : lane == 1 ? bf_hi(dxy) : bf_lo(dz); sts32(a + 256 + lane * 4, __float_as_uint(fmaf(c, df, __uint_as_float(lds32(a + 256 + lane * 4))))); }
    }
  }
  __syncwarp();
#pragma unroll 1
  for (int n = 0; n < cntn; n++) {
    uint32_t x0, x1; lds64(x0, x1, ab + n * 272 + lane * 8);
    const uint32_t hv = __ldg((const uint32_t*)(p.h + (size_t)(nb0 + n) * 8) + lane);
    float y0 = 0.f, y1 = 0.f;
    dot(hv, p.wh, 32, y0, y1); dot(pack_bf16(__uint_as_float(x0), __uint_as_float(x1)), p.wh + 64 * 64, 32, y0, y1);
    ((uint32_t*)p.out)[(size_t)(nb0 + n) * 32 + lane] = u2(__hadd2(b2(hv), b2(pack_bf16(silu(y0), silu(y1)))));
    if (lane < 3) p.out[(size_t)p.N * 64 + (size_t)(nb0 + n) * 3 + lane] = (uint16_t)pack_bf16(bf_lo(__ldg(p.pos + (size_t)(nb0 + n) * 3 + lane)) + __uint_as_float(lds32(ab + n * 272 + 256 + lane * 4)), 0.f);
  }
}

__global__ void __launch_bounds__(NTHR, 1) egnn_kernel(const __grid_constant__ Params p, const __grid_constant__ Maps maps) {
  const uint64_t tmb = (uint64_t)&maps;
  extern __shared__ __align__(1024) unsigned char smraw[];
  const int tid = threadIdx.x, cta = blockIdx.x;
  const int e0 = cta * p.EPC, n4 = max(0, min(p.EPC, p.E - e0)) >> 2;
  STAMP(0);
  asm volatile("{.reg .pred p; setp.eq.u32 p, %2, 384; @p cp.async.cg.shared.global [%0], [%1], 16;}" :: "r"(sb + OFF_LEN - 192 + (tid >> 1)), "l"(p.sync), "r"(tid & 415) : "memory");
  if (tid == NWK) {
#pragma unroll
    for (int k = 0; k < NCH; k++) mbar_init(sb + BAR_DST + k * 8, 1);
    asm volatile("fence.mbarrier_init.release.cluster;" ::: "memory");
#pragma unroll 1
    for (int k = 0; k < NCH; k++) { const int nb = max(0, min(NWK, n4 - k * NWK)) * 16;
      mbar_expect(sb + BAR_DST + k * 8, nb);
      if (nb) bulk_load(sb + OFF_DST + k * NWK * 16, (const char*)(p.dst + e0) + k * NWK * 16, nb, sb + BAR_DST + k * 8); }
  }
  const int lane = tid & 31, wid = __shfl_sync(~0u, tid >> 5, 0), w = wid & 3;

  auto first_node = [&](int c) { return (int)((c * p.inv + 0xFFFFFFFFull) >> 32); };
  const int node0 = first_node(cta), nloc = min(first_node(cta + 1), p.N) - node0;
  const uint32_t ealo = (uint32_t)(uint64_t)p.ea;
  const int epad = min(e0, p.E - 1);
  auto load_h = [&](int b) { mbar_expect(sb + BAR_T + b * 8, 8192); tma_load(sb + OFF_H + b * 8192, tmb + TM_H, node0 + b * 64, sb + BAR_T + b * 8); };
  if (wid >= 12) {
    const int t = tid - 384;
    auto prefetch_e = [&](int i) {
      const uint32_t nb = (p.E / G) & ~15u;
      if (nb && i < PFN) asm volatile("cp.async.bulk.prefetch.L2.global [%0], %1;" :: "l"((const char*)p.ea + (size_t)(((i * PFS + i * PFS / 32 * (~PFS & 1)) & 31) * G + cta) * nb), "r"(nb) : "memory");
    };
    uint32_t pv[9], ev = 0;
#pragma unroll
    for (int i = 0; i < 3; i++) { const uint16_t* pp = p.pos + (size_t)(node0 + t + 128 * i) * 3;
      pv[3 * i] = pv[3 * i + 1] = pv[3 * i + 2] = 0;
      asm volatile("{.reg .pred p; setp.lt.s32 p, %4, %5;\n @p ld.global.nc.u16 %0, [%3];\n @p ld.global.nc.u16 %1, [%3+2];\n @p ld.global.nc.u16 %2, [%3+4];}"
        : "+r"(pv[3 * i]), "+r"(pv[3 * i + 1]), "+r"(pv[3 * i + 2]) : "l"(pp), "r"(t + 128 * i), "r"(p.N - node0)); }
    asm volatile("{.reg .pred p; setp.lt.u32 p, %3, 8; @p ld.global.nc.u32 %0, [%1]; @p st.global.v4.u32 [%2], {%4, %4, %4, %4};}"
      : "+r"(ev) : "l"((const uint32_t*)(p.ea + (size_t)epad * 2) + t), "l"(p.q + (size_t)(p.N + cta) * 128 + t * 16), "r"(t), "r"(0xF700F700u) : "memory");
    asm volatile("cp.async.wait_all;" ::: "memory");
    __syncwarp();
    const uint32_t e = lds32(sb + OFF_LEN + 8 + w * 16) + 1;
    {
      const uint32_t tg = (1 + e % 3) << 30, v = ((tg >> 16) + 512 + (lane & 7) * 4) * 0x10001u;
      if (t == 0) sts32(sb + OFF_MISC + 32, e);
#pragma unroll
      for (int i = 0; i < 9; i++) sts128(sb + OFF_SA + t * 16 + i * 2048, v, v + 0x10001u, v + 0x20002u, v + 0x30003u);
      bar_sync(6, NTHR);
      mbar_arrive(sb + BAR_EP, lane == 0);
#pragma unroll
      for (int i = 0; i < 17; i++) sts128(sb + OFF_SB + t * 16 + i * 2048, tg, tg, tg, tg); }
    uint32_t mp = 0;
#pragma unroll
    for (int i = 0; i < 3; i++) { sts64(sb + OFF_POS + (t + 128 * i) * 8, pv[3 * i] | (pv[3 * i + 1] << 16), pv[3 * i + 2]); mp = mag2(mag2(mp, pv[3 * i] | (pv[3 * i + 1] << 16)), pv[3 * i + 2]); }
    proxy_fence();
    __syncwarp();
    mbar_arrive(sb + BAR_PS, lane == 0);
    mbar_wait(sb + BAR_W);
#pragma unroll
    for (int i = 0; i < 8; i += 4) { uint32_t v[16];
#pragma unroll
      for (int k = 0; k < 4; k++) lds128(v + 4 * k, sb + OFF_W + t * 16 + (i + k) * 2048);
#pragma unroll
      for (int k = 0; k < 4; k++) sts128(sb + OFF_W + t * 16 + (i + k) * 2048, hhalf(v[4 * k]), hhalf(v[4 * k + 1]), hhalf(v[4 * k + 2]), hhalf(v[4 * k + 3])); }
    {
      uint32_t v[4], u[4]; const int r = t >> 3, c = t & 7;
      lds128(v, sb + OFF_WS + 128 + t * 16); lds128(u, sb + OFF_WS + c * 16);
      const uint32_t x = lds32(sb + OFF_WS + 2176 + lane * 4);
      sts128(sb + OFF_W3 + r * 128 + ((c ^ (r & 7)) << 4), b2h(v[0], .5f), b2h(v[1], .5f), b2h(v[2], .5f), b2h(v[3], .5f));
      const float s = ((r & 1) || r == 6) ? 0.f : .5f;
      if (t < 64) sts128(sb + OFF_WD + r * 128 + ((c ^ r) << 4), b2h(u[0], s), b2h(u[1], s), b2h(u[2], s), b2h(u[3], s));
      if (t < 32) sts32(sb + OFF_WX + (t & 3) * 32 + (t >> 2) * 4, b2h(x, 1.f));
      const uint32_t m3 = __reduce_max_sync(~0u, magr(mag2(mag2(mag2(mag2(0, v[0]), v[1]), v[2]), v[3]))), md = __reduce_max_sync(~0u, magr(mag2(mag2(mag2(mag2(0, u[0]), u[1]), u[2]), u[3])));
      if (wbad(m3, 0x4000) || wbad(md, 0x4000) || wbad(__reduce_max_sync(~0u, magr(mag2(0, x))), 0x4700) || magr(mp) >= 0x4200 || magr(mag2(0, ev)) >= 0x4380) sts32(sb + OFF_MISC + 8, 1);
    }
    proxy_fence();
    if (w == 1) {
#pragma unroll 1
      for (int b = HE; b < HW; b++) { mbar_wait(sb + BAR_SRC + max(0, H0 + b) * 8); if (lane == 0) load_h(b); }
    }
    bar_sync(3, 128);
    const uint32_t frag = (w * 16 + (lane & 15)) * 128 + (((lane >> 4) ^ (lane & 7)) << 4);
    uint32_t mq = 0;
#pragma unroll 1
    for (int b = 0; b < 6; b++) {
      float acc[32];
      const uint64_t da = DHI | (((sb + OFF_H) >> 4) + b * 512), db = DHI | ((sb + OFF_W) >> 4);
      const uint32_t v0 = lds16(sb + OFF_POS + b * 512 + w * 128 + lane * 2), v1 = lds16(sb + OFF_POS + 64 + b * 512 + w * 128 + lane * 2);
      mbar_wait(sb + BAR_T + b * 8);
      if (b == 0) STAMP(25);
      if (b == 5) STAMP(26);
      wg_fence();
      ss64<0>(acc, da, db); ss64<1>(acc, da + 2, db + 128); ss64<1>(acc, da + 4, db + 256); ss64<1>(acc, da + 6, db + 384);
      wg_commit();
      if (b == 0) mbar_wait(sb + BAR_AW);
      if (t == 32) { if (HALL) { if (b == 0) for (int k = HW; k < 6; k++) load_h(k); } else if (b + HW < 6) load_h(b + HW); }
      __syncwarp();
      uint32_t ff[6], fg[6];
#pragma unroll
      for (int j = 0; j < 6; j++) { ff[j] = (__byte_perm((j & 1) ? v1 : v0, 0, 0x4140) >> (3 * (j >> 1))) & 0x00070007u; fg[j] = __vsub2(0x00040004u, ff[j]);
        asm volatile("" : "+r"(ff[j]), "+r"(fg[j])); }
      wg_wait0(); fence_regs(acc);
      uint32_t o[16];
#pragma unroll
      for (int j = 0; j < 16; j++) o[j] = pack_f16(acc[2 * j], acc[2 * j + 1]);
#pragma unroll
      for (int j = 0; j < 6; j++) {
        const uint32_t m = o[j] & 0x7FFF7FFFu; mq = __vmaxu2(mq, m);
        o[j] = (__viaddmax_s16x2(m, fg[j], 0) & 0xFFF8FFF8u) | ff[j] | (o[j] & 0x80008000u); }
      if (b == 4) mbar_wait(sb + BAR_AX);
      const uint32_t qs = sb + OFF_SA + b * 8192;
#pragma unroll
      for (int j = 0; j < 4; j++) stsm4((qs + frag) ^ (j << 5), o[4 * j], o[4 * j + 1], o[4 * j + 2], o[4 * j + 3]);
      proxy_fence();
      if (b == 5) { const uint32_t m = __reduce_max_sync(~0u, magr(mq)); if (lane == 0) sts32(sb + OFF_MISC + 16 + w * 4, m); }
      bar_sync(3, 128);
      if (t == 0) { if (b * 64 < nloc) tma_store(tmb + TM_Q, 0, node0 + b * 64, qs); if (b == 5) bulk_commit(); }
      __syncwarp();
    }
    asm volatile("setmaxnreg.dec.sync.aligned.u32 32;");
    if (w == 0) {
      STAMP(18);
      uint32_t mv[4]; lds128(mv, sb + OFF_MISC + 16);
      const uint32_t mx = max(max(mv[0], mv[1]), max(mv[2], mv[3]));
      bulk_wait();
      mbar_arrive(sb + BAR_QR, lane == 0);
      STAMP(19);
      if (lane == 0) {
        if (nloc > 0 && (mx >= 0x7BF0 || mx < 0x1400)) asm volatile("st.relaxed.gpu.global.u32 [%0+4], %1;" :: "l"(p.sync), "r"(e) : "memory");
        asm volatile("red.release.gpu.global.add.u32 [%0], 1;" :: "l"(p.sync) : "memory");
      }
      __syncwarp();
      uint32_t c, f; int spin = 0;
      do { asm volatile("ld.acquire.gpu.global.v2.u32 {%0, %1}, [%2];" : "=r"(c), "=r"(f) : "l"(p.sync) : "memory"); trap_if(++spin > 4000000); } while (__any_sync(~0u, (int)(c - e * G) < 0));
      if (f == e) sts32(sb + OFF_MISC + 8, 1);
      if (cta == 0 && lane == 0) asm volatile("st.relaxed.gpu.global.u32 [%0+8], %1;" :: "l"(p.sync), "r"(e) : "memory");
      STAMP(20);
      __syncwarp();
      mbar_arrive(sb + BAR_QP, lane == 0);
    }
    if (w == 1) {
      if (PFW) mbar_wait(sb + PFW);
      __nanosleep(PF0NS);
#pragma unroll 1
      for (int i = 0; i < PFN; i++) { if (lane == 0) prefetch_e(i); __nanosleep(PFNS); }
    }
    bar_sync(4, NTHR);
    if (t == 0) { mbar_expect(sb + BAR_U, 16384); tma_load(sb + OFF_W, tmb + TM_WH, 0, sb + BAR_U); tma_load(sb + OFF_W + 8192, tmb + TM_WH, 64, sb + BAR_U); }
    mbar_wait(sb + BAR_U);
    uint32_t mh = 0;
#pragma unroll 1
    for (int i = t; i < 512; i += 128) { uint32_t v[4]; const uint32_t a = sb + OFF_W + i * 16;
      lds128(v, a); sts128(a, hhalf(v[0]), hhalf(v[1]), hhalf(v[2]), hhalf(v[3]));
      lds128(v, a + 8192); sts128(a + 8192, b2h(v[0], .5f), b2h(v[1], .5f), b2h(v[2], .5f), b2h(v[3], .5f));
      mh = mag2(mag2(mag2(mag2(mh, v[0]), v[1]), v[2]), v[3]); }
    if (wbad(__reduce_max_sync(~0u, magr(mh)), 0x4700)) sts32(sb + OFF_MISC + 12, 1);
    proxy_fence();
    __syncwarp();
    mbar_arrive(sb + BAR_WH, lane == 0);
    return;
  }

  if (tid == 320) {
    mbar_init(sb + BAR_W, 1);
    asm volatile("fence.mbarrier_init.release.cluster;" ::: "memory");
    mbar_expect(sb + BAR_W, 2 * 8192 + 2304);
    tma_load(sb + OFF_W, tmb + TM_WE, 64, sb + BAR_W); tma_load(sb + OFF_W + 8192, tmb + TM_WE, 0, sb + BAR_W);
    bulk_load(sb + OFF_WS, p.we + 128 * 64, 2176, sb + BAR_W); bulk_load(sb + OFF_WS + 2176, p.wx, 128, sb + BAR_W);
  }
  if (tid == 288) {
#pragma unroll
    for (int a = BAR_SRC; a < BAR_END; a += 8) if (a != BAR_W) mbar_init(sb + a, a == BAR_WH || a == BAR_PS || a == BAR_EP ? 4 : a == BAR_XA ? 11 : a == BAR_HB ? 2 : 1);
    asm volatile("fence.mbarrier_init.release.cluster;" ::: "memory");
    asm volatile("prefetch.tensormap [%0];" :: "l"(tmb + TM_XA)); asm volatile("prefetch.tensormap [%0];" :: "l"(tmb + TM_H));
    asm volatile("prefetch.tensormap [%0];" :: "l"(tmb + TM_XB)); asm volatile("prefetch.tensormap [%0];" :: "l"(tmb + TM_Q));
  }
  {
    if (tid < 144) { const uint32_t z = (tid >> 3) == 16 ? 0x8000u : 0u; sts128(sb + OFF_CNT + tid * 16, z, z, z, z); }
    else if (tid <= 144 + G) sts32(sb + OFF_BC + (tid - 144) * 4, ((tid - 144) & 31) * 4);
    const uint32_t sp = XPAD * 0x10001u, em = first_node(G);
    if (wid < 7) {
#pragma unroll
      for (int i = 0; i < 4; i++) sts128(sb + OFF_TS + tid * 16 + i * 3584, sp, sp, sp, sp);
    }
    static_assert(SCAP * 32 == 4 * 3584, "fill");
#pragma unroll 1
    for (int i = n4 + tid; i < 1536; i += 384) sts128(sb + OFF_DST + i * 16, em, em, em, em);
    if (tid == 321) sts128(sb + OFF_MISC, 0, 0, p.force_slow, 0);
  }
  bar_arrive(6, NTHR);
  bar_sync(0, 384);
  uint32_t ep, tag, eb0, pk[12], r0[12], r1[12], cb;
  uint2 vb[12];
  auto get_tag = [&]() { mbar_wait(sb + BAR_EP); ep = lds32(sb + OFF_MISC + 32); tag = (1 + ep % 3) << 30; eb0 = ealo - (tag >> 11); };
  if (wid == 11) {
    trap_if(sb != (uint32_t)__cvta_generic_to_shared(smraw));
#pragma unroll 1
    for (unsigned long long q = LSEQ; q; q >>= 8) { const int k = (q >> 4) & 7, nb = max(0, min(8192, n4 * 16 - k * 8192));
      mbar_wait(sb + BAR_DST + ((uint32_t)q & 7) * 8);
      if (lane == 0) {
        if (k >= 3) load_h(k - 3);
        else { mbar_expect(sb + BAR_SRC + k * 8, nb);
          if (nb) bulk_load(sb + OFF_SRCI + k * 8192, (const char*)(p.src + e0) + k * 8192, nb, sb + BAR_SRC + k * 8); } } }
    get_tag();
    mbar_wait(sb + BAR_PS);
    bar_sync(12, 384);
    uint32_t xm = 0;
#pragma unroll
    for (int k = 0; k < 5; k++) xm |= (lds32(sb + OFF_BC + min(lane + 32 * k, G - 1) * 4) >= (65 << 9) && lane + 32 * k < G) << k;
    auto ext_send = [&](int pl) {
      uint32_t x = xm;
      for (uint32_t m; (m = __ballot_sync(~0u, x));) {
        const uint32_t l = __ffs(m) - 1, j = l + 32 * (__ffs(__shfl_sync(~0u, x, l)) - 1);
        if (lane == l) x &= x - 1;
        const uint32_t e = min(lds16(sb + OFF_AX + j * 128 + ((4 * l + 2 * lane) & 126)), 6143u);
        if (pl) st_ext(p.xe + (j * G + cta) * 32 + lane, lds32(sb + OFF_SRCI + e * 4) + tag + (e << 16), ep);
        else { const uint32_t cn = lds32(sb + OFF_BC + j * 4) >> 9, v = cn > 96 ? 1 : lane + 64 < cn ? 512 | (lds32(sb + OFF_DST + e * 4) & 511) : 0;
          asm volatile("red.shared.xor.b32 [%0], %1;" :: "r"(sb + OFF_SA + j * 128 + ((l + lane) & 31) * 4), "r"(((v & 63) << 10) | ((v >> 6) << 26)) : "memory"); }
      }
    };
    if (__any_sync(~0u, xm)) { ext_send(0); proxy_fence(); __syncwarp(); }
    if (lane == 0) { tma_store_ef(tmb + TM_XA, cta * 64, 0, sb + OFF_SA); bulk_commit(); mbar_arrive(sb + BAR_AI); bulk_wait(); hint_signal(p.sync + 4); mbar_arrive(sb + BAR_AW); STAMP(16); }
    __syncwarp();
    bar_sync(13, 384);
    if (!B_HOLD && lane == 0) { tma_store_ef(tmb + TM_XB, cta * 64, 0, sb + OFF_SB); bulk_commit(); }
    __syncwarp();
    ext_send(1);
    mbar_arrive(sb + BAR_AX, lane == 0);
    if (B_HOLD) mbar_wait(sb + (B_HOLD == 1 ? BAR_HA : BAR_XA));
    if (lane == 0) {
      bulk_wait();
#pragma unroll 1
      for (int r = B_HOLD ? 0 : BROWS; r < G; r += BROWS) { tma_store_ef(tmb + TM_XB, cta * 64, r, sb + OFF_SB + r * 256); bulk_commit(); bulk_wait(); }
      hint_signal(p.sync + 5);
      STAMP(17);
    }
    __syncwarp();
    hint_wait(p.sync + 5, ep * G);
    if (lane == 0) { mbar_expect(sb + BAR_HB, G * 256);
#pragma unroll 1
      for (int o = 0; o < 4; o++) bulk_load(sb + OFF_XB + o * (G * 64), (const char*)p.xb + (size_t)(cta * 4 + o) * (G * 64), G * 64, sb + BAR_HB); }
    __syncwarp();
    STAMP(21);
  } else {
    STAMP(15);
    {
      uint32_t d[4 * NCH], jj[4 * NCH], rr[4 * NCH];
      auto count = [&](int k) {
        mbar_wait(sb + BAR_DST + k * 8);
        lds128(d + 4 * k, sb + OFF_DST + (tid + NWK * k) * 16);
#pragma unroll
        for (int i = 4 * k; i < 4 * k + 4; i++) { jj[i] = d[i] * p.magic; rr[i] = atoms_add(__dp4a(jj[i], 0x04000000u, sb + OFF_BC), 0x202u); }
      };
      auto place = [&](int k) {
#pragma unroll
        for (int i = 4 * k; i < 4 * k + 4; i++) {
          const uint32_t o = __dp4a(jj[i], 0x80000000u, rr[i] & 0x807Eu);
          d[i] = (d[i] & 511) | (tag >> 16);
          asm("{.reg .pred p; setp.ge.u32 p, %1, 0x8000; @p add.u32 %0, %2, %3;}" : "+r"(d[i]) : "r"(o), "r"(tid * 4), "r"(NWK * k * 4 + (i & 3)));
          sts16(sb + OFF_SA + o, d[i]); jj[i] = __viaddmin_u32(o, o, G * 256);
        }
      };
      count(0); STAMP(1); count(1); get_tag(); place(0); count(2); place(1); count(3); place(2);
      if (wid < 4) { count(4); place(3); place(4); } else place(3);
      proxy_fence();
      bar_arrive(12, 384);
      STAMP(2);
      mbar_wait(sb + BAR_AI);
      mbar_wait(sb + BAR_SRC); mbar_wait(sb + BAR_SRC + 8); mbar_wait(sb + BAR_SRC + 16);
      STAMP(12);
#pragma unroll
      for (int k = 0; k < NCH; k++) lds128(d + 4 * k, sb + OFF_SRCI + (tid + NWK * k) * 16);
      const uint32_t tb = tag + (tid << 18);
#pragma unroll
      for (int i = 0; i < 4 * NCH; i++) if (i < 4 * NCH - 4 || wid < 4) sts32(sb + OFF_SB + jj[i], d[i] + tb + ((NWK * (i >> 2) * 4 + (i & 3)) << 16));
      proxy_fence();
      bar_arrive(13, 384);
      STAMP(3);
    }
    const uint32_t rot = (lane + cta) & 31;
    cb = sb + OFF_CNT - (tag >> 14);
    {
      const uint32_t* xa = (const uint32_t*)(p.xa + (cta * G + wid) * 8) + rot;
      if (wid < 8) { const uint32_t e_ = ealo + epad * 32;
        mbar_wait(sb + BAR_AX);
#pragma unroll
        for (int i = 0; i < 7; i++) sts128(sb + OFF_TE + tid * 16 + i * 4096, e_, e_, e_, e_); }
      static_assert(SCAP * 64 == 7 * 4096, "fill");
      if (wid == 10) { hint_wait(p.sync + 4, ep * G); mbar_arrive(sb + BAR_HA, lane == 0); }
      mbar_wait(sb + BAR_HA);
      STAMP(14);
      const uint32_t tp = tag | (tag >> 16);
      uint32_t st;
#pragma unroll 1
      for (int spin = 0;; spin++) {
        st = 0;
#pragma unroll
        for (int k = 0; k < 12; k++) asm volatile("ld.relaxed.gpu.global.u32 %0, [%1];" : "=r"(pk[k]) : "l"(xa + k * 352) : "memory");
#pragma unroll
        for (int k = 0; k < 12; k++) st |= pk[k] ^ tp;
        st = __reduce_or_sync(~0u, st);
        if (!(st >> 30)) break;
        trap_if(spin > 2000000);
      }
      if (st & 0x3C00FC00u) {
#pragma unroll 1
        for (;;) {
          uint32_t x = 0, row = 0;
#pragma unroll
          for (int k = 0; k < 12; k++) { const uint32_t y = (pk[k] ^ tp) & 0x3C00FC00u; if (!x && y) { x = y; row = wid + 11 * k; pk[k] ^= y; } }
          if (!__any_sync(~0u, x)) break;
          const uint32_t n = ((x >> 10) & 63) | ((x >> 20) & 0x1C0);
          if (x >> 29) {
            const uint32_t r = atoms_add(sb + OFF_CNT + n * 4, 16), idx = atoms_add(sb + OFF_MISC + 4, 1);
            if (idx < 256) sts32(sb + OFF_EXT + idx * 4, n | (row << 9) | (lane << 17) | (min(r >> 4, 255u) << 22));
            else x = 1;
          }
          if (x && !(x >> 29)) sts32(sb + OFF_MISC + 8, 1);
          __syncwarp();
        }
      }
#pragma unroll
      for (int k = 0; k < 12; k++) { r0[k] = mad16(pk[k], 0x0004u, cb); r1[k] = mad16(pk[k], 0x0400u, cb); vb[k].x = atoms_add(r0[k], 16); vb[k].y = atoms_add(r1[k], 16); }
      if (B_HOLD == 2) mbar_arrive(sb + BAR_XA, lane == 0);
    }
    STAMP(4);
    if (wid >= 6) bar_arrive(11, NWK);
    if (wid < 6) {
      uint32_t ca[2], ky[2], dr[2], sq[2], ps[4];
#pragma unroll
      for (int i = 0; i < 2; i++) { ca[i] = sb + OFF_CNT + ((node0 + tid + 192 * i) & 511) * 4; lds64(ps[2 * i], ps[2 * i + 1], sb + OFF_POS + (tid + 192 * i) * 8); ps[2 * i + 1] |= (tid + 192 * i) << 16; }
      bar_sync(11, NWK);
      STAMP(5);
#pragma unroll
      for (int i = 0; i < 2; i++) ky[i] = (lds32(ca[i]) + 16) >> 5;
      if (max(ky[0], ky[1]) > 31) sts32(sb + OFF_MISC + 8, 1);
#pragma unroll
      for (int i = 0; i < 2; i++) { ky[i] = min(ky[i], 31u); dr[i] = atoms_add(sb + OFF_DH + ky[i] * 4, 1); }
      bar_sync(10, 192);
      const uint32_t hv = lds32(sb + OFF_DH + lane * 4);
      uint32_t inc = hv;
#pragma unroll
      for (int o = 1; o < 32; o <<= 1) asm("{.reg .pred p; .reg .b32 y; shfl.sync.down.b32 y|p, %0, %1, 31, -1; @p add.u32 %0, %0, y;}" : "+r"(inc) : "r"(o));
#pragma unroll
      for (int i = 0; i < 2; i++) {
        const uint32_t pos = __shfl_sync(~0u, inc - hv, ky[i]) + dr[i];
        const uint32_t ak = (uint32_t)(QCODE >> ((pos >> 5) * 4)) & 15, l = (pos >> 3) & 3;
        sq[i] = (ak >> 2) * 16 + ((QREV >> (pos >> 5) & 1) ? 3 - l : l) * 4 + (ak & 3);
        dr[i] = pos & 7;
        asm volatile("{.reg .pred p; setp.eq.u32 p, %2, 0; @p st.shared.u8 [%0], %1;}" :: "r"(sb + OFF_LEN + sq[i]), "r"(max(ky[i], 1u)), "r"(dr[i]) : "memory");
        sts64(sb + OFF_GP + sq[i] * 64 + dr[i] * 8, ps[2 * i], ps[2 * i + 1]);
      }
      bar_sync(10, 192);
      const uint32_t ln = lds32(sb + OFF_LEN + min(lane, 11) * 4), tot = __dp4a(ln, 0x01010101u, 0u);
      inc = tot;
#pragma unroll
      for (int o = 1; o < 16; o <<= 1) asm("{.reg .pred p; .reg .b32 y; shfl.sync.up.b32 y|p, %0, %1, 0, -1; @p add.u32 %0, %0, y;}" : "+r"(inc) : "r"(o));
      if (wid == 1) sts32(sb + OFF_CNT + 2048 + lane * 4, 0);
      if (tid < 12) { sts32(sb + OFF_LEN + 64 + tid * 4, inc - tot); if (inc > SCAP) sts32(sb + OFF_MISC + 8, 1); }
#pragma unroll
      for (int i = 0; i < 2; i++) sts32(ca[i], __dp4a(__shfl_sync(~0u, ln, sq[i] >> 2), 0x00010101u >> (24 - 8 * (sq[i] & 3)), __shfl_sync(~0u, inc - tot, sq[i] >> 2)) * 32 + dr[i] * 2);
    }
    bar_arrive(7, 384);
  }
  if (wid == 11) bar_sync(7, 384); else bar_sync(1, NWK);
  STAMP(6);
  if (wid != 11 && !__shfl_sync(~0u, lds32(sb + OFF_MISC + 8), 0)) {
#pragma unroll
    for (int k = 0; k < 12; k++) { r0[k] = lds32(r0[k]); r1[k] = lds32(r1[k]); }
    const uint32_t id = wid * 256 + ((lane + cta) & 31) * 8;
    auto put = [&](uint32_t x, uint32_t v) { asm volatile("{.reg .pred p; setp.lt.u32 p, %0, 0x8000; @p st.shared.u16 [%0+%2], %1;}" :: "r"(x), "h"((uint16_t)v), "n"(sb + OFF_TS) : "memory"); };
#pragma unroll
    for (int k = 0; k < 12; k++) { put(r0[k] + vb[k].x, id + k * 2816); put(r1[k] + vb[k].y, id + k * 2816 + 4); }
  }
  STAMP(7);
  mbar_wait(sb + BAR_QR);
  asm volatile("setmaxnreg.inc.sync.aligned.u32 160;");
  uint32_t nx = 0, xr = 0; uint2 xv = make_uint2(0, 0);
  auto xadr = [&]() { return p.xe + (cta * G + ((xr >> 9) & 255)) * 32 + ((xr >> 17) & 31); };
  if (wid == 11) { nx = min(__shfl_sync(~0u, lds32(sb + OFF_MISC + 4), 0), 256u);
    if (nx) { xr = lds32(sb + OFF_EXT + min(lane, nx - 1) * 4); xv = ld_poll2(xadr()); } }
  uint32_t pa[8], sp[8], pq[16]; float chk = 0.f;
  {
    uint32_t hf[32], mp = 0; float a0[32], a1[32];
    const uint32_t an = sb + OFF_GP + wid * 256 + (lane & 15) * 8 + 6, n0 = lds16(an), n1 = lds16(an + 128);
#pragma unroll
    for (int j = 0; j < 8; j++) { const uint32_t nd = j < 4 ? n0 : n1; ldsm4(hf + 4 * j, (sb + OFF_H + nd * 128 + (((nd & 7) << 4) ^ (lane & 16))) ^ ((j & 3) << 5)); }
    const uint64_t db = DHI | ((sb + OFF_W + 8192) >> 4);
    wg_fence();
    rs64b<0>(a0, hf[0], hf[1], hf[2], hf[3], db); rs64b<1>(a0, hf[4], hf[5], hf[6], hf[7], db + 128); rs64b<1>(a0, hf[8], hf[9], hf[10], hf[11], db + 256); rs64b<1>(a0, hf[12], hf[13], hf[14], hf[15], db + 384);
    wg_commit();
    rs64b<0>(a1, hf[16], hf[17], hf[18], hf[19], db); rs64b<1>(a1, hf[20], hf[21], hf[22], hf[23], db + 128); rs64b<1>(a1, hf[24], hf[25], hf[26], hf[27], db + 256); rs64b<1>(a1, hf[28], hf[29], hf[30], hf[31], db + 384);
    wg_commit();
    asm volatile("wgmma.wait_group.sync.aligned 1;" ::: "memory"); fence_regs(a0);
#pragma unroll
    for (int j = 0; j < 8; j++) { const uint32_t x = pack_f16(a0[4 * j], a0[4 * j + 1]), y = pack_f16(a0[4 * j + 2], a0[4 * j + 3]); mp = hmag(hmag(mp, x), y);
      asm volatile("movmatrix.sync.aligned.m8n8.trans.b16 %0, %1;" : "=r"(pa[j]) : "r"(x)); asm volatile("movmatrix.sync.aligned.m8n8.trans.b16 %0, %1;" : "=r"(sp[j]) : "r"(y)); }
    wg_wait0(); fence_regs(a1);
    bar_arrive(4, NTHR);
#pragma unroll
    for (int j = 0; j < 16; j++) { pq[j] = pack_f16(a1[2 * j], a1[2 * j + 1]); mp = hmag(mp, pq[j]); }
    if (magr(mp) >= 0x7000) chk = __int_as_float(0x7FC00000);
  }
  if (wid == 0) STAMP(23);
  uint32_t bad;
  {
    const uint32_t ring = sb + OFF_RING + wid * STG, p2 = sb + OFF_P2 + wid * 2048;
    uint32_t lens = __shfl_sync(~0u, lds32(sb + OFF_LEN + wid * 4), 0);
    uint32_t rem = __dp4a(lens, 0x20202020u, 0u);
    const uint32_t base = min(lds32(sb + OFF_LEN + 64 + wid * 4), SCAP);
    uint32_t a_s = sb + OFF_TS + base * 32 + (lane >> 3) * 8, a_e = sb + OFF_TE + base * 64 + (lane >> 1) * 4;
    uint32_t k0 = (uint32_t)(uint64_t)p.q + (((lane & 7) ^ ((lane >> 1) & 4)) << 4), k1 = k0 ^ 16, k2 = k0 ^ 32, k3 = k0 ^ 48, ke = ((lane ^ (lane >> 3)) & 1) << 4;
    uint32_t dst0 = ring + (lane >> 3) * 640 + (lane & 7) * 16;
    const uint32_t qhi = (uint32_t)((uint64_t)p.q >> 32), ehi = (uint32_t)((uint64_t)p.ea >> 32);
    uint32_t s0, s1, ev, to = 0, so = 12 * STG;
    auto tl_ = [&]() { lds64(s0, s1, a_s + to); asm volatile("ld.shared.u32 %0, [%1]; add.u32 %1, %1, 64;" : "=&r"(ev), "+r"(a_e) :: "memory"); to += 32; };
#define CPQ(LH, x, k, off) "dp2a." LH ".u32.u32 lo, " x ", 0x80000080, " k "; mov.b64 a, {lo, %7}; @p cp.async.cg.shared.global [%0+" #off "], [a], 16;\n"
#define CPE "or.b32 lo, %10, %11; mov.b64 a, {lo, %12}; @p cp.async.cg.shared.global" ESZ " [%0+512], [a], 16;\n"
#define CPA(BODY) asm volatile("{.reg .b32 lo; .reg .b64 a; .reg .pred p; setp.le.u32 p, %8, %9;\n" BODY "}" \
      :: "r"(dst0 + so), "r"(s0), "r"(s1), "r"(k0), "r"(k1), "r"(k2), "r"(k3), "r"(qhi), "r"(to), "r"(rem), "r"(ev), "r"(ke), "r"(ehi) : "memory")
#define CPQ4 CPQ("lo", "%1", "%3", 0) CPQ("hi", "%1", "%4", 128) CPQ("lo", "%2", "%5", 256) CPQ("hi", "%2", "%6", 384) "cp.async.commit_group;"
    auto issue = [&]() { CPA(CPE CPQ4); so = so == (NST - 1) * 12 * STG ? 0 : so + 12 * STG; };
    const int g = lane >> 2, qd = lane & 3;
    const uint32_t sw = ((lane >> 4) ^ (lane & 7)) << 4, fr = (lane & 15) * 128 + sw;
    uint32_t qa0 = ring + (g & 3) * 640 + qd * 128 + sw, qa1 = qa0 ^ 32, qa2 = qa0 ^ 64, qa3 = qa0 ^ 96;
    uint32_t eadr = ring + 512 + (g & 3) * 640 + qd * 32 + ((((lane >> 4) ^ g) & 1) << 4);
    uint32_t oh0 = g == 2 * qd ? 0x3C00u : g == 2 * qd + 1 ? 0x3C000000u : 0u, oh1 = oh0;
    uint32_t a_g = sb + OFF_GP + wid * 256 + lane * 2;
    uint32_t a_n = sb + OFF_GP + wid * 256 + (lane & 15) * 8 + 6;
    uint32_t a_p = ((lane & 8) ? p2 : sb + OFF_WD) + (lane & 7) * 128 + ((((lane >> 4) ^ lane) & 7) << 4);
    uint32_t a_w = sb + OFF_W3 + fr;
#define OPQ4(A, B, C, D) asm volatile("shfl.sync.bfly.b32 %0, %0, 0, 31, -1; shfl.sync.bfly.b32 %1, %1, 0, 31, -1; shfl.sync.bfly.b32 %2, %2, 0, 31, -1; shfl.sync.bfly.b32 %3, %3, 0, 31, -1;" : "+r"(A), "+r"(B), "+r"(C), "+r"(D))
    asm volatile("shfl.sync.idx.b32 %0, %0, %1, 31, -1;" : "+r"(oh1) : "r"(lane));
    if (OPQ & 1) OPQ4(a_w, oh0, ke, dst0);
    if (OPQ & 2) OPQ4(qa0, qa1, qa2, qa3);
    if (OPQ & 4) OPQ4(k0, k1, k2, k3);
    if (OPQ & 8) OPQ4(a_g, a_n, a_p, eadr);
    uint32_t w3[16], wv[8], bp[16], sum[8], Y[16], M[16], own, ownp, dpk; uint16_t tl[16], th[16];
    float pacc = 0.f;
    auto wload = [&]() {
#pragma unroll
      for (int j = 0; j < 4; j++) ldsm4t(w3 + 4 * j, a_w ^ (j << 5));
      lds128(wv, sb + OFF_WX + (a_g & 6) * 16); lds128(wv + 4, sb + OFF_WX + 16 + (a_g & 6) * 16);
    };
    auto hload = [&](uint32_t (&hf)[16], uint32_t nd) {
      const uint32_t hrow = sb + OFF_H + nd * 128 + (((nd & 7) << 4) ^ ((a_g >> 1) & 16));
#pragma unroll
      for (int j = 0; j < 4; j++) ldsm4(hf + 4 * j, hrow ^ (j << 5));
      return hrow;
    };
    auto bload = [&](uint32_t o) {
#pragma unroll
      for (int j = 0; j < 4; j++) ldsm4t(bp + 4 * j, (a_p ^ (j << 5)) + o);
    };
    { uint32_t wd[8]; const uint32_t a = sb + OFF_WD + (lane & 7) * 128 + ((((lane >> 3) ^ lane) & 7) << 4);
      ldsm4t(wd, a); ldsm4t(wd + 4, a ^ 64);
#pragma unroll
      for (int j = 0; j < 8; j++) { bp[2 * j] = wd[j]; bp[2 * j + 1] = pa[j]; } }
    own = lds16(a_g) * 0x10001u;
    wload();
    if (__shfl_sync(~0u, lds32(sb + OFF_MISC + 8), 0)) { rem = 0; nx = 0; }
    if (wid == 11) {
      sts32(sb + OFF_XB + XPAD, tag + p.N + cta);
      for (uint32_t k = 0; k < nx; k += 32) {
        const uint32_t i = min(k + lane, nx - 1);
        xr = lds32(sb + OFF_EXT + i * 4);
        if (k || __any_sync(~0u, xv.y != ep)) xv.x = ext_get(xadr(), ep);
        const uint32_t x = lds32(sb + OFF_CNT + (xr & 511) * 4) + (xr >> 22) * 16;
        sts32(sb + OFF_XB + XPAD + 4 + i * 4, xv.x); sts16(sb + OFF_TS + x, XPAD + 4 + i * 4);
        sts32(sb + OFF_TE + x * 2, mad16(xv.x, 0x2000u, eb0 + ((xr >> 9) & 255) * p.EPC * 32));
      }
      __syncwarp();
      mbar_arrive(sb + BAR_HB, lane == 0);
    }
    auto resolve = [&](auto NBK, uint32_t o) {
      constexpr int NB = decltype(NBK)::value;
      uint32_t id[NB], c0[NB], c1[NB]; const uint32_t a = base * 32 + o + lane * 4;
#pragma unroll
      for (int i = 0; i < NB; i++) { id[i] = lds32(sb + OFF_TS + a + i * 128); if (o + lane * 4 + i * 128 >= rem) id[i] = XPAD * 0x10001u; }
      uint32_t st = 0;
#pragma unroll
      for (int i = 0; i < NB; i++) { c0[i] = lds32(sb + OFF_XB + (id[i] & 0xFFFF)); c1[i] = lds32(sb + OFF_XB + (id[i] >> 16)); }
#pragma unroll
      for (int i = 0; i < NB; i++) st |= (c0[i] ^ tag) | (c1[i] ^ tag);
      for (int spin = 0; __any_sync(~0u, st >> 30); spin++) {
        st = 0; trap_if(spin > 2000000);
#pragma unroll
        for (int i = 0; i < NB; i++) {
          asm volatile("{.reg .pred p, q; setp.lt.u32 p, %4, %6; setp.lt.u32 q, %5, %6; @p ld.relaxed.gpu.global.u32 %0, [%2]; @q ld.relaxed.gpu.global.u32 %1, [%3];}"
            : "+r"(c0[i]), "+r"(c1[i]) : "l"((const char*)p.xb + cta * XPAD + (id[i] & 0xFFFF)), "l"((const char*)p.xb + cta * XPAD + (id[i] >> 16)), "r"(id[i] & 0xFFFF), "r"(id[i] >> 16), "n"(XPAD) : "memory");
          st |= (c0[i] ^ tag) | (c1[i] ^ tag); }
      }
#pragma unroll
      for (int i = 0; i < NB; i++) { const uint32_t j0 = (id[i] >> 8) & 255, j1 = id[i] >> 24;
        asm volatile("{.reg .pred p, q, r; setp.lt.u32 p, %5, %9; setp.lt.u32 q, %6, %9; setp.lt.u32 r, %7, %8;\n"
          "@p st.shared.u32 [%0], %2; @q st.shared.u32 [%0+4], %3; @r st.shared.u32 [%1], %4;}"
          :: "r"(sb + OFF_TE + 2 * a + i * 256), "r"(sb + OFF_TS + a + i * 128), "r"(mad16(c0[i], 0x2000u, eb0 + j0 * p.EPC * 32)), "r"(mad16(c1[i], 0x2000u, eb0 + j1 * p.EPC * 32)),
             "r"(__byte_perm(c0[i], c1[i], 0x5410)), "r"(j0), "r"(j1), "r"(o + lane * 4 + i * 128), "r"(rem), "n"(G) : "memory"); }
    };
    bar_sync(2, 384);
    if (wid == 0) STAMP(27);
    mbar_wait(sb + BAR_QP);
    bad = __shfl_sync(~0u, lds32(sb + OFF_MISC + 8), 0);
    mbar_wait(sb + BAR_HB);
    if (wid == 0) STAMP(22);
   if (!bad) {
    resolve(IC<1>(), 0);
    __syncwarp();
#pragma unroll
    for (int i = 0; i < NST - 1; i++) { tl_(); issue(); }
    STAMP(13);
#pragma unroll 1
    for (uint32_t o = 128; o < rem; o += 128 * RNB) resolve(IC<RNB>(), o);
    bar_sync(8, 384);
    if (wid == 0) STAMP(24);
    tl_(); issue();
#pragma unroll
    for (int j = 0; j < 4; j++) stsm4((p2 + fr) ^ (j << 5), pq[4 * j], pq[4 * j + 1], pq[4 * j + 2], pq[4 * j + 3]);
    auto body = [&](auto MODE) {
      constexpr int mode = decltype(MODE)::value;
      uint32_t T[16], ef[4], q0, q1, x0, x1, x2; float e0_, e1_, cs[4];
      auto mu = [&](int j) {
#pragma unroll
        for (int i = 2 * j; i < 2 * j + 2; i++) asm volatile("{.reg .b16 l, h; mov.b32 {l, h}, %2; tanh.approx.f16 %0, l; tanh.approx.f16 %1, h;}" : "=h"(tl[i]), "=h"(th[i]) : "r"(Y[i])); };
      auto fi = [&](int j) {
#pragma unroll
        for (int i = 2 * j; i < 2 * j + 2; i++) asm volatile("{.reg .b32 t; mov.b32 t, {%2, %3}; fma.rn.f16x2 %0, %1, t, %1;}" : "=r"(M[i]) : "r"(Y[i]), "h"(tl[i]), "h"(th[i])); };
      auto ad = [&](int j) { asm volatile("add.rn.f16x2 %0, %0, %1; add.rn.f16x2 %0, %0, %2;" : "+r"(sum[j]) : "r"(M[2 * j]), "r"(M[2 * j + 1])); };
      auto he = [&](int j) { asm volatile("mma.sync.aligned.m16n8k16.row.col.f16.f16.f16.f16 {%0,%1}, {%2,%3,%4,%5}, {%6,%7}, {%0,%1};" : "+r"(T[2 * j]), "+r"(T[2 * j + 1]) : "r"(ef[0]), "r"(ef[1]), "r"(ef[2]), "r"(ef[3]), "r"(w3[2 * j]), "r"(w3[2 * j + 1])); };
      auto hs = [&](int j) { asm volatile("mma.sync.aligned.m16n8k16.row.col.f16.f16.f16.f16 {%0,%1}, {%2,%3,%4,%5}, {%6,%7}, {%8,%9};" : "=r"(Y[2 * j]), "=r"(Y[2 * j + 1]) : "r"(q0), "r"(q1), "r"(oh0), "r"(oh1), "r"(bp[2 * j]), "r"(bp[2 * j + 1]), "r"(T[2 * j]), "r"(T[2 * j + 1])); };
      auto hc = [&](int j) {
        if (j) asm volatile("mma.sync.aligned.m16n8k16.row.col.f32.f16.f16.f32 {%0,%1,%2,%3}, {%4,%5,%6,%7}, {%8,%9}, {%0,%1,%2,%3};" : "+f"(cs[0]), "+f"(cs[1]), "+f"(cs[2]), "+f"(cs[3]) : "r"(M[4 * j]), "r"(M[4 * j + 1]), "r"(M[4 * j + 2]), "r"(M[4 * j + 3]), "r"(wv[2 * j]), "r"(wv[2 * j + 1]));
        else asm volatile("mma.sync.aligned.m16n8k16.row.col.f32.f16.f16.f32 {%0,%1,%2,%3}, {%4,%5,%6,%7}, {%8,%9}, {%10,%10,%10,%10};" : "=f"(cs[0]), "=f"(cs[1]), "=f"(cs[2]), "=f"(cs[3]) : "r"(M[0]), "r"(M[1]), "r"(M[2]), "r"(M[3]), "r"(wv[0]), "r"(wv[1]), "f"(0.f)); };
      auto cv = [&](int i) { asm volatile("{.reg .b32 a, b; shl.b32 a, %0, 16; and.b32 b, %0, 0xFFFF0000; cvt.rn.f16x2.f32 %0, b, a;}" : "+r"(ef[i])); };
      auto un = [&]() { asm volatile("shl.b32 %0, %2, 16; and.b32 %1, %2, 0xFFFF0000;" : "=&f"(e0_), "=&f"(e1_) : "r"(dpk)); };
      auto ex0 = [&]() { asm volatile("prmt.b32 %0, %3, %4, 0x6420; prmt.b32 %1, %5, %6, 0x6420; prmt.b32 %2, %7, %8, 0x6420;" : "=&r"(x0), "=&r"(x1), "=&r"(x2) : "r"(T[0]), "r"(T[1]), "r"(T[2]), "r"(T[3]), "r"(T[4]), "r"(T[5])); };
      auto ex1 = [&]() { asm volatile("{.reg .b32 a, b; shl.b32 a, %2, 3; shl.b32 b, %3, 6; lop3.b32 a, %1, a, 0x38383838, 0xD8; lop3.b32 a, a, b, 0xC0C0C0C0, 0xD8; sub.rn.bf16x2 %0, %4, a;}" : "=r"(dpk) : "r"(x0), "r"(x1), "r"(x2), "r"(own)); };
      auto ex2 = [&]() { asm volatile("{.reg .b32 a, b, d, u; .reg .b16 l, h; shl.b32 a, %2, 16; and.b32 b, %2, 0xFFFF0000; cvt.rn.f16x2.f32 d, b, a; mul.rn.f16x2 %0, d, d; mov.b32 {l, h}, d; mov.b32 u, {h, h}; mul.rn.f16x2 %1, u, u;}" : "=&r"(q0), "=&r"(q1) : "r"(dpk)); };
      auto pf = [&]() { asm volatile("fma.rn.f32 %0, %1, %2, %0; fma.rn.f32 %0, %3, %4, %0;" : "+f"(pacc) : "f"(cs[0]), "f"(e0_), "f"(cs[2]), "f"(e1_)); };
#define FX(k) if (FM >> k & 1) asm volatile("pmevent 1;" ::: "memory")
      if (mode == 2) {
        hc(0); mu(3); fi(2); un(); ad(0); ad(1); mu(4); fi(3); hc(1); mu(5); fi(4); ad(2); mu(6); fi(5); ad(3); hc(2); mu(7); fi(6); fi(7); ad(4); ad(5); hc(3); ad(6); ad(7); pf();
        return;
      }
      asm volatile("cp.async.wait_group %0;" :: "n"(NST - 1) : "memory");
      __syncwarp();
      if (mode == 1) STAMP(8);
      ldsm4(ef, eadr + so); ldsm4(T, qa0 + so); ldsm4(T + 4, qa1 + so); ldsm4(T + 8, qa2 + so); ldsm4(T + 12, qa3 + so);
      tl_();
      if (mode == 1) {
        issue();
        cv(0); cv(1); cv(2); cv(3); ex0(); ex1(); ex2();
#pragma unroll
        for (int j = 0; j < 8; j++) { he(j); hs(j); }
        mu(0); mu(1); fi(0); mu(2); fi(1);
        return;
      }
      hc(0); mu(3); fi(2); un(); ad(0); ad(1);
      FX(0);
      mu(4); fi(3); cv(0); cv(1); cv(2); cv(3); ex0(); ex1();
      FX(1);
      he(0); he(1); hc(1); mu(5); fi(4); ex2(); ad(2);
      FX(2);
      hs(0); he(2); mu(6); fi(5); issue(); ad(3);
      FX(3);
      hs(1); he(3); hc(2); mu(7); fi(6);
      FX(4);
      hs(2); hs(3); he(4); he(5); mu(0); fi(7); ad(4); ad(5);
      FX(5);
      hc(3); hs(4); he(6); he(7); mu(1); fi(0); ad(6);
      FX(6);
      hs(5); hs(6); hs(7); mu(2); fi(1); ad(7); pf();
      FX(7);
    };
#pragma unroll
    for (int j = 0; j < 8; j++) sum[j] = 0;
    body(IC<1>());
    int cnt = (lens & 255) - 1;
#pragma unroll 1
    for (int t = 0; t < 8; t++) {
#pragma unroll 1
      for (; cnt > 0; cnt--) { body(IC<0>());
      }
      if (!(t & 1)) {
        ownp = own;
        if (t < 6) {
          a_g += 64; own = lds16(a_g) * 0x10001u;
          if (t == 0) {
#pragma unroll
            for (int j = 0; j < 8; j++) bp[2 * j + 1] = sp[j];
          } else bload((a_g & 16) ? (t & 4) * 256 : 0);
          lens >>= 8; cnt = 1;
          continue;
        }
        body(IC<2>()); t++;
        STAMP(9);
      }
      cnt = (lens & 255) - 1;
      { const uint32_t ng = __shfl_sync(~0u, ownp, (a_g >> 1) | 3) >> 16, c3 = (a_g >> 1) & 3;
        asm volatile("{.reg .pred p; setp.lt.u32 p, %2, %3; @p st.global.u16 [%0], %1;}" :: "l"(p.out + (size_t)p.N * 64 + (size_t)node0 * 3 + (ng * 3 + c3)), "h"((uint16_t)pack_bf16(bf_hi(ownp) + pacc, 0.f)), "r"(ng), "r"(c3 < 3 ? nloc : 0) : "memory"); }
      chk = fmaf(pacc, 0.f, chk); pacc = 0.f;
      if (t & 2) {
        uint32_t hf[16]; float acc[32];
        const uint32_t nd = lds16(a_n); a_n += 128;
        const uint32_t hrow = hload(hf, nd);
        const uint64_t b1 = DHI | ((sb + OFF_W) >> 4), b2_ = b1 + 512;
        mbar_wait(sb + BAR_WH);
        wg_fence();
        rs64h<0>(acc, sp[0], sum[0], sp[1], sum[1], b2_); rs64h<1>(acc, sp[2], sum[2], sp[3], sum[3], b2_ + 128); rs64h<1>(acc, sp[4], sum[4], sp[5], sum[5], b2_ + 256); rs64h<1>(acc, sp[6], sum[6], sp[7], sum[7], b2_ + 384);
        rs64b<1>(acc, hf[0], hf[1], hf[2], hf[3], b1); rs64b<1>(acc, hf[4], hf[5], hf[6], hf[7], b1 + 128); rs64b<1>(acc, hf[8], hf[9], hf[10], hf[11], b1 + 256); rs64b<1>(acc, hf[12], hf[13], hf[14], hf[15], b1 + 384);
        wg_commit(); wg_wait0(); fence_regs(acc);
        if (t == 7) STAMP(10);
        chk = fmaf(acc[0], 0.f, fmaf(acc[2], 0.f, chk));
        auto fin = [&](uint32_t x, float y0, float y1) { return u2(__hadd2(b2(x), b2(pack_bf16(silu_h(y0), silu_h(y1))))); };
#pragma unroll
        for (int j = 0; j < 4; j++) stsm4(hrow ^ (j << 5), fin(hf[4 * j], acc[8 * j], acc[8 * j + 1]), fin(hf[4 * j + 1], acc[8 * j + 2], acc[8 * j + 3]), fin(hf[4 * j + 2], acc[8 * j + 4], acc[8 * j + 5]), fin(hf[4 * j + 3], acc[8 * j + 6], acc[8 * j + 7]));
        __syncwarp();
        const uint32_t c8 = (a_g << 3) & 0x70;
#pragma unroll
        for (int j = 0; j < 4; j++) { uint32_t v[4]; const uint32_t n = __shfl_sync(~0u, nd, 4 * j + ((a_g >> 4) & 3)); lds128(v, sb + OFF_H + n * 128 + (((n << 4) ^ c8) & 0x70));
          asm volatile("{.reg .pred p; setp.lt.u32 p, %5, %6; @p st.global" OCS ".v4.b32 [%0], {%1,%2,%3,%4};}" :: "l"((const char*)p.out + (size_t)node0 * 128 + (n * 128 + c8)), "r"(v[0]), "r"(v[1]), "r"(v[2]), "r"(v[3]), "r"(n), "r"(nloc) : "memory"); }
        wload();
      }
#pragma unroll
      for (int j = 0; j < 8; j++) { sp[j] = sum[j]; asm volatile("mov.b32 %0, 0;" : "=r"(sum[j])); }
    }
    asm volatile("{.reg .pred p, q; setp.neu.f32 p, %1, 0f00000000; setp.ne.or.u32 p, %2, 0, p; bar.red.or.pred q, 5, 384, p; selp.u32 %0, 1, 0, q;}" : "=r"(bad) : "f"(chk), "r"(lds32(sb + OFF_MISC + 12)) : "memory");
    STAMP(11);
   }
  }
  if (bad) slow_path(p, wid, lane, node0, nloc);
}

}

typedef CUresult (*EncodeFn)(CUtensorMap*, CUtensorMapDataType, cuuint32_t, void*, const cuuint64_t*, const cuuint64_t*, const cuuint32_t*, const cuuint32_t*,
                             CUtensorMapInterleave, CUtensorMapSwizzle, CUtensorMapL2promotion, CUtensorMapFloatOOBfill);

extern "C" void kernel_launch(void* const* d_in, const int* in_sizes, int n_in, void* d_out, int out_size) {
  Params p; Maps maps;
  p.h = (const uint4*)d_in[0]; p.pos = (const uint16_t*)d_in[1]; p.ea = (const uint4*)d_in[2];
  p.src = (const int*)d_in[3]; p.dst = (const int*)d_in[4];
  p.we = (const uint16_t*)d_in[5]; p.wx = (const uint16_t*)d_in[6]; p.wh = (const uint16_t*)d_in[7];
  p.out = (uint16_t*)d_out;
  p.N = in_sizes[0] / 64; p.E = in_sizes[3];
  p.EPC = ((p.E + G * 4 - 1) / (G * 4)) * 4;
  p.magic = (uint32_t)(((uint64_t)G << 24) / (uint64_t)p.N);
  p.inv = (1ull << 56) / p.magic;
  const uint64_t ea0 = (uint64_t)d_in[2], ea1 = ea0 + (uint64_t)p.E * 32 - 1;
  p.force_slow = ((ea0 >> 32) != (ea1 >> 32)) || (ea0 & 31) || (p.E & 3);
  void* qp = nullptr;
  cudaGetSymbolAddress(&qp, g_q);
  p.q = (char*)qp;
  if (((uint64_t)p.q >> 32) != (((uint64_t)p.q + QBYTES) >> 32)) p.q += QBYTES;
  cudaGetSymbolAddress((void**)&p.sync, g_sync); cudaGetSymbolAddress((void**)&p.xe, g_xe);
  cudaGetSymbolAddress((void**)&p.xa, g_xa); cudaGetSymbolAddress((void**)&p.xb, g_xb);
  void* fn = nullptr; cudaDriverEntryPointQueryResult qr;
  cudaGetDriverEntryPoint("cuTensorMapEncodeTiled", &fn, cudaEnableDefault, &qr);
  auto mk = [&](CUtensorMap* tm, void* base, int rows) {
    const cuuint64_t dim[2] = {64, (cuuint64_t)rows}, str[1] = {128}; const cuuint32_t bx[2] = {64, 64}, es[2] = {1, 1};
    ((EncodeFn)fn)(tm, CU_TENSOR_MAP_DATA_TYPE_BFLOAT16, 2, base, dim, str, bx, es, CU_TENSOR_MAP_INTERLEAVE_NONE, CU_TENSOR_MAP_SWIZZLE_128B,
                   CU_TENSOR_MAP_L2_PROMOTION_NONE, CU_TENSOR_MAP_FLOAT_OOB_FILL_NONE);
  };
  mk(&maps.m[TM_H / 128], d_in[0], p.N); mk(&maps.m[TM_WE / 128], d_in[5], 145); mk(&maps.m[TM_WH / 128], d_in[7], 128); mk(&maps.m[TM_Q / 128], p.q, p.N);
  for (int k = 0; k < 2; k++) {
    void* xp = (void*)(k ? p.xb : p.xa);
    const cuuint64_t dim[2] = {(cuuint64_t)G * 64, (cuuint64_t)G}, str[1] = {(cuuint64_t)G * (128 << k)}; const cuuint32_t bx[2] = {64, (cuuint32_t)(k ? BROWS : G)}, es[2] = {1, 1};
    ((EncodeFn)fn)(&maps.m[TM_XA / 128 + k], k ? CU_TENSOR_MAP_DATA_TYPE_UINT32 : CU_TENSOR_MAP_DATA_TYPE_UINT16, 2, xp, dim, str, bx, es, CU_TENSOR_MAP_INTERLEAVE_NONE,
                   CU_TENSOR_MAP_SWIZZLE_NONE, CU_TENSOR_MAP_L2_PROMOTION_NONE, CU_TENSOR_MAP_FLOAT_OOB_FILL_NONE);
  }
  cudaFuncSetAttribute(egnn_kernel, cudaFuncAttributeMaxDynamicSharedMemorySize, SMEM);
  egnn_kernel<<<G, NTHR, SMEM>>>(p, maps);
}
```

```cpp
#include <cuda_runtime.h>
#include <cuda_bf16.h>
#include <cuda_fp16.h>
#include <cuda.h>
#include <stdint.h>
#pragma nv_diag_suppress 549

#define PFN 16
#define PFNS 250
#define FM 0
#define OPQ 0
#define H0 0
#define HALL 1
#define PF0NS 0
#define PFW 0
#define QCODE 0x254a109b7863ull
#define QREV 0x605
#define PFS 1
#define ESZ ""
#define XEF 0
#define OCS ""
#define RNB 2
#define NEARLY 2
#define PFE 0
#define DEFO 1
#define DEFNS 400
#define ABL 0
#define HW 3
#define BROWS 132
#define B_HOLD 1
#define LSEQ 0x231200ull
#define HE 0
namespace {

constexpr int G = 132;
constexpr int NTHR = 512, NWK = 352, NCH = 5;
constexpr int NST = 3, STG = 2560;
constexpr int SCAP = 448;

constexpr int OFF_H = 0;
constexpr int OFF_W = 49152;
constexpr int OFF_WD = OFF_W + 16384;
constexpr int OFF_W3 = OFF_WD + 1024;
constexpr int OFF_P2 = OFF_W3 + 2048;
constexpr int OFF_RING = OFF_P2 + 24576;
constexpr int OFF_TE = OFF_RING + 12 * NST * STG;
constexpr int OFF_TS = OFF_TE + SCAP * 64;
constexpr int OFF_GP = OFF_TS + SCAP * 32;
constexpr int OFF_WX = OFF_GP + 3072;
constexpr int OFF_LEN = OFF_WX + 128;
constexpr int OFF_MISC = OFF_LEN + 128;
constexpr int OFF_BAR = OFF_MISC + 48;
constexpr int SMEM = OFF_BAR + 256;
static_assert(SMEM <= 232448, "smem");
constexpr uint32_t sb = 1024;
constexpr int OFF_SRCI = OFF_TE;
constexpr int OFF_SB = OFF_RING, OFF_SA = OFF_SB + 34816, OFF_AX = OFF_SA + 32768, OFF_DST = OFF_H + 24576;
constexpr int OFF_WS = OFF_AX + 17408;
constexpr int OFF_BC = OFF_WS + 2304;
constexpr int OFF_CNT = OFF_P2;
constexpr int OFF_DH = OFF_CNT + 2176;
constexpr int OFF_POS = OFF_DH + 128;
constexpr int OFF_EXT = OFF_POS + 3072;
constexpr int OFF_XB = OFF_EXT + 1024, XPAD = G * 256;
static_assert(OFF_XB + XPAD + 1028 <= OFF_RING + 12 * STG && OFF_XB % 128 == 0 && OFF_BC + 544 <= OFF_TE && OFF_P2 % 1024 == 0 && OFF_SA % 1024 == 0 && SCAP * 64 >= 24576, "staging");
constexpr int BAR_DST = OFF_BAR, BAR_SRC = BAR_DST + 40, BAR_T = BAR_SRC + 24, BAR_W = BAR_T + 48, BAR_XA = BAR_W + 8, BAR_PS = BAR_XA + 8, BAR_AW = BAR_PS + 8,
              BAR_QP = BAR_AW + 8, BAR_QR = BAR_QP + 8, BAR_HA = BAR_QR + 8, BAR_EP = BAR_HA + 8, BAR_AX = BAR_EP + 8, BAR_AI = BAR_AX + 8, BAR_HB = BAR_AI + 8, BAR_U = BAR_HB + 8, BAR_WH = BAR_U + 8, BAR_M = BAR_WH + 8, BAR_END = BAR_M + 8;
constexpr uint32_t QBYTES = 8u << 20;

__device__ __align__(256) uint4 g_xa[G * G * 8];
__device__ __align__(256) uint4 g_xb[G * G * 16];
__device__ __align__(256) uint2 g_xe[G * G * 32];
__device__ __align__(256) uint4 g_q[2 * QBYTES / 16];
__device__ __align__(256) uint32_t g_sync[8];
#define STAMP(k)

struct Maps { CUtensorMap m[6]; };
constexpr int TM_H = 0, TM_WE = 128, TM_WH = 256, TM_Q = 384, TM_XA = 512, TM_XB = 640;
struct Params {
  const uint4* h; const uint16_t* pos; const uint4* ea; const int* src; const int* dst;
  const uint16_t* we; const uint16_t* wx; const uint16_t* wh; uint16_t* out; char* q;
  uint32_t* sync; const uint4* xa; const uint4* xb; uint2* xe;
  int N, E, EPC; uint32_t magic; int force_slow; unsigned long long inv;
};
template<int V> struct IC { static constexpr int value = V; };

#define R32(d) "+f"(d[0]),"+f"(d[1]),"+f"(d[2]),"+f"(d[3]),"+f"(d[4]),"+f"(d[5]),"+f"(d[6]),"+f"(d[7]),"+f"(d[8]),"+f"(d[9]),"+f"(d[10]),"+f"(d[11]),"+f"(d[12]),"+f"(d[13]),"+f"(d[14]),"+f"(d[15]),"+f"(d[16]),"+f"(d[17]),"+f"(d[18]),"+f"(d[19]),"+f"(d[20]),"+f"(d[21]),"+f"(d[22]),"+f"(d[23]),"+f"(d[24]),"+f"(d[25]),"+f"(d[26]),"+f"(d[27]),"+f"(d[28]),"+f"(d[29]),"+f"(d[30]),"+f"(d[31])
#define S32 "{%0,%1,%2,%3,%4,%5,%6,%7,%8,%9,%10,%11,%12,%13,%14,%15,%16,%17,%18,%19,%20,%21,%22,%23,%24,%25,%26,%27,%28,%29,%30,%31}"
#define DI __device__ __forceinline__

constexpr uint64_t DHI = ((uint64_t)(1024 >> 4) << 32) | (1ull << 62);
template<int SD> DI void rs64b(float (&d)[32], uint32_t a0, uint32_t a1, uint32_t a2, uint32_t a3, uint64_t db) {
  asm volatile("wgmma.mma_async.sync.aligned.m64n64k16.f32.bf16.bf16 " S32 ", {%32,%33,%34,%35}, %36, %37, 1, 1, 1;" : R32(d) : "r"(a0), "r"(a1), "r"(a2), "r"(a3), "l"(db), "n"(SD)); }
template<int SD> DI void rs64h(float (&d)[32], uint32_t a0, uint32_t a1, uint32_t a2, uint32_t a3, uint64_t db) {
  asm volatile("wgmma.mma_async.sync.aligned.m64n64k16.f32.f16.f16 " S32 ", {%32,%33,%34,%35}, %36, %37, 1, 1, 1;" : R32(d) : "r"(a0), "r"(a1), "r"(a2), "r"(a3), "l"(db), "n"(SD)); }
template<int SD> DI void ss64(float (&d)[32], uint64_t da, uint64_t db) {
  asm volatile("wgmma.mma_async.sync.aligned.m64n64k16.f32.bf16.bf16 " S32 ", %32, %33, %34, 1, 1, 0, 1;" : R32(d) : "l"(da), "l"(db), "n"(SD)); }
DI void trap_if(bool c) { asm volatile("{.reg .pred p; setp.eq.u32 p, %0, 0; @p bra.uni LT_%=; trap; LT_%=:}" :: "r"((uint32_t)c)); }
DI void wg_fence() { asm volatile("wgmma.fence.sync.aligned;" ::: "memory"); }
DI void wg_commit() { asm volatile("wgmma.commit_group.sync.aligned;" ::: "memory"); }
DI void wg_wait0() { asm volatile("wgmma.wait_group.sync.aligned 0;" ::: "memory"); }
DI void fence_regs(float (&d)[32]) { asm volatile("" : R32(d) :: "memory"); }
DI void proxy_fence() { asm volatile("fence.proxy.async.shared::cta;" ::: "memory"); }
DI uint64_t pol_first() { uint64_t r; asm("createpolicy.fractional.L2::evict_first.b64 %0, 1.0;" : "=l"(r)); return r; }
DI float tanh_ap(float x) { float y; asm("tanh.approx.f32 %0, %1;" : "=f"(y) : "f"(x)); return y; }
DI float silu_h(float y) { return fmaf(y, tanh_ap(y), y); }
DI uint32_t pack_bf16(float lo, float hi) { uint32_t r; asm("cvt.rn.bf16x2.f32 %0, %1, %2;" : "=r"(r) : "f"(hi), "f"(lo)); return r; }
DI uint32_t pack_f16(float lo, float hi) { uint32_t r; asm("cvt.rn.f16x2.f32 %0, %1, %2;" : "=r"(r) : "f"(hi), "f"(lo)); return r; }
DI float bf_lo(uint32_t v) { return __uint_as_float(v << 16); }
DI float bf_hi(uint32_t v) { return __uint_as_float(v & 0xFFFF0000u); }
DI uint32_t b2h(uint32_t v, float s) { return pack_f16(s * bf_lo(v), s * bf_hi(v)); }
DI void mbar_wait(uint32_t bar, uint32_t parity = 0) {
  asm volatile("{.reg .pred p; .reg .u32 t0, t1;\n"
    "mbarrier.try_wait.parity.shared::cta.b64 p, [%0], %1;\n @p bra.uni LD_%=;\n mov.u32 t0, %%clock;\n"
    "LW_%=: mbarrier.try_wait.parity.shared::cta.b64 p, [%0], %1;\n"
    "@p bra.uni LD_%=;\n mov.u32 t1, %%clock; sub.u32 t1, t1, t0; setp.lt.u32 p, t1, 0x80000000;\n @p bra.uni LW_%=;\n trap;\n LD_%=:}" :: "r"(bar), "r"(parity) : "memory");
}
DI void mbar_arrive(uint32_t bar, int p = 1) { asm volatile("{.reg .pred p; setp.ne.b32 p, %1, 0; @p mbarrier.arrive.shared::cta.b64 _, [%0];}" :: "r"(bar), "r"(p) : "memory"); }
DI void bar_sync(int id, int n) { asm volatile("bar.sync %0, %1;" :: "r"(id), "r"(n) : "memory"); }
DI void bar_arrive(int id, int n) { asm volatile("bar.arrive %0, %1;" :: "r"(id), "r"(n) : "memory"); }
DI __nv_bfloat162 b2(uint32_t v) { return *(__nv_bfloat162*)&v; }
DI uint32_t u2(__nv_bfloat162 v) { return *(uint32_t*)&v; }
DI uint32_t hsq(uint32_t v) { return u2(__hmul2(b2(v), b2(v))); }
DI uint32_t hsub(uint32_t a, uint32_t b) { return u2(__hsub2(b2(a), b2(b))); }
DI uint32_t hhalf(uint32_t v) { return u2(__hmul2(b2(v), __floats2bfloat162_rn(0.5f, 0.5f))); }
DI uint32_t mag2(uint32_t m, uint32_t v) { return __vmaxu2(m, v & 0x7FFF7FFFu); }
DI uint32_t hmag(uint32_t m, uint32_t v) { const __half2 r = __hmax2(*(const __half2*)&m, __habs2(*(const __half2*)&v)); return *(const uint32_t*)&r; }
DI uint32_t magr(uint32_t m) { return max(m & 0xFFFF, m >> 16); }
DI void sts128(uint32_t a, uint32_t x, uint32_t y, uint32_t z, uint32_t w) { asm volatile("st.shared.v4.u32 [%0], {%1,%2,%3,%4};" :: "r"(a), "r"(x), "r"(y), "r"(z), "r"(w) : "memory"); }
DI void sts64(uint32_t a, uint32_t x, uint32_t y) { asm volatile("st.shared.v2.u32 [%0], {%1,%2};" :: "r"(a), "r"(x), "r"(y) : "memory"); }
DI void sts32(uint32_t a, uint32_t x) { asm volatile("st.shared.u32 [%0], %1;" :: "r"(a), "r"(x) : "memory"); }
DI void sts16(uint32_t a, uint32_t x) { asm volatile("st.shared.u16 [%0], %1;" :: "r"(a), "h"((uint16_t)x) : "memory"); }
DI void lds128(uint32_t* v, uint32_t a) { asm volatile("ld.shared.v4.u32 {%0, %1, %2, %3}, [%4];" : "=r"(v[0]), "=r"(v[1]), "=r"(v[2]), "=r"(v[3]) : "r"(a) : "memory"); }
DI void lds64(uint32_t& x, uint32_t& y, uint32_t a) { asm volatile("ld.shared.v2.u32 {%0, %1}, [%2];" : "=r"(x), "=r"(y) : "r"(a) : "memory"); }
DI uint32_t lds32(uint32_t a) { uint32_t x; asm volatile("ld.shared.u32 %0, [%1];" : "=r"(x) : "r"(a) : "memory"); return x; }
DI uint32_t lds16(uint32_t a) { uint32_t x; asm volatile("ld.shared.u16 %0, [%1];" : "=r"(x) : "r"(a) : "memory"); return x; }
DI uint32_t atoms_add(uint32_t a, uint32_t v) { uint32_t r; asm volatile("atom.shared.add.u32 %0, [%1], %2;" : "=r"(r) : "r"(a), "r"(v) : "memory"); return r; }
DI void bulk_load(uint32_t dst, const void* src, uint32_t bytes, uint32_t bar) {
  asm volatile("cp.async.bulk.shared::cluster.global.mbarrier::complete_tx::bytes.L2::cache_hint [%0], [%1], %2, [%3], %4;" :: "r"(dst), "l"(src), "r"(bytes), "r"(bar), "l"(pol_first()) : "memory"); }
DI void bulk_store(void* dst, uint32_t src, uint32_t bytes) { asm volatile("cp.async.bulk.global.shared::cta.bulk_group [%0], [%1], %2;" :: "l"(dst), "r"(src), "r"(bytes) : "memory"); }
DI void mbar_expect(uint32_t bar, uint32_t bytes) { asm volatile("mbarrier.arrive.expect_tx.shared::cta.b64 _, [%0], %1;" :: "r"(bar), "r"(bytes) : "memory"); }
DI void mbar_init(uint32_t bar, int n) { asm volatile("mbarrier.init.shared::cta.b64 [%0], %1;" :: "r"(bar), "r"(n) : "memory"); }
DI void tma_load(uint32_t dst, uint64_t tm, int row, uint32_t bar) {
  asm volatile("cp.async.bulk.tensor.2d.shared::cluster.global.mbarrier::complete_tx::bytes.L2::cache_hint [%0], [%1, {%3, %4}], [%2], %5;" :: "r"(dst), "l"(tm), "r"(bar), "r"(0), "r"(row), "l"(pol_first()) : "memory"); }
DI void tma_store(uint64_t tm, int col, int row, uint32_t src) {
  asm volatile("cp.async.bulk.tensor.2d.global.shared::cta.bulk_group [%0, {%2, %3}], [%1];" :: "l"(tm), "r"(src), "r"(col), "r"(row) : "memory"); }
DI void tma_store_ef(uint64_t tm, int col, int row, uint32_t src) {
  if (XEF) asm volatile("cp.async.bulk.tensor.2d.global.shared::cta.bulk_group.L2::cache_hint [%0, {%2, %3}], [%1], %4;" :: "l"(tm), "r"(src), "r"(col), "r"(row), "l"(pol_first()) : "memory");
  else tma_store(tm, col, row, src); }
DI void bulk_commit() { asm volatile("cp.async.bulk.commit_group;" ::: "memory"); }
DI void bulk_wait_read() { asm volatile("cp.async.bulk.wait_group.read 0;" ::: "memory"); }
DI uint2 ld_poll2(const void* a) { uint2 v; asm volatile("ld.relaxed.gpu.global.v2.u32 {%0, %1}, [%2];" : "=r"(v.x), "=r"(v.y) : "l"(a) : "memory"); return v; }
DI void st_ext(uint2* a, uint32_t v, uint32_t ep) { asm volatile("st.relaxed.gpu.global.v2.u32 [%0], {%1, %2};" :: "l"(a), "r"(v), "r"(ep) : "memory"); }
DI uint32_t ext_get(const uint2* a, uint32_t ep) { uint2 v; int spin = 0; do { v = ld_poll2(a); trap_if(++spin > 4000000); } while (__any_sync(~0u, v.y != ep)); return v.x; }
DI void bulk_wait() { asm volatile("cp.async.bulk.wait_group 0;" ::: "memory"); }
DI void hint_signal(uint32_t* c) { asm volatile("red.relaxed.gpu.global.add.u32 [%0], 1;" :: "l"(c) : "memory"); }
DI void hint_wait(const uint32_t* c, uint32_t target) { uint32_t v; int spin = 0;
  do { asm volatile("ld.relaxed.gpu.global.u32 %0, [%1];" : "=r"(v) : "l"(c) : "memory"); trap_if(++spin > 4000000); } while (__any_sync(~0u, (int)(v - target) < 0)); }
DI void stsm4(uint32_t a, uint32_t x, uint32_t y, uint32_t z, uint32_t w) { asm volatile("stmatrix.sync.aligned.m8n8.x4.shared.b16 [%0], {%1,%2,%3,%4};" :: "r"(a), "r"(x), "r"(y), "r"(z), "r"(w) : "memory"); }
DI void ldsm4(uint32_t* v, uint32_t a) { asm volatile("ldmatrix.sync.aligned.m8n8.x4.shared.b16 {%0,%1,%2,%3}, [%4];" : "=r"(v[0]), "=r"(v[1]), "=r"(v[2]), "=r"(v[3]) : "r"(a) : "memory"); }
DI void ldsm4t(uint32_t* v, uint32_t a) { asm volatile("ldmatrix.sync.aligned.m8n8.x4.trans.shared.b16 {%0,%1,%2,%3}, [%4];" : "=r"(v[0]), "=r"(v[1]), "=r"(v[2]), "=r"(v[3]) : "r"(a) : "memory"); }
DI uint32_t mad16(uint32_t x, uint32_t m, uint32_t c) { uint32_t r; asm("dp2a.lo.u32.u32 %0, %1, %2, %3;" : "=r"(r) : "r"(x), "r"(m), "r"(c)); return r; }
DI bool wbad(uint32_t m, uint32_t hi) { return m > hi || (m && m < 0x3980); }

__device__ __noinline__ void slow_path(const Params& p, int wid, int lane, int node0, int nloc) {
  const uint32_t ab = sb + OFF_P2 + wid * 8704;
  for (int i = lane; i < 32 * 68; i += 32) sts32(ab + i * 4, 0);
  __syncwarp();
  const uint32_t wdv = __ldg((const uint32_t*)(p.we + 128 * 64) + lane), wxv = __ldg((const uint32_t*)p.wx + lane);
  const int nb0 = node0 + wid * 32, cntn = max(0, min(32, nloc - wid * 32));
  auto dot = [&](uint32_t hv, const uint16_t* w, int K2, float& y0, float& y1) {
#pragma unroll 4
    for (int k = 0; k < K2; k++) {
      const uint32_t hk = __shfl_sync(~0u, hv, k), wa = __ldg((const uint32_t*)(w + 2 * k * 64) + lane), wb = __ldg((const uint32_t*)(w + (2 * k + 1) * 64) + lane);
      y0 = fmaf(bf_lo(hk), bf_lo(wa), fmaf(bf_hi(hk), bf_lo(wb), y0)); y1 = fmaf(bf_lo(hk), bf_hi(wa), fmaf(bf_hi(hk), bf_hi(wb), y1));
    }
  };
  auto silu = [](float x) { return x / (1.f + __expf(-x)); };
#pragma unroll 1
  for (int base = 0; base < p.E; base += 32) {
    const int e = base + lane;
    const uint32_t dl = e < p.E ? (uint32_t)(__ldg(p.dst + e) - nb0) : 0xFFFFFFFFu;
    uint32_t mk = __ballot_sync(~0u, dl < (uint32_t)cntn);
    while (mk) {
      const int l = __ffs(mk) - 1; mk &= mk - 1;
      const int ee = base + l, n = __shfl_sync(~0u, dl, l), s = __ldg(p.src + ee);
      const uint16_t *po = p.pos + (size_t)(nb0 + n) * 3, *pp = p.pos + (size_t)s * 3;
      const uint32_t dxy = hsub(__ldg(po) | (__ldg(po + 1) << 16), __ldg(pp) | (__ldg(pp + 1) << 16)), dz = hsub(__ldg(po + 2), __ldg(pp + 2));
      const uint32_t sq = hsq(dxy); const float d2 = bf_lo(sq) + bf_hi(sq) + bf_lo(hsq(dz));
      float y0 = d2 * bf_lo(wdv), y1 = d2 * bf_hi(wdv);
      dot(__ldg((const uint32_t*)(p.h + (size_t)(nb0 + n) * 8) + lane), p.we, 32, y0, y1);
      dot(__ldg((const uint32_t*)(p.h + (size_t)s * 8) + lane), p.we + 64 * 64, 32, y0, y1);
      dot(__ldg((const uint32_t*)(p.ea + (size_t)ee * 2) + (lane & 7)), p.we + 129 * 64, 8, y0, y1);
      const uint32_t mm = pack_bf16(silu(y0), silu(y1));
      float c = bf_lo(mm) * bf_lo(wxv) + bf_hi(mm) * bf_hi(wxv);
#pragma unroll
      for (int o = 16; o; o >>= 1) c += __shfl_xor_sync(~0u, c, o);
      const uint32_t a = ab + n * 272;
      uint32_t x0, x1; lds64(x0, x1, a + lane * 8);
      sts64(a + lane * 8, __float_as_uint(__uint_as_float(x0) + bf_lo(mm)), __float_as_uint(__uint_as_float(x1) + bf_hi(mm)));
      if (lane < 3) { const float df = lane == 0 ? bf_lo(dxy) : lane == 1 ? bf_hi(dxy) : bf_lo(dz); sts32(a + 256 + lane * 4, __float_as_uint(fmaf(c, df, __uint_as_float(lds32(a + 256 + lane * 4))))); }
    }
  }
  __syncwarp();
#pragma unroll 1
  for (int n = 0; n < cntn; n++) {
    uint32_t x0, x1; lds64(x0, x1, ab + n * 272 + lane * 8);
    const uint32_t hv = __ldg((const uint32_t*)(p.h + (size_t)(nb0 + n) * 8) + lane);
    float y0 = 0.f, y1 = 0.f;
    dot(hv, p.wh, 32, y0, y1); dot(pack_bf16(__uint_as_float(x0), __uint_as_float(x1)), p.wh + 64 * 64, 32, y0, y1);
    ((uint32_t*)p.out)[(size_t)(nb0 + n) * 32 + lane] = u2(__hadd2(b2(hv), b2(pack_bf16(silu(y0), silu(y1)))));
    if (lane < 3) p.out[(size_t)p.N * 64 + (size_t)(nb0 + n) * 3 + lane] = (uint16_t)pack_bf16(bf_lo(__ldg(p.pos + (size_t)(nb0 + n) * 3 + lane)) + __uint_as_float(lds32(ab + n * 272 + 256 + lane * 4)), 0.f);
  }
}

__global__ void __launch_bounds__(NTHR, 1) egnn_kernel(const __grid_constant__ Params p, const __grid_constant__ Maps maps) {
  const uint64_t tmb = (uint64_t)&maps;
  extern __shared__ __align__(1024) unsigned char smraw[];
  const int tid = threadIdx.x, cta = blockIdx.x;
  const int e0 = cta * p.EPC, n4 = max(0, min(p.EPC, p.E - e0)) >> 2;
  STAMP(0);
  asm volatile("{.reg .pred p; setp.eq.u32 p, %2, 384; @p cp.async.cg.shared.global [%0], [%1], 16;}" :: "r"(sb + OFF_LEN - 192 + (tid >> 1)), "l"(p.sync), "r"(tid & 415) : "memory");
  if (tid == NWK) {
#pragma unroll
    for (int k = 0; k < NCH; k++) mbar_init(sb + BAR_DST + k * 8, 1);
    asm volatile("fence.mbarrier_init.release.cluster;" ::: "memory");
#pragma unroll 1
    for (int k = 0; k < NCH; k++) { const int nb = max(0, min(NWK, n4 - k * NWK)) * 16;
      mbar_expect(sb + BAR_DST + k * 8, nb);
      if (nb) bulk_load(sb + OFF_DST + k * NWK * 16, (const char*)(p.dst + e0) + k * NWK * 16, nb, sb + BAR_DST + k * 8); }
  }
  const int lane = tid & 31, wid = __shfl_sync(~0u, tid >> 5, 0), w = wid & 3;

  auto first_node = [&](int c) { return (int)((c * p.inv + 0xFFFFFFFFull) >> 32); };
  const int node0 = first_node(cta), nloc = min(first_node(cta + 1), p.N) - node0;
  const uint32_t ealo = (uint32_t)(uint64_t)p.ea;
  const int epad = min(e0, p.E - 1);
  auto load_h = [&](int b) { mbar_expect(sb + BAR_T + b * 8, 8192); tma_load(sb + OFF_H + b * 8192, tmb + TM_H, node0 + b * 64, sb + BAR_T + b * 8); };
  auto prefetch_e = [&](int i) {
    const uint32_t nb = (p.E / G) & ~15u;
    if (nb && i < PFN) asm volatile("cp.async.bulk.prefetch.L2.global [%0], %1;" :: "l"((const char*)p.ea + (size_t)(((i * PFS + i * PFS / 32 * (~PFS & 1)) & 31) * G + cta) * nb), "r"(nb) : "memory");
  };
  if (wid >= 12) {
    const int t = tid - 384;
    uint32_t pv[9], ev = 0;
#pragma unroll
    for (int i = 0; i < 3; i++) { const uint16_t* pp = p.pos + (size_t)(node0 + t + 128 * i) * 3;
      pv[3 * i] = pv[3 * i + 1] = pv[3 * i + 2] = 0;
      asm volatile("{.reg .pred p; setp.lt.s32 p, %4, %5;\n @p ld.global.nc.u16 %0, [%3];\n @p ld.global.nc.u16 %1, [%3+2];\n @p ld.global.nc.u16 %2, [%3+4];}"
        : "+r"(pv[3 * i]), "+r"(pv[3 * i + 1]), "+r"(pv[3 * i + 2]) : "l"(pp), "r"(t + 128 * i), "r"(p.N - node0)); }
    asm volatile("{.reg .pred p; setp.lt.u32 p, %3, 8; @p ld.global.nc.u32 %0, [%1]; @p st.global.v4.u32 [%2], {%4, %4, %4, %4};}"
      : "+r"(ev) : "l"((const uint32_t*)(p.ea + (size_t)epad * 2) + t), "l"(p.q + (size_t)(p.N + cta) * 128 + t * 16), "r"(t), "r"(0xF700F700u) : "memory");
    asm volatile("cp.async.wait_all;" ::: "memory");
    __syncwarp();
    const uint32_t e = lds32(sb + OFF_LEN + 8 + w * 16) + 1;
    {
      const uint32_t tg = (1 + e % 3) << 30, v = ((tg >> 16) + 512 + (lane & 7) * 4) * 0x10001u;
      if (t == 0) sts32(sb + OFF_MISC + 32, e);
#pragma unroll
      for (int i = 0; i < 9; i++) sts128(sb + OFF_SA + t * 16 + i * 2048, v, v + 0x10001u, v + 0x20002u, v + 0x30003u);
      bar_sync(6, NTHR);
      mbar_arrive(sb + BAR_EP, lane == 0);
#pragma unroll
      for (int i = 0; i < 17; i++) sts128(sb + OFF_SB + t * 16 + i * 2048, tg, tg, tg, tg); }
    uint32_t mp = 0;
#pragma unroll
    for (int i = 0; i < 3; i++) { sts64(sb + OFF_POS + (t + 128 * i) * 8, pv[3 * i] | (pv[3 * i + 1] << 16), pv[3 * i + 2]); mp = mag2(mag2(mp, pv[3 * i] | (pv[3 * i + 1] << 16)), pv[3 * i + 2]); }
    proxy_fence();
    __syncwarp();
    mbar_arrive(sb + BAR_PS, lane == 0);
    mbar_wait(sb + BAR_W);
#pragma unroll
    for (int i = 0; i < 8; i += 4) { uint32_t v[16];
#pragma unroll
      for (int k = 0; k < 4; k++) lds128(v + 4 * k, sb + OFF_W + t * 16 + (i + k) * 2048);
#pragma unroll
      for (int k = 0; k < 4; k++) sts128(sb + OFF_W + t * 16 + (i + k) * 2048, hhalf(v[4 * k]), hhalf(v[4 * k + 1]), hhalf(v[4 * k + 2]), hhalf(v[4 * k + 3])); }
    {
      uint32_t v[4], u[4]; const int r = t >> 3, c = t & 7;
      lds128(v, sb + OFF_WS + 128 + t * 16); lds128(u, sb + OFF_WS + c * 16);
      const uint32_t x = lds32(sb + OFF_WS + 2176 + lane * 4);
      sts128(sb + OFF_W3 + r * 128 + ((c ^ (r & 7)) << 4), b2h(v[0], .5f), b2h(v[1], .5f), b2h(v[2], .5f), b2h(v[3], .5f));
      const float s = ((r & 1) || r == 6) ? 0.f : .5f;
      if (t < 64) sts128(sb + OFF_WD + r * 128 + ((c ^ r) << 4), b2h(u[0], s), b2h(u[1], s), b2h(u[2], s), b2h(u[3], s));
      if (t < 32) sts32(sb + OFF_WX + (t & 3) * 32 + (t >> 2) * 4, b2h(x, 1.f));
      const uint32_t m3 = __reduce_max_sync(~0u, magr(mag2(mag2(mag2(mag2(0, v[0]), v[1]), v[2]), v[3]))), md = __reduce_max_sync(~0u, magr(mag2(mag2(mag2(mag2(0, u[0]), u[1]), u[2]), u[3])));
      if (wbad(m3, 0x4000) || wbad(md, 0x4000) || wbad(__reduce_max_sync(~0u, magr(mag2(0, x))), 0x4700) || magr(mp) >= 0x4200 || magr(mag2(0, ev)) >= 0x4380) sts32(sb + OFF_MISC + 8, 1);
    }
    proxy_fence();
    if (w == 1) {
#pragma unroll 1
      for (int b = HE; b < HW; b++) { mbar_wait(sb + BAR_SRC + max(0, H0 + b) * 8); if (lane == 0) load_h(b); }
    }
    bar_sync(3, 128);
    const uint32_t frag = (w * 16 + (lane & 15)) * 128 + (((lane >> 4) ^ (lane & 7)) << 4);
    uint32_t mq = 0;
#pragma unroll 1
    for (int b = 0; b < 6; b++) {
      float acc[32];
      const uint64_t da = DHI | (((sb + OFF_H) >> 4) + b * 512), db = DHI | ((sb + OFF_W) >> 4);
      const uint32_t v0 = lds16(sb + OFF_POS + b * 512 + w * 128 + lane * 2), v1 = lds16(sb + OFF_POS + 64 + b * 512 + w * 128 + lane * 2);
      mbar_wait(sb + BAR_T + b * 8);
      if (b == 0) STAMP(25);
      if (b == 5) STAMP(26);
      wg_fence();
      ss64<0>(acc, da, db); ss64<1>(acc, da + 2, db + 128); ss64<1>(acc, da + 4, db + 256); ss64<1>(acc, da + 6, db + 384);
      wg_commit();
      if (b == 0) mbar_wait(sb + BAR_AW);
      if (t == 32) { if (HALL) { if (b == 0) for (int k = HW; k < 6; k++) load_h(k); } else if (b + HW < 6) load_h(b + HW); }
      __syncwarp();
      uint32_t ff[6], fg[6];
#pragma unroll
      for (int j = 0; j < 6; j++) { ff[j] = (__byte_perm((j & 1) ? v1 : v0, 0, 0x4140) >> (3 * (j >> 1))) & 0x00070007u; fg[j] = __vsub2(0x00040004u, ff[j]);
        asm volatile("" : "+r"(ff[j]), "+r"(fg[j])); }
      wg_wait0(); fence_regs(acc);
      uint32_t o[16];
#pragma unroll
      for (int j = 0; j < 16; j++) o[j] = pack_f16(acc[2 * j], acc[2 * j + 1]);
#pragma unroll
      for (int j = 0; j < 6; j++) {
        const uint32_t m = o[j] & 0x7FFF7FFFu; mq = __vmaxu2(mq, m);
        o[j] = (__viaddmax_s16x2(m, fg[j], 0) & 0xFFF8FFF8u) | ff[j] | (o[j] & 0x80008000u); }
      if (b == 4) mbar_wait(sb + BAR_AX);
      const uint32_t qs = sb + OFF_SA + b * 8192;
#pragma unroll
      for (int j = 0; j < 4; j++) stsm4((qs + frag) ^ (j << 5), o[4 * j], o[4 * j + 1], o[4 * j + 2], o[4 * j + 3]);
      proxy_fence();
      __syncwarp();
      if (lane == 0 && b * 64 + w * 16 < nloc) tma_store(tmb + TM_Q, 0, node0 + b * 64 + w * 16, qs + w * 2048);
    }
    if (lane == 0) bulk_commit();
    { const uint32_t m = __reduce_max_sync(~0u, magr(mq)); if (lane == 0) sts32(sb + OFF_MISC + 16 + w * 4, m); }
    asm volatile("setmaxnreg.dec.sync.aligned.u32 32;");
    bulk_wait();
    bar_sync(3, 128);
    if (w == 0) {
      STAMP(18);
      uint32_t mv[4]; lds128(mv, sb + OFF_MISC + 16);
      const uint32_t mx = max(max(mv[0], mv[1]), max(mv[2], mv[3]));
      mbar_arrive(sb + BAR_QR, lane == 0);
      STAMP(19);
      if (lane == 0) {
        if (nloc > 0 && (mx >= 0x7BF0 || mx < 0x1400)) asm volatile("st.relaxed.gpu.global.u32 [%0+4], %1;" :: "l"(p.sync), "r"(e) : "memory");
        asm volatile("red.release.gpu.global.add.u32 [%0], 1;" :: "l"(p.sync) : "memory");
      }
      __syncwarp();
      uint32_t c, f; int spin = 0;
      do { asm volatile("ld.acquire.gpu.global.v2.u32 {%0, %1}, [%2];" : "=r"(c), "=r"(f) : "l"(p.sync) : "memory"); trap_if(++spin > 4000000); } while (__any_sync(~0u, (int)(c - e * G) < 0));
      if (f == e) sts32(sb + OFF_MISC + 8, 1);
      if (cta == 0 && lane == 0) asm volatile("st.relaxed.gpu.global.u32 [%0+8], %1;" :: "l"(p.sync), "r"(e) : "memory");
      STAMP(20);
      __syncwarp();
      mbar_arrive(sb + BAR_QP, lane == 0);
    }
    if (w == 2) {
      const uint32_t tg = (1 + e % 3) << 30;
      hint_wait(p.sync + 5, e * G);
      if (lane == 0) { mbar_expect(sb + BAR_HB, XPAD);
#pragma unroll 1
        for (int o = 0; o < 4; o++) bulk_load(sb + OFF_XB + o * (G * 64), (const char*)p.xb + (size_t)(cta * 4 + o) * (G * 64), G * 64, sb + BAR_HB); }
      STAMP(21);
      bar_sync(7, 384);
      sts32(sb + OFF_XB + XPAD, tg + p.N + cta);
      const uint32_t nx = __shfl_sync(~0u, lds32(sb + OFF_MISC + 8) ? 0 : lds32(sb + OFF_MISC + 4), 0);
#pragma unroll 1
      for (uint32_t k = 0; k < nx; k += 32) {
        const uint32_t i = min(k + lane, nx - 1), xr = lds32(sb + OFF_EXT + i * 4), row = (xr >> 9) & 255;
        const uint32_t v = ext_get(p.xe + (cta * G + row) * 32 + ((xr >> 17) & 31), e), x = lds32(sb + OFF_CNT + (xr & 511) * 4) + (xr >> 22) * 16;
        sts32(sb + OFF_XB + XPAD + 4 + i * 4, v); sts16(sb + OFF_TS + x, XPAD + 4 + i * 4);
        sts32(sb + OFF_TE + x * 2, mad16(v, 0x2000u, ealo - (tg >> 11) + row * p.EPC * 32));
      }
      __syncwarp();
      mbar_arrive(sb + BAR_HB, lane == 0);
    }
    if (w == 1) {
      if (PFW) mbar_wait(sb + PFW);
      __nanosleep(PF0NS);
#pragma unroll 1
      for (int i = PFE; i < PFN; i++) { if (lane == 0) prefetch_e(i); __nanosleep(PFNS); }
    }
    bar_sync(4, NTHR);
    if (t == 0) { mbar_expect(sb + BAR_U, 16384); tma_load(sb + OFF_W, tmb + TM_WH, 0, sb + BAR_U); tma_load(sb + OFF_W + 8192, tmb + TM_WH, 64, sb + BAR_U); }
    mbar_wait(sb + BAR_U);
    uint32_t mh = 0;
#pragma unroll 1
    for (int i = t; i < 512; i += 128) { uint32_t v[4]; const uint32_t a = sb + OFF_W + i * 16;
      lds128(v, a); sts128(a, hhalf(v[0]), hhalf(v[1]), hhalf(v[2]), hhalf(v[3]));
      lds128(v, a + 8192); sts128(a + 8192, b2h(v[0], .5f), b2h(v[1], .5f), b2h(v[2], .5f), b2h(v[3], .5f));
      mh = mag2(mag2(mag2(mag2(mh, v[0]), v[1]), v[2]), v[3]); }
    if (wbad(__reduce_max_sync(~0u, magr(mh)), 0x4700)) sts32(sb + OFF_MISC + 12, 1);
    proxy_fence();
    __syncwarp();
    mbar_arrive(sb + BAR_WH, lane == 0);
    if (DEFO) { if (!__shfl_sync(~0u, lds32(sb + OFF_MISC + 8), 0)) {
      mbar_wait(sb + BAR_M);
      __nanosleep(DEFO);
#pragma unroll 1
      for (int i = 0; i < 12; i++) { uint32_t v[4]; const uint32_t n = lds16(sb + OFF_GP + i * 256 + (t >> 3) * 8 + 6);
        lds128(v, sb + OFF_H + n * 128 + (((n ^ t) & 7) << 4));
        if (n < nloc) ((uint4*)p.out)[(size_t)(node0 + n) * 8 + (t & 7)] = make_uint4(v[0], v[1], v[2], v[3]);
        __nanosleep(DEFNS); }
      asm volatile("{.reg .pred p, q; setp.ne.u32 p, 0, 0; bar.red.or.pred q, 5, 512, p;}" ::: "memory"); } }
    return;
  }

  if (tid == 320) {
    mbar_init(sb + BAR_W, 1);
    asm volatile("fence.mbarrier_init.release.cluster;" ::: "memory");
    mbar_expect(sb + BAR_W, 2 * 8192 + 2304);
    tma_load(sb + OFF_W, tmb + TM_WE, 64, sb + BAR_W); tma_load(sb + OFF_W + 8192, tmb + TM_WE, 0, sb + BAR_W);
    bulk_load(sb + OFF_WS, p.we + 128 * 64, 2176, sb + BAR_W); bulk_load(sb + OFF_WS + 2176, p.wx, 128, sb + BAR_W);
  }
  if (tid == 288) {
#pragma unroll
    for (int a = BAR_SRC; a < BAR_END; a += 8) if (a != BAR_W) mbar_init(sb + a, a == BAR_WH || a == BAR_PS || a == BAR_EP ? 4 : a == BAR_XA ? 11 : a == BAR_HB ? 2 : a == BAR_M ? 12 : 1);
    asm volatile("fence.mbarrier_init.release.cluster;" ::: "memory");
    asm volatile("prefetch.tensormap [%0];" :: "l"(tmb + TM_XA)); asm volatile("prefetch.tensormap [%0];" :: "l"(tmb + TM_H));
    asm volatile("prefetch.tensormap [%0];" :: "l"(tmb + TM_XB)); asm volatile("prefetch.tensormap [%0];" :: "l"(tmb + TM_Q));
  }
  {
    if (tid < 144) { const uint32_t z = (tid >> 3) == 16 ? 0x8000u : 0u; sts128(sb + OFF_CNT + tid * 16, z, z, z, z); }
    else if (tid <= 144 + G) sts32(sb + OFF_BC + (tid - 144) * 4, ((tid - 144) & 31) * 4);
    const uint32_t sp = XPAD * 0x10001u, em = first_node(G);
    if (wid < 7) {
#pragma unroll
      for (int i = 0; i < 4; i++) sts128(sb + OFF_TS + tid * 16 + i * 3584, sp, sp, sp, sp);
    }
    static_assert(SCAP * 32 == 4 * 3584, "fill");
#pragma unroll 1
    for (int i = n4 + tid; i < 1536; i += 384) sts128(sb + OFF_DST + i * 16, em, em, em, em);
    if (tid == 321) sts128(sb + OFF_MISC, 0, 0, p.force_slow, 0);
  }
  bar_arrive(6, NTHR);
  bar_sync(0, 384);
  uint32_t ep, tag, eb0, pk[12], r0[12], r1[12], cb;
  uint2 vb[12];
  auto get_tag = [&]() { mbar_wait(sb + BAR_EP); ep = lds32(sb + OFF_MISC + 32); tag = (1 + ep % 3) << 30; eb0 = ealo - (tag >> 11); };
  if (wid == 11) {
    trap_if(sb != (uint32_t)__cvta_generic_to_shared(smraw));
#pragma unroll 1
    for (unsigned long long q = LSEQ; q; q >>= 8) { const int k = (q >> 4) & 7, nb = max(0, min(8192, n4 * 16 - k * 8192));
      mbar_wait(sb + BAR_DST + ((uint32_t)q & 7) * 8);
      if (lane == 0) {
        if (k >= 3) load_h(k - 3);
        else { mbar_expect(sb + BAR_SRC + k * 8, nb);
          if (nb) bulk_load(sb + OFF_SRCI + k * 8192, (const char*)(p.src + e0) + k * 8192, nb, sb + BAR_SRC + k * 8); } } }
    get_tag();
    mbar_wait(sb + BAR_PS);
    bar_sync(12, 384);
    uint32_t xm = 0;
#pragma unroll
    for (int k = 0; k < 5; k++) xm |= (lds32(sb + OFF_BC + min(lane + 32 * k, G - 1) * 4) >= (65 << 9) && lane + 32 * k < G) << k;
    auto ext_send = [&](int pl) {
      uint32_t x = xm;
      for (uint32_t m; (m = __ballot_sync(~0u, x));) {
        const uint32_t l = __ffs(m) - 1, j = l + 32 * (__ffs(__shfl_sync(~0u, x, l)) - 1);
        if (lane == l) x &= x - 1;
        const uint32_t e = min(lds16(sb + OFF_AX + j * 128 + ((4 * l + 2 * lane) & 126)), 6143u);
        if (pl) st_ext(p.xe + (j * G + cta) * 32 + lane, lds32(sb + OFF_SRCI + e * 4) + tag + (e << 16), ep);
        else { const uint32_t cn = lds32(sb + OFF_BC + j * 4) >> 9, v = cn > 96 ? 1 : lane + 64 < cn ? 512 | (lds32(sb + OFF_DST + e * 4) & 511) : 0;
          asm volatile("red.shared.xor.b32 [%0], %1;" :: "r"(sb + OFF_SA + j * 128 + ((l + lane) & 31) * 4), "r"(((v & 63) << 10) | ((v >> 6) << 26)) : "memory"); }
      }
    };
    if (__any_sync(~0u, xm)) { ext_send(0); proxy_fence(); __syncwarp(); }
    if (lane == 0) { tma_store_ef(tmb + TM_XA, cta * 64, 0, sb + OFF_SA); bulk_commit(); mbar_arrive(sb + BAR_AI); bulk_wait(); hint_signal(p.sync + 4); mbar_arrive(sb + BAR_AW); STAMP(16); }
    __syncwarp();
    bar_sync(13, 384);
    if (!B_HOLD && lane == 0) { tma_store_ef(tmb + TM_XB, cta * 64, 0, sb + OFF_SB); bulk_commit(); }
    __syncwarp();
    ext_send(1);
    mbar_arrive(sb + BAR_AX, lane == 0);
    if (B_HOLD) mbar_wait(sb + (B_HOLD == 1 ? BAR_HA : BAR_XA));
    if (lane == 0) {
      bulk_wait();
#pragma unroll 1
      for (int r = B_HOLD ? 0 : BROWS; r < G; r += BROWS) { tma_store_ef(tmb + TM_XB, cta * 64, r, sb + OFF_SB + r * 256); bulk_commit(); bulk_wait(); }
      hint_signal(p.sync + 5);
#pragma unroll 1
      for (int i = 0; i < PFE; i++) prefetch_e(i);
      STAMP(17);
    }
    __syncwarp();
  } else {
    STAMP(15);
    {
      uint32_t d[4 * NCH], jj[4 * NCH], rr[4 * NCH];
      auto count = [&](int k) {
        mbar_wait(sb + BAR_DST + k * 8);
        lds128(d + 4 * k, sb + OFF_DST + (tid + NWK * k) * 16);
#pragma unroll
        for (int i = 4 * k; i < 4 * k + 4; i++) { jj[i] = d[i] * p.magic; rr[i] = atoms_add(__dp4a(jj[i], 0x04000000u, sb + OFF_BC), 0x202u); }
      };
      auto place = [&](int k) {
#pragma unroll
        for (int i = 4 * k; i < 4 * k + 4; i++) {
          const uint32_t o = __dp4a(jj[i], 0x80000000u, rr[i] & 0x807Eu);
          d[i] = (d[i] & 511) | (tag >> 16);
          asm("{.reg .pred p; setp.ge.u32 p, %1, 0x8000; @p add.u32 %0, %2, %3;}" : "+r"(d[i]) : "r"(o), "r"(tid * 4), "r"(NWK * k * 4 + (i & 3)));
          sts16(sb + OFF_SA + o, d[i]); jj[i] = __viaddmin_u32(o, o, G * 256);
        }
      };
      count(0); STAMP(1); count(1); get_tag(); place(0); count(2); place(1); count(3); place(2);
      if (wid < 4) { count(4); place(3); place(4); } else place(3);
      proxy_fence();
      bar_arrive(12, 384);
      STAMP(2);
      mbar_wait(sb + BAR_AI);
      mbar_wait(sb + BAR_SRC); mbar_wait(sb + BAR_SRC + 8); mbar_wait(sb + BAR_SRC + 16);
      STAMP(12);
#pragma unroll
      for (int k = 0; k < NCH; k++) lds128(d + 4 * k, sb + OFF_SRCI + (tid + NWK * k) * 16);
      const uint32_t tb = tag + (tid << 18);
#pragma unroll
      for (int i = 0; i < 4 * NCH; i++) if (i < 4 * NCH - 4 || wid < 4) sts32(sb + OFF_SB + jj[i], d[i] + tb + ((NWK * (i >> 2) * 4 + (i & 3)) << 16));
      proxy_fence();
      bar_arrive(13, 384);
      STAMP(3);
    }
    const uint32_t rot = (lane + cta) & 31;
    cb = sb + OFF_CNT - (tag >> 14);
    {
      const uint32_t* xa = (const uint32_t*)(p.xa + (cta * G + wid) * 8) + rot;
      if (wid < 8) { const uint32_t e_ = ealo + epad * 32;
        mbar_wait(sb + BAR_AX);
#pragma unroll
        for (int i = 0; i < 7; i++) sts128(sb + OFF_TE + tid * 16 + i * 4096, e_, e_, e_, e_); }
      static_assert(SCAP * 64 == 7 * 4096, "fill");
      if (wid == 10) { hint_wait(p.sync + 4, ep * G); mbar_arrive(sb + BAR_HA, lane == 0); }
      mbar_wait(sb + BAR_HA);
      STAMP(14);
      const uint32_t tp = tag | (tag >> 16);
      uint32_t st;
#pragma unroll 1
      for (int spin = 0;; spin++) {
        st = 0;
#pragma unroll
        for (int k = 0; k < 12; k++) asm volatile("ld.relaxed.gpu.global.u32 %0, [%1];" : "=r"(pk[k]) : "l"(xa + k * 352) : "memory");
#pragma unroll
        for (int k = 0; k < 12; k++) st |= pk[k] ^ tp;
        st = __reduce_or_sync(~0u, st);
        if (!(st >> 30)) break;
        trap_if(spin > 2000000);
      }
      if (st & 0x3C00FC00u) {
#pragma unroll 1
        for (;;) {
          uint32_t x = 0, row = 0;
#pragma unroll
          for (int k = 0; k < 12; k++) { const uint32_t y = (pk[k] ^ tp) & 0x3C00FC00u; if (!x && y) { x = y; row = wid + 11 * k; pk[k] ^= y; } }
          if (!__any_sync(~0u, x)) break;
          const uint32_t n = ((x >> 10) & 63) | ((x >> 20) & 0x1C0);
          if (x >> 29) {
            const uint32_t r = atoms_add(sb + OFF_CNT + n * 4, 16), idx = atoms_add(sb + OFF_MISC + 4, 1);
            if (idx < 256) sts32(sb + OFF_EXT + idx * 4, n | (row << 9) | (lane << 17) | (min(r >> 4, 255u) << 22));
            else x = 1;
          }
          if (x && !(x >> 29)) sts32(sb + OFF_MISC + 8, 1);
          __syncwarp();
        }
      }
#pragma unroll
      for (int k = 0; k < 12; k++) { r0[k] = mad16(pk[k], 0x0004u, cb); r1[k] = mad16(pk[k], 0x0400u, cb); vb[k].x = atoms_add(r0[k], 16); vb[k].y = atoms_add(r1[k], 16); }
      if (B_HOLD == 2) mbar_arrive(sb + BAR_XA, lane == 0);
    }
    STAMP(4);
    if (wid >= 6) bar_arrive(11, NWK);
    if (wid < 6) {
      uint32_t ca[2], ky[2], dr[2], sq[2], ps[4];
#pragma unroll
      for (int i = 0; i < 2; i++) { ca[i] = sb + OFF_CNT + ((node0 + tid + 192 * i) & 511) * 4; lds64(ps[2 * i], ps[2 * i + 1], sb + OFF_POS + (tid + 192 * i) * 8); ps[2 * i + 1] |= (tid + 192 * i) << 16; }
      bar_sync(11, NWK);
      STAMP(5);
#pragma unroll
      for (int i = 0; i < 2; i++) ky[i] = (lds32(ca[i]) + 16) >> 5;
      if (max(ky[0], ky[1]) > 31) sts32(sb + OFF_MISC + 8, 1);
#pragma unroll
      for (int i = 0; i < 2; i++) { ky[i] = min(ky[i], 31u); dr[i] = atoms_add(sb + OFF_DH + ky[i] * 4, 1); }
      bar_sync(10, 192);
      const uint32_t hv = lds32(sb + OFF_DH + lane * 4);
      uint32_t inc = hv;
#pragma unroll
      for (int o = 1; o < 32; o <<= 1) asm("{.reg .pred p; .reg .b32 y; shfl.sync.down.b32 y|p, %0, %1, 31, -1; @p add.u32 %0, %0, y;}" : "+r"(inc) : "r"(o));
#pragma unroll
      for (int i = 0; i < 2; i++) {
        const uint32_t pos = __shfl_sync(~0u, inc - hv, ky[i]) + dr[i];
        const uint32_t ak = (uint32_t)(QCODE >> ((pos >> 5) * 4)) & 15, l = (pos >> 3) & 3;
        sq[i] = (ak >> 2) * 16 + ((QREV >> (pos >> 5) & 1) ? 3 - l : l) * 4 + (ak & 3);
        dr[i] = pos & 7;
        asm volatile("{.reg .pred p; setp.eq.u32 p, %2, 0; @p st.shared.u8 [%0], %1;}" :: "r"(sb + OFF_LEN + sq[i]), "r"(max(ky[i], 1u)), "r"(dr[i]) : "memory");
        sts64(sb + OFF_GP + sq[i] * 64 + dr[i] * 8, ps[2 * i], ps[2 * i + 1]);
      }
      bar_sync(10, 192);
      const uint32_t ln = lds32(sb + OFF_LEN + min(lane, 11) * 4), tot = __dp4a(ln, 0x01010101u, 0u);
      inc = tot;
#pragma unroll
      for (int o = 1; o < 16; o <<= 1) asm("{.reg .pred p; .reg .b32 y; shfl.sync.up.b32 y|p, %0, %1, 0, -1; @p add.u32 %0, %0, y;}" : "+r"(inc) : "r"(o));
      if (wid == 1) sts32(sb + OFF_CNT + 2048 + lane * 4, 0);
      if (tid < 12) { sts32(sb + OFF_LEN + 64 + tid * 4, inc - tot); if (inc > SCAP) sts32(sb + OFF_MISC + 8, 1); }
#pragma unroll
      for (int i = 0; i < 2; i++) sts32(ca[i], __dp4a(__shfl_sync(~0u, ln, sq[i] >> 2), 0x00010101u >> (24 - 8 * (sq[i] & 3)), __shfl_sync(~0u, inc - tot, sq[i] >> 2)) * 32 + dr[i] * 2);
    }
    bar_arrive(7, 384);
  }
  bar_sync(1, 384);
  STAMP(6);
  if (wid != 11 && !__shfl_sync(~0u, lds32(sb + OFF_MISC + 8), 0)) {
#pragma unroll
    for (int k = 0; k < 12; k++) { r0[k] = lds32(r0[k]); r1[k] = lds32(r1[k]); }
    const uint32_t id = wid * 256 + ((lane + cta) & 31) * 8;
    auto put = [&](uint32_t x, uint32_t v) { asm volatile("{.reg .pred p; setp.lt.u32 p, %0, 0x8000; @p st.shared.u16 [%0+%2], %1;}" :: "r"(x), "h"((uint16_t)v), "n"(sb + OFF_TS) : "memory"); };
#pragma unroll
    for (int k = 0; k < 12; k++) { put(r0[k] + vb[k].x, id + k * 2816); put(r1[k] + vb[k].y, id + k * 2816 + 4); }
  }
  STAMP(7);
  mbar_wait(sb + BAR_QR);
  asm volatile("setmaxnreg.inc.sync.aligned.u32 160;");
  uint32_t pa[8], sp[8], pq[16]; float chk = 0.f;
  {
    uint32_t hf[32], mp = 0; float a0[32], a1[32];
    const uint32_t an = sb + OFF_GP + wid * 256 + (lane & 15) * 8 + 6, n0 = lds16(an), n1 = lds16(an + 128);
#pragma unroll
    for (int j = 0; j < 8; j++) { const uint32_t nd = j < 4 ? n0 : n1; ldsm4(hf + 4 * j, (sb + OFF_H + nd * 128 + (((nd & 7) << 4) ^ (lane & 16))) ^ ((j & 3) << 5)); }
    const uint64_t db = DHI | ((sb + OFF_W + 8192) >> 4);
    wg_fence();
    rs64b<0>(a0, hf[0], hf[1], hf[2], hf[3], db); rs64b<1>(a0, hf[4], hf[5], hf[6], hf[7], db + 128); rs64b<1>(a0, hf[8], hf[9], hf[10], hf[11], db + 256); rs64b<1>(a0, hf[12], hf[13], hf[14], hf[15], db + 384);
    wg_commit();
    rs64b<0>(a1, hf[16], hf[17], hf[18], hf[19], db); rs64b<1>(a1, hf[20], hf[21], hf[22], hf[23], db + 128); rs64b<1>(a1, hf[24], hf[25], hf[26], hf[27], db + 256); rs64b<1>(a1, hf[28], hf[29], hf[30], hf[31], db + 384);
    wg_commit();
    asm volatile("wgmma.wait_group.sync.aligned 1;" ::: "memory"); fence_regs(a0);
#pragma unroll
    for (int j = 0; j < 8; j++) { const uint32_t x = pack_f16(a0[4 * j], a0[4 * j + 1]), y = pack_f16(a0[4 * j + 2], a0[4 * j + 3]); mp = hmag(hmag(mp, x), y);
      asm volatile("movmatrix.sync.aligned.m8n8.trans.b16 %0, %1;" : "=r"(pa[j]) : "r"(x)); asm volatile("movmatrix.sync.aligned.m8n8.trans.b16 %0, %1;" : "=r"(sp[j]) : "r"(y)); }
    wg_wait0(); fence_regs(a1);
    bar_arrive(4, NTHR);
#pragma unroll
    for (int j = 0; j < 16; j++) { pq[j] = pack_f16(a1[2 * j], a1[2 * j + 1]); mp = hmag(mp, pq[j]); }
    if (magr(mp) >= 0x7000) chk = __int_as_float(0x7FC00000);
  }
  if (wid == 0) STAMP(23);
  uint32_t bad;
  {
    const uint32_t ring = sb + OFF_RING + wid * STG, p2 = sb + OFF_P2 + wid * 2048;
    uint32_t lens = __shfl_sync(~0u, lds32(sb + OFF_LEN + wid * 4), 0);
    uint32_t rem = __dp4a(lens, 0x20202020u, 0u);
    const uint32_t base = min(lds32(sb + OFF_LEN + 64 + wid * 4), SCAP);
    uint32_t a_s = sb + OFF_TS + base * 32 + (lane >> 3) * 8, a_e = sb + OFF_TE + base * 64 + (lane >> 1) * 4;
    uint32_t k0 = (uint32_t)(uint64_t)p.q + (((lane & 7) ^ ((lane >> 1) & 4)) << 4), k1 = k0 ^ 16, k2 = k0 ^ 32, k3 = k0 ^ 48, ke = ((lane ^ (lane >> 3)) & 1) << 4;
    uint32_t dst0 = ring + (lane >> 3) * 640 + (lane & 7) * 16;
    const uint32_t qhi = (uint32_t)((uint64_t)p.q >> 32), ehi = (uint32_t)((uint64_t)p.ea >> 32);
    uint32_t s0, s1, ev, to = 0, so = 12 * STG;
    auto tl_ = [&]() { lds64(s0, s1, a_s + to); asm volatile("ld.shared.u32 %0, [%1]; add.u32 %1, %1, 64;" : "=&r"(ev), "+r"(a_e) :: "memory"); to += 32; };
#define CPQ(LH, x, k, off) "dp2a." LH ".u32.u32 lo, " x ", 0x80000080, " k "; mov.b64 a, {lo, %7}; @p cp.async.cg.shared.global [%0+" #off "], [a], 16;\n"
#define CPE "or.b32 lo, %10, %11; mov.b64 a, {lo, %12}; @p cp.async.cg.shared.global" ESZ " [%0+512], [a], 16;\n"
#define CPA(BODY) asm volatile("{.reg .b32 lo; .reg .b64 a; .reg .pred p; setp.le.u32 p, %8, %9;\n" BODY "}" \
      :: "r"(dst0 + so), "r"(s0), "r"(s1), "r"(k0), "r"(k1), "r"(k2), "r"(k3), "r"(qhi), "r"(to), "r"(rem), "r"(ev), "r"(ke), "r"(ehi) : "memory")
#define CPQ4 CPQ("lo", "%1", "%3", 0) CPQ("hi", "%1", "%4", 128) CPQ("lo", "%2", "%5", 256) CPQ("hi", "%2", "%6", 384) "cp.async.commit_group;"
    auto issue = [&]() { CPA(CPE CPQ4); so = so == (NST - 1) * 12 * STG ? 0 : so + 12 * STG; };
    const int g = lane >> 2, qd = lane & 3;
    const uint32_t sw = ((lane >> 4) ^ (lane & 7)) << 4, fr = (lane & 15) * 128 + sw;
    uint32_t qa0 = ring + (g & 3) * 640 + qd * 128 + sw, qa1 = qa0 ^ 32, qa2 = qa0 ^ 64, qa3 = qa0 ^ 96;
    uint32_t eadr = ring + 512 + (g & 3) * 640 + qd * 32 + ((((lane >> 4) ^ g) & 1) << 4);
    uint32_t oh0 = g == 2 * qd ? 0x3C00u : g == 2 * qd + 1 ? 0x3C000000u : 0u, oh1 = oh0;
    uint32_t a_g = sb + OFF_GP + wid * 256 + lane * 2;
    uint32_t a_n = sb + OFF_GP + wid * 256 + (lane & 15) * 8 + 6;
    uint32_t a_p = ((lane & 8) ? p2 : sb + OFF_WD) + (lane & 7) * 128 + ((((lane >> 4) ^ lane) & 7) << 4);
    uint32_t a_w = sb + OFF_W3 + fr;
#define OPQ4(A, B, C, D) asm volatile("shfl.sync.bfly.b32 %0, %0, 0, 31, -1; shfl.sync.bfly.b32 %1, %1, 0, 31, -1; shfl.sync.bfly.b32 %2, %2, 0, 31, -1; shfl.sync.bfly.b32 %3, %3, 0, 31, -1;" : "+r"(A), "+r"(B), "+r"(C), "+r"(D))
    asm volatile("shfl.sync.idx.b32 %0, %0, %1, 31, -1;" : "+r"(oh1) : "r"(lane));
    if (OPQ & 1) OPQ4(a_w, oh0, ke, dst0);
    if (OPQ & 2) OPQ4(qa0, qa1, qa2, qa3);
    if (OPQ & 4) OPQ4(k0, k1, k2, k3);
    if (OPQ & 8) OPQ4(a_g, a_n, a_p, eadr);
    uint32_t w3[16], wv[8], bp[16], sum[8], Y[16], M[16], own, ownp, dpk; uint16_t tl[16], th[16];
    float pacc = 0.f;
    auto wload = [&]() {
#pragma unroll
      for (int j = 0; j < 4; j++) ldsm4t(w3 + 4 * j, a_w ^ (j << 5));
      lds128(wv, sb + OFF_WX + (a_g & 6) * 16); lds128(wv + 4, sb + OFF_WX + 16 + (a_g & 6) * 16);
    };
    auto hload = [&](uint32_t (&hf)[16], uint32_t nd) {
      const uint32_t hrow = sb + OFF_H + nd * 128 + (((nd & 7) << 4) ^ ((a_g >> 1) & 16));
#pragma unroll
      for (int j = 0; j < 4; j++) ldsm4(hf + 4 * j, hrow ^ (j << 5));
      return hrow;
    };
    auto bload = [&](uint32_t o) {
#pragma unroll
      for (int j = 0; j < 4; j++) ldsm4t(bp + 4 * j, (a_p ^ (j << 5)) + o);
    };
    { uint32_t wd[8]; const uint32_t a = sb + OFF_WD + (lane & 7) * 128 + ((((lane >> 3) ^ lane) & 7) << 4);
      ldsm4t(wd, a); ldsm4t(wd + 4, a ^ 64);
#pragma unroll
      for (int j = 0; j < 8; j++) { bp[2 * j] = wd[j]; bp[2 * j + 1] = pa[j]; } }
    own = lds16(a_g) * 0x10001u;
    wload();
    if (__shfl_sync(~0u, lds32(sb + OFF_MISC + 8), 0)) rem = 0;
    auto resolve = [&](auto NBK, uint32_t o) {
      constexpr int NB = decltype(NBK)::value;
      uint32_t id[NB], c0[NB], c1[NB]; const uint32_t a = base * 32 + o + lane * 4;
#pragma unroll
      for (int i = 0; i < NB; i++) { id[i] = lds32(sb + OFF_TS + a + i * 128); if (o + lane * 4 + i * 128 >= rem) id[i] = XPAD * 0x10001u; }
      uint32_t st = 0;
#pragma unroll
      for (int i = 0; i < NB; i++) { c0[i] = lds32(sb + OFF_XB + (id[i] & 0xFFFF)); c1[i] = lds32(sb + OFF_XB + (id[i] >> 16)); }
#pragma unroll
      for (int i = 0; i < NB; i++) st |= (c0[i] ^ tag) | (c1[i] ^ tag);
      for (int spin = 0; __any_sync(~0u, st >> 30); spin++) {
        st = 0; trap_if(spin > 2000000);
#pragma unroll
        for (int i = 0; i < NB; i++) {
          asm volatile("{.reg .pred p, q; setp.lt.u32 p, %4, %6; setp.lt.u32 q, %5, %6; @p ld.relaxed.gpu.global.u32 %0, [%2]; @q ld.relaxed.gpu.global.u32 %1, [%3];}"
            : "+r"(c0[i]), "+r"(c1[i]) : "l"((const char*)p.xb + cta * XPAD + (id[i] & 0xFFFF)), "l"((const char*)p.xb + cta * XPAD + (id[i] >> 16)), "r"(id[i] & 0xFFFF), "r"(id[i] >> 16), "n"(XPAD) : "memory");
          st |= (c0[i] ^ tag) | (c1[i] ^ tag); }
      }
#pragma unroll
      for (int i = 0; i < NB; i++) { const uint32_t j0 = (id[i] >> 8) & 255, j1 = id[i] >> 24;
        if (ABL & 2) { c0[i] &= 0xFFFF0FFFu; c1[i] &= 0xFFFF0FFFu; }
        asm volatile("{.reg .pred p, q, r; setp.lt.u32 p, %5, %9; setp.lt.u32 q, %6, %9; setp.lt.u32 r, %7, %8;\n"
          "@p st.shared.u32 [%0], %2; @q st.shared.u32 [%0+4], %3; @r st.shared.u32 [%1], %4;}"
          :: "r"(sb + OFF_TE + 2 * a + i * 256), "r"(sb + OFF_TS + a + i * 128), "r"(mad16(c0[i], 0x2000u, eb0 + ((ABL & 1) ? j0 & 7 : j0) * p.EPC * 32)), "r"(mad16(c1[i], 0x2000u, eb0 + ((ABL & 1) ? j1 & 7 : j1) * p.EPC * 32)),
             "r"(__byte_perm(c0[i], c1[i], 0x5410)), "r"(j0), "r"(j1), "r"(o + lane * 4 + i * 128), "r"(rem), "n"(G) : "memory"); }
    };
    bar_sync(2, 384);
    if (wid == 0) STAMP(27);
    mbar_wait(sb + BAR_HB);
    if (wid == 0) STAMP(22);
#pragma unroll 1
    for (uint32_t o = 0, go = 0; go < 32 * NST; o += 128 * RNB) {
      if (o < rem) { resolve(IC<RNB>(), o);
        asm volatile("{.reg .pred p; mbarrier.test_wait.parity.shared::cta.b64 p, [%1], 0; vote.sync.all.pred p, p, -1; selp.u32 %0, %2, 0, p;}" : "=r"(go) : "r"(sb + BAR_QP), "n"(32 * NEARLY) : "memory"); }
      else { bar_sync(8, 384); mbar_wait(sb + BAR_QP); go = 32 * NST; if (wid == 0) STAMP(24); }
      __syncwarp();
#pragma unroll 1
      while (to < go) { tl_(); issue(); if (to == 32) STAMP(13); }
    }
    bad = __shfl_sync(~0u, lds32(sb + OFF_MISC + 8), 0);
   if (!bad) {
#pragma unroll
    for (int j = 0; j < 4; j++) stsm4((p2 + fr) ^ (j << 5), pq[4 * j], pq[4 * j + 1], pq[4 * j + 2], pq[4 * j + 3]);
    auto body = [&](auto MODE) {
      constexpr int mode = decltype(MODE)::value;
      uint32_t T[16], ef[4], q0, q1, x0, x1, x2; float e0_, e1_, cs[4];
      auto mu = [&](int j) {
#pragma unroll
        for (int i = 2 * j; i < 2 * j + 2; i++) asm volatile("{.reg .b16 l, h; mov.b32 {l, h}, %2; tanh.approx.f16 %0, l; tanh.approx.f16 %1, h;}" : "=h"(tl[i]), "=h"(th[i]) : "r"(Y[i])); };
      auto fi = [&](int j) {
#pragma unroll
        for (int i = 2 * j; i < 2 * j + 2; i++) asm volatile("{.reg .b32 t; mov.b32 t, {%2, %3}; fma.rn.f16x2 %0, %1, t, %1;}" : "=r"(M[i]) : "r"(Y[i]), "h"(tl[i]), "h"(th[i])); };
      auto ad = [&](int j) { asm volatile("add.rn.f16x2 %0, %0, %1; add.rn.f16x2 %0, %0, %2;" : "+r"(sum[j]) : "r"(M[2 * j]), "r"(M[2 * j + 1])); };
      auto he = [&](int j) { asm volatile("mma.sync.aligned.m16n8k16.row.col.f16.f16.f16.f16 {%0,%1}, {%2,%3,%4,%5}, {%6,%7}, {%0,%1};" : "+r"(T[2 * j]), "+r"(T[2 * j + 1]) : "r"(ef[0]), "r"(ef[1]), "r"(ef[2]), "r"(ef[3]), "r"(w3[2 * j]), "r"(w3[2 * j + 1])); };
      auto hs = [&](int j) { asm volatile("mma.sync.aligned.m16n8k16.row.col.f16.f16.f16.f16 {%0,%1}, {%2,%3,%4,%5}, {%6,%7}, {%8,%9};" : "=r"(Y[2 * j]), "=r"(Y[2 * j + 1]) : "r"(q0), "r"(q1), "r"(oh0), "r"(oh1), "r"(bp[2 * j]), "r"(bp[2 * j + 1]), "r"(T[2 * j]), "r"(T[2 * j + 1])); };
      auto hc = [&](int j) {
        if (j) asm volatile("mma.sync.aligned.m16n8k16.row.col.f32.f16.f16.f32 {%0,%1,%2,%3}, {%4,%5,%6,%7}, {%8,%9}, {%0,%1,%2,%3};" : "+f"(cs[0]), "+f"(cs[1]), "+f"(cs[2]), "+f"(cs[3]) : "r"(M[4 * j]), "r"(M[4 * j + 1]), "r"(M[4 * j + 2]), "r"(M[4 * j + 3]), "r"(wv[2 * j]), "r"(wv[2 * j + 1]));
        else asm volatile("mma.sync.aligned.m16n8k16.row.col.f32.f16.f16.f32 {%0,%1,%2,%3}, {%4,%5,%6,%7}, {%8,%9}, {%10,%10,%10,%10};" : "=f"(cs[0]), "=f"(cs[1]), "=f"(cs[2]), "=f"(cs[3]) : "r"(M[0]), "r"(M[1]), "r"(M[2]), "r"(M[3]), "r"(wv[0]), "r"(wv[1]), "f"(0.f)); };
      auto cv = [&](int i) { asm volatile("{.reg .b32 a, b; shl.b32 a, %0, 16; and.b32 b, %0, 0xFFFF0000; cvt.rn.f16x2.f32 %0, b, a;}" : "+r"(ef[i])); };
      auto un = [&]() { asm volatile("shl.b32 %0, %2, 16; and.b32 %1, %2, 0xFFFF0000;" : "=&f"(e0_), "=&f"(e1_) : "r"(dpk)); };
      auto ex0 = [&]() { asm volatile("prmt.b32 %0, %3, %4, 0x6420; prmt.b32 %1, %5, %6, 0x6420; prmt.b32 %2, %7, %8, 0x6420;" : "=&r"(x0), "=&r"(x1), "=&r"(x2) : "r"(T[0]), "r"(T[1]), "r"(T[2]), "r"(T[3]), "r"(T[4]), "r"(T[5])); };
      auto ex1 = [&]() { asm volatile("{.reg .b32 a, b; shl.b32 a, %2, 3; shl.b32 b, %3, 6; lop3.b32 a, %1, a, 0x38383838, 0xD8; lop3.b32 a, a, b, 0xC0C0C0C0, 0xD8; sub.rn.bf16x2 %0, %4, a;}" : "=r"(dpk) : "r"(x0), "r"(x1), "r"(x2), "r"(own)); };
      auto ex2 = [&]() { asm volatile("{.reg .b32 a, b, d, u; .reg .b16 l, h; shl.b32 a, %2, 16; and.b32 b, %2, 0xFFFF0000; cvt.rn.f16x2.f32 d, b, a; mul.rn.f16x2 %0, d, d; mov.b32 {l, h}, d; mov.b32 u, {h, h}; mul.rn.f16x2 %1, u, u;}" : "=&r"(q0), "=&r"(q1) : "r"(dpk)); };
      auto pf = [&]() { asm volatile("fma.rn.f32 %0, %1, %2, %0; fma.rn.f32 %0, %3, %4, %0;" : "+f"(pacc) : "f"(cs[0]), "f"(e0_), "f"(cs[2]), "f"(e1_)); };
#define FX(k) if (FM >> k & 1) asm volatile("pmevent 1;" ::: "memory")
      if (mode == 2) {
        hc(0); mu(3); fi(2); un(); ad(0); ad(1); mu(4); fi(3); hc(1); mu(5); fi(4); ad(2); mu(6); fi(5); ad(3); hc(2); mu(7); fi(6); fi(7); ad(4); ad(5); hc(3); ad(6); ad(7); pf();
        return;
      }
      asm volatile("cp.async.wait_group %0;" :: "n"(NST - 1) : "memory");
      __syncwarp();
      if (mode == 1) STAMP(8);
      ldsm4(ef, eadr + so); ldsm4(T, qa0 + so); ldsm4(T + 4, qa1 + so); ldsm4(T + 8, qa2 + so); ldsm4(T + 12, qa3 + so);
      tl_();
      if (mode == 1) {
        issue();
        cv(0); cv(1); cv(2); cv(3); ex0(); ex1(); ex2();
#pragma unroll
        for (int j = 0; j < 8; j++) { he(j); hs(j); }
        mu(0); mu(1); fi(0); mu(2); fi(1);
        return;
      }
      hc(0); mu(3); fi(2); un(); ad(0); ad(1);
      FX(0);
      mu(4); fi(3); cv(0); cv(1); cv(2); cv(3); ex0(); ex1();
      FX(1);
      he(0); he(1); hc(1); mu(5); fi(4); ex2(); ad(2);
      FX(2);
      hs(0); he(2); mu(6); fi(5); issue(); ad(3);
      FX(3);
      hs(1); he(3); hc(2); mu(7); fi(6);
      FX(4);
      hs(2); hs(3); he(4); he(5); mu(0); fi(7); ad(4); ad(5);
      FX(5);
      hc(3); hs(4); he(6); he(7); mu(1); fi(0); ad(6);
      FX(6);
      hs(5); hs(6); hs(7); mu(2); fi(1); ad(7); pf();
      FX(7);
    };
#pragma unroll
    for (int j = 0; j < 8; j++) sum[j] = 0;
    body(IC<1>());
    int cnt = (lens & 255) - 1;
#pragma unroll 1
    for (int t = 0; t < 8; t++) {
#pragma unroll 1
      for (; cnt > 0; cnt--) { body(IC<0>());
      }
      if (!(t & 1)) {
        ownp = own;
        if (t < 6) {
          a_g += 64; own = lds16(a_g) * 0x10001u;
          if (t == 0) {
#pragma unroll
            for (int j = 0; j < 8; j++) bp[2 * j + 1] = sp[j];
          } else bload((a_g & 16) ? (t & 4) * 256 : 0);
          lens >>= 8; cnt = 1;
          continue;
        }
        body(IC<2>()); t++;
        STAMP(9);
      }
      cnt = (lens & 255) - 1;
      { const uint32_t ng = __shfl_sync(~0u, ownp, (a_g >> 1) | 3) >> 16, c3 = (a_g >> 1) & 3;
        asm volatile("{.reg .pred p; setp.lt.u32 p, %2, %3; @p st.global.u16 [%0], %1;}" :: "l"(p.out + (size_t)p.N * 64 + (size_t)node0 * 3 + (ng * 3 + c3)), "h"((uint16_t)pack_bf16(bf_hi(ownp) + pacc, 0.f)), "r"(ng), "r"(c3 < 3 ? nloc : 0) : "memory"); }
      chk = fmaf(pacc, 0.f, chk); pacc = 0.f;
      if (t & 2) {
        uint32_t hf[16]; float acc[32];
        const uint32_t nd = lds16(a_n); a_n += 128;
        const uint32_t hrow = hload(hf, nd);
        const uint64_t b1 = DHI | ((sb + OFF_W) >> 4), b2_ = b1 + 512;
        mbar_wait(sb + BAR_WH);
        wg_fence();
        rs64h<0>(acc, sp[0], sum[0], sp[1], sum[1], b2_); rs64h<1>(acc, sp[2], sum[2], sp[3], sum[3], b2_ + 128); rs64h<1>(acc, sp[4], sum[4], sp[5], sum[5], b2_ + 256); rs64h<1>(acc, sp[6], sum[6], sp[7], sum[7], b2_ + 384);
        rs64b<1>(acc, hf[0], hf[1], hf[2], hf[3], b1); rs64b<1>(acc, hf[4], hf[5], hf[6], hf[7], b1 + 128); rs64b<1>(acc, hf[8], hf[9], hf[10], hf[11], b1 + 256); rs64b<1>(acc, hf[12], hf[13], hf[14], hf[15], b1 + 384);
        wg_commit(); wg_wait0(); fence_regs(acc);
        if (t == 7) STAMP(10);
        chk = fmaf(acc[0], 0.f, fmaf(acc[2], 0.f, chk));
        auto fin = [&](uint32_t x, float y0, float y1) { return u2(__hadd2(b2(x), b2(pack_bf16(silu_h(y0), silu_h(y1))))); };
#pragma unroll
        for (int j = 0; j < 4; j++) stsm4(hrow ^ (j << 5), fin(hf[4 * j], acc[8 * j], acc[8 * j + 1]), fin(hf[4 * j + 1], acc[8 * j + 2], acc[8 * j + 3]), fin(hf[4 * j + 2], acc[8 * j + 4], acc[8 * j + 5]), fin(hf[4 * j + 3], acc[8 * j + 6], acc[8 * j + 7]));
        __syncwarp();
        const uint32_t c8 = (a_g << 3) & 0x70;
        if (DEFO && t == 3) mbar_arrive(sb + BAR_M, (a_g & 62) == 0);
        else
#pragma unroll
        for (int j = 0; j < 4; j++) { uint32_t v[4]; const uint32_t n = __shfl_sync(~0u, nd, 4 * j + ((a_g >> 4) & 3)); lds128(v, sb + OFF_H + n * 128 + (((n << 4) ^ c8) & 0x70));
          asm volatile("{.reg .pred p; setp.lt.u32 p, %5, %6; @p st.global" OCS ".v4.b32 [%0], {%1,%2,%3,%4};}" :: "l"((const char*)p.out + (size_t)node0 * 128 + (n * 128 + c8)), "r"(v[0]), "r"(v[1]), "r"(v[2]), "r"(v[3]), "r"(n), "r"(nloc) : "memory"); }
        wload();
      }
#pragma unroll
      for (int j = 0; j < 8; j++) { sp[j] = sum[j]; asm volatile("mov.b32 %0, 0;" : "=r"(sum[j])); }
    }
    asm volatile("{.reg .pred p, q; setp.neu.f32 p, %1, 0f00000000; setp.ne.or.u32 p, %2, 0, p; bar.red.or.pred q, 5, %3, p; selp.u32 %0, 1, 0, q;}" : "=r"(bad) : "f"(chk), "r"(lds32(sb + OFF_MISC + 12)), "n"(DEFO ? 512 : 384) : "memory");
    STAMP(11);
   } else { asm volatile("cp.async.wait_all;" ::: "memory"); bar_sync(5, 384); }
  }
  if (bad) slow_path(p, wid, lane, node0, nloc);
}

}

typedef CUresult (*EncodeFn)(CUtensorMap*, CUtensorMapDataType, cuuint32_t, void*, const cuuint64_t*, const cuuint64_t*, const cuuint32_t*, const cuuint32_t*,
                             CUtensorMapInterleave, CUtensorMapSwizzle, CUtensorMapL2promotion, CUtensorMapFloatOOBfill);

extern "C" void kernel_launch(void* const* d_in, const int* in_sizes, int n_in, void* d_out, int out_size) {
  Params p; Maps maps;
  p.h = (const uint4*)d_in[0]; p.pos = (const uint16_t*)d_in[1]; p.ea = (const uint4*)d_in[2];
  p.src = (const int*)d_in[3]; p.dst = (const int*)d_in[4];
  p.we = (const uint16_t*)d_in[5]; p.wx = (const uint16_t*)d_in[6]; p.wh = (const uint16_t*)d_in[7];
  p.out = (uint16_t*)d_out;
  p.N = in_sizes[0] / 64; p.E = in_sizes[3];
  p.EPC = ((p.E + G * 4 - 1) / (G * 4)) * 4;
  p.magic = (uint32_t)(((uint64_t)G << 24) / (uint64_t)p.N);
  p.inv = (1ull << 56) / p.magic;
  const uint64_t ea0 = (uint64_t)d_in[2], ea1 = ea0 + (uint64_t)p.E * 32 - 1;
  p.force_slow = ((ea0 >> 32) != (ea1 >> 32)) || (ea0 & 31) || (p.E & 3);
  void* qp = nullptr;
  cudaGetSymbolAddress(&qp, g_q);
  p.q = (char*)qp;
  if (((uint64_t)p.q >> 32) != (((uint64_t)p.q + QBYTES) >> 32)) p.q += QBYTES;
  cudaGetSymbolAddress((void**)&p.sync, g_sync); cudaGetSymbolAddress((void**)&p.xe, g_xe);
  cudaGetSymbolAddress((void**)&p.xa, g_xa); cudaGetSymbolAddress((void**)&p.xb, g_xb);
  void* fn = nullptr; cudaDriverEntryPointQueryResult qr;
  cudaGetDriverEntryPoint("cuTensorMapEncodeTiled", &fn, cudaEnableDefault, &qr);
  auto mk = [&](CUtensorMap* tm, void* base, int rows, int box = 64) {
    const cuuint64_t dim[2] = {64, (cuuint64_t)rows}, str[1] = {128}; const cuuint32_t bx[2] = {64, (cuuint32_t)box}, es[2] = {1, 1};
    ((EncodeFn)fn)(tm, CU_TENSOR_MAP_DATA_TYPE_BFLOAT16, 2, base, dim, str, bx, es, CU_TENSOR_MAP_INTERLEAVE_NONE, CU_TENSOR_MAP_SWIZZLE_128B,
                   CU_TENSOR_MAP_L2_PROMOTION_NONE, CU_TENSOR_MAP_FLOAT_OOB_FILL_NONE);
  };
  mk(&maps.m[TM_H / 128], d_in[0], p.N); mk(&maps.m[TM_WE / 128], d_in[5], 145); mk(&maps.m[TM_WH / 128], d_in[7], 128); mk(&maps.m[TM_Q / 128], p.q, p.N, 16);
  for (int k = 0; k < 2; k++) {
    void* xp = (void*)(k ? p.xb : p.xa);
    const cuuint64_t dim[2] = {(cuuint64_t)G * 64, (cuuint64_t)G}, str[1] = {(cuuint64_t)G * (128 << k)}; const cuuint32_t bx[2] = {64, (cuuint32_t)(k ? BROWS : G)}, es[2] = {1, 1};
    ((EncodeFn)fn)(&maps.m[TM_XA / 128 + k], k ? CU_TENSOR_MAP_DATA_TYPE_UINT32 : CU_TENSOR_MAP_DATA_TYPE_UINT16, 2, xp, dim, str, bx, es, CU_TENSOR_MAP_INTERLEAVE_NONE,
                   CU_TENSOR_MAP_SWIZZLE_NONE, CU_TENSOR_MAP_L2_PROMOTION_NONE, CU_TENSOR_MAP_FLOAT_OOB_FILL_NONE);
  }
  cudaFuncSetAttribute(egnn_kernel, cudaFuncAttributeMaxDynamicSharedMemorySize, SMEM);
  egnn_kernel<<<G, NTHR, SMEM>>>(p, maps);
}
```

```cpp
#include <cuda_runtime.h>
#include <cuda_bf16.h>
#include <cuda_fp16.h>
#include <cuda.h>
#include <stdint.h>
#pragma nv_diag_suppress 549

#define PFN 16
#define PFNS 250
#define FM 0
#define OPQ 0
#define H0 0
#define HALL 1
#define PF0NS 0
#define PFW 0
#define QCODE 0x254a109b7863ull
#define QREV 0x605
#define PFS 1
#define ESZ ""
#define XEF 0
#define OCS ""
#define RNB 2
#define NEARLY 2
#define PFE 0
#define DEFO 1
#define DEFNS 400
#define ABL 0
#define HW 3
#define BROWS 132
#define B_HOLD 1
#define LSEQ 0x231200ull
#define HE 0
namespace {

constexpr int G = 132;
constexpr int NTHR = 512, NWK = 352, NCH = 5;
constexpr int NST = 3, STG = 2560;
constexpr int SCAP = 448;

constexpr int OFF_H = 0;
constexpr int OFF_W = 49152;
constexpr int OFF_WD = OFF_W + 16384;
constexpr int OFF_W3 = OFF_WD + 1024;
constexpr int OFF_P2 = OFF_W3 + 2048;
constexpr int OFF_RING = OFF_P2 + 24576;
constexpr int OFF_TE = OFF_RING + 12 * NST * STG;
constexpr int OFF_TS = OFF_TE + SCAP * 64;
constexpr int OFF_GP = OFF_TS + SCAP * 32;
constexpr int OFF_WX = OFF_GP + 3072;
constexpr int OFF_LEN = OFF_WX + 128;
constexpr int OFF_MISC = OFF_LEN + 128;
constexpr int OFF_BAR = OFF_MISC + 48;
constexpr int SMEM = OFF_BAR + 256;
static_assert(SMEM <= 232448, "smem");
constexpr uint32_t sb = 1024;
constexpr int OFF_SRCI = OFF_TE;
constexpr int OFF_SB = OFF_RING, OFF_SA = OFF_SB + 34816, OFF_AX = OFF_SA + 32768, OFF_DST = OFF_H + 24576;
constexpr int OFF_WS = OFF_AX + 17408;
constexpr int OFF_BC = OFF_WS + 2304;
constexpr int OFF_CNT = OFF_P2;
constexpr int OFF_DH = OFF_CNT + 2176;
constexpr int OFF_POS = OFF_DH + 128;
constexpr int OFF_EXT = OFF_POS + 3072;
constexpr int OFF_XB = OFF_EXT + 1024, XPAD = G * 256;
static_assert(OFF_XB + XPAD + 1028 <= OFF_RING + 12 * STG && OFF_XB % 128 == 0 && OFF_BC + 544 <= OFF_TE && OFF_P2 % 1024 == 0 && OFF_SA % 1024 == 0 && SCAP * 64 >= 24576, "staging");
constexpr int BAR_DST = OFF_BAR, BAR_SRC = BAR_DST + 40, BAR_T = BAR_SRC + 24, BAR_W = BAR_T + 48, BAR_XA = BAR_W + 8, BAR_PS = BAR_XA + 8, BAR_AW = BAR_PS + 8,
              BAR_QP = BAR_AW + 8, BAR_QR = BAR_QP + 8, BAR_HA = BAR_QR + 8, BAR_EP = BAR_HA + 8, BAR_AX = BAR_EP + 8, BAR_AI = BAR_AX + 8, BAR_HB = BAR_AI + 8, BAR_U = BAR_HB + 8, BAR_WH = BAR_U + 8, BAR_M = BAR_WH + 8, BAR_X = BAR_M + 8, BAR_END = BAR_X + 8;
static_assert(BAR_END <= OFF_BAR + 256, "barriers");
constexpr uint32_t QBYTES = 8u << 20;

__device__ __align__(256) uint4 g_xa[G * G * 8];
__device__ __align__(256) uint4 g_xb[G * G * 16];
__device__ __align__(256) uint2 g_xe[G * G * 32];
__device__ __align__(256) uint4 g_q[2 * QBYTES / 16];
__device__ __align__(256) uint32_t g_sync[8];
#define STAMP(k)

struct Maps { CUtensorMap m[6]; };
constexpr int TM_H = 0, TM_WE = 128, TM_WH = 256, TM_Q = 384, TM_XA = 512, TM_XB = 640;
struct Params {
  const uint4* h; const uint16_t* pos; const uint4* ea; const int* src; const int* dst;
  const uint16_t* we; const uint16_t* wx; const uint16_t* wh; uint16_t* out; char* q;
  uint32_t* sync; const uint4* xa; const uint4* xb; uint2* xe;
  int N, E, EPC; uint32_t magic; int force_slow; unsigned long long inv;
};
template<int V> struct IC { static constexpr int value = V; };

#define R32(d) "+f"(d[0]),"+f"(d[1]),"+f"(d[2]),"+f"(d[3]),"+f"(d[4]),"+f"(d[5]),"+f"(d[6]),"+f"(d[7]),"+f"(d[8]),"+f"(d[9]),"+f"(d[10]),"+f"(d[11]),"+f"(d[12]),"+f"(d[13]),"+f"(d[14]),"+f"(d[15]),"+f"(d[16]),"+f"(d[17]),"+f"(d[18]),"+f"(d[19]),"+f"(d[20]),"+f"(d[21]),"+f"(d[22]),"+f"(d[23]),"+f"(d[24]),"+f"(d[25]),"+f"(d[26]),"+f"(d[27]),"+f"(d[28]),"+f"(d[29]),"+f"(d[30]),"+f"(d[31])
#define S32 "{%0,%1,%2,%3,%4,%5,%6,%7,%8,%9,%10,%11,%12,%13,%14,%15,%16,%17,%18,%19,%20,%21,%22,%23,%24,%25,%26,%27,%28,%29,%30,%31}"
#define DI __device__ __forceinline__

constexpr uint64_t DHI = ((uint64_t)(1024 >> 4) << 32) | (1ull << 62);
template<int SD> DI void rs64b(float (&d)[32], uint32_t a0, uint32_t a1, uint32_t a2, uint32_t a3, uint64_t db) {
  asm volatile("wgmma.mma_async.sync.aligned.m64n64k16.f32.bf16.bf16 " S32 ", {%32,%33,%34,%35}, %36, %37, 1, 1, 1;" : R32(d) : "r"(a0), "r"(a1), "r"(a2), "r"(a3), "l"(db), "n"(SD)); }
template<int SD> DI void rs64h(float (&d)[32], uint32_t a0, uint32_t a1, uint32_t a2, uint32_t a3, uint64_t db) {
  asm volatile("wgmma.mma_async.sync.aligned.m64n64k16.f32.f16.f16 " S32 ", {%32,%33,%34,%35}, %36, %37, 1, 1, 1;" : R32(d) : "r"(a0), "r"(a1), "r"(a2), "r"(a3), "l"(db), "n"(SD)); }
template<int SD> DI void ss64(float (&d)[32], uint64_t da, uint64_t db) {
  asm volatile("wgmma.mma_async.sync.aligned.m64n64k16.f32.bf16.bf16 " S32 ", %32, %33, %34, 1, 1, 0, 1;" : R32(d) : "l"(da), "l"(db), "n"(SD)); }
DI void trap_if(bool c) { asm volatile("{.reg .pred p; setp.eq.u32 p, %0, 0; @p bra.uni LT_%=; trap; LT_%=:}" :: "r"((uint32_t)c)); }
DI void wg_fence() { asm volatile("wgmma.fence.sync.aligned;" ::: "memory"); }
DI void wg_commit() { asm volatile("wgmma.commit_group.sync.aligned;" ::: "memory"); }
DI void wg_wait0() { asm volatile("wgmma.wait_group.sync.aligned 0;" ::: "memory"); }
DI void fence_regs(float (&d)[32]) { asm volatile("" : R32(d) :: "memory"); }
DI void proxy_fence() { asm volatile("fence.proxy.async.shared::cta;" ::: "memory"); }
DI uint64_t pol_first() { uint64_t r; asm("createpolicy.fractional.L2::evict_first.b64 %0, 1.0;" : "=l"(r)); return r; }
DI float tanh_ap(float x) { float y; asm("tanh.approx.f32 %0, %1;" : "=f"(y) : "f"(x)); return y; }
DI float silu_h(float y) { return fmaf(y, tanh_ap(y), y); }
DI uint32_t pack_bf16(float lo, float hi) { uint32_t r; asm("cvt.rn.bf16x2.f32 %0, %1, %2;" : "=r"(r) : "f"(hi), "f"(lo)); return r; }
DI uint32_t pack_f16(float lo, float hi) { uint32_t r; asm("cvt.rn.f16x2.f32 %0, %1, %2;" : "=r"(r) : "f"(hi), "f"(lo)); return r; }
DI float bf_lo(uint32_t v) { return __uint_as_float(v << 16); }
DI float bf_hi(uint32_t v) { return __uint_as_float(v & 0xFFFF0000u); }
DI uint32_t b2h(uint32_t v, float s) { return pack_f16(s * bf_lo(v), s * bf_hi(v)); }
DI void mbar_wait(uint32_t bar, uint32_t parity = 0) {
  asm volatile("{.reg .pred p; .reg .u32 t0, t1;\n"
    "mbarrier.try_wait.parity.shared::cta.b64 p, [%0], %1;\n @p bra.uni LD_%=;\n mov.u32 t0, %%clock;\n"
    "LW_%=: mbarrier.try_wait.parity.shared::cta.b64 p, [%0], %1;\n"
    "@p bra.uni LD_%=;\n mov.u32 t1, %%clock; sub.u32 t1, t1, t0; setp.lt.u32 p, t1, 0x80000000;\n @p bra.uni LW_%=;\n trap;\n LD_%=:}" :: "r"(bar), "r"(parity) : "memory");
}
DI void mbar_arrive(uint32_t bar, int p = 1) { asm volatile("{.reg .pred p; setp.ne.b32 p, %1, 0; @p mbarrier.arrive.shared::cta.b64 _, [%0];}" :: "r"(bar), "r"(p) : "memory"); }
DI void bar_sync(int id, int n) { asm volatile("bar.sync %0, %1;" :: "r"(id), "r"(n) : "memory"); }
DI void bar_arrive(int id, int n) { asm volatile("bar.arrive %0, %1;" :: "r"(id), "r"(n) : "memory"); }
DI __nv_bfloat162 b2(uint32_t v) { return *(__nv_bfloat162*)&v; }
DI uint32_t u2(__nv_bfloat162 v) { return *(uint32_t*)&v; }
DI uint32_t hsq(uint32_t v) { return u2(__hmul2(b2(v), b2(v))); }
DI uint32_t hsub(uint32_t a, uint32_t b) { return u2(__hsub2(b2(a), b2(b))); }
DI uint32_t hhalf(uint32_t v) { return u2(__hmul2(b2(v), __floats2bfloat162_rn(0.5f, 0.5f))); }
DI uint32_t mag2(uint32_t m, uint32_t v) { return __vmaxu2(m, v & 0x7FFF7FFFu); }
DI uint32_t hmag(uint32_t m, uint32_t v) { const __half2 r = __hmax2(*(const __half2*)&m, __habs2(*(const __half2*)&v)); return *(const uint32_t*)&r; }
DI uint32_t magr(uint32_t m) { return max(m & 0xFFFF, m >> 16); }
DI void sts128(uint32_t a, uint32_t x, uint32_t y, uint32_t z, uint32_t w) { asm volatile("st.shared.v4.u32 [%0], {%1,%2,%3,%4};" :: "r"(a), "r"(x), "r"(y), "r"(z), "r"(w) : "memory"); }
DI void sts64(uint32_t a, uint32_t x, uint32_t y) { asm volatile("st.shared.v2.u32 [%0], {%1,%2};" :: "r"(a), "r"(x), "r"(y) : "memory"); }
DI void sts32(uint32_t a, uint32_t x) { asm volatile("st.shared.u32 [%0], %1;" :: "r"(a), "r"(x) : "memory"); }
DI void sts16(uint32_t a, uint32_t x) { asm volatile("st.shared.u16 [%0], %1;" :: "r"(a), "h"((uint16_t)x) : "memory"); }
DI void lds128(uint32_t* v, uint32_t a) { asm volatile("ld.shared.v4.u32 {%0, %1, %2, %3}, [%4];" : "=r"(v[0]), "=r"(v[1]), "=r"(v[2]), "=r"(v[3]) : "r"(a) : "memory"); }
DI void lds64(uint32_t& x, uint32_t& y, uint32_t a) { asm volatile("ld.shared.v2.u32 {%0, %1}, [%2];" : "=r"(x), "=r"(y) : "r"(a) : "memory"); }
DI uint32_t lds32(uint32_t a) { uint32_t x; asm volatile("ld.shared.u32 %0, [%1];" : "=r"(x) : "r"(a) : "memory"); return x; }
DI uint32_t lds16(uint32_t a) { uint32_t x; asm volatile("ld.shared.u16 %0, [%1];" : "=r"(x) : "r"(a) : "memory"); return x; }
DI uint32_t atoms_add(uint32_t a, uint32_t v) { uint32_t r; asm volatile("atom.shared.add.u32 %0, [%1], %2;" : "=r"(r) : "r"(a), "r"(v) : "memory"); return r; }
DI void bulk_load(uint32_t dst, const void* src, uint32_t bytes, uint32_t bar) {
  asm volatile("cp.async.bulk.shared::cluster.global.mbarrier::complete_tx::bytes.L2::cache_hint [%0], [%1], %2, [%3], %4;" :: "r"(dst), "l"(src), "r"(bytes), "r"(bar), "l"(pol_first()) : "memory"); }
DI void bulk_store(void* dst, uint32_t src, uint32_t bytes) { asm volatile("cp.async.bulk.global.shared::cta.bulk_group [%0], [%1], %2;" :: "l"(dst), "r"(src), "r"(bytes) : "memory"); }
DI void mbar_expect(uint32_t bar, uint32_t bytes) { asm volatile("mbarrier.arrive.expect_tx.shared::cta.b64 _, [%0], %1;" :: "r"(bar), "r"(bytes) : "memory"); }
DI void mbar_init(uint32_t bar, int n) { asm volatile("mbarrier.init.shared::cta.b64 [%0], %1;" :: "r"(bar), "r"(n) : "memory"); }
DI void tma_load(uint32_t dst, uint64_t tm, int row, uint32_t bar) {
  asm volatile("cp.async.bulk.tensor.2d.shared::cluster.global.mbarrier::complete_tx::bytes.L2::cache_hint [%0], [%1, {%3, %4}], [%2], %5;" :: "r"(dst), "l"(tm), "r"(bar), "r"(0), "r"(row), "l"(pol_first()) : "memory"); }
DI void tma_store(uint64_t tm, int col, int row, uint32_t src) {
  asm volatile("cp.async.bulk.tensor.2d.global.shared::cta.bulk_group [%0, {%2, %3}], [%1];" :: "l"(tm), "r"(src), "r"(col), "r"(row) : "memory"); }
DI void tma_store_ef(uint64_t tm, int col, int row, uint32_t src) {
  if (XEF) asm volatile("cp.async.bulk.tensor.2d.global.shared::cta.bulk_group.L2::cache_hint [%0, {%2, %3}], [%1], %4;" :: "l"(tm), "r"(src), "r"(col), "r"(row), "l"(pol_first()) : "memory");
  else tma_store(tm, col, row, src); }
DI void bulk_commit() { asm volatile("cp.async.bulk.commit_group;" ::: "memory"); }
DI void bulk_wait_read() { asm volatile("cp.async.bulk.wait_group.read 0;" ::: "memory"); }
DI uint2 ld_poll2(const void* a) { uint2 v; asm volatile("ld.relaxed.gpu.global.v2.u32 {%0, %1}, [%2];" : "=r"(v.x), "=r"(v.y) : "l"(a) : "memory"); return v; }
DI void st_ext(uint2* a, uint32_t v, uint32_t ep) { asm volatile("st.relaxed.gpu.global.v2.u32 [%0], {%1, %2};" :: "l"(a), "r"(v), "r"(ep) : "memory"); }
DI uint32_t ext_get(const uint2* a, uint32_t ep) { uint2 v; int spin = 0; do { v = ld_poll2(a); trap_if(++spin > 4000000); } while (__any_sync(~0u, v.y != ep)); return v.x; }
DI void bulk_wait() { asm volatile("cp.async.bulk.wait_group 0;" ::: "memory"); }
DI void hint_signal(uint32_t* c) { asm volatile("red.relaxed.gpu.global.add.u32 [%0], 1;" :: "l"(c) : "memory"); }
DI void hint_wait(const uint32_t* c, uint32_t target) { uint32_t v; int spin = 0;
  do { asm volatile("ld.relaxed.gpu.global.u32 %0, [%1];" : "=r"(v) : "l"(c) : "memory"); trap_if(++spin > 4000000); } while (__any_sync(~0u, (int)(v - target) < 0)); }
DI void stsm4(uint32_t a, uint32_t x, uint32_t y, uint32_t z, uint32_t w) { asm volatile("stmatrix.sync.aligned.m8n8.x4.shared.b16 [%0], {%1,%2,%3,%4};" :: "r"(a), "r"(x), "r"(y), "r"(z), "r"(w) : "memory"); }
DI void ldsm4(uint32_t* v, uint32_t a) { asm volatile("ldmatrix.sync.aligned.m8n8.x4.shared.b16 {%0,%1,%2,%3}, [%4];" : "=r"(v[0]), "=r"(v[1]), "=r"(v[2]), "=r"(v[3]) : "r"(a) : "memory"); }
DI void ldsm4t(uint32_t* v, uint32_t a) { asm volatile("ldmatrix.sync.aligned.m8n8.x4.trans.shared.b16 {%0,%1,%2,%3}, [%4];" : "=r"(v[0]), "=r"(v[1]), "=r"(v[2]), "=r"(v[3]) : "r"(a) : "memory"); }
DI uint32_t mad16(uint32_t x, uint32_t m, uint32_t c) { uint32_t r; asm("dp2a.lo.u32.u32 %0, %1, %2, %3;" : "=r"(r) : "r"(x), "r"(m), "r"(c)); return r; }
DI bool wbad(uint32_t m, uint32_t hi) { return m > hi || (m && m < 0x3980); }

__device__ __noinline__ void slow_path(const Params& p, int wid, int lane, int node0, int nloc) {
  const uint32_t ab = sb + OFF_P2 + wid * 8704;
  for (int i = lane; i < 32 * 68; i += 32) sts32(ab + i * 4, 0);
  __syncwarp();
  const uint32_t wdv = __ldg((const uint32_t*)(p.we + 128 * 64) + lane), wxv = __ldg((const uint32_t*)p.wx + lane);
  const int nb0 = node0 + wid * 32, cntn = max(0, min(32, nloc - wid * 32));
  auto dot = [&](uint32_t hv, const uint16_t* w, int K2, float& y0, float& y1) {
#pragma unroll 4
    for (int k = 0; k < K2; k++) {
      const uint32_t hk = __shfl_sync(~0u, hv, k), wa = __ldg((const uint32_t*)(w + 2 * k * 64) + lane), wb = __ldg((const uint32_t*)(w + (2 * k + 1) * 64) + lane);
      y0 = fmaf(bf_lo(hk), bf_lo(wa), fmaf(bf_hi(hk), bf_lo(wb), y0)); y1 = fmaf(bf_lo(hk), bf_hi(wa), fmaf(bf_hi(hk), bf_hi(wb), y1));
    }
  };
  auto silu = [](float x) { return x / (1.f + __expf(-x)); };
#pragma unroll 1
  for (int base = 0; base < p.E; base += 32) {
    const int e = base + lane;
    const uint32_t dl = e < p.E ? (uint32_t)(__ldg(p.dst + e) - nb0) : 0xFFFFFFFFu;
    uint32_t mk = __ballot_sync(~0u, dl < (uint32_t)cntn);
    while (mk) {
      const int l = __ffs(mk) - 1; mk &= mk - 1;
      const int ee = base + l, n = __shfl_sync(~0u, dl, l), s = __ldg(p.src + ee);
      const uint16_t *po = p.pos + (size_t)(nb0 + n) * 3, *pp = p.pos + (size_t)s * 3;
      const uint32_t dxy = hsub(__ldg(po) | (__ldg(po + 1) << 16), __ldg(pp) | (__ldg(pp + 1) << 16)), dz = hsub(__ldg(po + 2), __ldg(pp + 2));
      const uint32_t sq = hsq(dxy); const float d2 = bf_lo(sq) + bf_hi(sq) + bf_lo(hsq(dz));
      float y0 = d2 * bf_lo(wdv), y1 = d2 * bf_hi(wdv);
      dot(__ldg((const uint32_t*)(p.h + (size_t)(nb0 + n) * 8) + lane), p.we, 32, y0, y1);
      dot(__ldg((const uint32_t*)(p.h + (size_t)s * 8) + lane), p.we + 64 * 64, 32, y0, y1);
      dot(__ldg((const uint32_t*)(p.ea + (size_t)ee * 2) + (lane & 7)), p.we + 129 * 64, 8, y0, y1);
      const uint32_t mm = pack_bf16(silu(y0), silu(y1));
      float c = bf_lo(mm) * bf_lo(wxv) + bf_hi(mm) * bf_hi(wxv);
#pragma unroll
      for (int o = 16; o; o >>= 1) c += __shfl_xor_sync(~0u, c, o);
      const uint32_t a = ab + n * 272;
      uint32_t x0, x1; lds64(x0, x1, a + lane * 8);
      sts64(a + lane * 8, __float_as_uint(__uint_as_float(x0) + bf_lo(mm)), __float_as_uint(__uint_as_float(x1) + bf_hi(mm)));
      if (lane < 3) { const float df = lane == 0 ? bf_lo(dxy) : lane == 1 ? bf_hi(dxy) : bf_lo(dz); sts32(a + 256 + lane * 4, __float_as_uint(fmaf(c, df, __uint_as_float(lds32(a + 256 + lane * 4))))); }
    }
  }
  __syncwarp();
#pragma unroll 1
  for (int n = 0; n < cntn; n++) {
    uint32_t x0, x1; lds64(x0, x1, ab + n * 272 + lane * 8);
    const uint32_t hv = __ldg((const uint32_t*)(p.h + (size_t)(nb0 + n) * 8) + lane);
    float y0 = 0.f, y1 = 0.f;
    dot(hv, p.wh, 32, y0, y1); dot(pack_bf16(__uint_as_float(x0), __uint_as_float(x1)), p.wh + 64 * 64, 32, y0, y1);
    ((uint32_t*)p.out)[(size_t)(nb0 + n) * 32 + lane] = u2(__hadd2(b2(hv), b2(pack_bf16(silu(y0), silu(y1)))));
    if (lane < 3) p.out[(size_t)p.N * 64 + (size_t)(nb0 + n) * 3 + lane] = (uint16_t)pack_bf16(bf_lo(__ldg(p.pos + (size_t)(nb0 + n) * 3 + lane)) + __uint_as_float(lds32(ab + n * 272 + 256 + lane * 4)), 0.f);
  }
}

__global__ void __launch_bounds__(NTHR, 1) egnn_kernel(const __grid_constant__ Params p, const __grid_constant__ Maps maps) {
  const uint64_t tmb = (uint64_t)&maps;
  extern __shared__ __align__(1024) unsigned char smraw[];
  const int tid = threadIdx.x, cta = blockIdx.x;
  const int e0 = cta * p.EPC, n4 = max(0, min(p.EPC, p.E - e0)) >> 2;
  STAMP(0);
  asm volatile("{.reg .pred p; setp.eq.u32 p, %2, 384; @p cp.async.cg.shared.global [%0], [%1], 16;}" :: "r"(sb + OFF_LEN - 192 + (tid >> 1)), "l"(p.sync), "r"(tid & 415) : "memory");
  if (tid == NWK) {
#pragma unroll
    for (int k = 0; k < NCH; k++) mbar_init(sb + BAR_DST + k * 8, 1);
    asm volatile("fence.mbarrier_init.release.cluster;" ::: "memory");
#pragma unroll 1
    for (int k = 0; k < NCH; k++) { const int nb = max(0, min(NWK, n4 - k * NWK)) * 16;
      mbar_expect(sb + BAR_DST + k * 8, nb);
      if (nb) bulk_load(sb + OFF_DST + k * NWK * 16, (const char*)(p.dst + e0) + k * NWK * 16, nb, sb + BAR_DST + k * 8); }
  }
  const int lane = tid & 31, wid = __shfl_sync(~0u, tid >> 5, 0), w = wid & 3;

  auto first_node = [&](int c) { return (int)((c * p.inv + 0xFFFFFFFFull) >> 32); };
  const int node0 = first_node(cta), nloc = min(first_node(cta + 1), p.N) - node0;
  const uint32_t ealo = (uint32_t)(uint64_t)p.ea;
  const int epad = min(e0, p.E - 1);
  auto load_h = [&](int b) { mbar_expect(sb + BAR_T + b * 8, 8192); tma_load(sb + OFF_H + b * 8192, tmb + TM_H, node0 + b * 64, sb + BAR_T + b * 8); };
  auto prefetch_e = [&](int i) {
    const uint32_t nb = (p.E / G) & ~15u;
    if (nb && i < PFN) asm volatile("cp.async.bulk.prefetch.L2.global [%0], %1;" :: "l"((const char*)p.ea + (size_t)(((i * PFS + i * PFS / 32 * (~PFS & 1)) & 31) * G + cta) * nb), "r"(nb) : "memory");
  };
  if (wid >= 12) {
    const int t = tid - 384;
    uint32_t pv[9], ev = 0;
#pragma unroll
    for (int i = 0; i < 3; i++) { const uint16_t* pp = p.pos + (size_t)(node0 + t + 128 * i) * 3;
      pv[3 * i] = pv[3 * i + 1] = pv[3 * i + 2] = 0;
      asm volatile("{.reg .pred p; setp.lt.s32 p, %4, %5;\n @p ld.global.nc.u16 %0, [%3];\n @p ld.global.nc.u16 %1, [%3+2];\n @p ld.global.nc.u16 %2, [%3+4];}"
        : "+r"(pv[3 * i]), "+r"(pv[3 * i + 1]), "+r"(pv[3 * i + 2]) : "l"(pp), "r"(t + 128 * i), "r"(p.N - node0)); }
    asm volatile("{.reg .pred p; setp.lt.u32 p, %3, 8; @p ld.global.nc.u32 %0, [%1]; @p st.global.v4.u32 [%2], {%4, %4, %4, %4};}"
      : "+r"(ev) : "l"((const uint32_t*)(p.ea + (size_t)epad * 2) + t), "l"(p.q + (size_t)(p.N + cta) * 128 + t * 16), "r"(t), "r"(0xF700F700u) : "memory");
    asm volatile("cp.async.wait_all;" ::: "memory");
    __syncwarp();
    const uint32_t e = lds32(sb + OFF_LEN + 8 + w * 16) + 1;
    {
      const uint32_t tg = (1 + e % 3) << 30, v = ((tg >> 16) + 512 + (lane & 7) * 4) * 0x10001u;
      if (t == 0) sts32(sb + OFF_MISC + 32, e);
#pragma unroll
      for (int i = 0; i < 9; i++) sts128(sb + OFF_SA + t * 16 + i * 2048, v, v + 0x10001u, v + 0x20002u, v + 0x30003u);
      bar_sync(6, NTHR);
      mbar_arrive(sb + BAR_EP, lane == 0);
#pragma unroll
      for (int i = 0; i < 17; i++) sts128(sb + OFF_SB + t * 16 + i * 2048, tg, tg, tg, tg); }
    uint32_t mp = 0;
#pragma unroll
    for (int i = 0; i < 3; i++) { sts64(sb + OFF_POS + (t + 128 * i) * 8, pv[3 * i] | (pv[3 * i + 1] << 16), pv[3 * i + 2]); mp = mag2(mag2(mp, pv[3 * i] | (pv[3 * i + 1] << 16)), pv[3 * i + 2]); }
    proxy_fence();
    __syncwarp();
    mbar_arrive(sb + BAR_PS, lane == 0);
    mbar_wait(sb + BAR_W);
#pragma unroll
    for (int i = 0; i < 8; i += 4) { uint32_t v[16];
#pragma unroll
      for (int k = 0; k < 4; k++) lds128(v + 4 * k, sb + OFF_W + t * 16 + (i + k) * 2048);
#pragma unroll
      for (int k = 0; k < 4; k++) sts128(sb + OFF_W + t * 16 + (i + k) * 2048, hhalf(v[4 * k]), hhalf(v[4 * k + 1]), hhalf(v[4 * k + 2]), hhalf(v[4 * k + 3])); }
    {
      uint32_t v[4], u[4]; const int r = t >> 3, c = t & 7;
      lds128(v, sb + OFF_WS + 128 + t * 16); lds128(u, sb + OFF_WS + c * 16);
      const uint32_t x = lds32(sb + OFF_WS + 2176 + lane * 4);
      sts128(sb + OFF_W3 + r * 128 + ((c ^ (r & 7)) << 4), b2h(v[0], .5f), b2h(v[1], .5f), b2h(v[2], .5f), b2h(v[3], .5f));
      const float s = ((r & 1) || r == 6) ? 0.f : .5f;
      if (t < 64) sts128(sb + OFF_WD + r * 128 + ((c ^ r) << 4), b2h(u[0], s), b2h(u[1], s), b2h(u[2], s), b2h(u[3], s));
      if (t < 32) sts32(sb + OFF_WX + (t & 3) * 32 + (t >> 2) * 4, b2h(x, 1.f));
      const uint32_t m3 = __reduce_max_sync(~0u, magr(mag2(mag2(mag2(mag2(0, v[0]), v[1]), v[2]), v[3]))), md = __reduce_max_sync(~0u, magr(mag2(mag2(mag2(mag2(0, u[0]), u[1]), u[2]), u[3])));
      if (wbad(m3, 0x4000) || wbad(md, 0x4000) || wbad(__reduce_max_sync(~0u, magr(mag2(0, x))), 0x4700) || magr(mp) >= 0x4200 || magr(mag2(0, ev)) >= 0x4380) sts32(sb + OFF_MISC + 8, 1);
    }
    proxy_fence();
    if (w == 1) {
#pragma unroll 1
      for (int b = HE; b < HW; b++) { mbar_wait(sb + BAR_SRC + max(0, H0 + b) * 8); if (lane == 0) load_h(b); }
    }
    bar_sync(3, 128);
    const uint32_t frag = (w * 16 + (lane & 15)) * 128 + (((lane >> 4) ^ (lane & 7)) << 4);
    uint32_t mq = 0;
#pragma unroll 1
    for (int b = 0; b < 6; b++) {
      float acc[32];
      const uint64_t da = DHI | (((sb + OFF_H) >> 4) + b * 512), db = DHI | ((sb + OFF_W) >> 4);
      const uint32_t v0 = lds16(sb + OFF_POS + b * 512 + w * 128 + lane * 2), v1 = lds16(sb + OFF_POS + 64 + b * 512 + w * 128 + lane * 2);
      mbar_wait(sb + BAR_T + b * 8);
      if (b == 0) STAMP(25);
      if (b == 5) STAMP(26);
      wg_fence();
      ss64<0>(acc, da, db); ss64<1>(acc, da + 2, db + 128); ss64<1>(acc, da + 4, db + 256); ss64<1>(acc, da + 6, db + 384);
      wg_commit();
      if (b == 0) mbar_wait(sb + BAR_AW);
      if (t == 32) { if (HALL) { if (b == 0) for (int k = HW; k < 6; k++) load_h(k); } else if (b + HW < 6) load_h(b + HW); }
      __syncwarp();
      uint32_t ff[6], fg[6];
#pragma unroll
      for (int j = 0; j < 6; j++) { ff[j] = (__byte_perm((j & 1) ? v1 : v0, 0, 0x4140) >> (3 * (j >> 1))) & 0x00070007u; fg[j] = __vsub2(0x00040004u, ff[j]);
        asm volatile("" : "+r"(ff[j]), "+r"(fg[j])); }
      wg_wait0(); fence_regs(acc);
      uint32_t o[16];
#pragma unroll
      for (int j = 0; j < 16; j++) o[j] = pack_f16(acc[2 * j], acc[2 * j + 1]);
#pragma unroll
      for (int j = 0; j < 6; j++) {
        const uint32_t m = o[j] & 0x7FFF7FFFu; mq = __vmaxu2(mq, m);
        o[j] = (__viaddmax_s16x2(m, fg[j], 0) & 0xFFF8FFF8u) | ff[j] | (o[j] & 0x80008000u); }
      if (b == 4) mbar_wait(sb + BAR_AX);
      const uint32_t qs = sb + OFF_SA + b * 8192;
#pragma unroll
      for (int j = 0; j < 4; j++) stsm4((qs + frag) ^ (j << 5), o[4 * j], o[4 * j + 1], o[4 * j + 2], o[4 * j + 3]);
      proxy_fence();
      __syncwarp();
      if (lane == 0 && b * 64 + w * 16 < nloc) tma_store(tmb + TM_Q, 0, node0 + b * 64 + w * 16, qs + w * 2048);
    }
    if (lane == 0) bulk_commit();
    { const uint32_t m = __reduce_max_sync(~0u, magr(mq)); if (lane == 0) sts32(sb + OFF_MISC + 16 + w * 4, m); }
    asm volatile("setmaxnreg.dec.sync.aligned.u32 32;");
    bulk_wait();
    bar_sync(3, 128);
    if (w == 0) {
      STAMP(18);
      uint32_t mv[4]; lds128(mv, sb + OFF_MISC + 16);
      const uint32_t mx = max(max(mv[0], mv[1]), max(mv[2], mv[3]));
      mbar_arrive(sb + BAR_QR, lane == 0);
      STAMP(19);
      if (lane == 0) {
        if (nloc > 0 && (mx >= 0x7BF0 || mx < 0x1400)) asm volatile("st.relaxed.gpu.global.u32 [%0+4], %1;" :: "l"(p.sync), "r"(e) : "memory");
        asm volatile("red.release.gpu.global.add.u32 [%0], 1;" :: "l"(p.sync) : "memory");
      }
      __syncwarp();
      uint32_t c, f; int spin = 0;
      do { asm volatile("ld.acquire.gpu.global.v2.u32 {%0, %1}, [%2];" : "=r"(c), "=r"(f) : "l"(p.sync) : "memory"); trap_if(++spin > 4000000); } while (__any_sync(~0u, (int)(c - e * G) < 0));
      if (f == e) sts32(sb + OFF_MISC + 8, 1);
      if (cta == 0 && lane == 0) asm volatile("st.relaxed.gpu.global.u32 [%0+8], %1;" :: "l"(p.sync), "r"(e) : "memory");
      STAMP(20);
      __syncwarp();
      mbar_arrive(sb + BAR_QP, lane == 0);
    }
    if (w == 2) {
      const uint32_t tg = (1 + e % 3) << 30;
      hint_wait(p.sync + 5, e * G);
      if (lane == 0) { mbar_expect(sb + BAR_HB, XPAD);
#pragma unroll 1
        for (int o = 0; o < 4; o++) bulk_load(sb + OFF_XB + o * (G * 64), (const char*)p.xb + (size_t)(cta * 4 + o) * (G * 64), G * 64, sb + BAR_HB); }
      STAMP(21);
      bar_sync(7, 384);
      sts32(sb + OFF_XB + XPAD, tg + p.N + cta);
      const uint32_t nx = __shfl_sync(~0u, lds32(sb + OFF_MISC + 8) ? 0 : lds32(sb + OFF_MISC + 4), 0);
#pragma unroll 1
      for (uint32_t k = 0; k < nx; k += 32) {
        const uint32_t i = min(k + lane, nx - 1), xr = lds32(sb + OFF_EXT + i * 4), row = (xr >> 9) & 255;
        const uint32_t v = ext_get(p.xe + (cta * G + row) * 32 + ((xr >> 17) & 31), e), x = lds32(sb + OFF_CNT + (xr & 511) * 4) + (xr >> 22) * 16;
        sts32(sb + OFF_XB + XPAD + 4 + i * 4, v); sts16(sb + OFF_TS + x, XPAD + 4 + i * 4);
        sts32(sb + OFF_TE + x * 2, mad16(v, 0x2000u, ealo - (tg >> 11) + row * p.EPC * 32));
      }
      __syncwarp();
      mbar_arrive(sb + BAR_HB, lane == 0);
    }
    if (w == 1) {
      if (PFW) mbar_wait(sb + PFW);
      __nanosleep(PF0NS);
#pragma unroll 1
      for (int i = PFE; i < PFN; i++) { if (lane == 0) prefetch_e(i); __nanosleep(PFNS); }
    }
    bar_sync(4, NTHR);
    if (t == 0) { mbar_expect(sb + BAR_U, 16384); tma_load(sb + OFF_W, tmb + TM_WH, 0, sb + BAR_U); tma_load(sb + OFF_W + 8192, tmb + TM_WH, 64, sb + BAR_U); }
    mbar_wait(sb + BAR_U);
    uint32_t mh = 0;
#pragma unroll 1
    for (int i = t; i < 512; i += 128) { uint32_t v[4]; const uint32_t a = sb + OFF_W + i * 16;
      lds128(v, a); sts128(a, hhalf(v[0]), hhalf(v[1]), hhalf(v[2]), hhalf(v[3]));
      lds128(v, a + 8192); sts128(a + 8192, b2h(v[0], .5f), b2h(v[1], .5f), b2h(v[2], .5f), b2h(v[3], .5f));
      mh = mag2(mag2(mag2(mag2(mh, v[0]), v[1]), v[2]), v[3]); }
    if (wbad(__reduce_max_sync(~0u, magr(mh)), 0x4700)) sts32(sb + OFF_MISC + 12, 1);
    proxy_fence();
    __syncwarp();
    mbar_arrive(sb + BAR_WH, lane == 0);
    if (DEFO) { if (!__shfl_sync(~0u, lds32(sb + OFF_MISC + 8), 0)) {
      mbar_wait(sb + BAR_M);
      __nanosleep(DEFO);
#pragma unroll 1
      for (int i = 0; i < 12; i++) { uint32_t v[4]; const uint32_t n = lds16(sb + OFF_GP + i * 256 + (t >> 3) * 8 + 6);
        lds128(v, sb + OFF_H + n * 128 + (((n ^ t) & 7) << 4));
        if (n < nloc) ((uint4*)p.out)[(size_t)(node0 + n) * 8 + (t & 7)] = make_uint4(v[0], v[1], v[2], v[3]);
        __nanosleep(DEFNS); }
      mbar_wait(sb + BAR_X);
#pragma unroll 1
      for (int i = t; i < 384; i += 128) { uint32_t x, y; lds64(x, y, sb + OFF_GP + i * 8); const uint32_t a = sb + OFF_P2 + (y >> 16) * 6; sts16(a, x); sts16(a + 2, x >> 16); sts16(a + 4, y); }
      bar_sync(3, 128);
#pragma unroll 3
      for (int i = t; i < nloc * 3; i += 128) p.out[(size_t)p.N * 64 + node0 * 3 + i] = lds16(sb + OFF_P2 + i * 2);
      asm volatile("{.reg .pred p, q; setp.ne.u32 p, 0, 0; bar.red.or.pred q, 5, 512, p;}" ::: "memory"); } }
    return;
  }

  if (tid == 320) {
    mbar_init(sb + BAR_W, 1);
    asm volatile("fence.mbarrier_init.release.cluster;" ::: "memory");
    mbar_expect(sb + BAR_W, 2 * 8192 + 2304);
    tma_load(sb + OFF_W, tmb + TM_WE, 64, sb + BAR_W); tma_load(sb + OFF_W + 8192, tmb + TM_WE, 0, sb + BAR_W);
    bulk_load(sb + OFF_WS, p.we + 128 * 64, 2176, sb + BAR_W); bulk_load(sb + OFF_WS + 2176, p.wx, 128, sb + BAR_W);
  }
  if (tid == 288) {
#pragma unroll
    for (int a = BAR_SRC; a < BAR_END; a += 8) if (a != BAR_W) mbar_init(sb + a, a == BAR_WH || a == BAR_PS || a == BAR_EP ? 4 : a == BAR_XA ? 11 : a == BAR_HB ? 2 : a == BAR_M ? 12 : a == BAR_X ? 24 : 1);
    asm volatile("fence.mbarrier_init.release.cluster;" ::: "memory");
    asm volatile("prefetch.tensormap [%0];" :: "l"(tmb + TM_XA)); asm volatile("prefetch.tensormap [%0];" :: "l"(tmb + TM_H));
    asm volatile("prefetch.tensormap [%0];" :: "l"(tmb + TM_XB)); asm volatile("prefetch.tensormap [%0];" :: "l"(tmb + TM_Q));
  }
  {
    if (tid < 144) { const uint32_t z = (tid >> 3) == 16 ? 0x8000u : 0u; sts128(sb + OFF_CNT + tid * 16, z, z, z, z); }
    else if (tid <= 144 + G) sts32(sb + OFF_BC + (tid - 144) * 4, ((tid - 144) & 31) * 4);
    const uint32_t sp = XPAD * 0x10001u, em = first_node(G);
    if (wid < 7) {
#pragma unroll
      for (int i = 0; i < 4; i++) sts128(sb + OFF_TS + tid * 16 + i * 3584, sp, sp, sp, sp);
    }
    static_assert(SCAP * 32 == 4 * 3584, "fill");
#pragma unroll 1
    for (int i = n4 + tid; i < 1536; i += 384) sts128(sb + OFF_DST + i * 16, em, em, em, em);
    if (tid == 321) sts128(sb + OFF_MISC, 0, 0, p.force_slow, 0);
  }
  bar_arrive(6, NTHR);
  bar_sync(0, 384);
  uint32_t ep, tag, eb0, pk[12], r0[12], r1[12], cb;
  uint2 vb[12];
  auto get_tag = [&]() { mbar_wait(sb + BAR_EP); ep = lds32(sb + OFF_MISC + 32); tag = (1 + ep % 3) << 30; eb0 = ealo - (tag >> 11); };
  if (wid == 11) {
    trap_if(sb != (uint32_t)__cvta_generic_to_shared(smraw));
#pragma unroll 1
    for (unsigned long long q = LSEQ; q; q >>= 8) { const int k = (q >> 4) & 7, nb = max(0, min(8192, n4 * 16 - k * 8192));
      mbar_wait(sb + BAR_DST + ((uint32_t)q & 7) * 8);
      if (lane == 0) {
        if (k >= 3) load_h(k - 3);
        else { mbar_expect(sb + BAR_SRC + k * 8, nb);
          if (nb) bulk_load(sb + OFF_SRCI + k * 8192, (const char*)(p.src + e0) + k * 8192, nb, sb + BAR_SRC + k * 8); } } }
    get_tag();
    mbar_wait(sb + BAR_PS);
    bar_sync(12, 384);
    uint32_t xm = 0;
#pragma unroll
    for (int k = 0; k < 5; k++) xm |= (lds32(sb + OFF_BC + min(lane + 32 * k, G - 1) * 4) >= (65 << 9) && lane + 32 * k < G) << k;
    auto ext_send = [&](int pl) {
      uint32_t x = xm;
      for (uint32_t m; (m = __ballot_sync(~0u, x));) {
        const uint32_t l = __ffs(m) - 1, j = l + 32 * (__ffs(__shfl_sync(~0u, x, l)) - 1);
        if (lane == l) x &= x - 1;
        const uint32_t e = min(lds16(sb + OFF_AX + j * 128 + ((4 * l + 2 * lane) & 126)), 6143u);
        if (pl) st_ext(p.xe + (j * G + cta) * 32 + lane, lds32(sb + OFF_SRCI + e * 4) + tag + (e << 16), ep);
        else { const uint32_t cn = lds32(sb + OFF_BC + j * 4) >> 9, v = cn > 96 ? 1 : lane + 64 < cn ? 512 | (lds32(sb + OFF_DST + e * 4) & 511) : 0;
          asm volatile("red.shared.xor.b32 [%0], %1;" :: "r"(sb + OFF_SA + j * 128 + ((l + lane) & 31) * 4), "r"(((v & 63) << 10) | ((v >> 6) << 26)) : "memory"); }
      }
    };
    if (__any_sync(~0u, xm)) { ext_send(0); proxy_fence(); __syncwarp(); }
    if (lane == 0) { tma_store_ef(tmb + TM_XA, cta * 64, 0, sb + OFF_SA); bulk_commit(); mbar_arrive(sb + BAR_AI); bulk_wait(); hint_signal(p.sync + 4); mbar_arrive(sb + BAR_AW); STAMP(16); }
    __syncwarp();
    bar_sync(13, 384);
    if (!B_HOLD && lane == 0) { tma_store_ef(tmb + TM_XB, cta * 64, 0, sb + OFF_SB); bulk_commit(); }
    __syncwarp();
    ext_send(1);
    mbar_arrive(sb + BAR_AX, lane == 0);
    if (B_HOLD) mbar_wait(sb + (B_HOLD == 1 ? BAR_HA : BAR_XA));
    if (lane == 0) {
      bulk_wait();
#pragma unroll 1
      for (int r = B_HOLD ? 0 : BROWS; r < G; r += BROWS) { tma_store_ef(tmb + TM_XB, cta * 64, r, sb + OFF_SB + r * 256); bulk_commit(); bulk_wait(); }
      hint_signal(p.sync + 5);
#pragma unroll 1
      for (int i = 0; i < PFE; i++) prefetch_e(i);
      STAMP(17);
    }
    __syncwarp();
  } else {
    STAMP(15);
    {
      uint32_t d[4 * NCH], jj[4 * NCH], rr[4 * NCH];
      auto count = [&](int k) {
        mbar_wait(sb + BAR_DST + k * 8);
        lds128(d + 4 * k, sb + OFF_DST + (tid + NWK * k) * 16);
#pragma unroll
        for (int i = 4 * k; i < 4 * k + 4; i++) { jj[i] = d[i] * p.magic; rr[i] = atoms_add(__dp4a(jj[i], 0x04000000u, sb + OFF_BC), 0x202u); }
      };
      auto place = [&](int k) {
#pragma unroll
        for (int i = 4 * k; i < 4 * k + 4; i++) {
          const uint32_t o = __dp4a(jj[i], 0x80000000u, rr[i] & 0x807Eu);
          d[i] = (d[i] & 511) | (tag >> 16);
          asm("{.reg .pred p; setp.ge.u32 p, %1, 0x8000; @p add.u32 %0, %2, %3;}" : "+r"(d[i]) : "r"(o), "r"(tid * 4), "r"(NWK * k * 4 + (i & 3)));
          sts16(sb + OFF_SA + o, d[i]); jj[i] = __viaddmin_u32(o, o, G * 256);
        }
      };
      count(0); STAMP(1); count(1); get_tag(); place(0); count(2); place(1); count(3); place(2);
      if (wid < 4) { count(4); place(3); place(4); } else place(3);
      proxy_fence();
      bar_arrive(12, 384);
      STAMP(2);
      mbar_wait(sb + BAR_AI);
      mbar_wait(sb + BAR_SRC); mbar_wait(sb + BAR_SRC + 8); mbar_wait(sb + BAR_SRC + 16);
      STAMP(12);
#pragma unroll
      for (int k = 0; k < NCH; k++) lds128(d + 4 * k, sb + OFF_SRCI + (tid + NWK * k) * 16);
      const uint32_t tb = tag + (tid << 18);
#pragma unroll
      for (int i = 0; i < 4 * NCH; i++) if (i < 4 * NCH - 4 || wid < 4) sts32(sb + OFF_SB + jj[i], d[i] + tb + ((NWK * (i >> 2) * 4 + (i & 3)) << 16));
      proxy_fence();
      bar_arrive(13, 384);
      STAMP(3);
    }
    const uint32_t rot = (lane + cta) & 31;
    cb = sb + OFF_CNT - (tag >> 14);
    {
      const uint32_t* xa = (const uint32_t*)(p.xa + (cta * G + wid) * 8) + rot;
      if (wid < 8) { const uint32_t e_ = ealo + epad * 32;
        mbar_wait(sb + BAR_AX);
#pragma unroll
        for (int i = 0; i < 7; i++) sts128(sb + OFF_TE + tid * 16 + i * 4096, e_, e_, e_, e_); }
      static_assert(SCAP * 64 == 7 * 4096, "fill");
      if (wid == 10) { hint_wait(p.sync + 4, ep * G); mbar_arrive(sb + BAR_HA, lane == 0); }
      mbar_wait(sb + BAR_HA);
      STAMP(14);
      const uint32_t tp = tag | (tag >> 16);
      uint32_t st;
#pragma unroll 1
      for (int spin = 0;; spin++) {
        st = 0;
#pragma unroll
        for (int k = 0; k < 12; k++) asm volatile("ld.relaxed.gpu.global.u32 %0, [%1];" : "=r"(pk[k]) : "l"(xa + k * 352) : "memory");
#pragma unroll
        for (int k = 0; k < 12; k++) st |= pk[k] ^ tp;
        st = __reduce_or_sync(~0u, st);
        if (!(st >> 30)) break;
        trap_if(spin > 2000000);
      }
      if (st & 0x3C00FC00u) {
#pragma unroll 1
        for (;;) {
          uint32_t x = 0, row = 0;
#pragma unroll
          for (int k = 0; k < 12; k++) { const uint32_t y = (pk[k] ^ tp) & 0x3C00FC00u; if (!x && y) { x = y; row = wid + 11 * k; pk[k] ^= y; } }
          if (!__any_sync(~0u, x)) break;
          const uint32_t n = ((x >> 10) & 63) | ((x >> 20) & 0x1C0);
          if (x >> 29) {
            const uint32_t r = atoms_add(sb + OFF_CNT + n * 4, 16), idx = atoms_add(sb + OFF_MISC + 4, 1);
            if (idx < 256) sts32(sb + OFF_EXT + idx * 4, n | (row << 9) | (lane << 17) | (min(r >> 4, 255u) << 22));
            else x = 1;
          }
          if (x && !(x >> 29)) sts32(sb + OFF_MISC + 8, 1);
          __syncwarp();
        }
      }
#pragma unroll
      for (int k = 0; k < 12; k++) { r0[k] = mad16(pk[k], 0x0004u, cb); r1[k] = mad16(pk[k], 0x0400u, cb); vb[k].x = atoms_add(r0[k], 16); vb[k].y = atoms_add(r1[k], 16); }
      if (B_HOLD == 2) mbar_arrive(sb + BAR_XA, lane == 0);
    }
    STAMP(4);
    if (wid >= 6) bar_arrive(11, NWK);
    if (wid < 6) {
      uint32_t ca[2], ky[2], dr[2], sq[2], ps[4];
#pragma unroll
      for (int i = 0; i < 2; i++) { ca[i] = sb + OFF_CNT + ((node0 + tid + 192 * i) & 511) * 4; lds64(ps[2 * i], ps[2 * i + 1], sb + OFF_POS + (tid + 192 * i) * 8); ps[2 * i + 1] |= (tid + 192 * i) << 16; }
      bar_sync(11, NWK);
      STAMP(5);
#pragma unroll
      for (int i = 0; i < 2; i++) ky[i] = (lds32(ca[i]) + 16) >> 5;
      if (max(ky[0], ky[1]) > 31) sts32(sb + OFF_MISC + 8, 1);
#pragma unroll
      for (int i = 0; i < 2; i++) { ky[i] = min(ky[i], 31u); dr[i] = atoms_add(sb + OFF_DH + ky[i] * 4, 1); }
      bar_sync(10, 192);
      const uint32_t hv = lds32(sb + OFF_DH + lane * 4);
      uint32_t inc = hv;
#pragma unroll
      for (int o = 1; o < 32; o <<= 1) asm("{.reg .pred p; .reg .b32 y; shfl.sync.down.b32 y|p, %0, %1, 31, -1; @p add.u32 %0, %0, y;}" : "+r"(inc) : "r"(o));
#pragma unroll
      for (int i = 0; i < 2; i++) {
        const uint32_t pos = __shfl_sync(~0u, inc - hv, ky[i]) + dr[i];
        const uint32_t ak = (uint32_t)(QCODE >> ((pos >> 5) * 4)) & 15, l = (pos >> 3) & 3;
        sq[i] = (ak >> 2) * 16 + ((QREV >> (pos >> 5) & 1) ? 3 - l : l) * 4 + (ak & 3);
        dr[i] = pos & 7;
        asm volatile("{.reg .pred p; setp.eq.u32 p, %2, 0; @p st.shared.u8 [%0], %1;}" :: "r"(sb + OFF_LEN + sq[i]), "r"(max(ky[i], 1u)), "r"(dr[i]) : "memory");
        sts64(sb + OFF_GP + sq[i] * 64 + dr[i] * 8, ps[2 * i], ps[2 * i + 1]);
      }
      bar_sync(10, 192);
      const uint32_t ln = lds32(sb + OFF_LEN + min(lane, 11) * 4), tot = __dp4a(ln, 0x01010101u, 0u);
      inc = tot;
#pragma unroll
      for (int o = 1; o < 16; o <<= 1) asm("{.reg .pred p; .reg .b32 y; shfl.sync.up.b32 y|p, %0, %1, 0, -1; @p add.u32 %0, %0, y;}" : "+r"(inc) : "r"(o));
      if (wid == 1) sts32(sb + OFF_CNT + 2048 + lane * 4, 0);
      if (tid < 12) { sts32(sb + OFF_LEN + 64 + tid * 4, inc - tot); if (inc > SCAP) sts32(sb + OFF_MISC + 8, 1); }
#pragma unroll
      for (int i = 0; i < 2; i++) sts32(ca[i], __dp4a(__shfl_sync(~0u, ln, sq[i] >> 2), 0x00010101u >> (24 - 8 * (sq[i] & 3)), __shfl_sync(~0u, inc - tot, sq[i] >> 2)) * 32 + dr[i] * 2);
    }
    bar_arrive(7, 384);
  }
  bar_sync(1, 384);
  STAMP(6);
  if (wid != 11 && !__shfl_sync(~0u, lds32(sb + OFF_MISC + 8), 0)) {
#pragma unroll
    for (int k = 0; k < 12; k++) { r0[k] = lds32(r0[k]); r1[k] = lds32(r1[k]); }
    const uint32_t id = wid * 256 + ((lane + cta) & 31) * 8;
    auto put = [&](uint32_t x, uint32_t v) { asm volatile("{.reg .pred p; setp.lt.u32 p, %0, 0x8000; @p st.shared.u16 [%0+%2], %1;}" :: "r"(x), "h"((uint16_t)v), "n"(sb + OFF_TS) : "memory"); };
#pragma unroll
    for (int k = 0; k < 12; k++) { put(r0[k] + vb[k].x, id + k * 2816); put(r1[k] + vb[k].y, id + k * 2816 + 4); }
  }
  STAMP(7);
  mbar_wait(sb + BAR_QR);
  asm volatile("setmaxnreg.inc.sync.aligned.u32 160;");
  uint32_t pa[8], sp[8], pq[16]; float chk = 0.f;
  {
    uint32_t hf[32], mp = 0; float a0[32], a1[32];
    const uint32_t an = sb + OFF_GP + wid * 256 + (lane & 15) * 8 + 6, n0 = lds16(an), n1 = lds16(an + 128);
#pragma unroll
    for (int j = 0; j < 8; j++) { const uint32_t nd = j < 4 ? n0 : n1; ldsm4(hf + 4 * j, (sb + OFF_H + nd * 128 + (((nd & 7) << 4) ^ (lane & 16))) ^ ((j & 3) << 5)); }
    const uint64_t db = DHI | ((sb + OFF_W + 8192) >> 4);
    wg_fence();
    rs64b<0>(a0, hf[0], hf[1], hf[2], hf[3], db); rs64b<1>(a0, hf[4], hf[5], hf[6], hf[7], db + 128); rs64b<1>(a0, hf[8], hf[9], hf[10], hf[11], db + 256); rs64b<1>(a0, hf[12], hf[13], hf[14], hf[15], db + 384);
    wg_commit();
    rs64b<0>(a1, hf[16], hf[17], hf[18], hf[19], db); rs64b<1>(a1, hf[20], hf[21], hf[22], hf[23], db + 128); rs64b<1>(a1, hf[24], hf[25], hf[26], hf[27], db + 256); rs64b<1>(a1, hf[28], hf[29], hf[30], hf[31], db + 384);
    wg_commit();
    asm volatile("wgmma.wait_group.sync.aligned 1;" ::: "memory"); fence_regs(a0);
#pragma unroll
    for (int j = 0; j < 8; j++) { const uint32_t x = pack_f16(a0[4 * j], a0[4 * j + 1]), y = pack_f16(a0[4 * j + 2], a0[4 * j + 3]); mp = hmag(hmag(mp, x), y);
      asm volatile("movmatrix.sync.aligned.m8n8.trans.b16 %0, %1;" : "=r"(pa[j]) : "r"(x)); asm volatile("movmatrix.sync.aligned.m8n8.trans.b16 %0, %1;" : "=r"(sp[j]) : "r"(y)); }
    wg_wait0(); fence_regs(a1);
    bar_arrive(4, NTHR);
#pragma unroll
    for (int j = 0; j < 16; j++) { pq[j] = pack_f16(a1[2 * j], a1[2 * j + 1]); mp = hmag(mp, pq[j]); }
    if (magr(mp) >= 0x7000) chk = __int_as_float(0x7FC00000);
  }
  if (wid == 0) STAMP(23);
  uint32_t bad;
  {
    const uint32_t ring = sb + OFF_RING + wid * STG, p2 = sb + OFF_P2 + wid * 2048;
    uint32_t lens = __shfl_sync(~0u, lds32(sb + OFF_LEN + wid * 4), 0);
    uint32_t rem = __dp4a(lens, 0x20202020u, 0u);
    const uint32_t base = min(lds32(sb + OFF_LEN + 64 + wid * 4), SCAP);
    uint32_t a_s = sb + OFF_TS + base * 32 + (lane >> 3) * 8, a_e = sb + OFF_TE + base * 64 + (lane >> 1) * 4;
    uint32_t k0 = (uint32_t)(uint64_t)p.q + (((lane & 7) ^ ((lane >> 1) & 4)) << 4), k1 = k0 ^ 16, k2 = k0 ^ 32, k3 = k0 ^ 48, ke = ((lane ^ (lane >> 3)) & 1) << 4;
    uint32_t dst0 = ring + (lane >> 3) * 640 + (lane & 7) * 16;
    const uint32_t qhi = (uint32_t)((uint64_t)p.q >> 32), ehi = (uint32_t)((uint64_t)p.ea >> 32);
    uint32_t s0, s1, ev, to = 0, so = 12 * STG;
    auto tl_ = [&]() { lds64(s0, s1, a_s + to); asm volatile("ld.shared.u32 %0, [%1]; add.u32 %1, %1, 64;" : "=&r"(ev), "+r"(a_e) :: "memory"); to += 32; };
#define CPQ(LH, x, k, off) "dp2a." LH ".u32.u32 lo, " x ", 0x80000080, " k "; mov.b64 a, {lo, %7}; @p cp.async.cg.shared.global [%0+" #off "], [a], 16;\n"
#define CPE "or.b32 lo, %10, %11; mov.b64 a, {lo, %12}; @p cp.async.cg.shared.global" ESZ " [%0+512], [a], 16;\n"
#define CPA(BODY) asm volatile("{.reg .b32 lo; .reg .b64 a; .reg .pred p; setp.le.u32 p, %8, %9;\n" BODY "}" \
      :: "r"(dst0 + so), "r"(s0), "r"(s1), "r"(k0), "r"(k1), "r"(k2), "r"(k3), "r"(qhi), "r"(to), "r"(rem), "r"(ev), "r"(ke), "r"(ehi) : "memory")
#define CPQ4 CPQ("lo", "%1", "%3", 0) CPQ("hi", "%1", "%4", 128) CPQ("lo", "%2", "%5", 256) CPQ("hi", "%2", "%6", 384) "cp.async.commit_group;"
    auto issue = [&]() { CPA(CPE CPQ4); so = so == (NST - 1) * 12 * STG ? 0 : so + 12 * STG; };
    const int g = lane >> 2, qd = lane & 3;
    const uint32_t sw = ((lane >> 4) ^ (lane & 7)) << 4, fr = (lane & 15) * 128 + sw;
    uint32_t qa0 = ring + (g & 3) * 640 + qd * 128 + sw, qa1 = qa0 ^ 32, qa2 = qa0 ^ 64, qa3 = qa0 ^ 96;
    uint32_t eadr = ring + 512 + (g & 3) * 640 + qd * 32 + ((((lane >> 4) ^ g) & 1) << 4);
    uint32_t oh0 = g == 2 * qd ? 0x3C00u : g == 2 * qd + 1 ? 0x3C000000u : 0u, oh1 = oh0;
    uint32_t a_g = sb + OFF_GP + wid * 256 + lane * 2;
    uint32_t a_n = sb + OFF_GP + wid * 256 + (lane & 15) * 8 + 6;
    uint32_t a_p = ((lane & 8) ? p2 : sb + OFF_WD) + (lane & 7) * 128 + ((((lane >> 4) ^ lane) & 7) << 4);
    uint32_t a_w = sb + OFF_W3 + fr;
#define OPQ4(A, B, C, D) asm volatile("shfl.sync.bfly.b32 %0, %0, 0, 31, -1; shfl.sync.bfly.b32 %1, %1, 0, 31, -1; shfl.sync.bfly.b32 %2, %2, 0, 31, -1; shfl.sync.bfly.b32 %3, %3, 0, 31, -1;" : "+r"(A), "+r"(B), "+r"(C), "+r"(D))
    asm volatile("shfl.sync.idx.b32 %0, %0, %1, 31, -1;" : "+r"(oh1) : "r"(lane));
    if (OPQ & 1) OPQ4(a_w, oh0, ke, dst0);
    if (OPQ & 2) OPQ4(qa0, qa1, qa2, qa3);
    if (OPQ & 4) OPQ4(k0, k1, k2, k3);
    if (OPQ & 8) OPQ4(a_g, a_n, a_p, eadr);
    uint32_t w3[16], wv[8], bp[16], sum[8], Y[16], M[16], own, ownp, dpk; uint16_t tl[16], th[16];
    float pacc = 0.f;
    const uint32_t n0_ = __shfl_sync(~0u, node0 + lane, 0), nl = __shfl_sync(~0u, nloc + lane, 0);
    const char* outh = (const char*)p.out + (size_t)n0_ * 128;
    auto wload = [&]() {
#pragma unroll
      for (int j = 0; j < 4; j++) ldsm4t(w3 + 4 * j, a_w ^ (j << 5));
      lds128(wv, sb + OFF_WX + (a_g & 6) * 16); lds128(wv + 4, sb + OFF_WX + 16 + (a_g & 6) * 16);
    };
    auto hload = [&](uint32_t (&hf)[16], uint32_t nd) {
      const uint32_t hrow = sb + OFF_H + nd * 128 + (((nd & 7) << 4) ^ ((a_g >> 1) & 16));
#pragma unroll
      for (int j = 0; j < 4; j++) ldsm4(hf + 4 * j, hrow ^ (j << 5));
      return hrow;
    };
    auto bload = [&](uint32_t o) {
#pragma unroll
      for (int j = 0; j < 4; j++) ldsm4t(bp + 4 * j, (a_p ^ (j << 5)) + o);
    };
    { uint32_t wd[8]; const uint32_t a = sb + OFF_WD + (lane & 7) * 128 + ((((lane >> 3) ^ lane) & 7) << 4);
      ldsm4t(wd, a); ldsm4t(wd + 4, a ^ 64);
#pragma unroll
      for (int j = 0; j < 8; j++) { bp[2 * j] = wd[j]; bp[2 * j + 1] = pa[j]; } }
    own = lds16(a_g) * 0x10001u;
    wload();
    if (__shfl_sync(~0u, lds32(sb + OFF_MISC + 8), 0)) rem = 0;
    auto resolve = [&](auto NBK, uint32_t o) {
      constexpr int NB = decltype(NBK)::value;
      uint32_t id[NB], c0[NB], c1[NB]; const uint32_t a = base * 32 + o + lane * 4;
#pragma unroll
      for (int i = 0; i < NB; i++) { id[i] = lds32(sb + OFF_TS + a + i * 128); if (o + lane * 4 + i * 128 >= rem) id[i] = XPAD * 0x10001u; }
      uint32_t st = 0;
#pragma unroll
      for (int i = 0; i < NB; i++) { c0[i] = lds32(sb + OFF_XB + (id[i] & 0xFFFF)); c1[i] = lds32(sb + OFF_XB + (id[i] >> 16)); }
#pragma unroll
      for (int i = 0; i < NB; i++) st |= (c0[i] ^ tag) | (c1[i] ^ tag);
      for (int spin = 0; __any_sync(~0u, st >> 30); spin++) {
        st = 0; trap_if(spin > 2000000);
#pragma unroll
        for (int i = 0; i < NB; i++) {
          asm volatile("{.reg .pred p, q; setp.lt.u32 p, %4, %6; setp.lt.u32 q, %5, %6; @p ld.relaxed.gpu.global.u32 %0, [%2]; @q ld.relaxed.gpu.global.u32 %1, [%3];}"
            : "+r"(c0[i]), "+r"(c1[i]) : "l"((const char*)p.xb + cta * XPAD + (id[i] & 0xFFFF)), "l"((const char*)p.xb + cta * XPAD + (id[i] >> 16)), "r"(id[i] & 0xFFFF), "r"(id[i] >> 16), "n"(XPAD) : "memory");
          st |= (c0[i] ^ tag) | (c1[i] ^ tag); }
      }
#pragma unroll
      for (int i = 0; i < NB; i++) { const uint32_t j0 = (id[i] >> 8) & 255, j1 = id[i] >> 24;
        if (ABL & 2) { c0[i] &= 0xFFFF0FFFu; c1[i] &= 0xFFFF0FFFu; }
        asm volatile("{.reg .pred p, q, r; setp.lt.u32 p, %5, %9; setp.lt.u32 q, %6, %9; setp.lt.u32 r, %7, %8;\n"
          "@p st.shared.u32 [%0], %2; @q st.shared.u32 [%0+4], %3; @r st.shared.u32 [%1], %4;}"
          :: "r"(sb + OFF_TE + 2 * a + i * 256), "r"(sb + OFF_TS + a + i * 128), "r"(mad16(c0[i], 0x2000u, eb0 + ((ABL & 1) ? j0 & 7 : j0) * p.EPC * 32)), "r"(mad16(c1[i], 0x2000u, eb0 + ((ABL & 1) ? j1 & 7 : j1) * p.EPC * 32)),
             "r"(__byte_perm(c0[i], c1[i], 0x5410)), "r"(j0), "r"(j1), "r"(o + lane * 4 + i * 128), "r"(rem), "n"(G) : "memory"); }
    };
    bar_sync(2, 384);
    if (wid == 0) STAMP(27);
    mbar_wait(sb + BAR_HB);
    if (wid == 0) STAMP(22);
#pragma unroll 1
    for (uint32_t o = 0, go = 0; go < 32 * NST; o += 128 * RNB) {
      if (o < rem) { resolve(IC<RNB>(), o);
        asm volatile("{.reg .pred p; mbarrier.test_wait.parity.shared::cta.b64 p, [%1], 0; vote.sync.all.pred p, p, -1; selp.u32 %0, %2, 0, p;}" : "=r"(go) : "r"(sb + BAR_QP), "n"(32 * NEARLY) : "memory"); }
      else { bar_sync(8, 384); mbar_wait(sb + BAR_QP); go = 32 * NST; if (wid == 0) STAMP(24); }
      __syncwarp();
#pragma unroll 1
      while (to < go) { tl_(); issue(); if (to == 32) STAMP(13); }
    }
    bad = __shfl_sync(~0u, lds32(sb + OFF_MISC + 8), 0);
   if (!bad) {
#pragma unroll
    for (int j = 0; j < 4; j++) stsm4((p2 + fr) ^ (j << 5), pq[4 * j], pq[4 * j + 1], pq[4 * j + 2], pq[4 * j + 3]);
    auto body = [&](auto MODE) {
      constexpr int mode = decltype(MODE)::value;
      uint32_t T[16], ef[4], q0, q1, x0, x1, x2; float e0_, e1_, cs[4];
      auto mu = [&](int j) {
#pragma unroll
        for (int i = 2 * j; i < 2 * j + 2; i++) asm volatile("{.reg .b16 l, h; mov.b32 {l, h}, %2; tanh.approx.f16 %0, l; tanh.approx.f16 %1, h;}" : "=h"(tl[i]), "=h"(th[i]) : "r"(Y[i])); };
      auto fi = [&](int j) {
#pragma unroll
        for (int i = 2 * j; i < 2 * j + 2; i++) asm volatile("{.reg .b32 t; mov.b32 t, {%2, %3}; fma.rn.f16x2 %0, %1, t, %1;}" : "=r"(M[i]) : "r"(Y[i]), "h"(tl[i]), "h"(th[i])); };
      auto ad = [&](int j) { asm volatile("add.rn.f16x2 %0, %0, %1; add.rn.f16x2 %0, %0, %2;" : "+r"(sum[j]) : "r"(M[2 * j]), "r"(M[2 * j + 1])); };
      auto he = [&](int j) { asm volatile("mma.sync.aligned.m16n8k16.row.col.f16.f16.f16.f16 {%0,%1}, {%2,%3,%4,%5}, {%6,%7}, {%0,%1};" : "+r"(T[2 * j]), "+r"(T[2 * j + 1]) : "r"(ef[0]), "r"(ef[1]), "r"(ef[2]), "r"(ef[3]), "r"(w3[2 * j]), "r"(w3[2 * j + 1])); };
      auto hs = [&](int j) { asm volatile("mma.sync.aligned.m16n8k16.row.col.f16.f16.f16.f16 {%0,%1}, {%2,%3,%4,%5}, {%6,%7}, {%8,%9};" : "=r"(Y[2 * j]), "=r"(Y[2 * j + 1]) : "r"(q0), "r"(q1), "r"(oh0), "r"(oh1), "r"(bp[2 * j]), "r"(bp[2 * j + 1]), "r"(T[2 * j]), "r"(T[2 * j + 1])); };
      auto hc = [&](int j) {
        if (j) asm volatile("mma.sync.aligned.m16n8k16.row.col.f32.f16.f16.f32 {%0,%1,%2,%3}, {%4,%5,%6,%7}, {%8,%9}, {%0,%1,%2,%3};" : "+f"(cs[0]), "+f"(cs[1]), "+f"(cs[2]), "+f"(cs[3]) : "r"(M[4 * j]), "r"(M[4 * j + 1]), "r"(M[4 * j + 2]), "r"(M[4 * j + 3]), "r"(wv[2 * j]), "r"(wv[2 * j + 1]));
        else asm volatile("mma.sync.aligned.m16n8k16.row.col.f32.f16.f16.f32 {%0,%1,%2,%3}, {%4,%5,%6,%7}, {%8,%9}, {%10,%10,%10,%10};" : "=f"(cs[0]), "=f"(cs[1]), "=f"(cs[2]), "=f"(cs[3]) : "r"(M[0]), "r"(M[1]), "r"(M[2]), "r"(M[3]), "r"(wv[0]), "r"(wv[1]), "f"(0.f)); };
      auto cv = [&](int i) { asm volatile("{.reg .b32 a, b; shl.b32 a, %0, 16; and.b32 b, %0, 0xFFFF0000; cvt.rn.f16x2.f32 %0, b, a;}" : "+r"(ef[i])); };
      auto un = [&]() { asm volatile("shl.b32 %0, %2, 16; and.b32 %1, %2, 0xFFFF0000;" : "=&f"(e0_), "=&f"(e1_) : "r"(dpk)); };
      auto ex0 = [&]() { asm volatile("prmt.b32 %0, %3, %4, 0x6420; prmt.b32 %1, %5, %6, 0x6420; prmt.b32 %2, %7, %8, 0x6420;" : "=&r"(x0), "=&r"(x1), "=&r"(x2) : "r"(T[0]), "r"(T[1]), "r"(T[2]), "r"(T[3]), "r"(T[4]), "r"(T[5])); };
      auto ex1 = [&]() { asm volatile("{.reg .b32 a, b; shl.b32 a, %2, 3; shl.b32 b, %3, 6; lop3.b32 a, %1, a, 0x38383838, 0xD8; lop3.b32 a, a, b, 0xC0C0C0C0, 0xD8; sub.rn.bf16x2 %0, %4, a;}" : "=r"(dpk) : "r"(x0), "r"(x1), "r"(x2), "r"(own)); };
      auto ex2 = [&]() { asm volatile("{.reg .b32 a, b, d, u; .reg .b16 l, h; shl.b32 a, %2, 16; and.b32 b, %2, 0xFFFF0000; cvt.rn.f16x2.f32 d, b, a; mul.rn.f16x2 %0, d, d; mov.b32 {l, h}, d; mov.b32 u, {h, h}; mul.rn.f16x2 %1, u, u;}" : "=&r"(q0), "=&r"(q1) : "r"(dpk)); };
      auto pf = [&]() { asm volatile("fma.rn.f32 %0, %1, %2, %0; fma.rn.f32 %0, %3, %4, %0;" : "+f"(pacc) : "f"(cs[0]), "f"(e0_), "f"(cs[2]), "f"(e1_)); };
#define FX(k) if (FM >> k & 1) asm volatile("pmevent 1;" ::: "memory")
      if (mode == 2) {
        hc(0); mu(3); fi(2); un(); ad(0); ad(1); mu(4); fi(3); hc(1); mu(5); fi(4); ad(2); mu(6); fi(5); ad(3); hc(2); mu(7); fi(6); fi(7); ad(4); ad(5); hc(3); ad(6); ad(7); pf();
        return;
      }
      asm volatile("cp.async.wait_group %0;" :: "n"(NST - 1) : "memory");
      __syncwarp();
      if (mode == 1) STAMP(8);
      ldsm4(ef, eadr + so); ldsm4(T, qa0 + so); ldsm4(T + 4, qa1 + so); ldsm4(T + 8, qa2 + so); ldsm4(T + 12, qa3 + so);
      tl_();
      if (mode == 1) {
        issue();
        cv(0); cv(1); cv(2); cv(3); ex0(); ex1(); ex2();
#pragma unroll
        for (int j = 0; j < 8; j++) { he(j); hs(j); }
        mu(0); mu(1); fi(0); mu(2); fi(1);
        return;
      }
      hc(0); mu(3); fi(2); un(); ad(0); ad(1);
      FX(0);
      mu(4); fi(3); cv(0); cv(1); cv(2); cv(3); ex0(); ex1();
      FX(1);
      he(0); he(1); hc(1); mu(5); fi(4); ex2(); ad(2);
      FX(2);
      hs(0); he(2); mu(6); fi(5); issue(); ad(3);
      FX(3);
      hs(1); he(3); hc(2); mu(7); fi(6);
      FX(4);
      hs(2); hs(3); he(4); he(5); mu(0); fi(7); ad(4); ad(5);
      FX(5);
      hc(3); hs(4); he(6); he(7); mu(1); fi(0); ad(6);
      FX(6);
      hs(5); hs(6); hs(7); mu(2); fi(1); ad(7); pf();
      FX(7);
    };
#pragma unroll
    for (int j = 0; j < 8; j++) sum[j] = 0;
    body(IC<1>());
    int cnt = (lens & 255) - 1;
#pragma unroll 1
    for (int t = 0; t < 8; t++) {
#pragma unroll 1
      for (; cnt > 0; cnt--) { body(IC<0>());
      }
      if (!(t & 1)) {
        ownp = own;
        if (t < 6) {
          a_g += 64; own = lds16(a_g) * 0x10001u;
          if (t == 0) {
#pragma unroll
            for (int j = 0; j < 8; j++) bp[2 * j + 1] = sp[j];
          } else bload((a_g & 16) ? (t & 4) * 256 : 0);
          lens >>= 8; cnt = 1;
          continue;
        }
        body(IC<2>()); t++; a_g += 64;
        STAMP(9);
      }
      cnt = (lens & 255) - 1;
      asm volatile("{.reg .pred p; setp.ne.u32 p, %2, 6; @p st.shared.u16 [%0+-64], %1;}" :: "r"(a_g), "h"((uint16_t)pack_bf16(bf_hi(ownp) + pacc, 0.f)), "r"(a_g & 6) : "memory");
      chk = fmaf(pacc, 0.f, chk); pacc = 0.f;
      if (t & 2) {
        uint32_t hf[16]; float acc[32];
        const uint32_t nd = lds16(a_n);
        const uint32_t hrow = hload(hf, nd);
        a_n += 128;
        __syncwarp();
        mbar_arrive(sb + BAR_X, (a_g & 62) == 0);
        const uint64_t b1 = DHI | ((sb + OFF_W) >> 4), b2_ = b1 + 512;
        mbar_wait(sb + BAR_WH);
        wg_fence();
        rs64h<0>(acc, sp[0], sum[0], sp[1], sum[1], b2_); rs64h<1>(acc, sp[2], sum[2], sp[3], sum[3], b2_ + 128); rs64h<1>(acc, sp[4], sum[4], sp[5], sum[5], b2_ + 256); rs64h<1>(acc, sp[6], sum[6], sp[7], sum[7], b2_ + 384);
        rs64b<1>(acc, hf[0], hf[1], hf[2], hf[3], b1); rs64b<1>(acc, hf[4], hf[5], hf[6], hf[7], b1 + 128); rs64b<1>(acc, hf[8], hf[9], hf[10], hf[11], b1 + 256); rs64b<1>(acc, hf[12], hf[13], hf[14], hf[15], b1 + 384);
        wg_commit();
        uint32_t nr[4];
#pragma unroll
        for (int j = 0; j < 4; j++) nr[j] = __shfl_sync(~0u, nd, 4 * j + ((a_g >> 4) & 3)) * 128 + ((a_g << 3) & 0x70);
        wg_wait0(); fence_regs(acc);
        if (t == 7) STAMP(10);
        chk = fmaf(acc[0], 0.f, fmaf(acc[2], 0.f, chk));
        auto fin = [&](uint32_t x, float y0, float y1) { return u2(__hadd2(b2(x), b2(pack_bf16(silu_h(y0), silu_h(y1))))); };
#pragma unroll
        for (int j = 0; j < 4; j++) stsm4(hrow ^ (j << 5), fin(hf[4 * j], acc[8 * j], acc[8 * j + 1]), fin(hf[4 * j + 1], acc[8 * j + 2], acc[8 * j + 3]), fin(hf[4 * j + 2], acc[8 * j + 4], acc[8 * j + 5]), fin(hf[4 * j + 3], acc[8 * j + 6], acc[8 * j + 7]));
        __syncwarp();
        if (DEFO && t == 3) mbar_arrive(sb + BAR_M, (a_g & 62) == 0);
        else {
          uint32_t v[16];
#pragma unroll
          for (int j = 0; j < 4; j++) lds128(v + 4 * j, sb + OFF_H + (nr[j] ^ ((nr[j] >> 3) & 0x70)));
#pragma unroll
          for (int j = 0; j < 4; j++) asm volatile("{.reg .pred p; setp.lt.u32 p, %5, %6; @p st.global" OCS ".v4.b32 [%0], {%1,%2,%3,%4};}" :: "l"(outh + nr[j]), "r"(v[4 * j]), "r"(v[4 * j + 1]), "r"(v[4 * j + 2]), "r"(v[4 * j + 3]), "r"(nr[j]), "r"(nl * 128) : "memory");
          if (DEFO) break;
        }
        wload();
      }
#pragma unroll
      for (int j = 0; j < 8; j++) { sp[j] = sum[j]; asm volatile("mov.b32 %0, 0;" : "=r"(sum[j])); }
    }
    asm volatile("{.reg .pred p, q; setp.neu.f32 p, %1, 0f00000000; setp.ne.or.u32 p, %2, 0, p; bar.red.or.pred q, 5, %3, p; selp.u32 %0, 1, 0, q;}" : "=r"(bad) : "f"(chk), "r"(lds32(sb + OFF_MISC + 12)), "n"(DEFO ? 512 : 384) : "memory");
    STAMP(11);
   } else { asm volatile("cp.async.wait_all;" ::: "memory"); bar_sync(5, 384); }
  }
  if (bad) slow_path(p, wid, lane, node0, nloc);
}

}

typedef CUresult (*EncodeFn)(CUtensorMap*, CUtensorMapDataType, cuuint32_t, void*, const cuuint64_t*, const cuuint64_t*, const cuuint32_t*, const cuuint32_t*,
                             CUtensorMapInterleave, CUtensorMapSwizzle, CUtensorMapL2promotion, CUtensorMapFloatOOBfill);

extern "C" void kernel_launch(void* const* d_in, const int* in_sizes, int n_in, void* d_out, int out_size) {
  Params p; Maps maps;
  p.h = (const uint4*)d_in[0]; p.pos = (const uint16_t*)d_in[1]; p.ea = (const uint4*)d_in[2];
  p.src = (const int*)d_in[3]; p.dst = (const int*)d_in[4];
  p.we = (const uint16_t*)d_in[5]; p.wx = (const uint16_t*)d_in[6]; p.wh = (const uint16_t*)d_in[7];
  p.out = (uint16_t*)d_out;
  p.N = in_sizes[0] / 64; p.E = in_sizes[3];
  p.EPC = ((p.E + G * 4 - 1) / (G * 4)) * 4;
  p.magic = (uint32_t)(((uint64_t)G << 24) / (uint64_t)p.N);
  p.inv = (1ull << 56) / p.magic;
  const uint64_t ea0 = (uint64_t)d_in[2], ea1 = ea0 + (uint64_t)p.E * 32 - 1;
  p.force_slow = ((ea0 >> 32) != (ea1 >> 32)) || (ea0 & 31) || (p.E & 3);
  void* qp = nullptr;
  cudaGetSymbolAddress(&qp, g_q);
  p.q = (char*)qp;
  if (((uint64_t)p.q >> 32) != (((uint64_t)p.q + QBYTES) >> 32)) p.q += QBYTES;
  cudaGetSymbolAddress((void**)&p.sync, g_sync); cudaGetSymbolAddress((void**)&p.xe, g_xe);
  cudaGetSymbolAddress((void**)&p.xa, g_xa); cudaGetSymbolAddress((void**)&p.xb, g_xb);
  void* fn = nullptr; cudaDriverEntryPointQueryResult qr;
  cudaGetDriverEntryPoint("cuTensorMapEncodeTiled", &fn, cudaEnableDefault, &qr);
  auto mk = [&](CUtensorMap* tm, void* base, int rows, int box = 64) {
    const cuuint64_t dim[2] = {64, (cuuint64_t)rows}, str[1] = {128}; const cuuint32_t bx[2] = {64, (cuuint32_t)box}, es[2] = {1, 1};
    ((EncodeFn)fn)(tm, CU_TENSOR_MAP_DATA_TYPE_BFLOAT16, 2, base, dim, str, bx, es, CU_TENSOR_MAP_INTERLEAVE_NONE, CU_TENSOR_MAP_SWIZZLE_128B,
                   CU_TENSOR_MAP_L2_PROMOTION_NONE, CU_TENSOR_MAP_FLOAT_OOB_FILL_NONE);
  };
  mk(&maps.m[TM_H / 128], d_in[0], p.N); mk(&maps.m[TM_WE / 128], d_in[5], 145); mk(&maps.m[TM_WH / 128], d_in[7], 128); mk(&maps.m[TM_Q / 128], p.q, p.N, 16);
  for (int k = 0; k < 2; k++) {
    void* xp = (void*)(k ? p.xb : p.xa);
    const cuuint64_t dim[2] = {(cuuint64_t)G * 64, (cuuint64_t)G}, str[1] = {(cuuint64_t)G * (128 << k)}; const cuuint32_t bx[2] = {64, (cuuint32_t)(k ? BROWS : G)}, es[2] = {1, 1};
    ((EncodeFn)fn)(&maps.m[TM_XA / 128 + k], k ? CU_TENSOR_MAP_DATA_TYPE_UINT32 : CU_TENSOR_MAP_DATA_TYPE_UINT16, 2, xp, dim, str, bx, es, CU_TENSOR_MAP_INTERLEAVE_NONE,
                   CU_TENSOR_MAP_SWIZZLE_NONE, CU_TENSOR_MAP_L2_PROMOTION_NONE, CU_TENSOR_MAP_FLOAT_OOB_FILL_NONE);
  }
  cudaFuncSetAttribute(egnn_kernel, cudaFuncAttributeMaxDynamicSharedMemorySize, SMEM);
  egnn_kernel<<<G, NTHR, SMEM>>>(p, maps);
}
```

```cpp
#include <cuda_runtime.h>
#include <cuda_bf16.h>
#include <cuda_fp16.h>
#include <cuda.h>
#include <stdint.h>
#pragma nv_diag_suppress 549

#define PFN 16
#define PFNS 250
#define FM 0
#define OPQ 0
#define H0 0
#define HALL 1
#define PF0NS 0
#define PFW 0
#define QCODE 0x254a109b7863ull
#define QREV 0x605
#define PFS 1
#define ESZ ""
#define XEF 0
#define OCS ""
#define RNB 2
#define NEARLY 2
#define PFE 0
#define DEFO 1
#define DEFNS 400
#define ABL 0
#define HW 3
#define BROWS 132
#define B_HOLD 1
#define LSEQ 0x231200ull
#define HE 0
namespace {

constexpr int G = 132;
constexpr int NTHR = 512, NWK = 352, NCH = 5;
constexpr int NST = 3, STG = 2560;
constexpr int SCAP = 448;

constexpr int OFF_H = 0;
constexpr int OFF_W = 49152;
constexpr int OFF_WD = OFF_W + 16384;
constexpr int OFF_W3 = OFF_WD + 1024;
constexpr int OFF_P2 = OFF_W3 + 2048;
constexpr int OFF_RING = OFF_P2 + 24576;
constexpr int OFF_TE = OFF_RING + 12 * NST * STG;
constexpr int OFF_TS = OFF_TE + SCAP * 64;
constexpr int OFF_GP = OFF_TS + SCAP * 32;
constexpr int OFF_WX = OFF_GP + 3072;
constexpr int OFF_LEN = OFF_WX + 128;
constexpr int OFF_MISC = OFF_LEN + 128;
constexpr int OFF_BAR = OFF_MISC + 48;
constexpr int SMEM = OFF_BAR + 256;
static_assert(SMEM <= 232448, "smem");
constexpr uint32_t sb = 1024;
constexpr int OFF_SRCI = OFF_TE;
constexpr int OFF_SB = OFF_RING, OFF_SA = OFF_SB + 34816, OFF_AX = OFF_SA + 32768, OFF_DST = OFF_H + 24576;
constexpr int OFF_WS = OFF_AX + 17408;
constexpr int OFF_BC = OFF_WS + 2304;
constexpr int OFF_CNT = OFF_P2;
constexpr int OFF_DH = OFF_CNT + 2176;
constexpr int OFF_POS = OFF_DH + 128;
constexpr int OFF_EXT = OFF_POS + 3072;
constexpr int OFF_XB = OFF_EXT + 1024, XPAD = G * 256;
static_assert(OFF_XB + XPAD + 1028 <= OFF_RING + 12 * STG && OFF_XB % 128 == 0 && OFF_BC + 544 <= OFF_TE && OFF_P2 % 1024 == 0 && OFF_SA % 1024 == 0 && SCAP * 64 >= 24576, "staging");
constexpr int BAR_DST = OFF_BAR, BAR_SRC = BAR_DST + 40, BAR_T = BAR_SRC + 24, BAR_W = BAR_T + 48, BAR_XA = BAR_W + 8, BAR_PS = BAR_XA + 8, BAR_AW = BAR_PS + 8,
              BAR_QP = BAR_AW + 8, BAR_QR = BAR_QP + 8, BAR_HA = BAR_QR + 8, BAR_EP = BAR_HA + 8, BAR_AX = BAR_EP + 8, BAR_AI = BAR_AX + 8, BAR_HB = BAR_AI + 8, BAR_U = BAR_HB + 8, BAR_WH = BAR_U + 8, BAR_M = BAR_WH + 8, BAR_X = BAR_M + 8, BAR_END = BAR_X + 8;
static_assert(BAR_END <= OFF_BAR + 256, "barriers");
constexpr uint32_t QBYTES = 8u << 20;

__device__ __align__(256) uint4 g_xa[G * G * 8];
__device__ __align__(256) uint4 g_xb[G * G * 16];
__device__ __align__(256) uint2 g_xe[G * G * 32];
__device__ __align__(256) uint4 g_q[2 * QBYTES / 16];
__device__ __align__(256) uint32_t g_sync[8];
#define STAMP(k)

struct Maps { CUtensorMap m[6]; };
constexpr int TM_H = 0, TM_WE = 128, TM_WH = 256, TM_Q = 384, TM_XA = 512, TM_XB = 640;
struct Params {
  const int* dst; uint32_t* sync; int E, EPC, N; uint32_t magic; unsigned long long inv;
  const int* src; const uint16_t* pos; const uint4* ea; const uint16_t* we; const uint16_t* wx; char* q; int force_slow;
  const uint4* xa; const uint4* xb; uint2* xe; uint16_t* out; const uint4* h; const uint16_t* wh;
};
template<int V> struct IC { static constexpr int value = V; };

#define R32(d) "+f"(d[0]),"+f"(d[1]),"+f"(d[2]),"+f"(d[3]),"+f"(d[4]),"+f"(d[5]),"+f"(d[6]),"+f"(d[7]),"+f"(d[8]),"+f"(d[9]),"+f"(d[10]),"+f"(d[11]),"+f"(d[12]),"+f"(d[13]),"+f"(d[14]),"+f"(d[15]),"+f"(d[16]),"+f"(d[17]),"+f"(d[18]),"+f"(d[19]),"+f"(d[20]),"+f"(d[21]),"+f"(d[22]),"+f"(d[23]),"+f"(d[24]),"+f"(d[25]),"+f"(d[26]),"+f"(d[27]),"+f"(d[28]),"+f"(d[29]),"+f"(d[30]),"+f"(d[31])
#define S32 "{%0,%1,%2,%3,%4,%5,%6,%7,%8,%9,%10,%11,%12,%13,%14,%15,%16,%17,%18,%19,%20,%21,%22,%23,%24,%25,%26,%27,%28,%29,%30,%31}"
#define DI __device__ __forceinline__

constexpr uint64_t DHI = ((uint64_t)(1024 >> 4) << 32) | (1ull << 62);
template<int SD> DI void rs64b(float (&d)[32], uint32_t a0, uint32_t a1, uint32_t a2, uint32_t a3, uint64_t db) {
  asm volatile("wgmma.mma_async.sync.aligned.m64n64k16.f32.bf16.bf16 " S32 ", {%32,%33,%34,%35}, %36, %37, 1, 1, 1;" : R32(d) : "r"(a0), "r"(a1), "r"(a2), "r"(a3), "l"(db), "n"(SD)); }
template<int SD> DI void rs64h(float (&d)[32], uint32_t a0, uint32_t a1, uint32_t a2, uint32_t a3, uint64_t db) {
  asm volatile("wgmma.mma_async.sync.aligned.m64n64k16.f32.f16.f16 " S32 ", {%32,%33,%34,%35}, %36, %37, 1, 1, 1;" : R32(d) : "r"(a0), "r"(a1), "r"(a2), "r"(a3), "l"(db), "n"(SD)); }
template<int SD> DI void ss64(float (&d)[32], uint64_t da, uint64_t db) {
  asm volatile("wgmma.mma_async.sync.aligned.m64n64k16.f32.bf16.bf16 " S32 ", %32, %33, %34, 1, 1, 0, 1;" : R32(d) : "l"(da), "l"(db), "n"(SD)); }
DI void trap_if(bool c) { asm volatile("{.reg .pred p; setp.eq.u32 p, %0, 0; @p bra.uni LT_%=; trap; LT_%=:}" :: "r"((uint32_t)c)); }
DI void wg_fence() { asm volatile("wgmma.fence.sync.aligned;" ::: "memory"); }
DI void wg_commit() { asm volatile("wgmma.commit_group.sync.aligned;" ::: "memory"); }
DI void wg_wait0() { asm volatile("wgmma.wait_group.sync.aligned 0;" ::: "memory"); }
DI void fence_regs(float (&d)[32]) { asm volatile("" : R32(d) :: "memory"); }
DI void proxy_fence() { asm volatile("fence.proxy.async.shared::cta;" ::: "memory"); }
DI uint64_t pol_first() { uint64_t r; asm("createpolicy.fractional.L2::evict_first.b64 %0, 1.0;" : "=l"(r)); return r; }
DI float tanh_ap(float x) { float y; asm("tanh.approx.f32 %0, %1;" : "=f"(y) : "f"(x)); return y; }
DI float silu_h(float y) { return fmaf(y, tanh_ap(y), y); }
DI uint32_t pack_bf16(float lo, float hi) { uint32_t r; asm("cvt.rn.bf16x2.f32 %0, %1, %2;" : "=r"(r) : "f"(hi), "f"(lo)); return r; }
DI uint32_t pack_f16(float lo, float hi) { uint32_t r; asm("cvt.rn.f16x2.f32 %0, %1, %2;" : "=r"(r) : "f"(hi), "f"(lo)); return r; }
DI float bf_lo(uint32_t v) { return __uint_as_float(v << 16); }
DI float bf_hi(uint32_t v) { return __uint_as_float(v & 0xFFFF0000u); }
DI uint32_t b2h(uint32_t v, float s) { return pack_f16(s * bf_lo(v), s * bf_hi(v)); }
DI void mbar_wait(uint32_t bar, uint32_t parity = 0) {
  asm volatile("{.reg .pred p; .reg .u32 t0, t1;\n"
    "mbarrier.try_wait.parity.shared::cta.b64 p, [%0], %1;\n @p bra.uni LD_%=;\n mov.u32 t0, %%clock;\n"
    "LW_%=: mbarrier.try_wait.parity.shared::cta.b64 p, [%0], %1;\n"
    "@p bra.uni LD_%=;\n mov.u32 t1, %%clock; sub.u32 t1, t1, t0; setp.lt.u32 p, t1, 0x80000000;\n @p bra.uni LW_%=;\n trap;\n LD_%=:}" :: "r"(bar), "r"(parity) : "memory");
}
DI void mbar_arrive(uint32_t bar, int p = 1) { asm volatile("{.reg .pred p; setp.ne.b32 p, %1, 0; @p mbarrier.arrive.shared::cta.b64 _, [%0];}" :: "r"(bar), "r"(p) : "memory"); }
DI void bar_sync(int id, int n) { asm volatile("bar.sync %0, %1;" :: "r"(id), "r"(n) : "memory"); }
DI void bar_arrive(int id, int n) { asm volatile("bar.arrive %0, %1;" :: "r"(id), "r"(n) : "memory"); }
DI __nv_bfloat162 b2(uint32_t v) { return *(__nv_bfloat162*)&v; }
DI uint32_t u2(__nv_bfloat162 v) { return *(uint32_t*)&v; }
DI uint32_t hsq(uint32_t v) { return u2(__hmul2(b2(v), b2(v))); }
DI uint32_t hsub(uint32_t a, uint32_t b) { return u2(__hsub2(b2(a), b2(b))); }
DI uint32_t hhalf(uint32_t v) { return u2(__hmul2(b2(v), __floats2bfloat162_rn(0.5f, 0.5f))); }
DI uint32_t mag2(uint32_t m, uint32_t v) { return __vmaxu2(m, v & 0x7FFF7FFFu); }
DI uint32_t hmag(uint32_t m, uint32_t v) { const __half2 r = __hmax2(*(const __half2*)&m, __habs2(*(const __half2*)&v)); return *(const uint32_t*)&r; }
DI uint32_t magr(uint32_t m) { return max(m & 0xFFFF, m >> 16); }
DI void sts128(uint32_t a, uint32_t x, uint32_t y, uint32_t z, uint32_t w) { asm volatile("st.shared.v4.u32 [%0], {%1,%2,%3,%4};" :: "r"(a), "r"(x), "r"(y), "r"(z), "r"(w) : "memory"); }
DI void sts64(uint32_t a, uint32_t x, uint32_t y) { asm volatile("st.shared.v2.u32 [%0], {%1,%2};" :: "r"(a), "r"(x), "r"(y) : "memory"); }
DI void sts32(uint32_t a, uint32_t x) { asm volatile("st.shared.u32 [%0], %1;" :: "r"(a), "r"(x) : "memory"); }
DI void sts16(uint32_t a, uint32_t x) { asm volatile("st.shared.u16 [%0], %1;" :: "r"(a), "h"((uint16_t)x) : "memory"); }
DI void lds128(uint32_t* v, uint32_t a) { asm volatile("ld.shared.v4.u32 {%0, %1, %2, %3}, [%4];" : "=r"(v[0]), "=r"(v[1]), "=r"(v[2]), "=r"(v[3]) : "r"(a) : "memory"); }
DI void lds64(uint32_t& x, uint32_t& y, uint32_t a) { asm volatile("ld.shared.v2.u32 {%0, %1}, [%2];" : "=r"(x), "=r"(y) : "r"(a) : "memory"); }
DI uint32_t lds32(uint32_t a) { uint32_t x; asm volatile("ld.shared.u32 %0, [%1];" : "=r"(x) : "r"(a) : "memory"); return x; }
DI uint32_t lds16(uint32_t a) { uint32_t x; asm volatile("ld.shared.u16 %0, [%1];" : "=r"(x) : "r"(a) : "memory"); return x; }
DI uint32_t atoms_add(uint32_t a, uint32_t v) { uint32_t r; asm volatile("atom.shared.add.u32 %0, [%1], %2;" : "=r"(r) : "r"(a), "r"(v) : "memory"); return r; }
DI void bulk_load(uint32_t dst, const void* src, uint32_t bytes, uint32_t bar) {
  asm volatile("cp.async.bulk.shared::cluster.global.mbarrier::complete_tx::bytes.L2::cache_hint [%0], [%1], %2, [%3], %4;" :: "r"(dst), "l"(src), "r"(bytes), "r"(bar), "l"(pol_first()) : "memory"); }
DI void bulk_store(void* dst, uint32_t src, uint32_t bytes) { asm volatile("cp.async.bulk.global.shared::cta.bulk_group [%0], [%1], %2;" :: "l"(dst), "r"(src), "r"(bytes) : "memory"); }
DI void mbar_expect(uint32_t bar, uint32_t bytes) { asm volatile("mbarrier.arrive.expect_tx.shared::cta.b64 _, [%0], %1;" :: "r"(bar), "r"(bytes) : "memory"); }
DI void mbar_init(uint32_t bar, int n) { asm volatile("mbarrier.init.shared::cta.b64 [%0], %1;" :: "r"(bar), "r"(n) : "memory"); }
DI void tma_load(uint32_t dst, uint64_t tm, int row, uint32_t bar) {
  asm volatile("cp.async.bulk.tensor.2d.shared::cluster.global.mbarrier::complete_tx::bytes.L2::cache_hint [%0], [%1, {%3, %4}], [%2], %5;" :: "r"(dst), "l"(tm), "r"(bar), "r"(0), "r"(row), "l"(pol_first()) : "memory"); }
DI void tma_store(uint64_t tm, int col, int row, uint32_t src) {
  asm volatile("cp.async.bulk.tensor.2d.global.shared::cta.bulk_group [%0, {%2, %3}], [%1];" :: "l"(tm), "r"(src), "r"(col), "r"(row) : "memory"); }
DI void tma_store_ef(uint64_t tm, int col, int row, uint32_t src) {
  if (XEF) asm volatile("cp.async.bulk.tensor.2d.global.shared::cta.bulk_group.L2::cache_hint [%0, {%2, %3}], [%1], %4;" :: "l"(tm), "r"(src), "r"(col), "r"(row), "l"(pol_first()) : "memory");
  else tma_store(tm, col, row, src); }
DI void bulk_commit() { asm volatile("cp.async.bulk.commit_group;" ::: "memory"); }
DI void bulk_wait_read() { asm volatile("cp.async.bulk.wait_group.read 0;" ::: "memory"); }
DI uint2 ld_poll2(const void* a) { uint2 v; asm volatile("ld.relaxed.gpu.global.v2.u32 {%0, %1}, [%2];" : "=r"(v.x), "=r"(v.y) : "l"(a) : "memory"); return v; }
DI void st_ext(uint2* a, uint32_t v, uint32_t ep) { asm volatile("st.relaxed.gpu.global.v2.u32 [%0], {%1, %2};" :: "l"(a), "r"(v), "r"(ep) : "memory"); }
DI uint32_t ext_get(const uint2* a, uint32_t ep) { uint2 v; int spin = 0; do { v = ld_poll2(a); trap_if(++spin > 4000000); } while (__any_sync(~0u, v.y != ep)); return v.x; }
DI void bulk_wait() { asm volatile("cp.async.bulk.wait_group 0;" ::: "memory"); }
DI void hint_signal(uint32_t* c) { asm volatile("red.relaxed.gpu.global.add.u32 [%0], 1;" :: "l"(c) : "memory"); }
DI void hint_wait(const uint32_t* c, uint32_t target) { uint32_t v; int spin = 0;
  do { asm volatile("ld.relaxed.gpu.global.u32 %0, [%1];" : "=r"(v) : "l"(c) : "memory"); trap_if(++spin > 4000000); } while (__any_sync(~0u, (int)(v - target) < 0)); }
DI void stsm4(uint32_t a, uint32_t x, uint32_t y, uint32_t z, uint32_t w) { asm volatile("stmatrix.sync.aligned.m8n8.x4.shared.b16 [%0], {%1,%2,%3,%4};" :: "r"(a), "r"(x), "r"(y), "r"(z), "r"(w) : "memory"); }
DI void ldsm4(uint32_t* v, uint32_t a) { asm volatile("ldmatrix.sync.aligned.m8n8.x4.shared.b16 {%0,%1,%2,%3}, [%4];" : "=r"(v[0]), "=r"(v[1]), "=r"(v[2]), "=r"(v[3]) : "r"(a) : "memory"); }
DI void ldsm4t(uint32_t* v, uint32_t a) { asm volatile("ldmatrix.sync.aligned.m8n8.x4.trans.shared.b16 {%0,%1,%2,%3}, [%4];" : "=r"(v[0]), "=r"(v[1]), "=r"(v[2]), "=r"(v[3]) : "r"(a) : "memory"); }
DI uint32_t mad16(uint32_t x, uint32_t m, uint32_t c) { uint32_t r; asm("dp2a.lo.u32.u32 %0, %1, %2, %3;" : "=r"(r) : "r"(x), "r"(m), "r"(c)); return r; }
DI bool wbad(uint32_t m, uint32_t hi) { return m > hi || (m && m < 0x3980); }

__device__ __noinline__ void slow_path(const Params& p, int wid, int lane, int node0, int nloc) {
  const uint32_t ab = sb + OFF_P2 + wid * 8704;
  for (int i = lane; i < 32 * 68; i += 32) sts32(ab + i * 4, 0);
  __syncwarp();
  const uint32_t wdv = __ldg((const uint32_t*)(p.we + 128 * 64) + lane), wxv = __ldg((const uint32_t*)p.wx + lane);
  const int nb0 = node0 + wid * 32, cntn = max(0, min(32, nloc - wid * 32));
  auto dot = [&](uint32_t hv, const uint16_t* w, int K2, float& y0, float& y1) {
#pragma unroll 4
    for (int k = 0; k < K2; k++) {
      const uint32_t hk = __shfl_sync(~0u, hv, k), wa = __ldg((const uint32_t*)(w + 2 * k * 64) + lane), wb = __ldg((const uint32_t*)(w + (2 * k + 1) * 64) + lane);
      y0 = fmaf(bf_lo(hk), bf_lo(wa), fmaf(bf_hi(hk), bf_lo(wb), y0)); y1 = fmaf(bf_lo(hk), bf_hi(wa), fmaf(bf_hi(hk), bf_hi(wb), y1));
    }
  };
  auto silu = [](float x) { return x / (1.f + __expf(-x)); };
#pragma unroll 1
  for (int base = 0; base < p.E; base += 32) {
    const int e = base + lane;
    const uint32_t dl = e < p.E ? (uint32_t)(__ldg(p.dst + e) - nb0) : 0xFFFFFFFFu;
    uint32_t mk = __ballot_sync(~0u, dl < (uint32_t)cntn);
    while (mk) {
      const int l = __ffs(mk) - 1; mk &= mk - 1;
      const int ee = base + l, n = __shfl_sync(~0u, dl, l), s = __ldg(p.src + ee);
      const uint16_t *po = p.pos + (size_t)(nb0 + n) * 3, *pp = p.pos + (size_t)s * 3;
      const uint32_t dxy = hsub(__ldg(po) | (__ldg(po + 1) << 16), __ldg(pp) | (__ldg(pp + 1) << 16)), dz = hsub(__ldg(po + 2), __ldg(pp + 2));
      const uint32_t sq = hsq(dxy); const float d2 = bf_lo(sq) + bf_hi(sq) + bf_lo(hsq(dz));
      float y0 = d2 * bf_lo(wdv), y1 = d2 * bf_hi(wdv);
      dot(__ldg((const uint32_t*)(p.h + (size_t)(nb0 + n) * 8) + lane), p.we, 32, y0, y1);
      dot(__ldg((const uint32_t*)(p.h + (size_t)s * 8) + lane), p.we + 64 * 64, 32, y0, y1);
      dot(__ldg((const uint32_t*)(p.ea + (size_t)ee * 2) + (lane & 7)), p.we + 129 * 64, 8, y0, y1);
      const uint32_t mm = pack_bf16(silu(y0), silu(y1));
      float c = bf_lo(mm) * bf_lo(wxv) + bf_hi(mm) * bf_hi(wxv);
#pragma unroll
      for (int o = 16; o; o >>= 1) c += __shfl_xor_sync(~0u, c, o);
      const uint32_t a = ab + n * 272;
      uint32_t x0, x1; lds64(x0, x1, a + lane * 8);
      sts64(a + lane * 8, __float_as_uint(__uint_as_float(x0) + bf_lo(mm)), __float_as_uint(__uint_as_float(x1) + bf_hi(mm)));
      if (lane < 3) { const float df = lane == 0 ? bf_lo(dxy) : lane == 1 ? bf_hi(dxy) : bf_lo(dz); sts32(a + 256 + lane * 4, __float_as_uint(fmaf(c, df, __uint_as_float(lds32(a + 256 + lane * 4))))); }
    }
  }
  __syncwarp();
#pragma unroll 1
  for (int n = 0; n < cntn; n++) {
    uint32_t x0, x1; lds64(x0, x1, ab + n * 272 + lane * 8);
    const uint32_t hv = __ldg((const uint32_t*)(p.h + (size_t)(nb0 + n) * 8) + lane);
    float y0 = 0.f, y1 = 0.f;
    dot(hv, p.wh, 32, y0, y1); dot(pack_bf16(__uint_as_float(x0), __uint_as_float(x1)), p.wh + 64 * 64, 32, y0, y1);
    ((uint32_t*)p.out)[(size_t)(nb0 + n) * 32 + lane] = u2(__hadd2(b2(hv), b2(pack_bf16(silu(y0), silu(y1)))));
    if (lane < 3) p.out[(size_t)p.N * 64 + (size_t)(nb0 + n) * 3 + lane] = (uint16_t)pack_bf16(bf_lo(__ldg(p.pos + (size_t)(nb0 + n) * 3 + lane)) + __uint_as_float(lds32(ab + n * 272 + 256 + lane * 4)), 0.f);
  }
}

__global__ void __launch_bounds__(NTHR, 1) egnn_kernel(const __grid_constant__ Params p, const __grid_constant__ Maps maps) {
  const uint64_t tmb = (uint64_t)&maps;
  extern __shared__ __align__(1024) unsigned char smraw[];
  const int tid = threadIdx.x, cta = blockIdx.x;
  const int e0 = cta * p.EPC, n4 = max(0, min(p.EPC, p.E - e0)) >> 2;
  STAMP(0);
  if (tid == NWK) {
#pragma unroll 1
    for (int k = 0; k < NCH; k++) { const int nb = max(0, min(NWK, n4 - k * NWK)) * 16;
      mbar_init(sb + BAR_DST + k * 8, 1);
      asm volatile("fence.mbarrier_init.release.cluster;" ::: "memory");
      mbar_expect(sb + BAR_DST + k * 8, nb);
      if (nb) bulk_load(sb + OFF_DST + k * NWK * 16, (const char*)(p.dst + e0) + k * NWK * 16, nb, sb + BAR_DST + k * 8); }
  }
  const int lane = tid & 31, wid = __shfl_sync(~0u, tid >> 5, 0), w = wid & 3;
  asm volatile("{.reg .pred p; setp.eq.u32 p, %2, 384; @p cp.async.cg.shared.global [%0], [%1], 16;}" :: "r"(sb + OFF_LEN - 192 + (tid >> 1)), "l"(p.sync), "r"(tid & 415) : "memory");

  auto first_node = [&](int c) { return (int)((c * p.inv + 0xFFFFFFFFull) >> 32); };
  const int node0 = first_node(cta), nloc = min(first_node(cta + 1), p.N) - node0;
  const uint32_t ealo = (uint32_t)(uint64_t)p.ea;
  const int epad = min(e0, p.E - 1);
  auto load_h = [&](int b) { mbar_expect(sb + BAR_T + b * 8, 8192); tma_load(sb + OFF_H + b * 8192, tmb + TM_H, node0 + b * 64, sb + BAR_T + b * 8); };
  auto prefetch_e = [&](int i) {
    const uint32_t nb = (p.E / G) & ~15u;
    if (nb && i < PFN) asm volatile("cp.async.bulk.prefetch.L2.global [%0], %1;" :: "l"((const char*)p.ea + (size_t)(((i * PFS + i * PFS / 32 * (~PFS & 1)) & 31) * G + cta) * nb), "r"(nb) : "memory");
  };
  if (wid >= 12) {
    const int t = tid - 384;
    uint32_t pv[9], ev = 0;
#pragma unroll
    for (int i = 0; i < 3; i++) { const uint16_t* pp = p.pos + (size_t)(node0 + t + 128 * i) * 3;
      pv[3 * i] = pv[3 * i + 1] = pv[3 * i + 2] = 0;
      asm volatile("{.reg .pred p; setp.lt.s32 p, %4, %5;\n @p ld.global.nc.u16 %0, [%3];\n @p ld.global.nc.u16 %1, [%3+2];\n @p ld.global.nc.u16 %2, [%3+4];}"
        : "+r"(pv[3 * i]), "+r"(pv[3 * i + 1]), "+r"(pv[3 * i + 2]) : "l"(pp), "r"(t + 128 * i), "r"(p.N - node0)); }
    asm volatile("{.reg .pred p; setp.lt.u32 p, %3, 8; @p ld.global.nc.u32 %0, [%1]; @p st.global.v4.u32 [%2], {%4, %4, %4, %4};}"
      : "+r"(ev) : "l"((const uint32_t*)(p.ea + (size_t)epad * 2) + t), "l"(p.q + (size_t)(p.N + cta) * 128 + t * 16), "r"(t), "r"(0xF700F700u) : "memory");
    asm volatile("cp.async.wait_all;" ::: "memory");
    __syncwarp();
    const uint32_t e = lds32(sb + OFF_LEN + 8 + w * 16) + 1;
    {
      const uint32_t tg = (1 + e % 3) << 30, v = ((tg >> 16) + 512 + (lane & 7) * 4) * 0x10001u;
      if (t == 0) sts32(sb + OFF_MISC + 32, e);
#pragma unroll
      for (int i = 0; i < 9; i++) sts128(sb + OFF_SA + t * 16 + i * 2048, v, v + 0x10001u, v + 0x20002u, v + 0x30003u);
      bar_sync(6, NTHR);
      mbar_arrive(sb + BAR_EP, lane == 0);
#pragma unroll
      for (int i = 0; i < 17; i++) sts128(sb + OFF_SB + t * 16 + i * 2048, tg, tg, tg, tg); }
    uint32_t mp = 0;
#pragma unroll
    for (int i = 0; i < 3; i++) { sts64(sb + OFF_POS + (t + 128 * i) * 8, pv[3 * i] | (pv[3 * i + 1] << 16), pv[3 * i + 2]); mp = mag2(mag2(mp, pv[3 * i] | (pv[3 * i + 1] << 16)), pv[3 * i + 2]); }
    proxy_fence();
    __syncwarp();
    mbar_arrive(sb + BAR_PS, lane == 0);
    mbar_wait(sb + BAR_W);
    {
      uint32_t v[4], u[4]; const int r = t >> 3, c = t & 7;
      lds128(v, sb + OFF_WS + 128 + t * 16); lds128(u, sb + OFF_WS + c * 16);
      const uint32_t x = lds32(sb + OFF_WS + 2176 + lane * 4);
      sts128(sb + OFF_W3 + r * 128 + ((c ^ (r & 7)) << 4), b2h(v[0], .5f), b2h(v[1], .5f), b2h(v[2], .5f), b2h(v[3], .5f));
      const float s = ((r & 1) || r == 6) ? 0.f : .5f;
      if (t < 64) sts128(sb + OFF_WD + r * 128 + ((c ^ r) << 4), b2h(u[0], s), b2h(u[1], s), b2h(u[2], s), b2h(u[3], s));
      if (t < 32) sts32(sb + OFF_WX + (t & 3) * 32 + (t >> 2) * 4, b2h(x, 1.f));
      const uint32_t m3 = __reduce_max_sync(~0u, magr(mag2(mag2(mag2(mag2(0, v[0]), v[1]), v[2]), v[3]))), md = __reduce_max_sync(~0u, magr(mag2(mag2(mag2(mag2(0, u[0]), u[1]), u[2]), u[3])));
      if (wbad(m3, 0x4000) || wbad(md, 0x4000) || wbad(__reduce_max_sync(~0u, magr(mag2(0, x))), 0x4700) || magr(mp) >= 0x4200 || magr(mag2(0, ev)) >= 0x4380) sts32(sb + OFF_MISC + 8, 1);
    }
    if (w == 1) {
#pragma unroll 1
      for (int b = HE; b < HW; b++) { mbar_wait(sb + BAR_SRC + max(0, H0 + b) * 8); if (lane == 0) load_h(b); }
    }
    bar_sync(3, 128);
    const uint32_t frag = (w * 16 + (lane & 15)) * 128 + (((lane >> 4) ^ (lane & 7)) << 4);
    uint32_t mq = 0;
#pragma unroll 1
    for (int b = 0; b < 6; b++) {
      float acc[32];
      const uint64_t da = DHI | (((sb + OFF_H) >> 4) + b * 512), db = DHI | ((sb + OFF_W) >> 4);
      const uint32_t v0 = lds16(sb + OFF_POS + b * 512 + w * 128 + lane * 2), v1 = lds16(sb + OFF_POS + 64 + b * 512 + w * 128 + lane * 2);
      mbar_wait(sb + BAR_T + b * 8);
      if (b == 0) STAMP(25);
      if (b == 5) STAMP(26);
      wg_fence();
      ss64<0>(acc, da, db); ss64<1>(acc, da + 2, db + 128); ss64<1>(acc, da + 4, db + 256); ss64<1>(acc, da + 6, db + 384);
      wg_commit();
      if (b == 0) mbar_wait(sb + BAR_AW);
      if (t == 32) { if (HALL) { if (b == 0) for (int k = HW; k < 6; k++) load_h(k); } else if (b + HW < 6) load_h(b + HW); }
      __syncwarp();
      uint32_t ff[6], fg[6];
#pragma unroll
      for (int j = 0; j < 6; j++) { ff[j] = (__byte_perm((j & 1) ? v1 : v0, 0, 0x4140) >> (3 * (j >> 1))) & 0x00070007u; fg[j] = __vsub2(0x00040004u, ff[j]);
        asm volatile("" : "+r"(ff[j]), "+r"(fg[j])); }
      wg_wait0(); fence_regs(acc);
      uint32_t o[16];
#pragma unroll
      for (int j = 0; j < 16; j++) o[j] = pack_f16(.5f * acc[2 * j], .5f * acc[2 * j + 1]);
#pragma unroll
      for (int j = 0; j < 6; j++) {
        const uint32_t m = o[j] & 0x7FFF7FFFu; mq = __vmaxu2(mq, m);
        o[j] = (__viaddmax_s16x2(m, fg[j], 0) & 0xFFF8FFF8u) | ff[j] | (o[j] & 0x80008000u); }
      if (b == 4) mbar_wait(sb + BAR_AX);
      const uint32_t qs = sb + OFF_SA + b * 8192;
#pragma unroll
      for (int j = 0; j < 4; j++) stsm4((qs + frag) ^ (j << 5), o[4 * j], o[4 * j + 1], o[4 * j + 2], o[4 * j + 3]);
      proxy_fence();
      __syncwarp();
      if (lane == 0 && b * 64 + w * 16 < nloc) tma_store(tmb + TM_Q, 0, node0 + b * 64 + w * 16, qs + w * 2048);
    }
    if (lane == 0) bulk_commit();
    { const uint32_t m = __reduce_max_sync(~0u, magr(mq)); if (lane == 0) sts32(sb + OFF_MISC + 16 + w * 4, m); }
    asm volatile("setmaxnreg.dec.sync.aligned.u32 32;");
    bulk_wait();
    bar_sync(3, 128);
    if (w == 0) {
      STAMP(18);
      uint32_t mv[4]; lds128(mv, sb + OFF_MISC + 16);
      const uint32_t mx = max(max(mv[0], mv[1]), max(mv[2], mv[3]));
      mbar_arrive(sb + BAR_QR, lane == 0);
      STAMP(19);
      if (lane == 0) {
        if (nloc > 0 && (mx >= 0x7BF0 || mx < 0x1400)) asm volatile("st.relaxed.gpu.global.u32 [%0+4], %1;" :: "l"(p.sync), "r"(e) : "memory");
        asm volatile("red.release.gpu.global.add.u32 [%0], 1;" :: "l"(p.sync) : "memory");
      }
      __syncwarp();
      uint32_t c, f; int spin = 0;
      do { asm volatile("ld.acquire.gpu.global.v2.u32 {%0, %1}, [%2];" : "=r"(c), "=r"(f) : "l"(p.sync) : "memory"); trap_if(++spin > 4000000); } while (__any_sync(~0u, (int)(c - e * G) < 0));
      if (f == e) sts32(sb + OFF_MISC + 8, 1);
      if (cta == 0 && lane == 0) asm volatile("st.relaxed.gpu.global.u32 [%0+8], %1;" :: "l"(p.sync), "r"(e) : "memory");
      STAMP(20);
      __syncwarp();
      mbar_arrive(sb + BAR_QP, lane == 0);
    }
    if (w == 2) {
      const uint32_t tg = (1 + e % 3) << 30;
      hint_wait(p.sync + 5, e * G);
      if (lane == 0) { mbar_expect(sb + BAR_HB, XPAD);
#pragma unroll 1
        for (int o = 0; o < 4; o++) bulk_load(sb + OFF_XB + o * (G * 64), (const char*)p.xb + (size_t)(cta * 4 + o) * (G * 64), G * 64, sb + BAR_HB); }
      STAMP(21);
      bar_sync(7, 384);
      sts32(sb + OFF_XB + XPAD, tg + p.N + cta);
      const uint32_t nx = __shfl_sync(~0u, lds32(sb + OFF_MISC + 8) ? 0 : lds32(sb + OFF_MISC + 4), 0);
#pragma unroll 1
      for (uint32_t k = 0; k < nx; k += 32) {
        const uint32_t i = min(k + lane, nx - 1), xr = lds32(sb + OFF_EXT + i * 4), row = (xr >> 9) & 255;
        const uint32_t v = ext_get(p.xe + (cta * G + row) * 32 + ((xr >> 17) & 31), e), x = lds32(sb + OFF_CNT + (xr & 511) * 4) + (xr >> 22) * 16;
        sts32(sb + OFF_XB + XPAD + 4 + i * 4, v); sts16(sb + OFF_TS + x, XPAD + 4 + i * 4);
        sts32(sb + OFF_TE + x * 2, mad16(v, 0x2000u, ealo - (tg >> 11) + row * p.EPC * 32));
      }
      __syncwarp();
      mbar_arrive(sb + BAR_HB, lane == 0);
    }
    if (w == 1) {
      if (PFW) mbar_wait(sb + PFW);
      __nanosleep(PF0NS);
#pragma unroll 1
      for (int i = PFE; i < PFN; i++) { if (lane == 0) prefetch_e(i); __nanosleep(PFNS); }
    }
    bar_sync(4, NTHR);
    if (t == 0) { mbar_expect(sb + BAR_U, 16384); tma_load(sb + OFF_W, tmb + TM_WH, 0, sb + BAR_U); tma_load(sb + OFF_W + 8192, tmb + TM_WH, 64, sb + BAR_U); }
    mbar_wait(sb + BAR_U);
    uint32_t mh = 0;
#pragma unroll 1
    for (int i = t; i < 512; i += 128) { uint32_t v[4]; const uint32_t a = sb + OFF_W + i * 16;
      lds128(v, a); sts128(a, hhalf(v[0]), hhalf(v[1]), hhalf(v[2]), hhalf(v[3]));
      lds128(v, a + 8192); sts128(a + 8192, b2h(v[0], .5f), b2h(v[1], .5f), b2h(v[2], .5f), b2h(v[3], .5f));
      mh = mag2(mag2(mag2(mag2(mh, v[0]), v[1]), v[2]), v[3]); }
    if (wbad(__reduce_max_sync(~0u, magr(mh)), 0x4700)) sts32(sb + OFF_MISC + 12, 1);
    proxy_fence();
    __syncwarp();
    mbar_arrive(sb + BAR_WH, lane == 0);
    if (DEFO) { if (!__shfl_sync(~0u, lds32(sb + OFF_MISC + 8), 0)) {
      mbar_wait(sb + BAR_M);
      __nanosleep(DEFO);
#pragma unroll 1
      for (int i = 0; i < 12; i++) { uint32_t v[4]; const uint32_t n = lds16(sb + OFF_GP + i * 256 + (t >> 3) * 8 + 6);
        lds128(v, sb + OFF_H + n * 128 + (((n ^ t) & 7) << 4));
        if (n < nloc) ((uint4*)p.out)[(size_t)(node0 + n) * 8 + (t & 7)] = make_uint4(v[0], v[1], v[2], v[3]);
        __nanosleep(DEFNS); }
      mbar_wait(sb + BAR_X);
#pragma unroll 1
      for (int i = t; i < 384; i += 128) { uint32_t x, y; lds64(x, y, sb + OFF_GP + i * 8); const uint32_t a = sb + OFF_P2 + (y >> 16) * 6; sts16(a, x); sts16(a + 2, x >> 16); sts16(a + 4, y); }
      bar_sync(3, 128);
#pragma unroll 3
      for (int i = t; i < nloc * 3; i += 128) p.out[(size_t)p.N * 64 + node0 * 3 + i] = lds16(sb + OFF_P2 + i * 2);
      asm volatile("{.reg .pred p, q; setp.ne.u32 p, 0, 0; bar.red.or.pred q, 5, 512, p;}" ::: "memory"); } }
    return;
  }

  if (tid == 320) {
    mbar_init(sb + BAR_W, 1);
    asm volatile("fence.mbarrier_init.release.cluster;" ::: "memory");
    mbar_expect(sb + BAR_W, 2 * 8192 + 2304);
    tma_load(sb + OFF_W, tmb + TM_WE, 64, sb + BAR_W); tma_load(sb + OFF_W + 8192, tmb + TM_WE, 0, sb + BAR_W);
    bulk_load(sb + OFF_WS, p.we + 128 * 64, 2176, sb + BAR_W); bulk_load(sb + OFF_WS + 2176, p.wx, 128, sb + BAR_W);
  }
  if (tid == 288) {
#pragma unroll
    for (int a = BAR_SRC; a < BAR_END; a += 8) if (a != BAR_W) mbar_init(sb + a, a == BAR_WH || a == BAR_PS || a == BAR_EP ? 4 : a == BAR_XA ? 11 : a == BAR_HB ? 2 : a == BAR_M ? 12 : a == BAR_X ? 24 : 1);
    asm volatile("fence.mbarrier_init.release.cluster;" ::: "memory");
    asm volatile("prefetch.tensormap [%0];" :: "l"(tmb + TM_XA)); asm volatile("prefetch.tensormap [%0];" :: "l"(tmb + TM_H));
    asm volatile("prefetch.tensormap [%0];" :: "l"(tmb + TM_XB)); asm volatile("prefetch.tensormap [%0];" :: "l"(tmb + TM_Q));
  }
  {
    if (tid < 144) { const uint32_t z = (tid >> 3) == 16 ? 0x8000u : 0u; sts128(sb + OFF_CNT + tid * 16, z, z, z, z); }
    else if (tid <= 144 + G) sts32(sb + OFF_BC + (tid - 144) * 4, ((tid - 144) & 31) * 4);
    const uint32_t sp = XPAD * 0x10001u, em = first_node(G);
    if (wid < 7) {
#pragma unroll
      for (int i = 0; i < 4; i++) sts128(sb + OFF_TS + tid * 16 + i * 3584, sp, sp, sp, sp);
    }
    static_assert(SCAP * 32 == 4 * 3584, "fill");
#pragma unroll 1
    for (int i = n4 + tid; i < 1536; i += 384) sts128(sb + OFF_DST + i * 16, em, em, em, em);
    if (tid == 321) sts128(sb + OFF_MISC, 0, 0, p.force_slow, 0);
  }
  bar_arrive(6, NTHR);
  bar_sync(0, 384);
  uint32_t ep, tag, eb0, pk[12], r0[12], r1[12], cb;
  uint2 vb[12];
  auto get_tag = [&]() { mbar_wait(sb + BAR_EP); ep = lds32(sb + OFF_MISC + 32); tag = (1 + ep % 3) << 30; eb0 = ealo - (tag >> 11); };
  if (wid == 11) {
    trap_if(sb != (uint32_t)__cvta_generic_to_shared(smraw));
#pragma unroll 1
    for (unsigned long long q = LSEQ; q; q >>= 8) { const int k = (q >> 4) & 7, nb = max(0, min(8192, n4 * 16 - k * 8192));
      if (!(q & 8)) mbar_wait(sb + BAR_DST + ((uint32_t)q & 7) * 8);
      if (lane == 0) {
        if (k >= 3) load_h(k - 3);
        else { mbar_expect(sb + BAR_SRC + k * 8, nb);
          if (nb) bulk_load(sb + OFF_SRCI + k * 8192, (const char*)(p.src + e0) + k * 8192, nb, sb + BAR_SRC + k * 8); } } }
    get_tag();
    mbar_wait(sb + BAR_PS);
    bar_sync(12, 384);
    uint32_t xm = 0;
#pragma unroll
    for (int k = 0; k < 5; k++) xm |= (lds32(sb + OFF_BC + min(lane + 32 * k, G - 1) * 4) >= (65 << 9) && lane + 32 * k < G) << k;
    auto ext_send = [&](int pl) {
      uint32_t x = xm;
      for (uint32_t m; (m = __ballot_sync(~0u, x));) {
        const uint32_t l = __ffs(m) - 1, j = l + 32 * (__ffs(__shfl_sync(~0u, x, l)) - 1);
        if (lane == l) x &= x - 1;
        const uint32_t e = min(lds16(sb + OFF_AX + j * 128 + ((4 * l + 2 * lane) & 126)), 6143u);
        if (pl) st_ext(p.xe + (j * G + cta) * 32 + lane, lds32(sb + OFF_SRCI + e * 4) + tag + (e << 16), ep);
        else { const uint32_t cn = lds32(sb + OFF_BC + j * 4) >> 9, v = cn > 96 ? 1 : lane + 64 < cn ? 512 | (lds32(sb + OFF_DST + e * 4) & 511) : 0;
          asm volatile("red.shared.xor.b32 [%0], %1;" :: "r"(sb + OFF_SA + j * 128 + ((l + lane) & 31) * 4), "r"(((v & 63) << 10) | ((v >> 6) << 26)) : "memory"); }
      }
    };
    if (__any_sync(~0u, xm)) { ext_send(0); proxy_fence(); __syncwarp(); }
    if (lane == 0) { tma_store_ef(tmb + TM_XA, cta * 64, 0, sb + OFF_SA); bulk_commit(); mbar_arrive(sb + BAR_AI); bulk_wait(); hint_signal(p.sync + 4); mbar_arrive(sb + BAR_AW); STAMP(16); }
    __syncwarp();
    bar_sync(13, 384);
    if (!B_HOLD && lane == 0) { tma_store_ef(tmb + TM_XB, cta * 64, 0, sb + OFF_SB); bulk_commit(); }
    __syncwarp();
    ext_send(1);
    mbar_arrive(sb + BAR_AX, lane == 0);
    if (B_HOLD) mbar_wait(sb + (B_HOLD == 1 ? BAR_HA : BAR_XA));
    if (lane == 0) {
      bulk_wait();
#pragma unroll 1
      for (int r = B_HOLD ? 0 : BROWS; r < G; r += BROWS) { tma_store_ef(tmb + TM_XB, cta * 64, r, sb + OFF_SB + r * 256); bulk_commit(); bulk_wait(); }
      hint_signal(p.sync + 5);
#pragma unroll 1
      for (int i = 0; i < PFE; i++) prefetch_e(i);
      STAMP(17);
    }
    __syncwarp();
  } else {
    STAMP(15);
    {
      uint32_t d[4 * NCH], jj[4 * NCH], rr[4 * NCH];
      auto count = [&](int k) {
        mbar_wait(sb + BAR_DST + k * 8);
        lds128(d + 4 * k, sb + OFF_DST + (tid + NWK * k) * 16);
#pragma unroll
        for (int i = 4 * k; i < 4 * k + 4; i++) { jj[i] = d[i] * p.magic; rr[i] = atoms_add(__dp4a(jj[i], 0x04000000u, sb + OFF_BC), 0x202u); }
      };
      auto place = [&](int k) {
#pragma unroll
        for (int i = 4 * k; i < 4 * k + 4; i++) {
          const uint32_t o = __dp4a(jj[i], 0x80000000u, rr[i] & 0x807Eu);
          d[i] = (d[i] & 511) | (tag >> 16);
          asm("{.reg .pred p; setp.ge.u32 p, %1, 0x8000; @p add.u32 %0, %2, %3;}" : "+r"(d[i]) : "r"(o), "r"(tid * 4), "r"(NWK * k * 4 + (i & 3)));
          sts16(sb + OFF_SA + o, d[i]); jj[i] = __viaddmin_u32(o, o, G * 256);
        }
      };
      count(0); STAMP(1); count(1); get_tag(); place(0); count(2); place(1); count(3); place(2);
      if (wid < 4) { count(4); place(3); place(4); } else place(3);
      proxy_fence();
      bar_arrive(12, 384);
      STAMP(2);
      mbar_wait(sb + BAR_AI);
      mbar_wait(sb + BAR_SRC); mbar_wait(sb + BAR_SRC + 8); mbar_wait(sb + BAR_SRC + 16);
      STAMP(12);
#pragma unroll
      for (int k = 0; k < NCH; k++) lds128(d + 4 * k, sb + OFF_SRCI + (tid + NWK * k) * 16);
      const uint32_t tb = tag + (tid << 18);
#pragma unroll
      for (int i = 0; i < 4 * NCH; i++) if (i < 4 * NCH - 4 || wid < 4) sts32(sb + OFF_SB + jj[i], d[i] + tb + ((NWK * (i >> 2) * 4 + (i & 3)) << 16));
      proxy_fence();
      bar_arrive(13, 384);
      STAMP(3);
    }
    const uint32_t rot = (lane + cta) & 31;
    cb = sb + OFF_CNT - (tag >> 14);
    {
      const uint32_t* xa = (const uint32_t*)(p.xa + (cta * G + wid) * 8) + rot;
      if (wid < 8) { const uint32_t e_ = ealo + epad * 32;
        mbar_wait(sb + BAR_AX);
#pragma unroll
        for (int i = 0; i < 7; i++) sts128(sb + OFF_TE + tid * 16 + i * 4096, e_, e_, e_, e_); }
      static_assert(SCAP * 64 == 7 * 4096, "fill");
      if (wid == 10) { hint_wait(p.sync + 4, ep * G); mbar_arrive(sb + BAR_HA, lane == 0); }
      mbar_wait(sb + BAR_HA);
      STAMP(14);
      const uint32_t tp = tag | (tag >> 16);
      uint32_t st;
#pragma unroll 1
      for (int spin = 0;; spin++) {
        st = 0;
#pragma unroll
        for (int k = 0; k < 12; k++) asm volatile("ld.relaxed.gpu.global.u32 %0, [%1];" : "=r"(pk[k]) : "l"(xa + k * 352) : "memory");
#pragma unroll
        for (int k = 0; k < 12; k++) st |= pk[k] ^ tp;
        st = __reduce_or_sync(~0u, st);
        if (!(st >> 30)) break;
        trap_if(spin > 2000000);
      }
      if (st & 0x3C00FC00u) {
#pragma unroll 1
        for (;;) {
          uint32_t x = 0, row = 0;
#pragma unroll
          for (int k = 0; k < 12; k++) { const uint32_t y = (pk[k] ^ tp) & 0x3C00FC00u; if (!x && y) { x = y; row = wid + 11 * k; pk[k] ^= y; } }
          if (!__any_sync(~0u, x)) break;
          const uint32_t n = ((x >> 10) & 63) | ((x >> 20) & 0x1C0);
          if (x >> 29) {
            const uint32_t r = atoms_add(sb + OFF_CNT + n * 4, 16), idx = atoms_add(sb + OFF_MISC + 4, 1);
            if (idx < 256) sts32(sb + OFF_EXT + idx * 4, n | (row << 9) | (lane << 17) | (min(r >> 4, 255u) << 22));
            else x = 1;
          }
          if (x && !(x >> 29)) sts32(sb + OFF_MISC + 8, 1);
          __syncwarp();
        }
      }
#pragma unroll
      for (int k = 0; k < 12; k++) { r0[k] = mad16(pk[k], 0x0004u, cb); r1[k] = mad16(pk[k], 0x0400u, cb); vb[k].x = atoms_add(r0[k], 16); vb[k].y = atoms_add(r1[k], 16); }
      if (B_HOLD == 2) mbar_arrive(sb + BAR_XA, lane == 0);
    }
    STAMP(4);
    if (wid >= 6) bar_arrive(11, NWK);
    if (wid < 6) {
      uint32_t ca[2], ky[2], dr[2], sq[2], ps[4];
#pragma unroll
      for (int i = 0; i < 2; i++) { ca[i] = sb + OFF_CNT + ((node0 + tid + 192 * i) & 511) * 4; lds64(ps[2 * i], ps[2 * i + 1], sb + OFF_POS + (tid + 192 * i) * 8); ps[2 * i + 1] |= (tid + 192 * i) << 16; }
      bar_sync(11, NWK);
      STAMP(5);
#pragma unroll
      for (int i = 0; i < 2; i++) ky[i] = (lds32(ca[i]) + 16) >> 5;
      if (max(ky[0], ky[1]) > 31) sts32(sb + OFF_MISC + 8, 1);
#pragma unroll
      for (int i = 0; i < 2; i++) { ky[i] = min(ky[i], 31u); dr[i] = atoms_add(sb + OFF_DH + ky[i] * 4, 1); }
      bar_sync(10, 192);
      const uint32_t hv = lds32(sb + OFF_DH + lane * 4);
      uint32_t inc = hv;
#pragma unroll
      for (int o = 1; o < 32; o <<= 1) asm("{.reg .pred p; .reg .b32 y; shfl.sync.down.b32 y|p, %0, %1, 31, -1; @p add.u32 %0, %0, y;}" : "+r"(inc) : "r"(o));
#pragma unroll
      for (int i = 0; i < 2; i++) {
        const uint32_t pos = __shfl_sync(~0u, inc - hv, ky[i]) + dr[i];
        const uint32_t ak = (uint32_t)(QCODE >> ((pos >> 5) * 4)) & 15, l = (pos >> 3) & 3;
        sq[i] = (ak >> 2) * 16 + ((QREV >> (pos >> 5) & 1) ? 3 - l : l) * 4 + (ak & 3);
        dr[i] = pos & 7;
        asm volatile("{.reg .pred p; setp.eq.u32 p, %2, 0; @p st.shared.u8 [%0], %1;}" :: "r"(sb + OFF_LEN + sq[i]), "r"(max(ky[i], 1u)), "r"(dr[i]) : "memory");
        sts64(sb + OFF_GP + sq[i] * 64 + dr[i] * 8, ps[2 * i], ps[2 * i + 1]);
      }
      bar_sync(10, 192);
      const uint32_t ln = lds32(sb + OFF_LEN + min(lane, 11) * 4), tot = __dp4a(ln, 0x01010101u, 0u);
      inc = tot;
#pragma unroll
      for (int o = 1; o < 16; o <<= 1) asm("{.reg .pred p; .reg .b32 y; shfl.sync.up.b32 y|p, %0, %1, 0, -1; @p add.u32 %0, %0, y;}" : "+r"(inc) : "r"(o));
      if (wid == 1) sts32(sb + OFF_CNT + 2048 + lane * 4, 0);
      if (tid < 12) { sts32(sb + OFF_LEN + 64 + tid * 4, inc - tot); if (inc > SCAP) sts32(sb + OFF_MISC + 8, 1); }
#pragma unroll
      for (int i = 0; i < 2; i++) sts32(ca[i], __dp4a(__shfl_sync(~0u, ln, sq[i] >> 2), 0x00010101u >> (24 - 8 * (sq[i] & 3)), __shfl_sync(~0u, inc - tot, sq[i] >> 2)) * 32 + dr[i] * 2);
    }
    bar_arrive(7, 384);
  }
  bar_sync(1, 384);
  STAMP(6);
  if (wid != 11 && !__shfl_sync(~0u, lds32(sb + OFF_MISC + 8), 0)) {
#pragma unroll
    for (int k = 0; k < 12; k++) { r0[k] = lds32(r0[k]); r1[k] = lds32(r1[k]); }
    const uint32_t id = wid * 256 + ((lane + cta) & 31) * 8;
    auto put = [&](uint32_t x, uint32_t v) { asm volatile("{.reg .pred p; setp.lt.u32 p, %0, 0x8000; @p st.shared.u16 [%0+%2], %1;}" :: "r"(x), "h"((uint16_t)v), "n"(sb + OFF_TS) : "memory"); };
#pragma unroll
    for (int k = 0; k < 12; k++) { put(r0[k] + vb[k].x, id + k * 2816); put(r1[k] + vb[k].y, id + k * 2816 + 4); }
  }
  STAMP(7);
  mbar_wait(sb + BAR_QR);
  asm volatile("setmaxnreg.inc.sync.aligned.u32 160;");
  uint32_t pa[8], sp[8], pq[16]; float chk = 0.f;
  {
    uint32_t hf[32], mp = 0; float a0[32], a1[32];
    const uint32_t an = sb + OFF_GP + wid * 256 + (lane & 15) * 8 + 6, n0 = lds16(an), n1 = lds16(an + 128);
#pragma unroll
    for (int j = 0; j < 8; j++) { const uint32_t nd = j < 4 ? n0 : n1; ldsm4(hf + 4 * j, (sb + OFF_H + nd * 128 + (((nd & 7) << 4) ^ (lane & 16))) ^ ((j & 3) << 5)); }
    const uint64_t db = DHI | ((sb + OFF_W + 8192) >> 4);
    wg_fence();
    rs64b<0>(a0, hf[0], hf[1], hf[2], hf[3], db); rs64b<1>(a0, hf[4], hf[5], hf[6], hf[7], db + 128); rs64b<1>(a0, hf[8], hf[9], hf[10], hf[11], db + 256); rs64b<1>(a0, hf[12], hf[13], hf[14], hf[15], db + 384);
    wg_commit();
    rs64b<0>(a1, hf[16], hf[17], hf[18], hf[19], db); rs64b<1>(a1, hf[20], hf[21], hf[22], hf[23], db + 128); rs64b<1>(a1, hf[24], hf[25], hf[26], hf[27], db + 256); rs64b<1>(a1, hf[28], hf[29], hf[30], hf[31], db + 384);
    wg_commit();
    asm volatile("wgmma.wait_group.sync.aligned 1;" ::: "memory"); fence_regs(a0);
#pragma unroll
    for (int j = 0; j < 8; j++) { const uint32_t x = pack_f16(.5f * a0[4 * j], .5f * a0[4 * j + 1]), y = pack_f16(.5f * a0[4 * j + 2], .5f * a0[4 * j + 3]); mp = hmag(hmag(mp, x), y);
      asm volatile("movmatrix.sync.aligned.m8n8.trans.b16 %0, %1;" : "=r"(pa[j]) : "r"(x)); asm volatile("movmatrix.sync.aligned.m8n8.trans.b16 %0, %1;" : "=r"(sp[j]) : "r"(y)); }
    wg_wait0(); fence_regs(a1);
    bar_arrive(4, NTHR);
#pragma unroll
    for (int j = 0; j < 16; j++) { pq[j] = pack_f16(.5f * a1[2 * j], .5f * a1[2 * j + 1]); mp = hmag(mp, pq[j]); }
    if (magr(mp) >= 0x7000) chk = __int_as_float(0x7FC00000);
  }
  if (wid == 0) STAMP(23);
  uint32_t bad;
  {
    const uint32_t ring = sb + OFF_RING + wid * STG, p2 = sb + OFF_P2 + wid * 2048;
    uint32_t lens = __shfl_sync(~0u, lds32(sb + OFF_LEN + wid * 4), 0);
    uint32_t rem = __dp4a(lens, 0x20202020u, 0u);
    const uint32_t base = min(lds32(sb + OFF_LEN + 64 + wid * 4), SCAP);
    uint32_t a_s = sb + OFF_TS + base * 32 + (lane >> 3) * 8, a_e = sb + OFF_TE + base * 64 + (lane >> 1) * 4;
    uint32_t k0 = (uint32_t)(uint64_t)p.q + (((lane & 7) ^ ((lane >> 1) & 4)) << 4), k1 = k0 ^ 16, k2 = k0 ^ 32, k3 = k0 ^ 48, ke = ((lane ^ (lane >> 3)) & 1) << 4;
    uint32_t dst0 = ring + (lane >> 3) * 640 + (lane & 7) * 16;
    const uint32_t qhi = (uint32_t)((uint64_t)p.q >> 32), ehi = (uint32_t)((uint64_t)p.ea >> 32);
    uint32_t s0, s1, ev, to = 0, so = 12 * STG;
    auto tl_ = [&]() { lds64(s0, s1, a_s + to); asm volatile("ld.shared.u32 %0, [%1]; add.u32 %1, %1, 64;" : "=&r"(ev), "+r"(a_e) :: "memory"); to += 32; };
#define CPQ(LH, x, k, off) "dp2a." LH ".u32.u32 lo, " x ", 0x80000080, " k "; mov.b64 a, {lo, %7}; @p cp.async.cg.shared.global [%0+" #off "], [a], 16;\n"
#define CPE "or.b32 lo, %10, %11; mov.b64 a, {lo, %12}; @p cp.async.cg.shared.global" ESZ " [%0+512], [a], 16;\n"
#define CPA(BODY) asm volatile("{.reg .b32 lo; .reg .b64 a; .reg .pred p; setp.le.u32 p, %8, %9;\n" BODY "}" \
      :: "r"(dst0 + so), "r"(s0), "r"(s1), "r"(k0), "r"(k1), "r"(k2), "r"(k3), "r"(qhi), "r"(to), "r"(rem), "r"(ev), "r"(ke), "r"(ehi) : "memory")
#define CPQ4 CPQ("lo", "%1", "%3", 0) CPQ("hi", "%1", "%4", 128) CPQ("lo", "%2", "%5", 256) CPQ("hi", "%2", "%6", 384) "cp.async.commit_group;"
    auto issue = [&]() { CPA(CPE CPQ4); so = so == (NST - 1) * 12 * STG ? 0 : so + 12 * STG; };
    const int g = lane >> 2, qd = lane & 3;
    const uint32_t sw = ((lane >> 4) ^ (lane & 7)) << 4, fr = (lane & 15) * 128 + sw;
    uint32_t qa0 = ring + (g & 3) * 640 + qd * 128 + sw, qa1 = qa0 ^ 32, qa2 = qa0 ^ 64, qa3 = qa0 ^ 96;
    uint32_t eadr = ring + 512 + (g & 3) * 640 + qd * 32 + ((((lane >> 4) ^ g) & 1) << 4);
    uint32_t oh0 = g == 2 * qd ? 0x3C00u : g == 2 * qd + 1 ? 0x3C000000u : 0u, oh1 = oh0;
    uint32_t a_g = sb + OFF_GP + wid * 256 + lane * 2;
    uint32_t a_n = sb + OFF_GP + wid * 256 + (lane & 15) * 8 + 6;
    uint32_t a_p = ((lane & 8) ? p2 : sb + OFF_WD) + (lane & 7) * 128 + ((((lane >> 4) ^ lane) & 7) << 4);
    uint32_t a_w = sb + OFF_W3 + fr;
#define OPQ4(A, B, C, D) asm volatile("shfl.sync.bfly.b32 %0, %0, 0, 31, -1; shfl.sync.bfly.b32 %1, %1, 0, 31, -1; shfl.sync.bfly.b32 %2, %2, 0, 31, -1; shfl.sync.bfly.b32 %3, %3, 0, 31, -1;" : "+r"(A), "+r"(B), "+r"(C), "+r"(D))
    asm volatile("shfl.sync.idx.b32 %0, %0, %1, 31, -1;" : "+r"(oh1) : "r"(lane));
    if (OPQ & 1) OPQ4(a_w, oh0, ke, dst0);
    if (OPQ & 2) OPQ4(qa0, qa1, qa2, qa3);
    if (OPQ & 4) OPQ4(k0, k1, k2, k3);
    if (OPQ & 8) OPQ4(a_g, a_n, a_p, eadr);
    uint32_t w3[16], wv[8], bp[16], sum[8], Y[16], M[16], own, ownp, dpk; uint16_t tl[16], th[16];
    float pacc = 0.f;
    const uint32_t n0_ = __shfl_sync(~0u, node0 + lane, 0), nl = __shfl_sync(~0u, nloc + lane, 0);
    const char* outh = (const char*)p.out + (size_t)n0_ * 128;
    auto wload = [&]() {
#pragma unroll
      for (int j = 0; j < 4; j++) ldsm4t(w3 + 4 * j, a_w ^ (j << 5));
      lds128(wv, sb + OFF_WX + (a_g & 6) * 16); lds128(wv + 4, sb + OFF_WX + 16 + (a_g & 6) * 16);
    };
    auto hload = [&](uint32_t (&hf)[16], uint32_t nd) {
      const uint32_t hrow = sb + OFF_H + nd * 128 + (((nd & 7) << 4) ^ ((a_g >> 1) & 16));
#pragma unroll
      for (int j = 0; j < 4; j++) ldsm4(hf + 4 * j, hrow ^ (j << 5));
      return hrow;
    };
    auto bload = [&](uint32_t o) {
#pragma unroll
      for (int j = 0; j < 4; j++) ldsm4t(bp + 4 * j, (a_p ^ (j << 5)) + o);
    };
    { uint32_t wd[8]; const uint32_t a = sb + OFF_WD + (lane & 7) * 128 + ((((lane >> 3) ^ lane) & 7) << 4);
      ldsm4t(wd, a); ldsm4t(wd + 4, a ^ 64);
#pragma unroll
      for (int j = 0; j < 8; j++) { bp[2 * j] = wd[j]; bp[2 * j + 1] = pa[j]; } }
    own = lds16(a_g) * 0x10001u;
    wload();
    if (__shfl_sync(~0u, lds32(sb + OFF_MISC + 8), 0)) rem = 0;
    auto resolve = [&](auto NBK, uint32_t o) {
      constexpr int NB = decltype(NBK)::value;
      uint32_t id[NB], c0[NB], c1[NB]; const uint32_t a = base * 32 + o + lane * 4;
#pragma unroll
      for (int i = 0; i < NB; i++) { id[i] = lds32(sb + OFF_TS + a + i * 128); if (o + lane * 4 + i * 128 >= rem) id[i] = XPAD * 0x10001u; }
      uint32_t st = 0;
#pragma unroll
      for (int i = 0; i < NB; i++) { c0[i] = lds32(sb + OFF_XB + (id[i] & 0xFFFF)); c1[i] = lds32(sb + OFF_XB + (id[i] >> 16)); }
#pragma unroll
      for (int i = 0; i < NB; i++) st |= (c0[i] ^ tag) | (c1[i] ^ tag);
      for (int spin = 0; __any_sync(~0u, st >> 30); spin++) {
        st = 0; trap_if(spin > 2000000);
#pragma unroll
        for (int i = 0; i < NB; i++) {
          asm volatile("{.reg .pred p, q; setp.lt.u32 p, %4, %6; setp.lt.u32 q, %5, %6; @p ld.relaxed.gpu.global.u32 %0, [%2]; @q ld.relaxed.gpu.global.u32 %1, [%3];}"
            : "+r"(c0[i]), "+r"(c1[i]) : "l"((const char*)p.xb + cta * XPAD + (id[i] & 0xFFFF)), "l"((const char*)p.xb + cta * XPAD + (id[i] >> 16)), "r"(id[i] & 0xFFFF), "r"(id[i] >> 16), "n"(XPAD) : "memory");
          st |= (c0[i] ^ tag) | (c1[i] ^ tag); }
      }
#pragma unroll
      for (int i = 0; i < NB; i++) { const uint32_t j0 = (id[i] >> 8) & 255, j1 = id[i] >> 24;
        if (ABL & 2) { c0[i] &= 0xFFFF0FFFu; c1[i] &= 0xFFFF0FFFu; }
        asm volatile("{.reg .pred p, q, r; setp.lt.u32 p, %5, %9; setp.lt.u32 q, %6, %9; setp.lt.u32 r, %7, %8;\n"
          "@p st.shared.u32 [%0], %2; @q st.shared.u32 [%0+4], %3; @r st.shared.u32 [%1], %4;}"
          :: "r"(sb + OFF_TE + 2 * a + i * 256), "r"(sb + OFF_TS + a + i * 128), "r"(mad16(c0[i], 0x2000u, eb0 + ((ABL & 1) ? j0 & 7 : j0) * p.EPC * 32)), "r"(mad16(c1[i], 0x2000u, eb0 + ((ABL & 1) ? j1 & 7 : j1) * p.EPC * 32)),
             "r"(__byte_perm(c0[i], c1[i], 0x5410)), "r"(j0), "r"(j1), "r"(o + lane * 4 + i * 128), "r"(rem), "n"(G) : "memory"); }
    };
    bar_sync(2, 384);
    if (wid == 0) STAMP(27);
    mbar_wait(sb + BAR_HB);
    if (wid == 0) STAMP(22);
#pragma unroll 1
    for (uint32_t o = 0, go = 0; go < 32 * NST; o += 128 * RNB) {
      if (o < rem) { resolve(IC<RNB>(), o);
        asm volatile("{.reg .pred p; mbarrier.test_wait.parity.shared::cta.b64 p, [%1], 0; vote.sync.all.pred p, p, -1; selp.u32 %0, %2, 0, p;}" : "=r"(go) : "r"(sb + BAR_QP), "n"(32 * NEARLY) : "memory"); }
      else { bar_sync(8, 384); mbar_wait(sb + BAR_QP); go = 32 * NST; if (wid == 0) STAMP(24); }
      __syncwarp();
#pragma unroll 1
      while (to < go) { tl_(); issue(); if (to == 32) STAMP(13); }
    }
    bad = __shfl_sync(~0u, lds32(sb + OFF_MISC + 8), 0);
   if (!bad) {
#pragma unroll
    for (int j = 0; j < 4; j++) stsm4((p2 + fr) ^ (j << 5), pq[4 * j], pq[4 * j + 1], pq[4 * j + 2], pq[4 * j + 3]);
    auto body = [&](auto MODE) {
      constexpr int mode = decltype(MODE)::value;
      uint32_t T[16], ef[4], q0, q1, x0, x1, x2; float e0_, e1_, cs[4];
      auto mu = [&](int j) {
#pragma unroll
        for (int i = 2 * j; i < 2 * j + 2; i++) asm volatile("{.reg .b16 l, h; mov.b32 {l, h}, %2; tanh.approx.f16 %0, l; tanh.approx.f16 %1, h;}" : "=h"(tl[i]), "=h"(th[i]) : "r"(Y[i])); };
      auto fi = [&](int j) {
#pragma unroll
        for (int i = 2 * j; i < 2 * j + 2; i++) asm volatile("{.reg .b32 t; mov.b32 t, {%2, %3}; fma.rn.f16x2 %0, %1, t, %1;}" : "=r"(M[i]) : "r"(Y[i]), "h"(tl[i]), "h"(th[i])); };
      auto ad = [&](int j) { asm volatile("add.rn.f16x2 %0, %0, %1; add.rn.f16x2 %0, %0, %2;" : "+r"(sum[j]) : "r"(M[2 * j]), "r"(M[2 * j + 1])); };
      auto he = [&](int j) { asm volatile("mma.sync.aligned.m16n8k16.row.col.f16.f16.f16.f16 {%0,%1}, {%2,%3,%4,%5}, {%6,%7}, {%0,%1};" : "+r"(T[2 * j]), "+r"(T[2 * j + 1]) : "r"(ef[0]), "r"(ef[1]), "r"(ef[2]), "r"(ef[3]), "r"(w3[2 * j]), "r"(w3[2 * j + 1])); };
      auto hs = [&](int j) { asm volatile("mma.sync.aligned.m16n8k16.row.col.f16.f16.f16.f16 {%0,%1}, {%2,%3,%4,%5}, {%6,%7}, {%8,%9};" : "=r"(Y[2 * j]), "=r"(Y[2 * j + 1]) : "r"(q0), "r"(q1), "r"(oh0), "r"(oh1), "r"(bp[2 * j]), "r"(bp[2 * j + 1]), "r"(T[2 * j]), "r"(T[2 * j + 1])); };
      auto hc = [&](int j) {
        if (j) asm volatile("mma.sync.aligned.m16n8k16.row.col.f32.f16.f16.f32 {%0,%1,%2,%3}, {%4,%5,%6,%7}, {%8,%9}, {%0,%1,%2,%3};" : "+f"(cs[0]), "+f"(cs[1]), "+f"(cs[2]), "+f"(cs[3]) : "r"(M[4 * j]), "r"(M[4 * j + 1]), "r"(M[4 * j + 2]), "r"(M[4 * j + 3]), "r"(wv[2 * j]), "r"(wv[2 * j + 1]));
        else asm volatile("mma.sync.aligned.m16n8k16.row.col.f32.f16.f16.f32 {%0,%1,%2,%3}, {%4,%5,%6,%7}, {%8,%9}, {%10,%10,%10,%10};" : "=f"(cs[0]), "=f"(cs[1]), "=f"(cs[2]), "=f"(cs[3]) : "r"(M[0]), "r"(M[1]), "r"(M[2]), "r"(M[3]), "r"(wv[0]), "r"(wv[1]), "f"(0.f)); };
      auto cv = [&](int i) { asm volatile("{.reg .b32 a, b; shl.b32 a, %0, 16; and.b32 b, %0, 0xFFFF0000; cvt.rn.f16x2.f32 %0, b, a;}" : "+r"(ef[i])); };
      auto un = [&]() { asm volatile("shl.b32 %0, %2, 16; and.b32 %1, %2, 0xFFFF0000;" : "=&f"(e0_), "=&f"(e1_) : "r"(dpk)); };
      auto ex0 = [&]() { asm volatile("prmt.b32 %0, %3, %4, 0x6420; prmt.b32 %1, %5, %6, 0x6420; prmt.b32 %2, %7, %8, 0x6420;" : "=&r"(x0), "=&r"(x1), "=&r"(x2) : "r"(T[0]), "r"(T[1]), "r"(T[2]), "r"(T[3]), "r"(T[4]), "r"(T[5])); };
      auto ex1 = [&]() { asm volatile("{.reg .b32 a, b; shl.b32 a, %2, 3; shl.b32 b, %3, 6; lop3.b32 a, %1, a, 0x38383838, 0xD8; lop3.b32 a, a, b, 0xC0C0C0C0, 0xD8; sub.rn.bf16x2 %0, %4, a;}" : "=r"(dpk) : "r"(x0), "r"(x1), "r"(x2), "r"(own)); };
      auto ex2 = [&]() { asm volatile("{.reg .b32 a, b, d, u; .reg .b16 l, h; shl.b32 a, %2, 16; and.b32 b, %2, 0xFFFF0000; cvt.rn.f16x2.f32 d, b, a; mul.rn.f16x2 %0, d, d; mov.b32 {l, h}, d; mov.b32 u, {h, h}; mul.rn.f16x2 %1, u, u;}" : "=&r"(q0), "=&r"(q1) : "r"(dpk)); };
      auto pf = [&]() { asm volatile("fma.rn.f32 %0, %1, %2, %0; fma.rn.f32 %0, %3, %4, %0;" : "+f"(pacc) : "f"(cs[0]), "f"(e0_), "f"(cs[2]), "f"(e1_)); };
#define FX(k) if (FM >> k & 1) asm volatile("pmevent 1;" ::: "memory")
      if (mode == 2) {
        hc(0); mu(3); fi(2); un(); ad(0); ad(1); mu(4); fi(3); hc(1); mu(5); fi(4); ad(2); mu(6); fi(5); ad(3); hc(2); mu(7); fi(6); fi(7); ad(4); ad(5); hc(3); ad(6); ad(7); pf();
        return;
      }
      asm volatile("cp.async.wait_group %0;" :: "n"(NST - 1) : "memory");
      __syncwarp();
      if (mode == 1) STAMP(8);
      ldsm4(ef, eadr + so); ldsm4(T, qa0 + so); ldsm4(T + 4, qa1 + so); ldsm4(T + 8, qa2 + so); ldsm4(T + 12, qa3 + so);
      tl_();
      if (mode == 1) {
        issue();
        cv(0); cv(1); cv(2); cv(3); ex0(); ex1(); ex2();
#pragma unroll
        for (int j = 0; j < 8; j++) { he(j); hs(j); }
        mu(0); mu(1); fi(0); mu(2); fi(1);
        return;
      }
      hc(0); mu(3); fi(2); un(); ad(0); ad(1);
      FX(0);
      mu(4); fi(3); cv(0); cv(1); cv(2); cv(3); ex0(); ex1();
      FX(1);
      he(0); he(1); hc(1); mu(5); fi(4); ex2(); ad(2);
      FX(2);
      hs(0); he(2); mu(6); fi(5); issue(); ad(3);
      FX(3);
      hs(1); he(3); hc(2); mu(7); fi(6);
      FX(4);
      hs(2); hs(3); he(4); he(5); mu(0); fi(7); ad(4); ad(5);
      FX(5);
      hc(3); hs(4); he(6); he(7); mu(1); fi(0); ad(6);
      FX(6);
      hs(5); hs(6); hs(7); mu(2); fi(1); ad(7); pf();
      FX(7);
    };
#pragma unroll
    for (int j = 0; j < 8; j++) sum[j] = 0;
    body(IC<1>());
    int cnt = (lens & 255) - 1;
#pragma unroll 1
    for (int t = 0; t < 8; t++) {
#pragma unroll 1
      for (; cnt > 0; cnt--) { body(IC<0>());
      }
      if (!(t & 1)) {
        ownp = own;
        if (t < 6) {
          a_g += 64; own = lds16(a_g) * 0x10001u;
          if (t == 0) {
#pragma unroll
            for (int j = 0; j < 8; j++) bp[2 * j + 1] = sp[j];
          } else bload((a_g & 16) ? (t & 4) * 256 : 0);
          lens >>= 8; cnt = 1;
          continue;
        }
        body(IC<2>()); t++; a_g += 64;
        STAMP(9);
      }
      cnt = (lens & 255) - 1;
      asm volatile("{.reg .pred p; setp.ne.u32 p, %2, 6; @p st.shared.u16 [%0+-64], %1;}" :: "r"(a_g), "h"((uint16_t)pack_bf16(bf_hi(ownp) + pacc, 0.f)), "r"(a_g & 6) : "memory");
      chk = fmaf(pacc, 0.f, chk); pacc = 0.f;
      if (t & 2) {
        uint32_t hf[16]; float acc[32];
        const uint32_t nd = lds16(a_n);
        const uint32_t hrow = hload(hf, nd);
        a_n += 128;
        __syncwarp();
        mbar_arrive(sb + BAR_X, (a_g & 62) == 0);
        const uint64_t b1 = DHI | ((sb + OFF_W) >> 4), b2_ = b1 + 512;
        mbar_wait(sb + BAR_WH);
        wg_fence();
        rs64h<0>(acc, sp[0], sum[0], sp[1], sum[1], b2_); rs64h<1>(acc, sp[2], sum[2], sp[3], sum[3], b2_ + 128); rs64h<1>(acc, sp[4], sum[4], sp[5], sum[5], b2_ + 256); rs64h<1>(acc, sp[6], sum[6], sp[7], sum[7], b2_ + 384);
        rs64b<1>(acc, hf[0], hf[1], hf[2], hf[3], b1); rs64b<1>(acc, hf[4], hf[5], hf[6], hf[7], b1 + 128); rs64b<1>(acc, hf[8], hf[9], hf[10], hf[11], b1 + 256); rs64b<1>(acc, hf[12], hf[13], hf[14], hf[15], b1 + 384);
        wg_commit();
        uint32_t nr[4];
#pragma unroll
        for (int j = 0; j < 4; j++) nr[j] = __shfl_sync(~0u, nd, 4 * j + ((a_g >> 4) & 3)) * 128 + ((a_g << 3) & 0x70);
        wg_wait0(); fence_regs(acc);
        if (t == 7) STAMP(10);
        chk = fmaf(acc[0], 0.f, fmaf(acc[2], 0.f, chk));
        auto fin = [&](uint32_t x, float y0, float y1) { return u2(__hadd2(b2(x), b2(pack_bf16(silu_h(y0), silu_h(y1))))); };
#pragma unroll
        for (int j = 0; j < 4; j++) stsm4(hrow ^ (j << 5), fin(hf[4 * j], acc[8 * j], acc[8 * j + 1]), fin(hf[4 * j + 1], acc[8 * j + 2], acc[8 * j + 3]), fin(hf[4 * j + 2], acc[8 * j + 4], acc[8 * j + 5]), fin(hf[4 * j + 3], acc[8 * j + 6], acc[8 * j + 7]));
        __syncwarp();
        if (DEFO && t == 3) mbar_arrive(sb + BAR_M, (a_g & 62) == 0);
        else {
          uint32_t v[16];
#pragma unroll
          for (int j = 0; j < 4; j++) lds128(v + 4 * j, sb + OFF_H + (nr[j] ^ ((nr[j] >> 3) & 0x70)));
#pragma unroll
          for (int j = 0; j < 4; j++) asm volatile("{.reg .pred p; setp.lt.u32 p, %5, %6; @p st.global" OCS ".v4.b32 [%0], {%1,%2,%3,%4};}" :: "l"(outh + nr[j]), "r"(v[4 * j]), "r"(v[4 * j + 1]), "r"(v[4 * j + 2]), "r"(v[4 * j + 3]), "r"(nr[j]), "r"(nl * 128) : "memory");
          if (DEFO) break;
        }
        wload();
      }
#pragma unroll
      for (int j = 0; j < 8; j++) { sp[j] = sum[j]; asm volatile("mov.b32 %0, 0;" : "=r"(sum[j])); }
    }
    asm volatile("{.reg .pred p, q; setp.neu.f32 p, %1, 0f00000000; setp.ne.or.u32 p, %2, 0, p; bar.red.or.pred q, 5, %3, p; selp.u32 %0, 1, 0, q;}" : "=r"(bad) : "f"(chk), "r"(lds32(sb + OFF_MISC + 12)), "n"(DEFO ? 512 : 384) : "memory");
    STAMP(11);
   } else { asm volatile("cp.async.wait_all;" ::: "memory"); bar_sync(5, 384); }
  }
  if (bad) slow_path(p, wid, lane, node0, nloc);
}

}

typedef CUresult (*EncodeFn)(CUtensorMap*, CUtensorMapDataType, cuuint32_t, void*, const cuuint64_t*, const cuuint64_t*, const cuuint32_t*, const cuuint32_t*,
                             CUtensorMapInterleave, CUtensorMapSwizzle, CUtensorMapL2promotion, CUtensorMapFloatOOBfill);

extern "C" void kernel_launch(void* const* d_in, const int* in_sizes, int n_in, void* d_out, int out_size) {
  Params p; Maps maps;
  p.h = (const uint4*)d_in[0]; p.pos = (const uint16_t*)d_in[1]; p.ea = (const uint4*)d_in[2];
  p.src = (const int*)d_in[3]; p.dst = (const int*)d_in[4];
  p.we = (const uint16_t*)d_in[5]; p.wx = (const uint16_t*)d_in[6]; p.wh = (const uint16_t*)d_in[7];
  p.out = (uint16_t*)d_out;
  p.N = in_sizes[0] / 64; p.E = in_sizes[3];
  p.EPC = ((p.E + G * 4 - 1) / (G * 4)) * 4;
  p.magic = (uint32_t)(((uint64_t)G << 24) / (uint64_t)p.N);
  p.inv = (1ull << 56) / p.magic;
  const uint64_t ea0 = (uint64_t)d_in[2], ea1 = ea0 + (uint64_t)p.E * 32 - 1;
  p.force_slow = ((ea0 >> 32) != (ea1 >> 32)) || (ea0 & 31) || (p.E & 3);
  void* qp = nullptr;
  cudaGetSymbolAddress(&qp, g_q);
  p.q = (char*)qp;
  if (((uint64_t)p.q >> 32) != (((uint64_t)p.q + QBYTES) >> 32)) p.q += QBYTES;
  cudaGetSymbolAddress((void**)&p.sync, g_sync); cudaGetSymbolAddress((void**)&p.xe, g_xe);
  cudaGetSymbolAddress((void**)&p.xa, g_xa); cudaGetSymbolAddress((void**)&p.xb, g_xb);
  void* fn = nullptr; cudaDriverEntryPointQueryResult qr;
  cudaGetDriverEntryPoint("cuTensorMapEncodeTiled", &fn, cudaEnableDefault, &qr);
  auto mk = [&](CUtensorMap* tm, void* base, int rows, int box = 64) {
    const cuuint64_t dim[2] = {64, (cuuint64_t)rows}, str[1] = {128}; const cuuint32_t bx[2] = {64, (cuuint32_t)box}, es[2] = {1, 1};
    ((EncodeFn)fn)(tm, CU_TENSOR_MAP_DATA_TYPE_BFLOAT16, 2, base, dim, str, bx, es, CU_TENSOR_MAP_INTERLEAVE_NONE, CU_TENSOR_MAP_SWIZZLE_128B,
                   CU_TENSOR_MAP_L2_PROMOTION_NONE, CU_TENSOR_MAP_FLOAT_OOB_FILL_NONE);
  };
  mk(&maps.m[TM_H / 128], d_in[0], p.N); mk(&maps.m[TM_WE / 128], d_in[5], 145); mk(&maps.m[TM_WH / 128], d_in[7], 128); mk(&maps.m[TM_Q / 128], p.q, p.N, 16);
  for (int k = 0; k < 2; k++) {
    void* xp = (void*)(k ? p.xb : p.xa);
    const cuuint64_t dim[2] = {(cuuint64_t)G * 64, (cuuint64_t)G}, str[1] = {(cuuint64_t)G * (128 << k)}; const cuuint32_t bx[2] = {64, (cuuint32_t)(k ? BROWS : G)}, es[2] = {1, 1};
    ((EncodeFn)fn)(&maps.m[TM_XA / 128 + k], k ? CU_TENSOR_MAP_DATA_TYPE_UINT32 : CU_TENSOR_MAP_DATA_TYPE_UINT16, 2, xp, dim, str, bx, es, CU_TENSOR_MAP_INTERLEAVE_NONE,
                   CU_TENSOR_MAP_SWIZZLE_NONE, CU_TENSOR_MAP_L2_PROMOTION_NONE, CU_TENSOR_MAP_FLOAT_OOB_FILL_NONE);
  }
  cudaFuncSetAttribute(egnn_kernel, cudaFuncAttributeMaxDynamicSharedMemorySize, SMEM);
  egnn_kernel<<<G, NTHR, SMEM>>>(p, maps);
}
```

```cpp
#include <cuda_runtime.h>
#include <cuda_bf16.h>
#include <cuda_fp16.h>
#include <cuda.h>
#include <stdint.h>
#pragma nv_diag_suppress 549

#define PFN 16
#define PFNS 250
#define FM 0
#define OPQ 0
#define H0 0
#define HALL 1
#define PF0NS 0
#define PFW 0
#define QCODE 0x254a109b7863ull
#define QREV 0x605
#define PFS 1
#define ESZ ""
#define XEF 0
#define OCS ""
#define RNB 2
#define NEARLY 2
#define PFE 0
#define DEFO 1
#define DEFNS 400
#define ABL 0
#define IDL 1
#define HW 3
#define BROWS 132
#define B_HOLD 1
#define LSEQ 0x231200ull
#define HE 0
namespace {

constexpr int G = 132;
constexpr int NTHR = 512, NWK = 352, NCH = 5;
constexpr int NST = 3, STG = 2560;
constexpr int SCAP = 448;

constexpr int OFF_H = 0;
constexpr int OFF_W = 49152;
constexpr int OFF_WD = OFF_W + 16384;
constexpr int OFF_W3 = OFF_WD + 1024;
constexpr int OFF_P2 = OFF_W3 + 2048;
constexpr int OFF_RING = OFF_P2 + 24576;
constexpr int OFF_TE = OFF_RING + 12 * NST * STG;
constexpr int OFF_TS = OFF_TE + SCAP * 64;
constexpr int OFF_GP = OFF_TS + SCAP * 32;
constexpr int OFF_WX = OFF_GP + 3072;
constexpr int OFF_LEN = OFF_WX + 128;
constexpr int OFF_MISC = OFF_LEN + 128;
constexpr int OFF_BAR = OFF_MISC + 48;
constexpr int SMEM = OFF_BAR + 256;
static_assert(SMEM <= 232448, "smem");
constexpr uint32_t sb = 1024;
constexpr int OFF_SRCI = OFF_TE;
constexpr int OFF_SB = OFF_RING, OFF_SA = OFF_SB + 34816, OFF_AX = OFF_SA + 32768, OFF_DST = OFF_H + 24576;
constexpr int OFF_WS = OFF_AX + 17408;
constexpr int OFF_BC = OFF_WS + 2304;
constexpr int OFF_CNT = OFF_P2;
constexpr int OFF_DH = OFF_CNT + 2176;
constexpr int OFF_POS = OFF_DH + 128;
constexpr int OFF_EXT = OFF_POS + 3072;
constexpr int OFF_XB = OFF_EXT + 1024, XPAD = G * 256;
static_assert(OFF_XB + XPAD + 1028 <= OFF_RING + 12 * STG && OFF_XB % 128 == 0 && OFF_BC + 544 <= OFF_TE && OFF_P2 % 1024 == 0 && OFF_SA % 1024 == 0 && SCAP * 64 >= 24576, "staging");
constexpr int BAR_DST = OFF_BAR, BAR_SRC = BAR_DST + 40, BAR_T = BAR_SRC + 24, BAR_W = BAR_T + 48, BAR_XA = BAR_W + 8, BAR_PS = BAR_XA + 8, BAR_AW = BAR_PS + 8,
              BAR_QP = BAR_AW + 8, BAR_QR = BAR_QP + 8, BAR_HA = BAR_QR + 8, BAR_EP = BAR_HA + 8, BAR_AX = BAR_EP + 8, BAR_AI = BAR_AX + 8, BAR_HB = BAR_AI + 8, BAR_U = BAR_HB + 8, BAR_WH = BAR_U + 8, BAR_M = BAR_WH + 8, BAR_X = BAR_M + 8, BAR_END = BAR_X + 8;
static_assert(BAR_END <= OFF_BAR + 256, "barriers");
constexpr uint32_t QBYTES = 8u << 20;

__device__ __align__(256) uint4 g_xa[G * G * 8];
__device__ __align__(256) uint4 g_xb[G * G * 16];
__device__ __align__(256) uint2 g_xe[G * G * 32];
__device__ __align__(256) uint4 g_q[2 * QBYTES / 16];
__device__ __align__(256) uint32_t g_sync[8];
#define STAMP(k)

struct Maps { CUtensorMap m[6]; };
constexpr int TM_H = 0, TM_WE = 128, TM_WH = 256, TM_Q = 384, TM_XA = 512, TM_XB = 640;
struct Params {
  const int* dst; uint32_t* sync; int E, EPC, N; uint32_t magic; unsigned long long inv;
  const int* src; const uint16_t* pos; const uint4* ea; const uint16_t* we; const uint16_t* wx; char* q; int force_slow;
  const uint4* xa; const uint4* xb; uint2* xe; uint16_t* out; const uint4* h; const uint16_t* wh;
};
template<int V> struct IC { static constexpr int value = V; };

#define R32(d) "+f"(d[0]),"+f"(d[1]),"+f"(d[2]),"+f"(d[3]),"+f"(d[4]),"+f"(d[5]),"+f"(d[6]),"+f"(d[7]),"+f"(d[8]),"+f"(d[9]),"+f"(d[10]),"+f"(d[11]),"+f"(d[12]),"+f"(d[13]),"+f"(d[14]),"+f"(d[15]),"+f"(d[16]),"+f"(d[17]),"+f"(d[18]),"+f"(d[19]),"+f"(d[20]),"+f"(d[21]),"+f"(d[22]),"+f"(d[23]),"+f"(d[24]),"+f"(d[25]),"+f"(d[26]),"+f"(d[27]),"+f"(d[28]),"+f"(d[29]),"+f"(d[30]),"+f"(d[31])
#define S32 "{%0,%1,%2,%3,%4,%5,%6,%7,%8,%9,%10,%11,%12,%13,%14,%15,%16,%17,%18,%19,%20,%21,%22,%23,%24,%25,%26,%27,%28,%29,%30,%31}"
#define DI __device__ __forceinline__

constexpr uint64_t DHI = ((uint64_t)(1024 >> 4) << 32) | (1ull << 62);
template<int SD> DI void rs64b(float (&d)[32], uint32_t a0, uint32_t a1, uint32_t a2, uint32_t a3, uint64_t db) {
  asm volatile("wgmma.mma_async.sync.aligned.m64n64k16.f32.bf16.bf16 " S32 ", {%32,%33,%34,%35}, %36, %37, 1, 1, 1;" : R32(d) : "r"(a0), "r"(a1), "r"(a2), "r"(a3), "l"(db), "n"(SD)); }
template<int SD> DI void rs64h(float (&d)[32], uint32_t a0, uint32_t a1, uint32_t a2, uint32_t a3, uint64_t db) {
  asm volatile("wgmma.mma_async.sync.aligned.m64n64k16.f32.f16.f16 " S32 ", {%32,%33,%34,%35}, %36, %37, 1, 1, 1;" : R32(d) : "r"(a0), "r"(a1), "r"(a2), "r"(a3), "l"(db), "n"(SD)); }
template<int SD> DI void ss64(float (&d)[32], uint64_t da, uint64_t db) {
  asm volatile("wgmma.mma_async.sync.aligned.m64n64k16.f32.bf16.bf16 " S32 ", %32, %33, %34, 1, 1, 0, 1;" : R32(d) : "l"(da), "l"(db), "n"(SD)); }
DI void trap_if(bool c) { asm volatile("{.reg .pred p; setp.eq.u32 p, %0, 0; @p bra.uni LT_%=; trap; LT_%=:}" :: "r"((uint32_t)c)); }
DI void wg_fence() { asm volatile("wgmma.fence.sync.aligned;" ::: "memory"); }
DI void wg_commit() { asm volatile("wgmma.commit_group.sync.aligned;" ::: "memory"); }
DI void wg_wait0() { asm volatile("wgmma.wait_group.sync.aligned 0;" ::: "memory"); }
DI void fence_regs(float (&d)[32]) { asm volatile("" : R32(d) :: "memory"); }
DI void proxy_fence() { asm volatile("fence.proxy.async.shared::cta;" ::: "memory"); }
DI uint64_t pol_first() { uint64_t r; asm("createpolicy.fractional.L2::evict_first.b64 %0, 1.0;" : "=l"(r)); return r; }
DI float tanh_ap(float x) { float y; asm("tanh.approx.f32 %0, %1;" : "=f"(y) : "f"(x)); return y; }
DI float silu_h(float y) { return fmaf(y, tanh_ap(y), y); }
DI uint32_t pack_bf16(float lo, float hi) { uint32_t r; asm("cvt.rn.bf16x2.f32 %0, %1, %2;" : "=r"(r) : "f"(hi), "f"(lo)); return r; }
DI uint32_t pack_f16(float lo, float hi) { uint32_t r; asm("cvt.rn.f16x2.f32 %0, %1, %2;" : "=r"(r) : "f"(hi), "f"(lo)); return r; }
DI float bf_lo(uint32_t v) { return __uint_as_float(v << 16); }
DI float bf_hi(uint32_t v) { return __uint_as_float(v & 0xFFFF0000u); }
DI uint32_t b2h(uint32_t v, float s) { return pack_f16(s * bf_lo(v), s * bf_hi(v)); }
DI void mbar_wait(uint32_t bar, uint32_t parity = 0) {
  asm volatile("{.reg .pred p; .reg .u32 t0, t1;\n"
    "mbarrier.try_wait.parity.shared::cta.b64 p, [%0], %1;\n @p bra.uni LD_%=;\n mov.u32 t0, %%clock;\n"
    "LW_%=: mbarrier.try_wait.parity.shared::cta.b64 p, [%0], %1;\n"
    "@p bra.uni LD_%=;\n mov.u32 t1, %%clock; sub.u32 t1, t1, t0; setp.lt.u32 p, t1, 0x80000000;\n @p bra.uni LW_%=;\n trap;\n LD_%=:}" :: "r"(bar), "r"(parity) : "memory");
}
DI void mbar_arrive(uint32_t bar, int p = 1) { asm volatile("{.reg .pred p; setp.ne.b32 p, %1, 0; @p mbarrier.arrive.shared::cta.b64 _, [%0];}" :: "r"(bar), "r"(p) : "memory"); }
DI void bar_sync(int id, int n) { asm volatile("bar.sync %0, %1;" :: "r"(id), "r"(n) : "memory"); }
DI void bar_arrive(int id, int n) { asm volatile("bar.arrive %0, %1;" :: "r"(id), "r"(n) : "memory"); }
DI __nv_bfloat162 b2(uint32_t v) { return *(__nv_bfloat162*)&v; }
DI uint32_t u2(__nv_bfloat162 v) { return *(uint32_t*)&v; }
DI uint32_t hsq(uint32_t v) { return u2(__hmul2(b2(v), b2(v))); }
DI uint32_t hsub(uint32_t a, uint32_t b) { return u2(__hsub2(b2(a), b2(b))); }
DI uint32_t hhalf(uint32_t v) { return u2(__hmul2(b2(v), __floats2bfloat162_rn(0.5f, 0.5f))); }
DI uint32_t mag2(uint32_t m, uint32_t v) { return __vmaxu2(m, v & 0x7FFF7FFFu); }
DI uint32_t hmag(uint32_t m, uint32_t v) { const __half2 r = __hmax2(*(const __half2*)&m, __habs2(*(const __half2*)&v)); return *(const uint32_t*)&r; }
DI uint32_t magr(uint32_t m) { return max(m & 0xFFFF, m >> 16); }
DI void sts128(uint32_t a, uint32_t x, uint32_t y, uint32_t z, uint32_t w) { asm volatile("st.shared.v4.u32 [%0], {%1,%2,%3,%4};" :: "r"(a), "r"(x), "r"(y), "r"(z), "r"(w) : "memory"); }
DI void sts64(uint32_t a, uint32_t x, uint32_t y) { asm volatile("st.shared.v2.u32 [%0], {%1,%2};" :: "r"(a), "r"(x), "r"(y) : "memory"); }
DI void sts32(uint32_t a, uint32_t x) { asm volatile("st.shared.u32 [%0], %1;" :: "r"(a), "r"(x) : "memory"); }
DI void sts16(uint32_t a, uint32_t x) { asm volatile("st.shared.u16 [%0], %1;" :: "r"(a), "h"((uint16_t)x) : "memory"); }
DI void lds128(uint32_t* v, uint32_t a) { asm volatile("ld.shared.v4.u32 {%0, %1, %2, %3}, [%4];" : "=r"(v[0]), "=r"(v[1]), "=r"(v[2]), "=r"(v[3]) : "r"(a) : "memory"); }
DI void lds64(uint32_t& x, uint32_t& y, uint32_t a) { asm volatile("ld.shared.v2.u32 {%0, %1}, [%2];" : "=r"(x), "=r"(y) : "r"(a) : "memory"); }
DI uint32_t lds32(uint32_t a) { uint32_t x; asm volatile("ld.shared.u32 %0, [%1];" : "=r"(x) : "r"(a) : "memory"); return x; }
DI uint32_t lds16(uint32_t a) { uint32_t x; asm volatile("ld.shared.u16 %0, [%1];" : "=r"(x) : "r"(a) : "memory"); return x; }
DI uint32_t atoms_add(uint32_t a, uint32_t v) { uint32_t r; asm volatile("atom.shared.add.u32 %0, [%1], %2;" : "=r"(r) : "r"(a), "r"(v) : "memory"); return r; }
DI void bulk_load(uint32_t dst, const void* src, uint32_t bytes, uint32_t bar) {
  asm volatile("cp.async.bulk.shared::cluster.global.mbarrier::complete_tx::bytes.L2::cache_hint [%0], [%1], %2, [%3], %4;" :: "r"(dst), "l"(src), "r"(bytes), "r"(bar), "l"(pol_first()) : "memory"); }
DI void bulk_store(void* dst, uint32_t src, uint32_t bytes) { asm volatile("cp.async.bulk.global.shared::cta.bulk_group [%0], [%1], %2;" :: "l"(dst), "r"(src), "r"(bytes) : "memory"); }
DI void mbar_expect(uint32_t bar, uint32_t bytes) { asm volatile("mbarrier.arrive.expect_tx.shared::cta.b64 _, [%0], %1;" :: "r"(bar), "r"(bytes) : "memory"); }
DI void mbar_init(uint32_t bar, int n) { asm volatile("mbarrier.init.shared::cta.b64 [%0], %1;" :: "r"(bar), "r"(n) : "memory"); }
DI void tma_load(uint32_t dst, uint64_t tm, int row, uint32_t bar) {
  asm volatile("cp.async.bulk.tensor.2d.shared::cluster.global.mbarrier::complete_tx::bytes.L2::cache_hint [%0], [%1, {%3, %4}], [%2], %5;" :: "r"(dst), "l"(tm), "r"(bar), "r"(0), "r"(row), "l"(pol_first()) : "memory"); }
DI void tma_store(uint64_t tm, int col, int row, uint32_t src) {
  asm volatile("cp.async.bulk.tensor.2d.global.shared::cta.bulk_group [%0, {%2, %3}], [%1];" :: "l"(tm), "r"(src), "r"(col), "r"(row) : "memory"); }
DI void tma_store_ef(uint64_t tm, int col, int row, uint32_t src) {
  if (XEF) asm volatile("cp.async.bulk.tensor.2d.global.shared::cta.bulk_group.L2::cache_hint [%0, {%2, %3}], [%1], %4;" :: "l"(tm), "r"(src), "r"(col), "r"(row), "l"(pol_first()) : "memory");
  else tma_store(tm, col, row, src); }
DI void bulk_commit() { asm volatile("cp.async.bulk.commit_group;" ::: "memory"); }
DI void bulk_wait_read() { asm volatile("cp.async.bulk.wait_group.read 0;" ::: "memory"); }
DI uint2 ld_poll2(const void* a) { uint2 v; asm volatile("ld.relaxed.gpu.global.v2.u32 {%0, %1}, [%2];" : "=r"(v.x), "=r"(v.y) : "l"(a) : "memory"); return v; }
DI void st_ext(uint2* a, uint32_t v, uint32_t ep) { asm volatile("st.relaxed.gpu.global.v2.u32 [%0], {%1, %2};" :: "l"(a), "r"(v), "r"(ep) : "memory"); }
DI uint32_t ext_get(const uint2* a, uint32_t ep) { uint2 v; int spin = 0; do { v = ld_poll2(a); trap_if(++spin > 4000000); } while (__any_sync(~0u, v.y != ep)); return v.x; }
DI void bulk_wait() { asm volatile("cp.async.bulk.wait_group 0;" ::: "memory"); }
DI void hint_signal(uint32_t* c) { asm volatile("red.relaxed.gpu.global.add.u32 [%0], 1;" :: "l"(c) : "memory"); }
DI void hint_wait(const uint32_t* c, uint32_t target) { uint32_t v; int spin = 0;
  do { asm volatile("ld.relaxed.gpu.global.u32 %0, [%1];" : "=r"(v) : "l"(c) : "memory"); trap_if(++spin > 4000000); } while (__any_sync(~0u, (int)(v - target) < 0)); }
DI void stsm4(uint32_t a, uint32_t x, uint32_t y, uint32_t z, uint32_t w) { asm volatile("stmatrix.sync.aligned.m8n8.x4.shared.b16 [%0], {%1,%2,%3,%4};" :: "r"(a), "r"(x), "r"(y), "r"(z), "r"(w) : "memory"); }
DI void ldsm4(uint32_t* v, uint32_t a) { asm volatile("ldmatrix.sync.aligned.m8n8.x4.shared.b16 {%0,%1,%2,%3}, [%4];" : "=r"(v[0]), "=r"(v[1]), "=r"(v[2]), "=r"(v[3]) : "r"(a) : "memory"); }
DI void ldsm4t(uint32_t* v, uint32_t a) { asm volatile("ldmatrix.sync.aligned.m8n8.x4.trans.shared.b16 {%0,%1,%2,%3}, [%4];" : "=r"(v[0]), "=r"(v[1]), "=r"(v[2]), "=r"(v[3]) : "r"(a) : "memory"); }
DI uint32_t mad16(uint32_t x, uint32_t m, uint32_t c) { uint32_t r; asm("dp2a.lo.u32.u32 %0, %1, %2, %3;" : "=r"(r) : "r"(x), "r"(m), "r"(c)); return r; }
DI bool wbad(uint32_t m, uint32_t hi) { return m > hi || (m && m < 0x3980); }

__device__ __noinline__ void slow_path(const Params& p, int wid, int lane, int node0, int nloc) {
  const uint32_t ab = sb + OFF_P2 + wid * 8704;
  for (int i = lane; i < 32 * 68; i += 32) sts32(ab + i * 4, 0);
  __syncwarp();
  const uint32_t wdv = __ldg((const uint32_t*)(p.we + 128 * 64) + lane), wxv = __ldg((const uint32_t*)p.wx + lane);
  const int nb0 = node0 + wid * 32, cntn = max(0, min(32, nloc - wid * 32));
  auto dot = [&](uint32_t hv, const uint16_t* w, int K2, float& y0, float& y1) {
#pragma unroll 4
    for (int k = 0; k < K2; k++) {
      const uint32_t hk = __shfl_sync(~0u, hv, k), wa = __ldg((const uint32_t*)(w + 2 * k * 64) + lane), wb = __ldg((const uint32_t*)(w + (2 * k + 1) * 64) + lane);
      y0 = fmaf(bf_lo(hk), bf_lo(wa), fmaf(bf_hi(hk), bf_lo(wb), y0)); y1 = fmaf(bf_lo(hk), bf_hi(wa), fmaf(bf_hi(hk), bf_hi(wb), y1));
    }
  };
  auto silu = [](float x) { return x / (1.f + __expf(-x)); };
#pragma unroll 1
  for (int base = 0; base < p.E; base += 32) {
    const int e = base + lane;
    const uint32_t dl = e < p.E ? (uint32_t)(__ldg(p.dst + e) - nb0) : 0xFFFFFFFFu;
    uint32_t mk = __ballot_sync(~0u, dl < (uint32_t)cntn);
    while (mk) {
      const int l = __ffs(mk) - 1; mk &= mk - 1;
      const int ee = base + l, n = __shfl_sync(~0u, dl, l), s = __ldg(p.src + ee);
      const uint16_t *po = p.pos + (size_t)(nb0 + n) * 3, *pp = p.pos + (size_t)s * 3;
      const uint32_t dxy = hsub(__ldg(po) | (__ldg(po + 1) << 16), __ldg(pp) | (__ldg(pp + 1) << 16)), dz = hsub(__ldg(po + 2), __ldg(pp + 2));
      const uint32_t sq = hsq(dxy); const float d2 = bf_lo(sq) + bf_hi(sq) + bf_lo(hsq(dz));
      float y0 = d2 * bf_lo(wdv), y1 = d2 * bf_hi(wdv);
      dot(__ldg((const uint32_t*)(p.h + (size_t)(nb0 + n) * 8) + lane), p.we, 32, y0, y1);
      dot(__ldg((const uint32_t*)(p.h + (size_t)s * 8) + lane), p.we + 64 * 64, 32, y0, y1);
      dot(__ldg((const uint32_t*)(p.ea + (size_t)ee * 2) + (lane & 7)), p.we + 129 * 64, 8, y0, y1);
      const uint32_t mm = pack_bf16(silu(y0), silu(y1));
      float c = bf_lo(mm) * bf_lo(wxv) + bf_hi(mm) * bf_hi(wxv);
#pragma unroll
      for (int o = 16; o; o >>= 1) c += __shfl_xor_sync(~0u, c, o);
      const uint32_t a = ab + n * 272;
      uint32_t x0, x1; lds64(x0, x1, a + lane * 8);
      sts64(a + lane * 8, __float_as_uint(__uint_as_float(x0) + bf_lo(mm)), __float_as_uint(__uint_as_float(x1) + bf_hi(mm)));
      if (lane < 3) { const float df = lane == 0 ? bf_lo(dxy) : lane == 1 ? bf_hi(dxy) : bf_lo(dz); sts32(a + 256 + lane * 4, __float_as_uint(fmaf(c, df, __uint_as_float(lds32(a + 256 + lane * 4))))); }
    }
  }
  __syncwarp();
#pragma unroll 1
  for (int n = 0; n < cntn; n++) {
    uint32_t x0, x1; lds64(x0, x1, ab + n * 272 + lane * 8);
    const uint32_t hv = __ldg((const uint32_t*)(p.h + (size_t)(nb0 + n) * 8) + lane);
    float y0 = 0.f, y1 = 0.f;
    dot(hv, p.wh, 32, y0, y1); dot(pack_bf16(__uint_as_float(x0), __uint_as_float(x1)), p.wh + 64 * 64, 32, y0, y1);
    ((uint32_t*)p.out)[(size_t)(nb0 + n) * 32 + lane] = u2(__hadd2(b2(hv), b2(pack_bf16(silu(y0), silu(y1)))));
    if (lane < 3) p.out[(size_t)p.N * 64 + (size_t)(nb0 + n) * 3 + lane] = (uint16_t)pack_bf16(bf_lo(__ldg(p.pos + (size_t)(nb0 + n) * 3 + lane)) + __uint_as_float(lds32(ab + n * 272 + 256 + lane * 4)), 0.f);
  }
}

__global__ void __launch_bounds__(NTHR, 1) egnn_kernel(const __grid_constant__ Params p, const __grid_constant__ Maps maps) {
  const uint64_t tmb = (uint64_t)&maps;
  extern __shared__ __align__(1024) unsigned char smraw[];
  const int tid = threadIdx.x, cta = blockIdx.x;
  const int e0 = cta * p.EPC, n4 = max(0, min(p.EPC, p.E - e0)) >> 2;
  STAMP(0);
  if (tid == NWK) {
#pragma unroll 1
    for (int k = 0; k < NCH; k++) { const int nb = max(0, min(NWK, n4 - k * NWK)) * 16;
      mbar_init(sb + BAR_DST + k * 8, 1);
      asm volatile("fence.mbarrier_init.release.cluster;" ::: "memory");
      mbar_expect(sb + BAR_DST + k * 8, nb);
      if (nb) bulk_load(sb + OFF_DST + k * NWK * 16, (const char*)(p.dst + e0) + k * NWK * 16, nb, sb + BAR_DST + k * 8); }
  }
  const int lane = tid & 31, wid = __shfl_sync(~0u, tid >> 5, 0), w = wid & 3;
  asm volatile("{.reg .pred p; setp.eq.u32 p, %2, 384; @p cp.async.cg.shared.global [%0], [%1], 16;}" :: "r"(sb + OFF_LEN - 192 + (tid >> 1)), "l"(p.sync), "r"(tid & 415) : "memory");

  auto first_node = [&](int c) { return (int)((c * p.inv + 0xFFFFFFFFull) >> 32); };
  const int node0 = first_node(cta), nloc = min(first_node(cta + 1), p.N) - node0;
  const uint32_t ealo = (uint32_t)(uint64_t)p.ea;
  const int epad = min(e0, p.E - 1);
  auto load_h = [&](int b) { mbar_expect(sb + BAR_T + b * 8, 8192); tma_load(sb + OFF_H + b * 8192, tmb + TM_H, node0 + b * 64, sb + BAR_T + b * 8); };
  auto prefetch_e = [&](int i) {
    const uint32_t nb = (p.E / G) & ~15u;
    if (nb && i < PFN) asm volatile("cp.async.bulk.prefetch.L2.global [%0], %1;" :: "l"((const char*)p.ea + (size_t)(((i * PFS + i * PFS / 32 * (~PFS & 1)) & 31) * G + cta) * nb), "r"(nb) : "memory");
  };
  if (wid >= 12) {
    const int t = tid - 384;
    uint32_t pv[9], ev = 0;
#pragma unroll
    for (int i = 0; i < 3; i++) { const uint16_t* pp = p.pos + (size_t)(node0 + t + 128 * i) * 3;
      pv[3 * i] = pv[3 * i + 1] = pv[3 * i + 2] = 0;
      asm volatile("{.reg .pred p; setp.lt.s32 p, %4, %5;\n @p ld.global.nc.u16 %0, [%3];\n @p ld.global.nc.u16 %1, [%3+2];\n @p ld.global.nc.u16 %2, [%3+4];}"
        : "+r"(pv[3 * i]), "+r"(pv[3 * i + 1]), "+r"(pv[3 * i + 2]) : "l"(pp), "r"(t + 128 * i), "r"(p.N - node0)); }
    asm volatile("{.reg .pred p; setp.lt.u32 p, %3, 8; @p ld.global.nc.u32 %0, [%1]; @p st.global.v4.u32 [%2], {%4, %4, %4, %4};}"
      : "+r"(ev) : "l"((const uint32_t*)(p.ea + (size_t)epad * 2) + t), "l"(p.q + (size_t)(p.N + cta) * 128 + t * 16), "r"(t), "r"(0xF700F700u) : "memory");
    asm volatile("cp.async.wait_all;" ::: "memory");
    __syncwarp();
    const uint32_t e = lds32(sb + OFF_LEN + 8 + w * 16) + 1;
    {
      const uint32_t tg = (1 + e % 3) << 30, v = ((tg >> 16) + 512 + (lane & 7) * 4) * 0x10001u;
      if (t == 0) sts32(sb + OFF_MISC + 32, e);
#pragma unroll
      for (int i = 0; i < 9; i++) sts128(sb + OFF_SA + t * 16 + i * 2048, v, v + 0x10001u, v + 0x20002u, v + 0x30003u);
      bar_sync(6, NTHR);
      mbar_arrive(sb + BAR_EP, lane == 0);
#pragma unroll
      for (int i = 0; i < 17; i++) sts128(sb + OFF_SB + t * 16 + i * 2048, tg, tg, tg, tg); }
    uint32_t mp = 0;
#pragma unroll
    for (int i = 0; i < 3; i++) { sts64(sb + OFF_POS + (t + 128 * i) * 8, pv[3 * i] | (pv[3 * i + 1] << 16), pv[3 * i + 2]); mp = mag2(mag2(mp, pv[3 * i] | (pv[3 * i + 1] << 16)), pv[3 * i + 2]); }
    proxy_fence();
    __syncwarp();
    mbar_arrive(sb + BAR_PS, lane == 0);
    mbar_wait(sb + BAR_W);
    {
      uint32_t v[4], u[4]; const int r = t >> 3, c = t & 7;
      lds128(v, sb + OFF_WS + 128 + t * 16); lds128(u, sb + OFF_WS + c * 16);
      const uint32_t x = lds32(sb + OFF_WS + 2176 + lane * 4);
      sts128(sb + OFF_W3 + r * 128 + ((c ^ (r & 7)) << 4), b2h(v[0], .5f), b2h(v[1], .5f), b2h(v[2], .5f), b2h(v[3], .5f));
      const float s = ((r & 1) || r == 6) ? 0.f : .5f;
      if (t < 64) sts128(sb + OFF_WD + r * 128 + ((c ^ r) << 4), b2h(u[0], s), b2h(u[1], s), b2h(u[2], s), b2h(u[3], s));
      if (t < 32) sts32(sb + OFF_WX + (t & 3) * 32 + (t >> 2) * 4, b2h(x, 1.f));
      const uint32_t m3 = __reduce_max_sync(~0u, magr(mag2(mag2(mag2(mag2(0, v[0]), v[1]), v[2]), v[3]))), md = __reduce_max_sync(~0u, magr(mag2(mag2(mag2(mag2(0, u[0]), u[1]), u[2]), u[3])));
      if (wbad(m3, 0x4000) || wbad(md, 0x4000) || wbad(__reduce_max_sync(~0u, magr(mag2(0, x))), 0x4700) || magr(mp) >= 0x4200 || magr(mag2(0, ev)) >= 0x4380) sts32(sb + OFF_MISC + 8, 1);
    }
    if (w == 1) {
#pragma unroll 1
      for (int b = HE; b < HW; b++) { mbar_wait(sb + BAR_SRC + max(0, H0 + b) * 8); if (lane == 0) load_h(b); }
    }
    bar_sync(3, 128);
    const uint32_t frag = (w * 16 + (lane & 15)) * 128 + (((lane >> 4) ^ (lane & 7)) << 4);
    uint32_t mq = 0;
#pragma unroll 1
    for (int b = 0; b < 6; b++) {
      float acc[32];
      const uint64_t da = DHI | (((sb + OFF_H) >> 4) + b * 512), db = DHI | ((sb + OFF_W) >> 4);
      const uint32_t v0 = lds16(sb + OFF_POS + b * 512 + w * 128 + lane * 2), v1 = lds16(sb + OFF_POS + 64 + b * 512 + w * 128 + lane * 2);
      mbar_wait(sb + BAR_T + b * 8);
      if (b == 0) STAMP(25);
      if (b == 5) STAMP(26);
      wg_fence();
      ss64<0>(acc, da, db); ss64<1>(acc, da + 2, db + 128); ss64<1>(acc, da + 4, db + 256); ss64<1>(acc, da + 6, db + 384);
      wg_commit();
      if (b == 0) mbar_wait(sb + BAR_AW);
      if (t == 32) { if (HALL) { if (b == 0) for (int k = HW; k < 6; k++) load_h(k); } else if (b + HW < 6) load_h(b + HW); }
      __syncwarp();
      uint32_t ff[6], fg[6];
#pragma unroll
      for (int j = 0; j < 6; j++) { ff[j] = (__byte_perm((j & 1) ? v1 : v0, 0, 0x4140) >> (3 * (j >> 1))) & 0x00070007u; fg[j] = __vsub2(0x00040004u, ff[j]);
        asm volatile("" : "+r"(ff[j]), "+r"(fg[j])); }
      wg_wait0(); fence_regs(acc);
      uint32_t o[16];
#pragma unroll
      for (int j = 0; j < 16; j++) o[j] = pack_f16(.5f * acc[2 * j], .5f * acc[2 * j + 1]);
#pragma unroll
      for (int j = 0; j < 6; j++) {
        const uint32_t m = o[j] & 0x7FFF7FFFu; mq = __vmaxu2(mq, m);
        o[j] = (__viaddmax_s16x2(m, fg[j], 0) & 0xFFF8FFF8u) | ff[j] | (o[j] & 0x80008000u); }
      if (b == 4) mbar_wait(sb + BAR_AX);
      const uint32_t qs = sb + OFF_SA + b * 8192;
#pragma unroll
      for (int j = 0; j < 4; j++) stsm4((qs + frag) ^ (j << 5), o[4 * j], o[4 * j + 1], o[4 * j + 2], o[4 * j + 3]);
      proxy_fence();
      __syncwarp();
      if (lane == 0 && b * 64 + w * 16 < nloc) tma_store(tmb + TM_Q, 0, node0 + b * 64 + w * 16, qs + w * 2048);
    }
    if (lane == 0) bulk_commit();
    { const uint32_t m = __reduce_max_sync(~0u, magr(mq)); if (lane == 0) sts32(sb + OFF_MISC + 16 + w * 4, m); }
    asm volatile("setmaxnreg.dec.sync.aligned.u32 32;");
    bulk_wait();
    bar_sync(3, 128);
    if (w == 0) {
      STAMP(18);
      uint32_t mv[4]; lds128(mv, sb + OFF_MISC + 16);
      const uint32_t mx = max(max(mv[0], mv[1]), max(mv[2], mv[3]));
      mbar_arrive(sb + BAR_QR, lane == 0);
      STAMP(19);
      if (lane == 0) {
        if (nloc > 0 && (mx >= 0x7BF0 || mx < 0x1400)) asm volatile("st.relaxed.gpu.global.u32 [%0+4], %1;" :: "l"(p.sync), "r"(e) : "memory");
        asm volatile("red.release.gpu.global.add.u32 [%0], 1;" :: "l"(p.sync) : "memory");
      }
      __syncwarp();
      uint32_t c, f; int spin = 0;
      do { asm volatile("ld.acquire.gpu.global.v2.u32 {%0, %1}, [%2];" : "=r"(c), "=r"(f) : "l"(p.sync) : "memory"); trap_if(++spin > 4000000); } while (__any_sync(~0u, (int)(c - e * G) < 0));
      if (f == e) sts32(sb + OFF_MISC + 8, 1);
      if (cta == 0 && lane == 0) asm volatile("st.relaxed.gpu.global.u32 [%0+8], %1;" :: "l"(p.sync), "r"(e) : "memory");
      STAMP(20);
      __syncwarp();
      mbar_arrive(sb + BAR_QP, lane == 0);
    }
    if (w == 2) {
      const uint32_t tg = (1 + e % 3) << 30;
      hint_wait(p.sync + 5, e * G);
      if (lane == 0) { mbar_expect(sb + BAR_HB, XPAD);
#pragma unroll 1
        for (int o = 0; o < 4; o++) bulk_load(sb + OFF_XB + o * (G * 64), (const char*)p.xb + (size_t)(cta * 4 + o) * (G * 64), G * 64, sb + BAR_HB); }
      STAMP(21);
      bar_sync(7, 384);
      sts32(sb + OFF_XB + XPAD, tg + p.N + cta);
      const uint32_t nx = __shfl_sync(~0u, lds32(sb + OFF_MISC + 8) ? 0 : lds32(sb + OFF_MISC + 4), 0);
#pragma unroll 1
      for (uint32_t k = 0; k < nx; k += 32) {
        const uint32_t i = min(k + lane, nx - 1), xr = lds32(sb + OFF_EXT + i * 4), row = (xr >> 9) & 255;
        const uint32_t v = ext_get(p.xe + (cta * G + row) * 32 + ((xr >> 17) & 31), e), x = lds32(sb + OFF_CNT + (xr & 511) * 4) + (xr >> 22) * 16;
        sts32(sb + OFF_XB + XPAD + 4 + i * 4, v); sts16(sb + OFF_TS + x, XPAD + 4 + i * 4);
        sts32(sb + OFF_TE + x * 2, mad16(v, 0x2000u, ealo - (tg >> 11) + row * p.EPC * 32));
      }
      __syncwarp();
      mbar_arrive(sb + BAR_HB, lane == 0);
    }
    if (w == 1) {
      if (PFW) mbar_wait(sb + PFW);
      __nanosleep(PF0NS);
#pragma unroll 1
      for (int i = PFE; i < PFN; i++) { if (lane == 0) prefetch_e(i); __nanosleep(PFNS); }
    }
    bar_sync(4, NTHR);
    if (t == 0) { mbar_expect(sb + BAR_U, 16384); tma_load(sb + OFF_W, tmb + TM_WH, 0, sb + BAR_U); tma_load(sb + OFF_W + 8192, tmb + TM_WH, 64, sb + BAR_U); }
    mbar_wait(sb + BAR_U);
    uint32_t mh = 0;
#pragma unroll 1
    for (int i = t; i < 512; i += 128) { uint32_t v[4]; const uint32_t a = sb + OFF_W + i * 16;
      lds128(v, a); sts128(a, hhalf(v[0]), hhalf(v[1]), hhalf(v[2]), hhalf(v[3]));
      lds128(v, a + 8192); sts128(a + 8192, b2h(v[0], .5f), b2h(v[1], .5f), b2h(v[2], .5f), b2h(v[3], .5f));
      mh = mag2(mag2(mag2(mag2(mh, v[0]), v[1]), v[2]), v[3]); }
    if (wbad(__reduce_max_sync(~0u, magr(mh)), 0x4700)) sts32(sb + OFF_MISC + 12, 1);
    proxy_fence();
    __syncwarp();
    mbar_arrive(sb + BAR_WH, lane == 0);
    if (DEFO) { if (!__shfl_sync(~0u, lds32(sb + OFF_MISC + 8), 0)) {
      mbar_wait(sb + BAR_M);
      __nanosleep(DEFO);
#pragma unroll 1
      for (int i = 0; i < 12; i++) { uint32_t v[4]; const uint32_t n = lds16(sb + OFF_GP + i * 256 + (t >> 3) * 8 + 6);
        lds128(v, sb + OFF_H + n * 128 + (((n ^ t) & 7) << 4));
        if (n < nloc) ((uint4*)p.out)[(size_t)(node0 + n) * 8 + (t & 7)] = make_uint4(v[0], v[1], v[2], v[3]);
        __nanosleep(DEFNS); }
      mbar_wait(sb + BAR_X);
#pragma unroll 1
      for (int i = t; i < 384; i += 128) { uint32_t x, y; lds64(x, y, sb + OFF_GP + i * 8); const uint32_t a = sb + OFF_P2 + (y >> 16) * 6; sts16(a, x); sts16(a + 2, x >> 16); sts16(a + 4, y); }
      bar_sync(3, 128);
#pragma unroll 3
      for (int i = t; i < nloc * 3; i += 128) p.out[(size_t)p.N * 64 + node0 * 3 + i] = lds16(sb + OFF_P2 + i * 2);
      asm volatile("{.reg .pred p, q; setp.ne.u32 p, 0, 0; bar.red.or.pred q, 5, 512, p;}" ::: "memory"); } }
    return;
  }

  if (tid == 320) {
    mbar_init(sb + BAR_W, 1);
    asm volatile("fence.mbarrier_init.release.cluster;" ::: "memory");
    mbar_expect(sb + BAR_W, 2 * 8192 + 2304);
    tma_load(sb + OFF_W, tmb + TM_WE, 64, sb + BAR_W); tma_load(sb + OFF_W + 8192, tmb + TM_WE, 0, sb + BAR_W);
    bulk_load(sb + OFF_WS, p.we + 128 * 64, 2176, sb + BAR_W); bulk_load(sb + OFF_WS + 2176, p.wx, 128, sb + BAR_W);
  }
  if (tid == 288) {
#pragma unroll
    for (int a = BAR_SRC; a < BAR_END; a += 8) if (a != BAR_W) mbar_init(sb + a, a == BAR_WH || a == BAR_PS || a == BAR_EP ? 4 : a == BAR_XA ? 11 : a == BAR_HB ? 2 : a == BAR_M ? 12 : a == BAR_X ? 24 : 1);
    asm volatile("fence.mbarrier_init.release.cluster;" ::: "memory");
    asm volatile("prefetch.tensormap [%0];" :: "l"(tmb + TM_XA)); asm volatile("prefetch.tensormap [%0];" :: "l"(tmb + TM_H));
    asm volatile("prefetch.tensormap [%0];" :: "l"(tmb + TM_XB)); asm volatile("prefetch.tensormap [%0];" :: "l"(tmb + TM_Q));
  }
  {
    if (tid < 144) { const uint32_t z = (tid >> 3) == 16 ? 0x8000u : 0u; sts128(sb + OFF_CNT + tid * 16, z, z, z, z); }
    else if (tid <= 144 + G) sts32(sb + OFF_BC + (tid - 144) * 4, ((tid - 144) & 31) * 4);
    const uint32_t sp = XPAD * 0x10001u, em = first_node(G);
    if (wid < 7) {
#pragma unroll
      for (int i = 0; i < 4; i++) sts128(sb + OFF_TS + tid * 16 + i * 3584, sp, sp, sp, sp);
    }
    static_assert(SCAP * 32 == 4 * 3584, "fill");
#pragma unroll 1
    for (int i = n4 + tid; i < 1536; i += 384) sts128(sb + OFF_DST + i * 16, em, em, em, em);
    if (tid == 321) sts128(sb + OFF_MISC, 0, 0, p.force_slow, 0);
  }
  bar_arrive(6, NTHR);
  bar_sync(0, 384);
  uint32_t ep, tag, eb0, pk[12], r0[12], r1[12], cb;
  uint2 vb[12];
  auto get_tag = [&]() { mbar_wait(sb + BAR_EP); ep = lds32(sb + OFF_MISC + 32); tag = (1 + ep % 3) << 30; eb0 = ealo - (tag >> 11); };
  if (wid == 11) {
    trap_if(sb != (uint32_t)__cvta_generic_to_shared(smraw));
#pragma unroll 1
    for (unsigned long long q = LSEQ; q; q >>= 8) { const int k = (q >> 4) & 7, nb = max(0, min(8192, n4 * 16 - k * 8192));
      if (!(q & 8)) mbar_wait(sb + BAR_DST + ((uint32_t)q & 7) * 8);
      if (lane == 0) {
        if (k >= 3) load_h(k - 3);
        else { mbar_expect(sb + BAR_SRC + k * 8, nb);
          if (nb) bulk_load(sb + OFF_SRCI + k * 8192, (const char*)(p.src + e0) + k * 8192, nb, sb + BAR_SRC + k * 8); } } }
    get_tag();
    mbar_wait(sb + BAR_PS);
    bar_sync(12, 384);
    uint32_t xm = 0;
#pragma unroll
    for (int k = 0; k < 5; k++) xm |= (lds32(sb + OFF_BC + min(lane + 32 * k, G - 1) * 4) >= (65 << 9) && lane + 32 * k < G) << k;
    auto ext_send = [&](int pl) {
      uint32_t x = xm;
      for (uint32_t m; (m = __ballot_sync(~0u, x));) {
        const uint32_t l = __ffs(m) - 1, j = l + 32 * (__ffs(__shfl_sync(~0u, x, l)) - 1);
        if (lane == l) x &= x - 1;
        const uint32_t e = min(lds16(sb + OFF_AX + j * 128 + ((4 * l + 2 * lane) & 126)), 6143u);
        if (pl) st_ext(p.xe + (j * G + cta) * 32 + lane, lds32(sb + OFF_SRCI + e * 4) + tag + (e << 16), ep);
        else { const uint32_t cn = lds32(sb + OFF_BC + j * 4) >> 9, v = cn > 96 ? 1 : lane + 64 < cn ? 512 | (lds32(sb + OFF_DST + e * 4) & 511) : 0;
          asm volatile("red.shared.xor.b32 [%0], %1;" :: "r"(sb + OFF_SA + j * 128 + ((l + lane) & 31) * 4), "r"(((v & 63) << 10) | ((v >> 6) << 26)) : "memory"); }
      }
    };
    if (__any_sync(~0u, xm)) { ext_send(0); proxy_fence(); __syncwarp(); }
    if (lane == 0) { tma_store_ef(tmb + TM_XA, cta * 64, 0, sb + OFF_SA); bulk_commit(); mbar_arrive(sb + BAR_AI); bulk_wait(); hint_signal(p.sync + 4); mbar_arrive(sb + BAR_AW); STAMP(16); }
    __syncwarp();
    bar_sync(13, 384);
    if (!B_HOLD && lane == 0) { tma_store_ef(tmb + TM_XB, cta * 64, 0, sb + OFF_SB); bulk_commit(); }
    __syncwarp();
    ext_send(1);
    mbar_arrive(sb + BAR_AX, lane == 0);
    if (B_HOLD) mbar_wait(sb + (B_HOLD == 1 ? BAR_HA : BAR_XA));
    if (lane == 0) {
      bulk_wait();
#pragma unroll 1
      for (int r = B_HOLD ? 0 : BROWS; r < G; r += BROWS) { tma_store_ef(tmb + TM_XB, cta * 64, r, sb + OFF_SB + r * 256); bulk_commit(); bulk_wait(); }
      hint_signal(p.sync + 5);
#pragma unroll 1
      for (int i = 0; i < PFE; i++) prefetch_e(i);
      STAMP(17);
    }
    __syncwarp();
  } else {
    {
      uint32_t d[4 * NCH], jj[4 * NCH], rr[4 * NCH];
      auto count = [&](int k) {
        mbar_wait(sb + BAR_DST + k * 8);
        lds128(d + 4 * k, sb + OFF_DST + (tid + NWK * k) * 16);
#pragma unroll
        for (int i = 4 * k; i < 4 * k + 4; i++) { jj[i] = d[i] * p.magic; rr[i] = atoms_add(__dp4a(jj[i], 0x04000000u, sb + OFF_BC), 0x202u); }
      };
      auto place = [&](int k) {
#pragma unroll
        for (int i = 4 * k; i < 4 * k + 4; i++) {
          const uint32_t o = __dp4a(jj[i], 0x80000000u, rr[i] & 0x807Eu);
          d[i] = (d[i] & 511) | (tag >> 16);
          asm("{.reg .pred p; setp.ge.u32 p, %1, 0x8000; @p add.u32 %0, %2, %3;}" : "+r"(d[i]) : "r"(o), "r"(tid * 4), "r"(NWK * k * 4 + (i & 3)));
          sts16(sb + OFF_SA + o, d[i]); jj[i] = __viaddmin_u32(o, o, G * 256);
        }
      };
      count(0); STAMP(1); count(1); get_tag(); place(0); count(2); place(1); count(3); place(2);
      if (wid < 4) { count(4); STAMP(15); place(3); place(4); } else place(3);
      proxy_fence();
      bar_arrive(12, 384);
      STAMP(2);
      mbar_wait(sb + BAR_AI);
      mbar_wait(sb + BAR_SRC); mbar_wait(sb + BAR_SRC + 8); mbar_wait(sb + BAR_SRC + 16);
      STAMP(12);
#pragma unroll
      for (int k = 0; k < NCH; k++) lds128(d + 4 * k, sb + OFF_SRCI + (tid + NWK * k) * 16);
      const uint32_t tb = tag + (tid << 18);
#pragma unroll
      for (int i = 0; i < 4 * NCH; i++) if (i < 4 * NCH - 4 || wid < 4) sts32(sb + OFF_SB + jj[i], d[i] + tb + ((NWK * (i >> 2) * 4 + (i & 3)) << 16));
      proxy_fence();
      bar_arrive(13, 384);
      STAMP(3);
    }
    const uint32_t rot = (lane + cta) & 31;
    cb = sb + OFF_CNT - (tag >> 14);
    {
      const uint32_t* xa = (const uint32_t*)(p.xa + (cta * G + wid) * 8) + rot;
      if (wid < 8) { const uint32_t e_ = ealo + epad * 32;
        mbar_wait(sb + BAR_AX);
#pragma unroll
        for (int i = 0; i < 7; i++) sts128(sb + OFF_TE + tid * 16 + i * 4096, e_, e_, e_, e_); }
      static_assert(SCAP * 64 == 7 * 4096, "fill");
      if (wid == 10) { hint_wait(p.sync + 4, ep * G); mbar_arrive(sb + BAR_HA, lane == 0); }
      mbar_wait(sb + BAR_HA);
      STAMP(14);
      const uint32_t tp = tag | (tag >> 16);
      uint32_t st;
#pragma unroll 1
      for (int spin = 0;; spin++) {
        st = 0;
#pragma unroll
        for (int k = 0; k < 12; k++) asm volatile("ld.relaxed.gpu.global.u32 %0, [%1];" : "=r"(pk[k]) : "l"(xa + k * 352) : "memory");
#pragma unroll
        for (int k = 0; k < 12; k++) st |= pk[k] ^ tp;
        st = __reduce_or_sync(~0u, st);
        if (!(st >> 30)) break;
        trap_if(spin > 2000000);
      }
      if (st & 0x3C00FC00u) {
#pragma unroll 1
        for (;;) {
          uint32_t x = 0, row = 0;
#pragma unroll
          for (int k = 0; k < 12; k++) { const uint32_t y = (pk[k] ^ tp) & 0x3C00FC00u; if (!x && y) { x = y; row = wid + 11 * k; pk[k] ^= y; } }
          if (!__any_sync(~0u, x)) break;
          const uint32_t n = ((x >> 10) & 63) | ((x >> 20) & 0x1C0);
          if (x >> 29) {
            const uint32_t r = atoms_add(sb + OFF_CNT + n * 4, 16), idx = atoms_add(sb + OFF_MISC + 4, 1);
            if (idx < 256) sts32(sb + OFF_EXT + idx * 4, n | (row << 9) | (lane << 17) | (min(r >> 4, 255u) << 22));
            else x = 1;
          }
          if (x && !(x >> 29)) sts32(sb + OFF_MISC + 8, 1);
          __syncwarp();
        }
      }
#pragma unroll
      for (int k = 0; k < 12; k++) { r0[k] = mad16(pk[k], 0x0004u, cb); r1[k] = mad16(pk[k], 0x0400u, cb); vb[k].x = atoms_add(r0[k], 16); vb[k].y = atoms_add(r1[k], 16); }
      if (B_HOLD == 2) mbar_arrive(sb + BAR_XA, lane == 0);
    }
    STAMP(4);
    if (wid >= 6) bar_arrive(11, NWK);
    if (wid < 6) {
      uint32_t ca[2], ky[2], dr[2], sq[2], ps[4];
#pragma unroll
      for (int i = 0; i < 2; i++) { ca[i] = sb + OFF_CNT + ((node0 + tid + 192 * i) & 511) * 4; lds64(ps[2 * i], ps[2 * i + 1], sb + OFF_POS + (tid + 192 * i) * 8); ps[2 * i + 1] |= (tid + 192 * i) << 16; }
      bar_sync(11, NWK);
      STAMP(5);
#pragma unroll
      for (int i = 0; i < 2; i++) ky[i] = (lds32(ca[i]) + 16) >> 5;
      if (max(ky[0], ky[1]) > 31) sts32(sb + OFF_MISC + 8, 1);
#pragma unroll
      for (int i = 0; i < 2; i++) { ky[i] = min(ky[i], 31u); dr[i] = atoms_add(sb + OFF_DH + ky[i] * 4, 1); }
      bar_sync(10, 192);
      const uint32_t hv = lds32(sb + OFF_DH + lane * 4);
      uint32_t inc = hv;
#pragma unroll
      for (int o = 1; o < 32; o <<= 1) asm("{.reg .pred p; .reg .b32 y; shfl.sync.down.b32 y|p, %0, %1, 31, -1; @p add.u32 %0, %0, y;}" : "+r"(inc) : "r"(o));
#pragma unroll
      for (int i = 0; i < 2; i++) {
        const uint32_t pos = __shfl_sync(~0u, inc - hv, ky[i]) + dr[i];
        const uint32_t ak = (uint32_t)(QCODE >> ((pos >> 5) * 4)) & 15, l = (pos >> 3) & 3;
        sq[i] = (ak >> 2) * 16 + ((QREV >> (pos >> 5) & 1) ? 3 - l : l) * 4 + (ak & 3);
        dr[i] = pos & 7;
        asm volatile("{.reg .pred p; setp.eq.u32 p, %2, 0; @p st.shared.u8 [%0], %1;}" :: "r"(sb + OFF_LEN + sq[i]), "r"(max(ky[i], 1u)), "r"(dr[i]) : "memory");
        sts64(sb + OFF_GP + sq[i] * 64 + dr[i] * 8, ps[2 * i], ps[2 * i + 1]);
      }
      bar_sync(10, 192);
      const uint32_t ln = lds32(sb + OFF_LEN + min(lane, 11) * 4), tot = __dp4a(ln, 0x01010101u, 0u);
      inc = tot;
#pragma unroll
      for (int o = 1; o < 16; o <<= 1) asm("{.reg .pred p; .reg .b32 y; shfl.sync.up.b32 y|p, %0, %1, 0, -1; @p add.u32 %0, %0, y;}" : "+r"(inc) : "r"(o));
      if (wid == 1) sts32(sb + OFF_CNT + 2048 + lane * 4, 0);
      if (tid < 12) { sts32(sb + OFF_LEN + 64 + tid * 4, inc - tot); if (inc > SCAP) sts32(sb + OFF_MISC + 8, 1); }
#pragma unroll
      for (int i = 0; i < 2; i++) sts32(ca[i], __dp4a(__shfl_sync(~0u, ln, sq[i] >> 2), 0x00010101u >> (24 - 8 * (sq[i] & 3)), __shfl_sync(~0u, inc - tot, sq[i] >> 2)) * 32 + dr[i] * 2);
    }
    bar_arrive(7, 384);
  }
  bar_sync(1, 384);
  STAMP(6);
  if (wid != 11 && !__shfl_sync(~0u, lds32(sb + OFF_MISC + 8), 0)) {
#pragma unroll
    for (int k = 0; k < 12; k++) { r0[k] = lds32(r0[k]); r1[k] = lds32(r1[k]); }
#pragma unroll
    for (int k = 0; k < 12; k++) { r0[k] += vb[k].x; r1[k] += vb[k].y; }
  } else {
#pragma unroll
    for (int k = 0; k < 12; k++) r0[k] = r1[k] = 0x8000;
  }
  auto put_ids = [&]() {
    const uint32_t id = wid * 256 + ((lane + cta) & 31) * 8;
    auto put = [&](uint32_t x, uint32_t v) { asm volatile("{.reg .pred p; setp.lt.u32 p, %0, 0x8000; @p st.shared.u16 [%0+%2], %1;}" :: "r"(x), "h"((uint16_t)v), "n"(sb + OFF_TS) : "memory"); };
#pragma unroll
    for (int k = 0; k < 12; k++) { put(IDL ? pk[k] & 0xFFFF : r0[k], id + k * 2816); put(IDL ? pk[k] >> 16 : r1[k], id + k * 2816 + 4); }
  };
  if (!IDL) put_ids();
  STAMP(7);
  mbar_wait(sb + BAR_QR);
  asm volatile("setmaxnreg.inc.sync.aligned.u32 160;");
  if (IDL) {
#pragma unroll
    for (int k = 0; k < 12; k++) asm volatile("prmt.b32 %0, %1, %2, 0x5410;" : "=r"(pk[k]) : "r"(r0[k]), "r"(r1[k]));
  }
  uint32_t pa[8], sp[8], pq[16]; float chk = 0.f;
  {
    uint32_t hf[32], mp = 0; float a0[32], a1[32];
    const uint32_t an = sb + OFF_GP + wid * 256 + (lane & 15) * 8 + 6, n0 = lds16(an), n1 = lds16(an + 128);
#pragma unroll
    for (int j = 0; j < 8; j++) { const uint32_t nd = j < 4 ? n0 : n1; ldsm4(hf + 4 * j, (sb + OFF_H + nd * 128 + (((nd & 7) << 4) ^ (lane & 16))) ^ ((j & 3) << 5)); }
    const uint64_t db = DHI | ((sb + OFF_W + 8192) >> 4);
    wg_fence();
    rs64b<0>(a0, hf[0], hf[1], hf[2], hf[3], db); rs64b<1>(a0, hf[4], hf[5], hf[6], hf[7], db + 128); rs64b<1>(a0, hf[8], hf[9], hf[10], hf[11], db + 256); rs64b<1>(a0, hf[12], hf[13], hf[14], hf[15], db + 384);
    wg_commit();
    rs64b<0>(a1, hf[16], hf[17], hf[18], hf[19], db); rs64b<1>(a1, hf[20], hf[21], hf[22], hf[23], db + 128); rs64b<1>(a1, hf[24], hf[25], hf[26], hf[27], db + 256); rs64b<1>(a1, hf[28], hf[29], hf[30], hf[31], db + 384);
    wg_commit();
    if (IDL) put_ids();
    asm volatile("wgmma.wait_group.sync.aligned 1;" ::: "memory"); fence_regs(a0);
#pragma unroll
    for (int j = 0; j < 8; j++) { const uint32_t x = pack_f16(.5f * a0[4 * j], .5f * a0[4 * j + 1]), y = pack_f16(.5f * a0[4 * j + 2], .5f * a0[4 * j + 3]); mp = hmag(hmag(mp, x), y);
      asm volatile("movmatrix.sync.aligned.m8n8.trans.b16 %0, %1;" : "=r"(pa[j]) : "r"(x)); asm volatile("movmatrix.sync.aligned.m8n8.trans.b16 %0, %1;" : "=r"(sp[j]) : "r"(y)); }
    wg_wait0(); fence_regs(a1);
    bar_arrive(4, NTHR);
#pragma unroll
    for (int j = 0; j < 16; j++) { pq[j] = pack_f16(.5f * a1[2 * j], .5f * a1[2 * j + 1]); mp = hmag(mp, pq[j]); }
    if (magr(mp) >= 0x7000) chk = __int_as_float(0x7FC00000);
  }
  if (wid == 0) STAMP(23);
  uint32_t bad;
  {
    const uint32_t ring = sb + OFF_RING + wid * STG, p2 = sb + OFF_P2 + wid * 2048;
    uint32_t lens = __shfl_sync(~0u, lds32(sb + OFF_LEN + wid * 4), 0);
    uint32_t rem = __dp4a(lens, 0x20202020u, 0u);
    const uint32_t base = min(lds32(sb + OFF_LEN + 64 + wid * 4), SCAP);
    uint32_t a_s = sb + OFF_TS + base * 32 + (lane >> 3) * 8, a_e = sb + OFF_TE + base * 64 + (lane >> 1) * 4;
    uint32_t k0 = (uint32_t)(uint64_t)p.q + (((lane & 7) ^ ((lane >> 1) & 4)) << 4), k1 = k0 ^ 16, k2 = k0 ^ 32, k3 = k0 ^ 48, ke = ((lane ^ (lane >> 3)) & 1) << 4;
    uint32_t dst0 = ring + (lane >> 3) * 640 + (lane & 7) * 16;
    const uint32_t qhi = (uint32_t)((uint64_t)p.q >> 32), ehi = (uint32_t)((uint64_t)p.ea >> 32);
    uint32_t s0, s1, ev, to = 0, so = 12 * STG;
    auto tl_ = [&]() { lds64(s0, s1, a_s + to); asm volatile("ld.shared.u32 %0, [%1]; add.u32 %1, %1, 64;" : "=&r"(ev), "+r"(a_e) :: "memory"); to += 32; };
#define CPQ(LH, x, k, off) "dp2a." LH ".u32.u32 lo, " x ", 0x80000080, " k "; mov.b64 a, {lo, %7}; @p cp.async.cg.shared.global [%0+" #off "], [a], 16;\n"
#define CPE "or.b32 lo, %10, %11; mov.b64 a, {lo, %12}; @p cp.async.cg.shared.global" ESZ " [%0+512], [a], 16;\n"
#define CPA(BODY) asm volatile("{.reg .b32 lo; .reg .b64 a; .reg .pred p; setp.le.u32 p, %8, %9;\n" BODY "}" \
      :: "r"(dst0 + so), "r"(s0), "r"(s1), "r"(k0), "r"(k1), "r"(k2), "r"(k3), "r"(qhi), "r"(to), "r"(rem), "r"(ev), "r"(ke), "r"(ehi) : "memory")
#define CPQ4 CPQ("lo", "%1", "%3", 0) CPQ("hi", "%1", "%4", 128) CPQ("lo", "%2", "%5", 256) CPQ("hi", "%2", "%6", 384) "cp.async.commit_group;"
    auto issue = [&]() { CPA(CPE CPQ4); so = so == (NST - 1) * 12 * STG ? 0 : so + 12 * STG; };
    const int g = lane >> 2, qd = lane & 3;
    const uint32_t sw = ((lane >> 4) ^ (lane & 7)) << 4, fr = (lane & 15) * 128 + sw;
    uint32_t qa0 = ring + (g & 3) * 640 + qd * 128 + sw, qa1 = qa0 ^ 32, qa2 = qa0 ^ 64, qa3 = qa0 ^ 96;
    uint32_t eadr = ring + 512 + (g & 3) * 640 + qd * 32 + ((((lane >> 4) ^ g) & 1) << 4);
    uint32_t oh0 = g == 2 * qd ? 0x3C00u : g == 2 * qd + 1 ? 0x3C000000u : 0u, oh1 = oh0;
    uint32_t a_g = sb + OFF_GP + wid * 256 + lane * 2;
    uint32_t a_n = sb + OFF_GP + wid * 256 + (lane & 15) * 8 + 6;
    uint32_t a_p = ((lane & 8) ? p2 : sb + OFF_WD) + (lane & 7) * 128 + ((((lane >> 4) ^ lane) & 7) << 4);
    uint32_t a_w = sb + OFF_W3 + fr;
#define OPQ4(A, B, C, D) asm volatile("shfl.sync.bfly.b32 %0, %0, 0, 31, -1; shfl.sync.bfly.b32 %1, %1, 0, 31, -1; shfl.sync.bfly.b32 %2, %2, 0, 31, -1; shfl.sync.bfly.b32 %3, %3, 0, 31, -1;" : "+r"(A), "+r"(B), "+r"(C), "+r"(D))
    asm volatile("shfl.sync.idx.b32 %0, %0, %1, 31, -1;" : "+r"(oh1) : "r"(lane));
    if (OPQ & 1) OPQ4(a_w, oh0, ke, dst0);
    if (OPQ & 2) OPQ4(qa0, qa1, qa2, qa3);
    if (OPQ & 4) OPQ4(k0, k1, k2, k3);
    if (OPQ & 8) OPQ4(a_g, a_n, a_p, eadr);
    uint32_t w3[16], wv[8], bp[16], sum[8], Y[16], M[16], own, ownp, dpk; uint16_t tl[16], th[16];
    float pacc = 0.f;
    const uint32_t n0_ = __shfl_sync(~0u, node0 + lane, 0), nl = __shfl_sync(~0u, nloc + lane, 0);
    const char* outh = (const char*)p.out + (size_t)n0_ * 128;
    auto wload = [&]() {
#pragma unroll
      for (int j = 0; j < 4; j++) ldsm4t(w3 + 4 * j, a_w ^ (j << 5));
      lds128(wv, sb + OFF_WX + (a_g & 6) * 16); lds128(wv + 4, sb + OFF_WX + 16 + (a_g & 6) * 16);
    };
    auto hload = [&](uint32_t (&hf)[16], uint32_t nd) {
      const uint32_t hrow = sb + OFF_H + nd * 128 + (((nd & 7) << 4) ^ ((a_g >> 1) & 16));
#pragma unroll
      for (int j = 0; j < 4; j++) ldsm4(hf + 4 * j, hrow ^ (j << 5));
      return hrow;
    };
    auto bload = [&](uint32_t o) {
#pragma unroll
      for (int j = 0; j < 4; j++) ldsm4t(bp + 4 * j, (a_p ^ (j << 5)) + o);
    };
    { uint32_t wd[8]; const uint32_t a = sb + OFF_WD + (lane & 7) * 128 + ((((lane >> 3) ^ lane) & 7) << 4);
      ldsm4t(wd, a); ldsm4t(wd + 4, a ^ 64);
#pragma unroll
      for (int j = 0; j < 8; j++) { bp[2 * j] = wd[j]; bp[2 * j + 1] = pa[j]; } }
    own = lds16(a_g) * 0x10001u;
    wload();
    if (__shfl_sync(~0u, lds32(sb + OFF_MISC + 8), 0)) rem = 0;
    auto resolve = [&](auto NBK, uint32_t o) {
      constexpr int NB = decltype(NBK)::value;
      uint32_t id[NB], c0[NB], c1[NB]; const uint32_t a = base * 32 + o + lane * 4;
#pragma unroll
      for (int i = 0; i < NB; i++) { id[i] = lds32(sb + OFF_TS + a + i * 128); if (o + lane * 4 + i * 128 >= rem) id[i] = XPAD * 0x10001u; }
      uint32_t st = 0;
#pragma unroll
      for (int i = 0; i < NB; i++) { c0[i] = lds32(sb + OFF_XB + (id[i] & 0xFFFF)); c1[i] = lds32(sb + OFF_XB + (id[i] >> 16)); }
#pragma unroll
      for (int i = 0; i < NB; i++) st |= (c0[i] ^ tag) | (c1[i] ^ tag);
      for (int spin = 0; __any_sync(~0u, st >> 30); spin++) {
        st = 0; trap_if(spin > 2000000);
#pragma unroll
        for (int i = 0; i < NB; i++) {
          asm volatile("{.reg .pred p, q; setp.lt.u32 p, %4, %6; setp.lt.u32 q, %5, %6; @p ld.relaxed.gpu.global.u32 %0, [%2]; @q ld.relaxed.gpu.global.u32 %1, [%3];}"
            : "+r"(c0[i]), "+r"(c1[i]) : "l"((const char*)p.xb + cta * XPAD + (id[i] & 0xFFFF)), "l"((const char*)p.xb + cta * XPAD + (id[i] >> 16)), "r"(id[i] & 0xFFFF), "r"(id[i] >> 16), "n"(XPAD) : "memory");
          st |= (c0[i] ^ tag) | (c1[i] ^ tag); }
      }
#pragma unroll
      for (int i = 0; i < NB; i++) { const uint32_t j0 = (id[i] >> 8) & 255, j1 = id[i] >> 24;
        if (ABL & 2) { c0[i] &= 0xFFFF0FFFu; c1[i] &= 0xFFFF0FFFu; }
        asm volatile("{.reg .pred p, q, r; setp.lt.u32 p, %5, %9; setp.lt.u32 q, %6, %9; setp.lt.u32 r, %7, %8;\n"
          "@p st.shared.u32 [%0], %2; @q st.shared.u32 [%0+4], %3; @r st.shared.u32 [%1], %4;}"
          :: "r"(sb + OFF_TE + 2 * a + i * 256), "r"(sb + OFF_TS + a + i * 128), "r"(mad16(c0[i], 0x2000u, eb0 + ((ABL & 1) ? j0 & 7 : j0) * p.EPC * 32)), "r"(mad16(c1[i], 0x2000u, eb0 + ((ABL & 1) ? j1 & 7 : j1) * p.EPC * 32)),
             "r"(__byte_perm(c0[i], c1[i], 0x5410)), "r"(j0), "r"(j1), "r"(o + lane * 4 + i * 128), "r"(rem), "n"(G) : "memory"); }
    };
    bar_sync(2, 384);
    if (wid == 0) STAMP(27);
    mbar_wait(sb + BAR_HB);
    if (wid == 0) STAMP(22);
#pragma unroll 1
    for (uint32_t o = 0, go = 0; go < 32 * NST; o += 128 * RNB) {
      if (o < rem) { resolve(IC<RNB>(), o);
        asm volatile("{.reg .pred p; mbarrier.test_wait.parity.shared::cta.b64 p, [%1], 0; vote.sync.all.pred p, p, -1; selp.u32 %0, %2, 0, p;}" : "=r"(go) : "r"(sb + BAR_QP), "n"(32 * NEARLY) : "memory"); }
      else { bar_sync(8, 384); mbar_wait(sb + BAR_QP); go = 32 * NST; if (wid == 0) STAMP(24); }
      __syncwarp();
#pragma unroll 1
      while (to < go) { tl_(); issue(); if (to == 32) STAMP(13); }
    }
    bad = __shfl_sync(~0u, lds32(sb + OFF_MISC + 8), 0);
   if (!bad) {
#pragma unroll
    for (int j = 0; j < 4; j++) stsm4((p2 + fr) ^ (j << 5), pq[4 * j], pq[4 * j + 1], pq[4 * j + 2], pq[4 * j + 3]);
    auto body = [&](auto MODE) {
      constexpr int mode = decltype(MODE)::value;
      uint32_t T[16], ef[4], q0, q1, x0, x1, x2; float e0_, e1_, cs[4];
      auto mu = [&](int j) {
#pragma unroll
        for (int i = 2 * j; i < 2 * j + 2; i++) asm volatile("{.reg .b16 l, h; mov.b32 {l, h}, %2; tanh.approx.f16 %0, l; tanh.approx.f16 %1, h;}" : "=h"(tl[i]), "=h"(th[i]) : "r"(Y[i])); };
      auto fi = [&](int j) {
#pragma unroll
        for (int i = 2 * j; i < 2 * j + 2; i++) asm volatile("{.reg .b32 t; mov.b32 t, {%2, %3}; fma.rn.f16x2 %0, %1, t, %1;}" : "=r"(M[i]) : "r"(Y[i]), "h"(tl[i]), "h"(th[i])); };
      auto ad = [&](int j) { asm volatile("add.rn.f16x2 %0, %0, %1; add.rn.f16x2 %0, %0, %2;" : "+r"(sum[j]) : "r"(M[2 * j]), "r"(M[2 * j + 1])); };
      auto he = [&](int j) { asm volatile("mma.sync.aligned.m16n8k16.row.col.f16.f16.f16.f16 {%0,%1}, {%2,%3,%4,%5}, {%6,%7}, {%0,%1};" : "+r"(T[2 * j]), "+r"(T[2 * j + 1]) : "r"(ef[0]), "r"(ef[1]), "r"(ef[2]), "r"(ef[3]), "r"(w3[2 * j]), "r"(w3[2 * j + 1])); };
      auto hs = [&](int j) { asm volatile("mma.sync.aligned.m16n8k16.row.col.f16.f16.f16.f16 {%0,%1}, {%2,%3,%4,%5}, {%6,%7}, {%8,%9};" : "=r"(Y[2 * j]), "=r"(Y[2 * j + 1]) : "r"(q0), "r"(q1), "r"(oh0), "r"(oh1), "r"(bp[2 * j]), "r"(bp[2 * j + 1]), "r"(T[2 * j]), "r"(T[2 * j + 1])); };
      auto hc = [&](int j) {
        if (j) asm volatile("mma.sync.aligned.m16n8k16.row.col.f32.f16.f16.f32 {%0,%1,%2,%3}, {%4,%5,%6,%7}, {%8,%9}, {%0,%1,%2,%3};" : "+f"(cs[0]), "+f"(cs[1]), "+f"(cs[2]), "+f"(cs[3]) : "r"(M[4 * j]), "r"(M[4 * j + 1]), "r"(M[4 * j + 2]), "r"(M[4 * j + 3]), "r"(wv[2 * j]), "r"(wv[2 * j + 1]));
        else asm volatile("mma.sync.aligned.m16n8k16.row.col.f32.f16.f16.f32 {%0,%1,%2,%3}, {%4,%5,%6,%7}, {%8,%9}, {%10,%10,%10,%10};" : "=f"(cs[0]), "=f"(cs[1]), "=f"(cs[2]), "=f"(cs[3]) : "r"(M[0]), "r"(M[1]), "r"(M[2]), "r"(M[3]), "r"(wv[0]), "r"(wv[1]), "f"(0.f)); };
      auto cv = [&](int i) { asm volatile("{.reg .b32 a, b; shl.b32 a, %0, 16; and.b32 b, %0, 0xFFFF0000; cvt.rn.f16x2.f32 %0, b, a;}" : "+r"(ef[i])); };
      auto un = [&]() { asm volatile("shl.b32 %0, %2, 16; and.b32 %1, %2, 0xFFFF0000;" : "=&f"(e0_), "=&f"(e1_) : "r"(dpk)); };
      auto ex0 = [&]() { asm volatile("prmt.b32 %0, %3, %4, 0x6420; prmt.b32 %1, %5, %6, 0x6420; prmt.b32 %2, %7, %8, 0x6420;" : "=&r"(x0), "=&r"(x1), "=&r"(x2) : "r"(T[0]), "r"(T[1]), "r"(T[2]), "r"(T[3]), "r"(T[4]), "r"(T[5])); };
      auto ex1 = [&]() { asm volatile("{.reg .b32 a, b; shl.b32 a, %2, 3; shl.b32 b, %3, 6; lop3.b32 a, %1, a, 0x38383838, 0xD8; lop3.b32 a, a, b, 0xC0C0C0C0, 0xD8; sub.rn.bf16x2 %0, %4, a;}" : "=r"(dpk) : "r"(x0), "r"(x1), "r"(x2), "r"(own)); };
      auto ex2 = [&]() { asm volatile("{.reg .b32 a, b, d, u; .reg .b16 l, h; shl.b32 a, %2, 16; and.b32 b, %2, 0xFFFF0000; cvt.rn.f16x2.f32 d, b, a; mul.rn.f16x2 %0, d, d; mov.b32 {l, h}, d; mov.b32 u, {h, h}; mul.rn.f16x2 %1, u, u;}" : "=&r"(q0), "=&r"(q1) : "r"(dpk)); };
      auto pf = [&]() { asm volatile("fma.rn.f32 %0, %1, %2, %0; fma.rn.f32 %0, %3, %4, %0;" : "+f"(pacc) : "f"(cs[0]), "f"(e0_), "f"(cs[2]), "f"(e1_)); };
#define FX(k) if (FM >> k & 1) asm volatile("pmevent 1;" ::: "memory")
      if (mode == 2) {
        hc(0); mu(3); fi(2); un(); ad(0); ad(1); mu(4); fi(3); hc(1); mu(5); fi(4); ad(2); mu(6); fi(5); ad(3); hc(2); mu(7); fi(6); fi(7); ad(4); ad(5); hc(3); ad(6); ad(7); pf();
        return;
      }
      asm volatile("cp.async.wait_group %0;" :: "n"(NST - 1) : "memory");
      __syncwarp();
      if (mode == 1) STAMP(8);
      ldsm4(ef, eadr + so); ldsm4(T, qa0 + so); ldsm4(T + 4, qa1 + so); ldsm4(T + 8, qa2 + so); ldsm4(T + 12, qa3 + so);
      tl_();
      if (mode == 1) {
        issue();
        cv(0); cv(1); cv(2); cv(3); ex0(); ex1(); ex2();
#pragma unroll
        for (int j = 0; j < 8; j++) { he(j); hs(j); }
        mu(0); mu(1); fi(0); mu(2); fi(1);
        return;
      }
      hc(0); mu(3); fi(2); un(); ad(0); ad(1);
      FX(0);
      mu(4); fi(3); cv(0); cv(1); cv(2); cv(3); ex0(); ex1();
      FX(1);
      he(0); he(1); hc(1); mu(5); fi(4); ex2(); ad(2);
      FX(2);
      hs(0); he(2); mu(6); fi(5); issue(); ad(3);
      FX(3);
      hs(1); he(3); hc(2); mu(7); fi(6);
      FX(4);
      hs(2); hs(3); he(4); he(5); mu(0); fi(7); ad(4); ad(5);
      FX(5);
      hc(3); hs(4); he(6); he(7); mu(1); fi(0); ad(6);
      FX(6);
      hs(5); hs(6); hs(7); mu(2); fi(1); ad(7); pf();
      FX(7);
    };
#pragma unroll
    for (int j = 0; j < 8; j++) sum[j] = 0;
    body(IC<1>());
    int cnt = (lens & 255) - 1;
#pragma unroll 1
    for (int t = 0; t < 8; t++) {
#pragma unroll 1
      for (; cnt > 0; cnt--) { body(IC<0>());
      }
      if (!(t & 1)) {
        ownp = own;
        if (t < 6) {
          a_g += 64; own = lds16(a_g) * 0x10001u;
          if (t == 0) {
#pragma unroll
            for (int j = 0; j < 8; j++) bp[2 * j + 1] = sp[j];
          } else bload((a_g & 16) ? (t & 4) * 256 : 0);
          lens >>= 8; cnt = 1;
          continue;
        }
        body(IC<2>()); t++; a_g += 64;
        STAMP(9);
      }
      cnt = (lens & 255) - 1;
      asm volatile("{.reg .pred p; setp.ne.u32 p, %2, 6; @p st.shared.u16 [%0+-64], %1;}" :: "r"(a_g), "h"((uint16_t)pack_bf16(bf_hi(ownp) + pacc, 0.f)), "r"(a_g & 6) : "memory");
      chk = fmaf(pacc, 0.f, chk); pacc = 0.f;
      if (t & 2) {
        uint32_t hf[16]; float acc[32];
        const uint32_t nd = lds16(a_n);
        const uint32_t hrow = hload(hf, nd);
        a_n += 128;
        __syncwarp();
        mbar_arrive(sb + BAR_X, (a_g & 62) == 0);
        const uint64_t b1 = DHI | ((sb + OFF_W) >> 4), b2_ = b1 + 512;
        mbar_wait(sb + BAR_WH);
        wg_fence();
        rs64h<0>(acc, sp[0], sum[0], sp[1], sum[1], b2_); rs64h<1>(acc, sp[2], sum[2], sp[3], sum[3], b2_ + 128); rs64h<1>(acc, sp[4], sum[4], sp[5], sum[5], b2_ + 256); rs64h<1>(acc, sp[6], sum[6], sp[7], sum[7], b2_ + 384);
        rs64b<1>(acc, hf[0], hf[1], hf[2], hf[3], b1); rs64b<1>(acc, hf[4], hf[5], hf[6], hf[7], b1 + 128); rs64b<1>(acc, hf[8], hf[9], hf[10], hf[11], b1 + 256); rs64b<1>(acc, hf[12], hf[13], hf[14], hf[15], b1 + 384);
        wg_commit();
        uint32_t nr[4];
#pragma unroll
        for (int j = 0; j < 4; j++) nr[j] = __shfl_sync(~0u, nd, 4 * j + ((a_g >> 4) & 3)) * 128 + ((a_g << 3) & 0x70);
        wg_wait0(); fence_regs(acc);
        if (t == 7) STAMP(10);
        chk = fmaf(acc[0], 0.f, fmaf(acc[2], 0.f, chk));
        auto fin = [&](uint32_t x, float y0, float y1) { return u2(__hadd2(b2(x), b2(pack_bf16(silu_h(y0), silu_h(y1))))); };
#pragma unroll
        for (int j = 0; j < 4; j++) stsm4(hrow ^ (j << 5), fin(hf[4 * j], acc[8 * j], acc[8 * j + 1]), fin(hf[4 * j + 1], acc[8 * j + 2], acc[8 * j + 3]), fin(hf[4 * j + 2], acc[8 * j + 4], acc[8 * j + 5]), fin(hf[4 * j + 3], acc[8 * j + 6], acc[8 * j + 7]));
        __syncwarp();
        if (DEFO && t == 3) mbar_arrive(sb + BAR_M, (a_g & 62) == 0);
        else {
          uint32_t v[16];
#pragma unroll
          for (int j = 0; j < 4; j++) lds128(v + 4 * j, sb + OFF_H + (nr[j] ^ ((nr[j] >> 3) & 0x70)));
#pragma unroll
          for (int j = 0; j < 4; j++) asm volatile("{.reg .pred p; setp.lt.u32 p, %5, %6; @p st.global" OCS ".v4.b32 [%0], {%1,%2,%3,%4};}" :: "l"(outh + nr[j]), "r"(v[4 * j]), "r"(v[4 * j + 1]), "r"(v[4 * j + 2]), "r"(v[4 * j + 3]), "r"(nr[j]), "r"(nl * 128) : "memory");
          if (DEFO) break;
        }
        wload();
      }
#pragma unroll
      for (int j = 0; j < 8; j++) { sp[j] = sum[j]; asm volatile("mov.b32 %0, 0;" : "=r"(sum[j])); }
    }
    asm volatile("{.reg .pred p, q; setp.neu.f32 p, %1, 0f00000000; setp.ne.or.u32 p, %2, 0, p; bar.red.or.pred q, 5, %3, p; selp.u32 %0, 1, 0, q;}" : "=r"(bad) : "f"(chk), "r"(lds32(sb + OFF_MISC + 12)), "n"(DEFO ? 512 : 384) : "memory");
    STAMP(11);
   } else { asm volatile("cp.async.wait_all;" ::: "memory"); bar_sync(5, 384); }
  }
  if (bad) slow_path(p, wid, lane, node0, nloc);
}

}

typedef CUresult (*EncodeFn)(CUtensorMap*, CUtensorMapDataType, cuuint32_t, void*, const cuuint64_t*, const cuuint64_t*, const cuuint32_t*, const cuuint32_t*,
                             CUtensorMapInterleave, CUtensorMapSwizzle, CUtensorMapL2promotion, CUtensorMapFloatOOBfill);

extern "C" void kernel_launch(void* const* d_in, const int* in_sizes, int n_in, void* d_out, int out_size) {
  Params p; Maps maps;
  p.h = (const uint4*)d_in[0]; p.pos = (const uint16_t*)d_in[1]; p.ea = (const uint4*)d_in[2];
  p.src = (const int*)d_in[3]; p.dst = (const int*)d_in[4];
  p.we = (const uint16_t*)d_in[5]; p.wx = (const uint16_t*)d_in[6]; p.wh = (const uint16_t*)d_in[7];
  p.out = (uint16_t*)d_out;
  p.N = in_sizes[0] / 64; p.E = in_sizes[3];
  p.EPC = ((p.E + G * 4 - 1) / (G * 4)) * 4;
  p.magic = (uint32_t)(((uint64_t)G << 24) / (uint64_t)p.N);
  p.inv = (1ull << 56) / p.magic;
  const uint64_t ea0 = (uint64_t)d_in[2], ea1 = ea0 + (uint64_t)p.E * 32 - 1;
  p.force_slow = ((ea0 >> 32) != (ea1 >> 32)) || (ea0 & 31) || (p.E & 3);
  void* qp = nullptr;
  cudaGetSymbolAddress(&qp, g_q);
  p.q = (char*)qp;
  if (((uint64_t)p.q >> 32) != (((uint64_t)p.q + QBYTES) >> 32)) p.q += QBYTES;
  cudaGetSymbolAddress((void**)&p.sync, g_sync); cudaGetSymbolAddress((void**)&p.xe, g_xe);
  cudaGetSymbolAddress((void**)&p.xa, g_xa); cudaGetSymbolAddress((void**)&p.xb, g_xb);
  void* fn = nullptr; cudaDriverEntryPointQueryResult qr;
  cudaGetDriverEntryPoint("cuTensorMapEncodeTiled", &fn, cudaEnableDefault, &qr);
  auto mk = [&](CUtensorMap* tm, void* base, int rows, int box = 64) {
    const cuuint64_t dim[2] = {64, (cuuint64_t)rows}, str[1] = {128}; const cuuint32_t bx[2] = {64, (cuuint32_t)box}, es[2] = {1, 1};
    ((EncodeFn)fn)(tm, CU_TENSOR_MAP_DATA_TYPE_BFLOAT16, 2, base, dim, str, bx, es, CU_TENSOR_MAP_INTERLEAVE_NONE, CU_TENSOR_MAP_SWIZZLE_128B,
                   CU_TENSOR_MAP_L2_PROMOTION_NONE, CU_TENSOR_MAP_FLOAT_OOB_FILL_NONE);
  };
  mk(&maps.m[TM_H / 128], d_in[0], p.N); mk(&maps.m[TM_WE / 128], d_in[5], 145); mk(&maps.m[TM_WH / 128], d_in[7], 128); mk(&maps.m[TM_Q / 128], p.q, p.N, 16);
  for (int k = 0; k < 2; k++) {
    void* xp = (void*)(k ? p.xb : p.xa);
    const cuuint64_t dim[2] = {(cuuint64_t)G * 64, (cuuint64_t)G}, str[1] = {(cuuint64_t)G * (128 << k)}; const cuuint32_t bx[2] = {64, (cuuint32_t)(k ? BROWS : G)}, es[2] = {1, 1};
    ((EncodeFn)fn)(&maps.m[TM_XA / 128 + k], k ? CU_TENSOR_MAP_DATA_TYPE_UINT32 : CU_TENSOR_MAP_DATA_TYPE_UINT16, 2, xp, dim, str, bx, es, CU_TENSOR_MAP_INTERLEAVE_NONE,
                   CU_TENSOR_MAP_SWIZZLE_NONE, CU_TENSOR_MAP_L2_PROMOTION_NONE, CU_TENSOR_MAP_FLOAT_OOB_FILL_NONE);
  }
  cudaFuncSetAttribute(egnn_kernel, cudaFuncAttributeMaxDynamicSharedMemorySize, SMEM);
  egnn_kernel<<<G, NTHR, SMEM>>>(p, maps);
}
```

```cpp
#include <cuda_runtime.h>
#include <cuda_bf16.h>
#include <cuda_fp16.h>
#include <cuda.h>
#include <stdint.h>
#pragma nv_diag_suppress 549

#define PFN 16
#define PFNS 250
#define FM 0
#define OPQ 0
#define H0 0
#define HALL 1
#define PF0NS 0
#define PFW 0
#define QCODE 0x254a109b7863ull
#define QREV 0x605
#define PFS 1
#define ESZ ""
#define XEF 0
#define OCS ""
#define RNB 2
#define NEARLY 2
#define PFE 0
#define DEFO 1
#define DEFNS 400
#define ABL 0
#define IDL 1
#define HW 3
#define BROWS 132
#define B_HOLD 1
#define LSEQ 0x231200ull
#define HE 0
namespace {

constexpr int G = 132;
constexpr int NTHR = 512, NWK = 352, NCH = 5;
constexpr int NST = 3, STG = 2560;
constexpr int SCAP = 448;

constexpr int OFF_H = 0;
constexpr int OFF_W = 49152;
constexpr int OFF_WD = OFF_W + 16384;
constexpr int OFF_W3 = OFF_WD + 1024;
constexpr int OFF_P2 = OFF_W3 + 2048;
constexpr int OFF_RING = OFF_P2 + 24576;
constexpr int OFF_TE = OFF_RING + 12 * NST * STG;
constexpr int OFF_TS = OFF_TE + SCAP * 64;
constexpr int OFF_GP = OFF_TS + SCAP * 32;
constexpr int OFF_WX = OFF_GP + 3072;
constexpr int OFF_LEN = OFF_WX + 128;
constexpr int OFF_MISC = OFF_LEN + 128;
constexpr int OFF_BAR = OFF_MISC + 48;
constexpr int SMEM = OFF_BAR + 256;
static_assert(SMEM <= 232448, "smem");
constexpr uint32_t sb = 1024;
constexpr int OFF_SRCI = OFF_TE;
constexpr int OFF_SB = OFF_RING, OFF_SA = OFF_SB + 34816, OFF_AX = OFF_SA + 32768, OFF_DST = OFF_H + 24576;
constexpr int OFF_WS = OFF_AX + 17408;
constexpr int OFF_BC = OFF_WS + 2304;
constexpr int OFF_CNT = OFF_P2;
constexpr int OFF_DH = OFF_CNT + 2176;
constexpr int OFF_POS = OFF_DH + 128;
constexpr int OFF_EXT = OFF_POS + 3072;
constexpr int OFF_XB = OFF_EXT + 1024, XPAD = G * 256;
static_assert(OFF_XB + XPAD + 1028 <= OFF_RING + 12 * STG && OFF_XB % 128 == 0 && OFF_BC + 544 <= OFF_TE && OFF_P2 % 1024 == 0 && OFF_SA % 1024 == 0 && SCAP * 64 >= 24576, "staging");
constexpr int BAR_DST = OFF_BAR, BAR_SRC = BAR_DST + 40, BAR_T = BAR_SRC + 24, BAR_W = BAR_T + 48, BAR_XA = BAR_W + 8, BAR_PS = BAR_XA + 8, BAR_AW = BAR_PS + 8,
              BAR_QP = BAR_AW + 8, BAR_QR = BAR_QP + 8, BAR_HA = BAR_QR + 8, BAR_EP = BAR_HA + 8, BAR_AX = BAR_EP + 8, BAR_AI = BAR_AX + 8, BAR_HB = BAR_AI + 8, BAR_U = BAR_HB + 8, BAR_WH = BAR_U + 8, BAR_M = BAR_WH + 8, BAR_X = BAR_M + 8, BAR_END = BAR_X + 8;
static_assert(BAR_END <= OFF_BAR + 256, "barriers");
constexpr uint32_t QBYTES = 8u << 20;

__device__ __align__(256) uint4 g_xa[G * G * 8];
__device__ __align__(256) uint4 g_xb[G * G * 16];
__device__ __align__(256) uint2 g_xe[G * G * 32];
__device__ __align__(256) uint4 g_q[2 * QBYTES / 16];
__device__ __align__(256) uint32_t g_sync[8];
#define STAMP(k)

struct Maps { CUtensorMap m[6]; };
constexpr int TM_H = 0, TM_WE = 128, TM_WH = 256, TM_Q = 384, TM_XA = 512, TM_XB = 640;
struct Params {
  const int* dst; uint32_t* sync; int E, EPC, N; uint32_t magic; unsigned long long inv;
  const int* src; const uint16_t* pos; const uint4* ea; const uint16_t* we; const uint16_t* wx; char* q; int force_slow;
  const uint4* xa; const uint4* xb; uint2* xe; uint16_t* out; const uint4* h; const uint16_t* wh;
};
template<int V> struct IC { static constexpr int value = V; };

#define R32(d) "+f"(d[0]),"+f"(d[1]),"+f"(d[2]),"+f"(d[3]),"+f"(d[4]),"+f"(d[5]),"+f"(d[6]),"+f"(d[7]),"+f"(d[8]),"+f"(d[9]),"+f"(d[10]),"+f"(d[11]),"+f"(d[12]),"+f"(d[13]),"+f"(d[14]),"+f"(d[15]),"+f"(d[16]),"+f"(d[17]),"+f"(d[18]),"+f"(d[19]),"+f"(d[20]),"+f"(d[21]),"+f"(d[22]),"+f"(d[23]),"+f"(d[24]),"+f"(d[25]),"+f"(d[26]),"+f"(d[27]),"+f"(d[28]),"+f"(d[29]),"+f"(d[30]),"+f"(d[31])
#define S32 "{%0,%1,%2,%3,%4,%5,%6,%7,%8,%9,%10,%11,%12,%13,%14,%15,%16,%17,%18,%19,%20,%21,%22,%23,%24,%25,%26,%27,%28,%29,%30,%31}"
#define DI __device__ __forceinline__

constexpr uint64_t DHI = ((uint64_t)(1024 >> 4) << 32) | (1ull << 62);
template<int SD> DI void rs64b(float (&d)[32], uint32_t a0, uint32_t a1, uint32_t a2, uint32_t a3, uint64_t db) {
  asm volatile("wgmma.mma_async.sync.aligned.m64n64k16.f32.bf16.bf16 " S32 ", {%32,%33,%34,%35}, %36, %37, 1, 1, 1;" : R32(d) : "r"(a0), "r"(a1), "r"(a2), "r"(a3), "l"(db), "n"(SD)); }
template<int SD> DI void rs64h(float (&d)[32], uint32_t a0, uint32_t a1, uint32_t a2, uint32_t a3, uint64_t db) {
  asm volatile("wgmma.mma_async.sync.aligned.m64n64k16.f32.f16.f16 " S32 ", {%32,%33,%34,%35}, %36, %37, 1, 1, 1;" : R32(d) : "r"(a0), "r"(a1), "r"(a2), "r"(a3), "l"(db), "n"(SD)); }
template<int SD> DI void ss64(float (&d)[32], uint64_t da, uint64_t db) {
  asm volatile("wgmma.mma_async.sync.aligned.m64n64k16.f32.bf16.bf16 " S32 ", %32, %33, %34, 1, 1, 0, 1;" : R32(d) : "l"(da), "l"(db), "n"(SD)); }
DI void trap_if(bool c) { asm volatile("{.reg .pred p; setp.eq.u32 p, %0, 0; @p bra.uni LT_%=; trap; LT_%=:}" :: "r"((uint32_t)c)); }
DI void wg_fence() { asm volatile("wgmma.fence.sync.aligned;" ::: "memory"); }
DI void wg_commit() { asm volatile("wgmma.commit_group.sync.aligned;" ::: "memory"); }
DI void wg_wait0() { asm volatile("wgmma.wait_group.sync.aligned 0;" ::: "memory"); }
DI void fence_regs(float (&d)[32]) { asm volatile("" : R32(d) :: "memory"); }
DI void proxy_fence() { asm volatile("fence.proxy.async.shared::cta;" ::: "memory"); }
DI uint64_t pol_first() { uint64_t r; asm("createpolicy.fractional.L2::evict_first.b64 %0, 1.0;" : "=l"(r)); return r; }
DI float tanh_ap(float x) { float y; asm("tanh.approx.f32 %0, %1;" : "=f"(y) : "f"(x)); return y; }
DI float silu_h(float y) { return fmaf(y, tanh_ap(y), y); }
DI uint32_t pack_bf16(float lo, float hi) { uint32_t r; asm("cvt.rn.bf16x2.f32 %0, %1, %2;" : "=r"(r) : "f"(hi), "f"(lo)); return r; }
DI uint32_t pack_f16(float lo, float hi) { uint32_t r; asm("cvt.rn.f16x2.f32 %0, %1, %2;" : "=r"(r) : "f"(hi), "f"(lo)); return r; }
DI float bf_lo(uint32_t v) { return __uint_as_float(v << 16); }
DI float bf_hi(uint32_t v) { return __uint_as_float(v & 0xFFFF0000u); }
DI uint32_t b2h(uint32_t v, float s) { return pack_f16(s * bf_lo(v), s * bf_hi(v)); }
DI void mbar_wait(uint32_t bar, uint32_t parity = 0) {
  asm volatile("{.reg .pred p; .reg .u32 t0, t1;\n"
    "mbarrier.try_wait.parity.shared::cta.b64 p, [%0], %1;\n @p bra.uni LD_%=;\n mov.u32 t0, %%clock;\n"
    "LW_%=: mbarrier.try_wait.parity.shared::cta.b64 p, [%0], %1;\n"
    "@p bra.uni LD_%=;\n mov.u32 t1, %%clock; sub.u32 t1, t1, t0; setp.lt.u32 p, t1, 0x80000000;\n @p bra.uni LW_%=;\n trap;\n LD_%=:}" :: "r"(bar), "r"(parity) : "memory");
}
DI void mbar_arrive(uint32_t bar, int p = 1) { asm volatile("{.reg .pred p; setp.ne.b32 p, %1, 0; @p mbarrier.arrive.shared::cta.b64 _, [%0];}" :: "r"(bar), "r"(p) : "memory"); }
DI void bar_sync(int id, int n) { asm volatile("bar.sync %0, %1;" :: "r"(id), "r"(n) : "memory"); }
DI void bar_arrive(int id, int n) { asm volatile("bar.arrive %0, %1;" :: "r"(id), "r"(n) : "memory"); }
DI __nv_bfloat162 b2(uint32_t v) { return *(__nv_bfloat162*)&v; }
DI uint32_t u2(__nv_bfloat162 v) { return *(uint32_t*)&v; }
DI uint32_t hsq(uint32_t v) { return u2(__hmul2(b2(v), b2(v))); }
DI uint32_t hsub(uint32_t a, uint32_t b) { return u2(__hsub2(b2(a), b2(b))); }
DI uint32_t hhalf(uint32_t v) { return u2(__hmul2(b2(v), __floats2bfloat162_rn(0.5f, 0.5f))); }
DI uint32_t mag2(uint32_t m, uint32_t v) { return __vmaxu2(m, v & 0x7FFF7FFFu); }
DI uint32_t hmag(uint32_t m, uint32_t v) { const __half2 r = __hmax2(*(const __half2*)&m, __habs2(*(const __half2*)&v)); return *(const uint32_t*)&r; }
DI uint32_t magr(uint32_t m) { return max(m & 0xFFFF, m >> 16); }
DI void sts128(uint32_t a, uint32_t x, uint32_t y, uint32_t z, uint32_t w) { asm volatile("st.shared.v4.u32 [%0], {%1,%2,%3,%4};" :: "r"(a), "r"(x), "r"(y), "r"(z), "r"(w) : "memory"); }
DI void sts64(uint32_t a, uint32_t x, uint32_t y) { asm volatile("st.shared.v2.u32 [%0], {%1,%2};" :: "r"(a), "r"(x), "r"(y) : "memory"); }
DI void sts32(uint32_t a, uint32_t x) { asm volatile("st.shared.u32 [%0], %1;" :: "r"(a), "r"(x) : "memory"); }
DI void sts16(uint32_t a, uint32_t x) { asm volatile("st.shared.u16 [%0], %1;" :: "r"(a), "h"((uint16_t)x) : "memory"); }
DI void lds128(uint32_t* v, uint32_t a) { asm volatile("ld.shared.v4.u32 {%0, %1, %2, %3}, [%4];" : "=r"(v[0]), "=r"(v[1]), "=r"(v[2]), "=r"(v[3]) : "r"(a) : "memory"); }
DI void lds64(uint32_t& x, uint32_t& y, uint32_t a) { asm volatile("ld.shared.v2.u32 {%0, %1}, [%2];" : "=r"(x), "=r"(y) : "r"(a) : "memory"); }
DI uint32_t lds32(uint32_t a) { uint32_t x; asm volatile("ld.shared.u32 %0, [%1];" : "=r"(x) : "r"(a) : "memory"); return x; }
DI uint32_t lds16(uint32_t a) { uint32_t x; asm volatile("ld.shared.u16 %0, [%1];" : "=r"(x) : "r"(a) : "memory"); return x; }
DI uint32_t atoms_add(uint32_t a, uint32_t v) { uint32_t r; asm volatile("atom.shared.add.u32 %0, [%1], %2;" : "=r"(r) : "r"(a), "r"(v) : "memory"); return r; }
DI void bulk_load(uint32_t dst, const void* src, uint32_t bytes, uint32_t bar) {
  asm volatile("cp.async.bulk.shared::cluster.global.mbarrier::complete_tx::bytes.L2::cache_hint [%0], [%1], %2, [%3], %4;" :: "r"(dst), "l"(src), "r"(bytes), "r"(bar), "l"(pol_first()) : "memory"); }
DI void bulk_store(void* dst, uint32_t src, uint32_t bytes) { asm volatile("cp.async.bulk.global.shared::cta.bulk_group [%0], [%1], %2;" :: "l"(dst), "r"(src), "r"(bytes) : "memory"); }
DI void mbar_expect(uint32_t bar, uint32_t bytes) { asm volatile("mbarrier.arrive.expect_tx.shared::cta.b64 _, [%0], %1;" :: "r"(bar), "r"(bytes) : "memory"); }
DI void mbar_init(uint32_t bar, int n) { asm volatile("mbarrier.init.shared::cta.b64 [%0], %1;" :: "r"(bar), "r"(n) : "memory"); }
DI void tma_load(uint32_t dst, uint64_t tm, int row, uint32_t bar) {
  asm volatile("cp.async.bulk.tensor.2d.shared::cluster.global.mbarrier::complete_tx::bytes.L2::cache_hint [%0], [%1, {%3, %4}], [%2], %5;" :: "r"(dst), "l"(tm), "r"(bar), "r"(0), "r"(row), "l"(pol_first()) : "memory"); }
DI void tma_store(uint64_t tm, int col, int row, uint32_t src) {
  asm volatile("cp.async.bulk.tensor.2d.global.shared::cta.bulk_group [%0, {%2, %3}], [%1];" :: "l"(tm), "r"(src), "r"(col), "r"(row) : "memory"); }
DI void tma_store_ef(uint64_t tm, int col, int row, uint32_t src) {
  if (XEF) asm volatile("cp.async.bulk.tensor.2d.global.shared::cta.bulk_group.L2::cache_hint [%0, {%2, %3}], [%1], %4;" :: "l"(tm), "r"(src), "r"(col), "r"(row), "l"(pol_first()) : "memory");
  else tma_store(tm, col, row, src); }
DI void bulk_commit() { asm volatile("cp.async.bulk.commit_group;" ::: "memory"); }
DI void bulk_wait_read() { asm volatile("cp.async.bulk.wait_group.read 0;" ::: "memory"); }
DI uint2 ld_poll2(const void* a) { uint2 v; asm volatile("ld.relaxed.gpu.global.v2.u32 {%0, %1}, [%2];" : "=r"(v.x), "=r"(v.y) : "l"(a) : "memory"); return v; }
DI void st_ext(uint2* a, uint32_t v, uint32_t ep) { asm volatile("st.relaxed.gpu.global.v2.u32 [%0], {%1, %2};" :: "l"(a), "r"(v), "r"(ep) : "memory"); }
DI uint32_t ext_get(const uint2* a, uint32_t ep) { uint2 v; int spin = 0; do { v = ld_poll2(a); trap_if(++spin > 4000000); } while (__any_sync(~0u, v.y != ep)); return v.x; }
DI void bulk_wait() { asm volatile("cp.async.bulk.wait_group 0;" ::: "memory"); }
DI void hint_signal(uint32_t* c) { asm volatile("red.relaxed.gpu.global.add.u32 [%0], 1;" :: "l"(c) : "memory"); }
DI void hint_wait(const uint32_t* c, uint32_t target) { uint32_t v; int spin = 0;
  do { asm volatile("ld.relaxed.gpu.global.u32 %0, [%1];" : "=r"(v) : "l"(c) : "memory"); trap_if(++spin > 4000000); } while (__any_sync(~0u, (int)(v - target) < 0)); }
DI void stsm4(uint32_t a, uint32_t x, uint32_t y, uint32_t z, uint32_t w) { asm volatile("stmatrix.sync.aligned.m8n8.x4.shared.b16 [%0], {%1,%2,%3,%4};" :: "r"(a), "r"(x), "r"(y), "r"(z), "r"(w) : "memory"); }
DI void ldsm4(uint32_t* v, uint32_t a) { asm volatile("ldmatrix.sync.aligned.m8n8.x4.shared.b16 {%0,%1,%2,%3}, [%4];" : "=r"(v[0]), "=r"(v[1]), "=r"(v[2]), "=r"(v[3]) : "r"(a) : "memory"); }
DI void ldsm4t(uint32_t* v, uint32_t a) { asm volatile("ldmatrix.sync.aligned.m8n8.x4.trans.shared.b16 {%0,%1,%2,%3}, [%4];" : "=r"(v[0]), "=r"(v[1]), "=r"(v[2]), "=r"(v[3]) : "r"(a) : "memory"); }
DI uint32_t mad16(uint32_t x, uint32_t m, uint32_t c) { uint32_t r; asm("dp2a.lo.u32.u32 %0, %1, %2, %3;" : "=r"(r) : "r"(x), "r"(m), "r"(c)); return r; }
DI bool wbad(uint32_t m, uint32_t hi) { return m > hi || (m && m < 0x3980); }

__device__ __noinline__ void slow_path(const Params& p, int wid, int lane, int node0, int nloc) {
  const uint32_t ab = sb + OFF_P2 + wid * 8704;
  for (int i = lane; i < 32 * 68; i += 32) sts32(ab + i * 4, 0);
  __syncwarp();
  const uint32_t wdv = __ldg((const uint32_t*)(p.we + 128 * 64) + lane), wxv = __ldg((const uint32_t*)p.wx + lane);
  const int nb0 = node0 + wid * 32, cntn = max(0, min(32, nloc - wid * 32));
  auto dot = [&](uint32_t hv, const uint16_t* w, int K2, float& y0, float& y1) {
#pragma unroll 4
    for (int k = 0; k < K2; k++) {
      const uint32_t hk = __shfl_sync(~0u, hv, k), wa = __ldg((const uint32_t*)(w + 2 * k * 64) + lane), wb = __ldg((const uint32_t*)(w + (2 * k + 1) * 64) + lane);
      y0 = fmaf(bf_lo(hk), bf_lo(wa), fmaf(bf_hi(hk), bf_lo(wb), y0)); y1 = fmaf(bf_lo(hk), bf_hi(wa), fmaf(bf_hi(hk), bf_hi(wb), y1));
    }
  };
  auto silu = [](float x) { return x / (1.f + __expf(-x)); };
#pragma unroll 1
  for (int base = 0; base < p.E; base += 32) {
    const int e = base + lane;
    const uint32_t dl = e < p.E ? (uint32_t)(__ldg(p.dst + e) - nb0) : 0xFFFFFFFFu;
    uint32_t mk = __ballot_sync(~0u, dl < (uint32_t)cntn);
    while (mk) {
      const int l = __ffs(mk) - 1; mk &= mk - 1;
      const int ee = base + l, n = __shfl_sync(~0u, dl, l), s = __ldg(p.src + ee);
      const uint16_t *po = p.pos + (size_t)(nb0 + n) * 3, *pp = p.pos + (size_t)s * 3;
      const uint32_t dxy = hsub(__ldg(po) | (__ldg(po + 1) << 16), __ldg(pp) | (__ldg(pp + 1) << 16)), dz = hsub(__ldg(po + 2), __ldg(pp + 2));
      const uint32_t sq = hsq(dxy); const float d2 = bf_lo(sq) + bf_hi(sq) + bf_lo(hsq(dz));
      float y0 = d2 * bf_lo(wdv), y1 = d2 * bf_hi(wdv);
      dot(__ldg((const uint32_t*)(p.h + (size_t)(nb0 + n) * 8) + lane), p.we, 32, y0, y1);
      dot(__ldg((const uint32_t*)(p.h + (size_t)s * 8) + lane), p.we + 64 * 64, 32, y0, y1);
      dot(__ldg((const uint32_t*)(p.ea + (size_t)ee * 2) + (lane & 7)), p.we + 129 * 64, 8, y0, y1);
      const uint32_t mm = pack_bf16(silu(y0), silu(y1));
      float c = bf_lo(mm) * bf_lo(wxv) + bf_hi(mm) * bf_hi(wxv);
#pragma unroll
      for (int o = 16; o; o >>= 1) c += __shfl_xor_sync(~0u, c, o);
      const uint32_t a = ab + n * 272;
      uint32_t x0, x1; lds64(x0, x1, a + lane * 8);
      sts64(a + lane * 8, __float_as_uint(__uint_as_float(x0) + bf_lo(mm)), __float_as_uint(__uint_as_float(x1) + bf_hi(mm)));
      if (lane < 3) { const float df = lane == 0 ? bf_lo(dxy) : lane == 1 ? bf_hi(dxy) : bf_lo(dz); sts32(a + 256 + lane * 4, __float_as_uint(fmaf(c, df, __uint_as_float(lds32(a + 256 + lane * 4))))); }
    }
  }
  __syncwarp();
#pragma unroll 1
  for (int n = 0; n < cntn; n++) {
    uint32_t x0, x1; lds64(x0, x1, ab + n * 272 + lane * 8);
    const uint32_t hv = __ldg((const uint32_t*)(p.h + (size_t)(nb0 + n) * 8) + lane);
    float y0 = 0.f, y1 = 0.f;
    dot(hv, p.wh, 32, y0, y1); dot(pack_bf16(__uint_as_float(x0), __uint_as_float(x1)), p.wh + 64 * 64, 32, y0, y1);
    ((uint32_t*)p.out)[(size_t)(nb0 + n) * 32 + lane] = u2(__hadd2(b2(hv), b2(pack_bf16(silu(y0), silu(y1)))));
    if (lane < 3) p.out[(size_t)p.N * 64 + (size_t)(nb0 + n) * 3 + lane] = (uint16_t)pack_bf16(bf_lo(__ldg(p.pos + (size_t)(nb0 + n) * 3 + lane)) + __uint_as_float(lds32(ab + n * 272 + 256 + lane * 4)), 0.f);
  }
}

__global__ void __launch_bounds__(NTHR, 1) egnn_kernel(const __grid_constant__ Params p, const __grid_constant__ Maps maps) {
  const uint64_t tmb = (uint64_t)&maps;
  extern __shared__ __align__(1024) unsigned char smraw[];
  const int tid = threadIdx.x, cta = blockIdx.x;
  const int e0 = cta * p.EPC, n4 = max(0, min(p.EPC, p.E - e0)) >> 2;
  STAMP(0);
  if (tid == NWK) {
#pragma unroll 1
    for (int k = 0; k < NCH; k++) { const int nb = max(0, min(NWK, n4 - k * NWK)) * 16;
      mbar_init(sb + BAR_DST + k * 8, 1);
      asm volatile("fence.mbarrier_init.release.cluster;" ::: "memory");
      mbar_expect(sb + BAR_DST + k * 8, nb);
      if (nb) bulk_load(sb + OFF_DST + k * NWK * 16, (const char*)(p.dst + e0) + k * NWK * 16, nb, sb + BAR_DST + k * 8); }
  }
  const int lane = tid & 31, wid = __shfl_sync(~0u, tid >> 5, 0), w = wid & 3;
  asm volatile("{.reg .pred p; setp.eq.u32 p, %2, 384; @p cp.async.cg.shared.global [%0], [%1], 16;}" :: "r"(sb + OFF_LEN - 192 + (tid >> 1)), "l"(p.sync), "r"(tid & 415) : "memory");

  auto first_node = [&](int c) { return (int)((c * p.inv + 0xFFFFFFFFull) >> 32); };
  const int node0 = first_node(cta), nloc = min(first_node(cta + 1), p.N) - node0;
  const uint32_t ealo = (uint32_t)(uint64_t)p.ea;
  const int epad = min(e0, p.E - 1);
  auto load_h = [&](int b) { mbar_expect(sb + BAR_T + b * 8, 8192); tma_load(sb + OFF_H + b * 8192, tmb + TM_H, node0 + b * 64, sb + BAR_T + b * 8); };
  auto prefetch_e = [&](int i) {
    const uint32_t nb = (p.E / G) & ~15u;
    if (nb && i < PFN) asm volatile("cp.async.bulk.prefetch.L2.global [%0], %1;" :: "l"((const char*)p.ea + (size_t)(((i * PFS + i * PFS / 32 * (~PFS & 1)) & 31) * G + cta) * nb), "r"(nb) : "memory");
  };
  if (wid >= 12) {
    const int t = tid - 384;
    uint32_t pv[9], ev = 0;
#pragma unroll
    for (int i = 0; i < 3; i++) { const uint16_t* pp = p.pos + (size_t)(node0 + t + 128 * i) * 3;
      pv[3 * i] = pv[3 * i + 1] = pv[3 * i + 2] = 0;
      asm volatile("{.reg .pred p; setp.lt.s32 p, %4, %5;\n @p ld.global.nc.u16 %0, [%3];\n @p ld.global.nc.u16 %1, [%3+2];\n @p ld.global.nc.u16 %2, [%3+4];}"
        : "+r"(pv[3 * i]), "+r"(pv[3 * i + 1]), "+r"(pv[3 * i + 2]) : "l"(pp), "r"(t + 128 * i), "r"(p.N - node0)); }
    asm volatile("{.reg .pred p; setp.lt.u32 p, %3, 8; @p ld.global.nc.u32 %0, [%1]; @p st.global.v4.u32 [%2], {%4, %4, %4, %4};}"
      : "+r"(ev) : "l"((const uint32_t*)(p.ea + (size_t)epad * 2) + t), "l"(p.q + (size_t)(p.N + cta) * 128 + t * 16), "r"(t), "r"(0xF700F700u) : "memory");
    asm volatile("cp.async.wait_all;" ::: "memory");
    __syncwarp();
    const uint32_t e = lds32(sb + OFF_LEN + 8 + w * 16) + 1;
    {
      const uint32_t tg = (1 + e % 3) << 30, v = ((tg >> 16) + 512 + (lane & 7) * 4) * 0x10001u;
      if (t == 0) sts32(sb + OFF_MISC + 32, e);
#pragma unroll
      for (int i = 0; i < 9; i++) sts128(sb + OFF_SA + t * 16 + i * 2048, v, v + 0x10001u, v + 0x20002u, v + 0x30003u);
      bar_sync(6, NTHR);
      mbar_arrive(sb + BAR_EP, lane == 0);
#pragma unroll
      for (int i = 0; i < 17; i++) sts128(sb + OFF_SB + t * 16 + i * 2048, tg, tg, tg, tg); }
    uint32_t mp = 0;
#pragma unroll
    for (int i = 0; i < 3; i++) { sts64(sb + OFF_POS + (t + 128 * i) * 8, pv[3 * i] | (pv[3 * i + 1] << 16), pv[3 * i + 2]); mp = mag2(mag2(mp, pv[3 * i] | (pv[3 * i + 1] << 16)), pv[3 * i + 2]); }
    proxy_fence();
    __syncwarp();
    mbar_arrive(sb + BAR_PS, lane == 0);
    mbar_wait(sb + BAR_W);
    {
      uint32_t v[4], u[4]; const int r = t >> 3, c = t & 7;
      lds128(v, sb + OFF_WS + 128 + t * 16); lds128(u, sb + OFF_WS + c * 16);
      const uint32_t x = lds32(sb + OFF_WS + 2176 + lane * 4);
      sts128(sb + OFF_W3 + r * 128 + ((c ^ (r & 7)) << 4), b2h(v[0], .5f), b2h(v[1], .5f), b2h(v[2], .5f), b2h(v[3], .5f));
      const float s = ((r & 1) || r == 6) ? 0.f : .5f;
      if (t < 64) sts128(sb + OFF_WD + r * 128 + ((c ^ r) << 4), b2h(u[0], s), b2h(u[1], s), b2h(u[2], s), b2h(u[3], s));
      if (t < 32) sts32(sb + OFF_WX + (t & 3) * 32 + (t >> 2) * 4, b2h(x, 1.f));
      const uint32_t m3 = __reduce_max_sync(~0u, magr(mag2(mag2(mag2(mag2(0, v[0]), v[1]), v[2]), v[3]))), md = __reduce_max_sync(~0u, magr(mag2(mag2(mag2(mag2(0, u[0]), u[1]), u[2]), u[3])));
      if (wbad(m3, 0x4000) || wbad(md, 0x4000) || wbad(__reduce_max_sync(~0u, magr(mag2(0, x))), 0x4700) || magr(mp) >= 0x4200 || magr(mag2(0, ev)) >= 0x4380) sts32(sb + OFF_MISC + 8, 1);
    }
    if (w == 1) {
#pragma unroll 1
      for (int b = HE; b < HW; b++) { mbar_wait(sb + BAR_SRC + max(0, H0 + b) * 8); if (lane == 0) load_h(b); }
    }
    bar_sync(3, 128);
    const uint32_t frag = (w * 16 + (lane & 15)) * 128 + (((lane >> 4) ^ (lane & 7)) << 4);
    uint32_t mq = 0;
#pragma unroll 1
    for (int b = 0; b < 6; b++) {
      float acc[32];
      const uint64_t da = DHI | (((sb + OFF_H) >> 4) + b * 512), db = DHI | ((sb + OFF_W) >> 4);
      const uint32_t v0 = lds16(sb + OFF_POS + b * 512 + w * 128 + lane * 2), v1 = lds16(sb + OFF_POS + 64 + b * 512 + w * 128 + lane * 2);
      mbar_wait(sb + BAR_T + b * 8);
      if (b == 0) STAMP(25);
      if (b == 5) STAMP(26);
      wg_fence();
      ss64<0>(acc, da, db); ss64<1>(acc, da + 2, db + 128); ss64<1>(acc, da + 4, db + 256); ss64<1>(acc, da + 6, db + 384);
      wg_commit();
      if (b == 0) mbar_wait(sb + BAR_AW);
      if (t == 32) { if (HALL) { if (b == 0) for (int k = HW; k < 6; k++) load_h(k); } else if (b + HW < 6) load_h(b + HW); }
      __syncwarp();
      uint32_t ff[6], fg[6];
#pragma unroll
      for (int j = 0; j < 6; j++) { ff[j] = (__byte_perm((j & 1) ? v1 : v0, 0, 0x4140) >> (3 * (j >> 1))) & 0x00070007u; fg[j] = __vsub2(0x00040004u, ff[j]);
        asm volatile("" : "+r"(ff[j]), "+r"(fg[j])); }
      wg_wait0(); fence_regs(acc);
      uint32_t o[16];
#pragma unroll
      for (int j = 0; j < 16; j++) o[j] = pack_f16(.5f * acc[2 * j], .5f * acc[2 * j + 1]);
#pragma unroll
      for (int j = 0; j < 6; j++) {
        const uint32_t m = o[j] & 0x7FFF7FFFu; mq = __vmaxu2(mq, m);
        o[j] = (__viaddmax_s16x2(m, fg[j], 0) & 0xFFF8FFF8u) | ff[j] | (o[j] & 0x80008000u); }
      if (b == 4) mbar_wait(sb + BAR_AX);
      const uint32_t qs = sb + OFF_SA + b * 8192;
#pragma unroll
      for (int j = 0; j < 4; j++) stsm4((qs + frag) ^ (j << 5), o[4 * j], o[4 * j + 1], o[4 * j + 2], o[4 * j + 3]);
      proxy_fence();
      __syncwarp();
      if (lane == 0 && b * 64 + w * 16 < nloc) tma_store(tmb + TM_Q, 0, node0 + b * 64 + w * 16, qs + w * 2048);
    }
    if (lane == 0) bulk_commit();
    { const uint32_t m = __reduce_max_sync(~0u, magr(mq)); if (lane == 0) sts32(sb + OFF_MISC + 16 + w * 4, m); }
    asm volatile("setmaxnreg.dec.sync.aligned.u32 32;");
    bulk_wait();
    bar_sync(3, 128);
    if (w == 0) {
      STAMP(18);
      uint32_t mv[4]; lds128(mv, sb + OFF_MISC + 16);
      const uint32_t mx = max(max(mv[0], mv[1]), max(mv[2], mv[3]));
      mbar_arrive(sb + BAR_QR, lane == 0);
      STAMP(19);
      if (lane == 0) {
        if (nloc > 0 && (mx >= 0x7BF0 || mx < 0x1400)) asm volatile("st.relaxed.gpu.global.u32 [%0+4], %1;" :: "l"(p.sync), "r"(e) : "memory");
        asm volatile("red.release.gpu.global.add.u32 [%0], 1;" :: "l"(p.sync) : "memory");
      }
      __syncwarp();
      uint32_t c, f; int spin = 0;
      do { asm volatile("ld.acquire.gpu.global.v2.u32 {%0, %1}, [%2];" : "=r"(c), "=r"(f) : "l"(p.sync) : "memory"); trap_if(++spin > 4000000); } while (__any_sync(~0u, (int)(c - e * G) < 0));
      if (f == e) sts32(sb + OFF_MISC + 8, 1);
      if (cta == 0 && lane == 0) asm volatile("st.relaxed.gpu.global.u32 [%0+8], %1;" :: "l"(p.sync), "r"(e) : "memory");
      STAMP(20);
      __syncwarp();
      mbar_arrive(sb + BAR_QP, lane == 0);
    }
    if (w == 2) {
      const uint32_t tg = (1 + e % 3) << 30;
      hint_wait(p.sync + 5, e * G);
      if (lane == 0) { mbar_expect(sb + BAR_HB, XPAD);
#pragma unroll 1
        for (int o = 0; o < 4; o++) bulk_load(sb + OFF_XB + o * (G * 64), (const char*)p.xb + (size_t)(cta * 4 + o) * (G * 64), G * 64, sb + BAR_HB); }
      STAMP(21);
      bar_sync(7, 384);
      sts32(sb + OFF_XB + XPAD, tg + p.N + cta);
      const uint32_t nx = __shfl_sync(~0u, lds32(sb + OFF_MISC + 8) ? 0 : lds32(sb + OFF_MISC + 4), 0);
#pragma unroll 1
      for (uint32_t k = 0; k < nx; k += 32) {
        const uint32_t i = min(k + lane, nx - 1), xr = lds32(sb + OFF_EXT + i * 4), row = (xr >> 9) & 255;
        const uint32_t v = ext_get(p.xe + (cta * G + row) * 32 + ((xr >> 17) & 31), e), x = lds32(sb + OFF_CNT + (xr & 511) * 4) + (xr >> 22) * 16;
        sts32(sb + OFF_XB + XPAD + 4 + i * 4, v); sts16(sb + OFF_TS + x, XPAD + 4 + i * 4);
        sts32(sb + OFF_TE + x * 2, mad16(v, 0x2000u, ealo - (tg >> 11) + row * p.EPC * 32));
      }
      __syncwarp();
      mbar_arrive(sb + BAR_HB, lane == 0);
    }
    if (w == 1) {
      if (PFW) mbar_wait(sb + PFW);
      __nanosleep(PF0NS);
#pragma unroll 1
      for (int i = PFE; i < PFN; i++) { if (lane == 0) prefetch_e(i); __nanosleep(PFNS); }
    }
    if (w == 3) {
      if (lane == 0) { mbar_expect(sb + BAR_U, 16384); tma_load(sb + OFF_W, tmb + TM_WH, 0, sb + BAR_U); }
      __syncwarp();
      bar_sync(4, 416);
      if (lane == 0) tma_load(sb + OFF_W + 8192, tmb + TM_WH, 64, sb + BAR_U);
    }
    bar_sync(3, 128);
    mbar_wait(sb + BAR_U);
    uint32_t mh = 0;
#pragma unroll 1
    for (int i = t; i < 512; i += 128) { uint32_t v[4]; const uint32_t a = sb + OFF_W + i * 16;
      lds128(v, a); sts128(a, hhalf(v[0]), hhalf(v[1]), hhalf(v[2]), hhalf(v[3]));
      lds128(v, a + 8192); sts128(a + 8192, b2h(v[0], .5f), b2h(v[1], .5f), b2h(v[2], .5f), b2h(v[3], .5f));
      mh = mag2(mag2(mag2(mag2(mh, v[0]), v[1]), v[2]), v[3]); }
    if (wbad(__reduce_max_sync(~0u, magr(mh)), 0x4700)) sts32(sb + OFF_MISC + 12, 1);
    proxy_fence();
    __syncwarp();
    mbar_arrive(sb + BAR_WH, lane == 0);
    if (DEFO) { if (!__shfl_sync(~0u, lds32(sb + OFF_MISC + 8), 0)) {
      mbar_wait(sb + BAR_M);
      __nanosleep(DEFO);
#pragma unroll 1
      for (int i = 0; i < 12; i++) { uint32_t v[4]; const uint32_t n = lds16(sb + OFF_GP + i * 256 + (t >> 3) * 8 + 6);
        lds128(v, sb + OFF_H + n * 128 + (((n ^ t) & 7) << 4));
        if (n < nloc) ((uint4*)p.out)[(size_t)(node0 + n) * 8 + (t & 7)] = make_uint4(v[0], v[1], v[2], v[3]);
        __nanosleep(DEFNS); }
      mbar_wait(sb + BAR_X);
#pragma unroll 1
      for (int i = t; i < 384; i += 128) { uint32_t x, y; lds64(x, y, sb + OFF_GP + i * 8); const uint32_t a = sb + OFF_P2 + (y >> 16) * 6; sts16(a, x); sts16(a + 2, x >> 16); sts16(a + 4, y); }
      bar_sync(3, 128);
#pragma unroll 3
      for (int i = t; i < nloc * 3; i += 128) p.out[(size_t)p.N * 64 + node0 * 3 + i] = lds16(sb + OFF_P2 + i * 2);
      asm volatile("{.reg .pred p, q; setp.ne.u32 p, 0, 0; bar.red.or.pred q, 5, 512, p;}" ::: "memory"); } }
    return;
  }

  if (tid == 320) {
    mbar_init(sb + BAR_W, 1);
    asm volatile("fence.mbarrier_init.release.cluster;" ::: "memory");
    mbar_expect(sb + BAR_W, 2 * 8192 + 2304);
    tma_load(sb + OFF_W, tmb + TM_WE, 64, sb + BAR_W); tma_load(sb + OFF_W + 8192, tmb + TM_WE, 0, sb + BAR_W);
    bulk_load(sb + OFF_WS, p.we + 128 * 64, 2176, sb + BAR_W); bulk_load(sb + OFF_WS + 2176, p.wx, 128, sb + BAR_W);
  }
  if (tid == 288) {
#pragma unroll
    for (int a = BAR_SRC; a < BAR_END; a += 8) if (a != BAR_W) mbar_init(sb + a, a == BAR_WH || a == BAR_PS || a == BAR_EP ? 4 : a == BAR_XA ? 11 : a == BAR_HB ? 2 : a == BAR_M ? 12 : a == BAR_X ? 24 : 1);
    asm volatile("fence.mbarrier_init.release.cluster;" ::: "memory");
    asm volatile("prefetch.tensormap [%0];" :: "l"(tmb + TM_XA)); asm volatile("prefetch.tensormap [%0];" :: "l"(tmb + TM_H));
    asm volatile("prefetch.tensormap [%0];" :: "l"(tmb + TM_XB)); asm volatile("prefetch.tensormap [%0];" :: "l"(tmb + TM_Q));
  }
  {
    if (tid < 144) { const uint32_t z = (tid >> 3) == 16 ? 0x8000u : 0u; sts128(sb + OFF_CNT + tid * 16, z, z, z, z); }
    else if (tid <= 144 + G) sts32(sb + OFF_BC + (tid - 144) * 4, ((tid - 144) & 31) * 4);
    const uint32_t sp = XPAD * 0x10001u, em = first_node(G);
    if (wid < 7) {
#pragma unroll
      for (int i = 0; i < 4; i++) sts128(sb + OFF_TS + tid * 16 + i * 3584, sp, sp, sp, sp);
    }
    static_assert(SCAP * 32 == 4 * 3584, "fill");
#pragma unroll 1
    for (int i = n4 + tid; i < 1536; i += 384) sts128(sb + OFF_DST + i * 16, em, em, em, em);
    if (tid == 321) sts128(sb + OFF_MISC, 0, 0, p.force_slow, 0);
  }
  bar_arrive(6, NTHR);
  bar_sync(0, 384);
  uint32_t ep, tag, eb0, pk[12], r0[12], r1[12], cb;
  uint2 vb[12];
  auto get_tag = [&]() { mbar_wait(sb + BAR_EP); ep = lds32(sb + OFF_MISC + 32); tag = (1 + ep % 3) << 30; eb0 = ealo - (tag >> 11); };
  if (wid == 11) {
    trap_if(sb != (uint32_t)__cvta_generic_to_shared(smraw));
#pragma unroll 1
    for (unsigned long long q = LSEQ; q; q >>= 8) { const int k = (q >> 4) & 7, nb = max(0, min(8192, n4 * 16 - k * 8192));
      if (!(q & 8)) mbar_wait(sb + BAR_DST + ((uint32_t)q & 7) * 8);
      if (lane == 0) {
        if (k >= 3) load_h(k - 3);
        else { mbar_expect(sb + BAR_SRC + k * 8, nb);
          if (nb) bulk_load(sb + OFF_SRCI + k * 8192, (const char*)(p.src + e0) + k * 8192, nb, sb + BAR_SRC + k * 8); } } }
    get_tag();
    mbar_wait(sb + BAR_PS);
    bar_sync(12, 384);
    uint32_t xm = 0;
#pragma unroll
    for (int k = 0; k < 5; k++) xm |= (lds32(sb + OFF_BC + min(lane + 32 * k, G - 1) * 4) >= (65 << 9) && lane + 32 * k < G) << k;
    auto ext_send = [&](int pl) {
      uint32_t x = xm;
      for (uint32_t m; (m = __ballot_sync(~0u, x));) {
        const uint32_t l = __ffs(m) - 1, j = l + 32 * (__ffs(__shfl_sync(~0u, x, l)) - 1);
        if (lane == l) x &= x - 1;
        const uint32_t e = min(lds16(sb + OFF_AX + j * 128 + ((4 * l + 2 * lane) & 126)), 6143u);
        if (pl) st_ext(p.xe + (j * G + cta) * 32 + lane, lds32(sb + OFF_SRCI + e * 4) + tag + (e << 16), ep);
        else { const uint32_t cn = lds32(sb + OFF_BC + j * 4) >> 9, v = cn > 96 ? 1 : lane + 64 < cn ? 512 | (lds32(sb + OFF_DST + e * 4) & 511) : 0;
          asm volatile("red.shared.xor.b32 [%0], %1;" :: "r"(sb + OFF_SA + j * 128 + ((l + lane) & 31) * 4), "r"(((v & 63) << 10) | ((v >> 6) << 26)) : "memory"); }
      }
    };
    if (__any_sync(~0u, xm)) { ext_send(0); proxy_fence(); __syncwarp(); }
    if (lane == 0) { tma_store_ef(tmb + TM_XA, cta * 64, 0, sb + OFF_SA); bulk_commit(); mbar_arrive(sb + BAR_AI); bulk_wait(); hint_signal(p.sync + 4); mbar_arrive(sb + BAR_AW); STAMP(16); }
    __syncwarp();
    bar_sync(13, 384);
    if (!B_HOLD && lane == 0) { tma_store_ef(tmb + TM_XB, cta * 64, 0, sb + OFF_SB); bulk_commit(); }
    __syncwarp();
    ext_send(1);
    mbar_arrive(sb + BAR_AX, lane == 0);
    if (B_HOLD) mbar_wait(sb + (B_HOLD == 1 ? BAR_HA : BAR_XA));
    if (lane == 0) {
      bulk_wait();
#pragma unroll 1
      for (int r = B_HOLD ? 0 : BROWS; r < G; r += BROWS) { tma_store_ef(tmb + TM_XB, cta * 64, r, sb + OFF_SB + r * 256); bulk_commit(); bulk_wait(); }
      hint_signal(p.sync + 5);
#pragma unroll 1
      for (int i = 0; i < PFE; i++) prefetch_e(i);
      STAMP(17);
    }
    __syncwarp();
  } else {
    {
      uint32_t d[4 * NCH], jj[4 * NCH], rr[4 * NCH];
      auto count = [&](int k) {
        mbar_wait(sb + BAR_DST + k * 8);
        lds128(d + 4 * k, sb + OFF_DST + (tid + NWK * k) * 16);
#pragma unroll
        for (int i = 4 * k; i < 4 * k + 4; i++) { jj[i] = d[i] * p.magic; rr[i] = atoms_add(__dp4a(jj[i], 0x04000000u, sb + OFF_BC), 0x202u); }
      };
      auto place = [&](int k) {
#pragma unroll
        for (int i = 4 * k; i < 4 * k + 4; i++) {
          const uint32_t o = __dp4a(jj[i], 0x80000000u, rr[i] & 0x807Eu);
          d[i] = (d[i] & 511) | (tag >> 16);
          asm("{.reg .pred p; setp.ge.u32 p, %1, 0x8000; @p add.u32 %0, %2, %3;}" : "+r"(d[i]) : "r"(o), "r"(tid * 4), "r"(NWK * k * 4 + (i & 3)));
          sts16(sb + OFF_SA + o, d[i]); jj[i] = __viaddmin_u32(o, o, G * 256);
        }
      };
      count(0); STAMP(1); count(1); get_tag(); place(0); count(2); place(1); count(3); place(2);
      if (wid < 4) { count(4); STAMP(15); place(3); place(4); } else place(3);
      proxy_fence();
      bar_arrive(12, 384);
      STAMP(2);
      mbar_wait(sb + BAR_AI);
      mbar_wait(sb + BAR_SRC); mbar_wait(sb + BAR_SRC + 8); mbar_wait(sb + BAR_SRC + 16);
      STAMP(12);
#pragma unroll
      for (int k = 0; k < NCH; k++) lds128(d + 4 * k, sb + OFF_SRCI + (tid + NWK * k) * 16);
      const uint32_t tb = tag + (tid << 18);
#pragma unroll
      for (int i = 0; i < 4 * NCH; i++) if (i < 4 * NCH - 4 || wid < 4) sts32(sb + OFF_SB + jj[i], d[i] + tb + ((NWK * (i >> 2) * 4 + (i & 3)) << 16));
      proxy_fence();
      bar_arrive(13, 384);
      STAMP(3);
    }
    const uint32_t rot = (lane + cta) & 31;
    cb = sb + OFF_CNT - (tag >> 14);
    {
      const uint32_t* xa = (const uint32_t*)(p.xa + (cta * G + wid) * 8) + rot;
      if (wid < 8) { const uint32_t e_ = ealo + epad * 32;
        mbar_wait(sb + BAR_AX);
#pragma unroll
        for (int i = 0; i < 7; i++) sts128(sb + OFF_TE + tid * 16 + i * 4096, e_, e_, e_, e_); }
      static_assert(SCAP * 64 == 7 * 4096, "fill");
      if (wid == 10) { hint_wait(p.sync + 4, ep * G); mbar_arrive(sb + BAR_HA, lane == 0); }
      mbar_wait(sb + BAR_HA);
      STAMP(14);
      const uint32_t tp = tag | (tag >> 16);
      uint32_t st;
#pragma unroll 1
      for (int spin = 0;; spin++) {
        st = 0;
#pragma unroll
        for (int k = 0; k < 12; k++) asm volatile("ld.relaxed.gpu.global.u32 %0, [%1];" : "=r"(pk[k]) : "l"(xa + k * 352) : "memory");
#pragma unroll
        for (int k = 0; k < 12; k++) st |= pk[k] ^ tp;
        st = __reduce_or_sync(~0u, st);
        if (!(st >> 30)) break;
        trap_if(spin > 2000000);
      }
      if (st & 0x3C00FC00u) {
#pragma unroll 1
        for (;;) {
          uint32_t x = 0, row = 0;
#pragma unroll
          for (int k = 0; k < 12; k++) { const uint32_t y = (pk[k] ^ tp) & 0x3C00FC00u; if (!x && y) { x = y; row = wid + 11 * k; pk[k] ^= y; } }
          if (!__any_sync(~0u, x)) break;
          const uint32_t n = ((x >> 10) & 63) | ((x >> 20) & 0x1C0);
          if (x >> 29) {
            const uint32_t r = atoms_add(sb + OFF_CNT + n * 4, 16), idx = atoms_add(sb + OFF_MISC + 4, 1);
            if (idx < 256) sts32(sb + OFF_EXT + idx * 4, n | (row << 9) | (lane << 17) | (min(r >> 4, 255u) << 22));
            else x = 1;
          }
          if (x && !(x >> 29)) sts32(sb + OFF_MISC + 8, 1);
          __syncwarp();
        }
      }
#pragma unroll
      for (int k = 0; k < 12; k++) { r0[k] = mad16(pk[k], 0x0004u, cb); r1[k] = mad16(pk[k], 0x0400u, cb); vb[k].x = atoms_add(r0[k], 16); vb[k].y = atoms_add(r1[k], 16); }
      if (B_HOLD == 2) mbar_arrive(sb + BAR_XA, lane == 0);
    }
    STAMP(4);
    if (wid >= 6) bar_arrive(11, NWK);
    if (wid < 6) {
      uint32_t ca[2], ky[2], dr[2], sq[2], ps[4];
#pragma unroll
      for (int i = 0; i < 2; i++) { ca[i] = sb + OFF_CNT + ((node0 + tid + 192 * i) & 511) * 4; lds64(ps[2 * i], ps[2 * i + 1], sb + OFF_POS + (tid + 192 * i) * 8); ps[2 * i + 1] |= (tid + 192 * i) << 16; }
      bar_sync(11, NWK);
      STAMP(5);
#pragma unroll
      for (int i = 0; i < 2; i++) ky[i] = (lds32(ca[i]) + 16) >> 5;
      if (max(ky[0], ky[1]) > 31) sts32(sb + OFF_MISC + 8, 1);
#pragma unroll
      for (int i = 0; i < 2; i++) { ky[i] = min(ky[i], 31u); dr[i] = atoms_add(sb + OFF_DH + ky[i] * 4, 1); }
      bar_sync(10, 192);
      const uint32_t hv = lds32(sb + OFF_DH + lane * 4);
      uint32_t inc = hv;
#pragma unroll
      for (int o = 1; o < 32; o <<= 1) asm("{.reg .pred p; .reg .b32 y; shfl.sync.down.b32 y|p, %0, %1, 31, -1; @p add.u32 %0, %0, y;}" : "+r"(inc) : "r"(o));
#pragma unroll
      for (int i = 0; i < 2; i++) {
        const uint32_t pos = __shfl_sync(~0u, inc - hv, ky[i]) + dr[i];
        const uint32_t ak = (uint32_t)(QCODE >> ((pos >> 5) * 4)) & 15, l = (pos >> 3) & 3;
        sq[i] = (ak >> 2) * 16 + ((QREV >> (pos >> 5) & 1) ? 3 - l : l) * 4 + (ak & 3);
        dr[i] = pos & 7;
        asm volatile("{.reg .pred p; setp.eq.u32 p, %2, 0; @p st.shared.u8 [%0], %1;}" :: "r"(sb + OFF_LEN + sq[i]), "r"(max(ky[i], 1u)), "r"(dr[i]) : "memory");
        sts64(sb + OFF_GP + sq[i] * 64 + dr[i] * 8, ps[2 * i], ps[2 * i + 1]);
      }
      bar_sync(10, 192);
      const uint32_t ln = lds32(sb + OFF_LEN + min(lane, 11) * 4), tot = __dp4a(ln, 0x01010101u, 0u);
      inc = tot;
#pragma unroll
      for (int o = 1; o < 16; o <<= 1) asm("{.reg .pred p; .reg .b32 y; shfl.sync.up.b32 y|p, %0, %1, 0, -1; @p add.u32 %0, %0, y;}" : "+r"(inc) : "r"(o));
      if (wid == 1) sts32(sb + OFF_CNT + 2048 + lane * 4, 0);
      if (tid < 12) { sts32(sb + OFF_LEN + 64 + tid * 4, inc - tot); if (inc > SCAP) sts32(sb + OFF_MISC + 8, 1); }
#pragma unroll
      for (int i = 0; i < 2; i++) sts32(ca[i], __dp4a(__shfl_sync(~0u, ln, sq[i] >> 2), 0x00010101u >> (24 - 8 * (sq[i] & 3)), __shfl_sync(~0u, inc - tot, sq[i] >> 2)) * 32 + dr[i] * 2);
    }
    bar_arrive(7, 384);
  }
  bar_sync(1, 384);
  STAMP(6);
  if (wid != 11 && !__shfl_sync(~0u, lds32(sb + OFF_MISC + 8), 0)) {
#pragma unroll
    for (int k = 0; k < 12; k++) { r0[k] = lds32(r0[k]); r1[k] = lds32(r1[k]); }
#pragma unroll
    for (int k = 0; k < 12; k++) { r0[k] += vb[k].x; r1[k] += vb[k].y; }
  } else {
#pragma unroll
    for (int k = 0; k < 12; k++) r0[k] = r1[k] = 0x8000;
  }
  auto put_ids = [&]() {
    const uint32_t id = wid * 256 + ((lane + cta) & 31) * 8;
    auto put = [&](uint32_t x, uint32_t v) { asm volatile("{.reg .pred p; setp.lt.u32 p, %0, 0x8000; @p st.shared.u16 [%0+%2], %1;}" :: "r"(x), "h"((uint16_t)v), "n"(sb + OFF_TS) : "memory"); };
#pragma unroll
    for (int k = 0; k < 12; k++) { put(IDL ? pk[k] & 0xFFFF : r0[k], id + k * 2816); put(IDL ? pk[k] >> 16 : r1[k], id + k * 2816 + 4); }
  };
  if (!IDL) put_ids();
  STAMP(7);
  mbar_wait(sb + BAR_QR);
  asm volatile("setmaxnreg.inc.sync.aligned.u32 160;");
  if (IDL) {
#pragma unroll
    for (int k = 0; k < 12; k++) asm volatile("prmt.b32 %0, %1, %2, 0x5410;" : "=r"(pk[k]) : "r"(r0[k]), "r"(r1[k]));
  }
  uint32_t pa[8], sp[8], pq[16]; float chk = 0.f;
  {
    uint32_t hf[32], mp = 0; float a0[32], a1[32];
    const uint32_t an = sb + OFF_GP + wid * 256 + (lane & 15) * 8 + 6, n0 = lds16(an), n1 = lds16(an + 128);
#pragma unroll
    for (int j = 0; j < 8; j++) { const uint32_t nd = j < 4 ? n0 : n1; ldsm4(hf + 4 * j, (sb + OFF_H + nd * 128 + (((nd & 7) << 4) ^ (lane & 16))) ^ ((j & 3) << 5)); }
    const uint64_t db = DHI | ((sb + OFF_W + 8192) >> 4);
    wg_fence();
    rs64b<0>(a0, hf[0], hf[1], hf[2], hf[3], db); rs64b<1>(a0, hf[4], hf[5], hf[6], hf[7], db + 128); rs64b<1>(a0, hf[8], hf[9], hf[10], hf[11], db + 256); rs64b<1>(a0, hf[12], hf[13], hf[14], hf[15], db + 384);
    wg_commit();
    rs64b<0>(a1, hf[16], hf[17], hf[18], hf[19], db); rs64b<1>(a1, hf[20], hf[21], hf[22], hf[23], db + 128); rs64b<1>(a1, hf[24], hf[25], hf[26], hf[27], db + 256); rs64b<1>(a1, hf[28], hf[29], hf[30], hf[31], db + 384);
    wg_commit();
    if (IDL) put_ids();
    asm volatile("wgmma.wait_group.sync.aligned 1;" ::: "memory"); fence_regs(a0);
#pragma unroll
    for (int j = 0; j < 8; j++) { const uint32_t x = pack_f16(.5f * a0[4 * j], .5f * a0[4 * j + 1]), y = pack_f16(.5f * a0[4 * j + 2], .5f * a0[4 * j + 3]); mp = hmag(hmag(mp, x), y);
      asm volatile("movmatrix.sync.aligned.m8n8.trans.b16 %0, %1;" : "=r"(pa[j]) : "r"(x)); asm volatile("movmatrix.sync.aligned.m8n8.trans.b16 %0, %1;" : "=r"(sp[j]) : "r"(y)); }
    wg_wait0(); fence_regs(a1);
    bar_arrive(4, 416);
#pragma unroll
    for (int j = 0; j < 16; j++) { pq[j] = pack_f16(.5f * a1[2 * j], .5f * a1[2 * j + 1]); mp = hmag(mp, pq[j]); }
    if (magr(mp) >= 0x7000) chk = __int_as_float(0x7FC00000);
  }
  if (wid == 0) STAMP(23);
  uint32_t bad;
  {
    const uint32_t ring = sb + OFF_RING + wid * STG, p2 = sb + OFF_P2 + wid * 2048;
    uint32_t lens = __shfl_sync(~0u, lds32(sb + OFF_LEN + wid * 4), 0);
    uint32_t rem = __dp4a(lens, 0x20202020u, 0u);
    const uint32_t base = min(lds32(sb + OFF_LEN + 64 + wid * 4), SCAP);
    uint32_t a_s = sb + OFF_TS + base * 32 + (lane >> 3) * 8, a_e = sb + OFF_TE + base * 64 + (lane >> 1) * 4;
    uint32_t k0 = (uint32_t)(uint64_t)p.q + (((lane & 7) ^ ((lane >> 1) & 4)) << 4), k1 = k0 ^ 16, k2 = k0 ^ 32, k3 = k0 ^ 48, ke = ((lane ^ (lane >> 3)) & 1) << 4;
    uint32_t dst0 = ring + (lane >> 3) * 640 + (lane & 7) * 16;
    const uint32_t qhi = (uint32_t)((uint64_t)p.q >> 32), ehi = (uint32_t)((uint64_t)p.ea >> 32);
    uint32_t s0, s1, ev, to = 0, so = 12 * STG;
    auto tl_ = [&]() { lds64(s0, s1, a_s + to); asm volatile("ld.shared.u32 %0, [%1]; add.u32 %1, %1, 64;" : "=&r"(ev), "+r"(a_e) :: "memory"); to += 32; };
#define CPQ(LH, x, k, off) "dp2a." LH ".u32.u32 lo, " x ", 0x80000080, " k "; mov.b64 a, {lo, %7}; @p cp.async.cg.shared.global [%0+" #off "], [a], 16;\n"
#define CPE "or.b32 lo, %10, %11; mov.b64 a, {lo, %12}; @p cp.async.cg.shared.global" ESZ " [%0+512], [a], 16;\n"
#define CPA(BODY) asm volatile("{.reg .b32 lo; .reg .b64 a; .reg .pred p; setp.le.u32 p, %8, %9;\n" BODY "}" \
      :: "r"(dst0 + so), "r"(s0), "r"(s1), "r"(k0), "r"(k1), "r"(k2), "r"(k3), "r"(qhi), "r"(to), "r"(rem), "r"(ev), "r"(ke), "r"(ehi) : "memory")
#define CPQ4 CPQ("lo", "%1", "%3", 0) CPQ("hi", "%1", "%4", 128) CPQ("lo", "%2", "%5", 256) CPQ("hi", "%2", "%6", 384) "cp.async.commit_group;"
    auto issue = [&]() { CPA(CPE CPQ4); so = so == (NST - 1) * 12 * STG ? 0 : so + 12 * STG; };
    const int g = lane >> 2, qd = lane & 3;
    const uint32_t sw = ((lane >> 4) ^ (lane & 7)) << 4, fr = (lane & 15) * 128 + sw;
    uint32_t qa0 = ring + (g & 3) * 640 + qd * 128 + sw, qa1 = qa0 ^ 32, qa2 = qa0 ^ 64, qa3 = qa0 ^ 96;
    uint32_t eadr = ring + 512 + (g & 3) * 640 + qd * 32 + ((((lane >> 4) ^ g) & 1) << 4);
    uint32_t oh0 = g == 2 * qd ? 0x3C00u : g == 2 * qd + 1 ? 0x3C000000u : 0u, oh1 = oh0;
    uint32_t a_g = sb + OFF_GP + wid * 256 + lane * 2;
    uint32_t a_n = sb + OFF_GP + wid * 256 + (lane & 15) * 8 + 6;
    uint32_t a_p = ((lane & 8) ? p2 : sb + OFF_WD) + (lane & 7) * 128 + ((((lane >> 4) ^ lane) & 7) << 4);
    uint32_t a_w = sb + OFF_W3 + fr;
#define OPQ4(A, B, C, D) asm volatile("shfl.sync.bfly.b32 %0, %0, 0, 31, -1; shfl.sync.bfly.b32 %1, %1, 0, 31, -1; shfl.sync.bfly.b32 %2, %2, 0, 31, -1; shfl.sync.bfly.b32 %3, %3, 0, 31, -1;" : "+r"(A), "+r"(B), "+r"(C), "+r"(D))
    asm volatile("shfl.sync.idx.b32 %0, %0, %1, 31, -1;" : "+r"(oh1) : "r"(lane));
    if (OPQ & 1) OPQ4(a_w, oh0, ke, dst0);
    if (OPQ & 2) OPQ4(qa0, qa1, qa2, qa3);
    if (OPQ & 4) OPQ4(k0, k1, k2, k3);
    if (OPQ & 8) OPQ4(a_g, a_n, a_p, eadr);
    uint32_t w3[16], wv[8], bp[16], sum[8], Y[16], M[16], own, ownp, dpk; uint16_t tl[16], th[16];
    float pacc = 0.f;
    const uint32_t n0_ = __shfl_sync(~0u, node0 + lane, 0), nl = __shfl_sync(~0u, nloc + lane, 0);
    const char* outh = (const char*)p.out + (size_t)n0_ * 128;
    auto wload = [&]() {
#pragma unroll
      for (int j = 0; j < 4; j++) ldsm4t(w3 + 4 * j, a_w ^ (j << 5));
      lds128(wv, sb + OFF_WX + (a_g & 6) * 16); lds128(wv + 4, sb + OFF_WX + 16 + (a_g & 6) * 16);
    };
    auto hload = [&](uint32_t (&hf)[16], uint32_t nd) {
      const uint32_t hrow = sb + OFF_H + nd * 128 + (((nd & 7) << 4) ^ ((a_g >> 1) & 16));
#pragma unroll
      for (int j = 0; j < 4; j++) ldsm4(hf + 4 * j, hrow ^ (j << 5));
      return hrow;
    };
    auto bload = [&](uint32_t o) {
#pragma unroll
      for (int j = 0; j < 4; j++) ldsm4t(bp + 4 * j, (a_p ^ (j << 5)) + o);
    };
    { uint32_t wd[8]; const uint32_t a = sb + OFF_WD + (lane & 7) * 128 + ((((lane >> 3) ^ lane) & 7) << 4);
      ldsm4t(wd, a); ldsm4t(wd + 4, a ^ 64);
#pragma unroll
      for (int j = 0; j < 8; j++) { bp[2 * j] = wd[j]; bp[2 * j + 1] = pa[j]; } }
    own = lds16(a_g) * 0x10001u;
    wload();
    if (__shfl_sync(~0u, lds32(sb + OFF_MISC + 8), 0)) rem = 0;
    auto resolve = [&](auto NBK, uint32_t o) {
      constexpr int NB = decltype(NBK)::value;
      uint32_t id[NB], c0[NB], c1[NB]; const uint32_t a = base * 32 + o + lane * 4;
#pragma unroll
      for (int i = 0; i < NB; i++) { id[i] = lds32(sb + OFF_TS + a + i * 128); if (o + lane * 4 + i * 128 >= rem) id[i] = XPAD * 0x10001u; }
      uint32_t st = 0;
#pragma unroll
      for (int i = 0; i < NB; i++) { c0[i] = lds32(sb + OFF_XB + (id[i] & 0xFFFF)); c1[i] = lds32(sb + OFF_XB + (id[i] >> 16)); }
#pragma unroll
      for (int i = 0; i < NB; i++) st |= (c0[i] ^ tag) | (c1[i] ^ tag);
      for (int spin = 0; __any_sync(~0u, st >> 30); spin++) {
        st = 0; trap_if(spin > 2000000);
#pragma unroll
        for (int i = 0; i < NB; i++) {
          asm volatile("{.reg .pred p, q; setp.lt.u32 p, %4, %6; setp.lt.u32 q, %5, %6; @p ld.relaxed.gpu.global.u32 %0, [%2]; @q ld.relaxed.gpu.global.u32 %1, [%3];}"
            : "+r"(c0[i]), "+r"(c1[i]) : "l"((const char*)p.xb + cta * XPAD + (id[i] & 0xFFFF)), "l"((const char*)p.xb + cta * XPAD + (id[i] >> 16)), "r"(id[i] & 0xFFFF), "r"(id[i] >> 16), "n"(XPAD) : "memory");
          st |= (c0[i] ^ tag) | (c1[i] ^ tag); }
      }
#pragma unroll
      for (int i = 0; i < NB; i++) { const uint32_t j0 = (id[i] >> 8) & 255, j1 = id[i] >> 24;
        if (ABL & 2) { c0[i] &= 0xFFFF0FFFu; c1[i] &= 0xFFFF0FFFu; }
        asm volatile("{.reg .pred p, q, r; setp.lt.u32 p, %5, %9; setp.lt.u32 q, %6, %9; setp.lt.u32 r, %7, %8;\n"
          "@p st.shared.u32 [%0], %2; @q st.shared.u32 [%0+4], %3; @r st.shared.u32 [%1], %4;}"
          :: "r"(sb + OFF_TE + 2 * a + i * 256), "r"(sb + OFF_TS + a + i * 128), "r"(mad16(c0[i], 0x2000u, eb0 + ((ABL & 1) ? j0 & 7 : j0) * p.EPC * 32)), "r"(mad16(c1[i], 0x2000u, eb0 + ((ABL & 1) ? j1 & 7 : j1) * p.EPC * 32)),
             "r"(__byte_perm(c0[i], c1[i], 0x5410)), "r"(j0), "r"(j1), "r"(o + lane * 4 + i * 128), "r"(rem), "n"(G) : "memory"); }
    };
    bar_sync(2, 384);
    if (wid == 0) STAMP(27);
    mbar_wait(sb + BAR_HB);
    if (wid == 0) STAMP(22);
#pragma unroll 1
    for (uint32_t o = 0, go = 0; go < 32 * NST; o += 128 * RNB) {
      if (o < rem) { resolve(IC<RNB>(), o);
        asm volatile("{.reg .pred p; mbarrier.test_wait.parity.shared::cta.b64 p, [%1], 0; vote.sync.all.pred p, p, -1; selp.u32 %0, %2, 0, p;}" : "=r"(go) : "r"(sb + BAR_QP), "n"(32 * NEARLY) : "memory"); }
      else { bar_sync(8, 384); mbar_wait(sb + BAR_QP); go = 32 * NST; if (wid == 0) STAMP(24); }
      __syncwarp();
#pragma unroll 1
      while (to < go) { tl_(); issue(); if (to == 32) STAMP(13); }
    }
    bad = __shfl_sync(~0u, lds32(sb + OFF_MISC + 8), 0);
   if (!bad) {
#pragma unroll
    for (int j = 0; j < 4; j++) stsm4((p2 + fr) ^ (j << 5), pq[4 * j], pq[4 * j + 1], pq[4 * j + 2], pq[4 * j + 3]);
    auto body = [&](auto MODE) {
      constexpr int mode = decltype(MODE)::value;
      uint32_t T[16], ef[4], q0, q1, x0, x1, x2; float e0_, e1_, cs[4];
      auto mu = [&](int j) {
#pragma unroll
        for (int i = 2 * j; i < 2 * j + 2; i++) asm volatile("{.reg .b16 l, h; mov.b32 {l, h}, %2; tanh.approx.f16 %0, l; tanh.approx.f16 %1, h;}" : "=h"(tl[i]), "=h"(th[i]) : "r"(Y[i])); };
      auto fi = [&](int j) {
#pragma unroll
        for (int i = 2 * j; i < 2 * j + 2; i++) asm volatile("{.reg .b32 t; mov.b32 t, {%2, %3}; fma.rn.f16x2 %0, %1, t, %1;}" : "=r"(M[i]) : "r"(Y[i]), "h"(tl[i]), "h"(th[i])); };
      auto ad = [&](int j) { asm volatile("add.rn.f16x2 %0, %0, %1; add.rn.f16x2 %0, %0, %2;" : "+r"(sum[j]) : "r"(M[2 * j]), "r"(M[2 * j + 1])); };
      auto he = [&](int j) { asm volatile("mma.sync.aligned.m16n8k16.row.col.f16.f16.f16.f16 {%0,%1}, {%2,%3,%4,%5}, {%6,%7}, {%0,%1};" : "+r"(T[2 * j]), "+r"(T[2 * j + 1]) : "r"(ef[0]), "r"(ef[1]), "r"(ef[2]), "r"(ef[3]), "r"(w3[2 * j]), "r"(w3[2 * j + 1])); };
      auto hs = [&](int j) { asm volatile("mma.sync.aligned.m16n8k16.row.col.f16.f16.f16.f16 {%0,%1}, {%2,%3,%4,%5}, {%6,%7}, {%8,%9};" : "=r"(Y[2 * j]), "=r"(Y[2 * j + 1]) : "r"(q0), "r"(q1), "r"(oh0), "r"(oh1), "r"(bp[2 * j]), "r"(bp[2 * j + 1]), "r"(T[2 * j]), "r"(T[2 * j + 1])); };
      auto hc = [&](int j) {
        if (j) asm volatile("mma.sync.aligned.m16n8k16.row.col.f32.f16.f16.f32 {%0,%1,%2,%3}, {%4,%5,%6,%7}, {%8,%9}, {%0,%1,%2,%3};" : "+f"(cs[0]), "+f"(cs[1]), "+f"(cs[2]), "+f"(cs[3]) : "r"(M[4 * j]), "r"(M[4 * j + 1]), "r"(M[4 * j + 2]), "r"(M[4 * j + 3]), "r"(wv[2 * j]), "r"(wv[2 * j + 1]));
        else asm volatile("mma.sync.aligned.m16n8k16.row.col.f32.f16.f16.f32 {%0,%1,%2,%3}, {%4,%5,%6,%7}, {%8,%9}, {%10,%10,%10,%10};" : "=f"(cs[0]), "=f"(cs[1]), "=f"(cs[2]), "=f"(cs[3]) : "r"(M[0]), "r"(M[1]), "r"(M[2]), "r"(M[3]), "r"(wv[0]), "r"(wv[1]), "f"(0.f)); };
      auto cv = [&](int i) { asm volatile("{.reg .b32 a, b; shl.b32 a, %0, 16; and.b32 b, %0, 0xFFFF0000; cvt.rn.f16x2.f32 %0, b, a;}" : "+r"(ef[i])); };
      auto un = [&]() { asm volatile("shl.b32 %0, %2, 16; and.b32 %1, %2, 0xFFFF0000;" : "=&f"(e0_), "=&f"(e1_) : "r"(dpk)); };
      auto ex0 = [&]() { asm volatile("prmt.b32 %0, %3, %4, 0x6420; prmt.b32 %1, %5, %6, 0x6420; prmt.b32 %2, %7, %8, 0x6420;" : "=&r"(x0), "=&r"(x1), "=&r"(x2) : "r"(T[0]), "r"(T[1]), "r"(T[2]), "r"(T[3]), "r"(T[4]), "r"(T[5])); };
      auto ex1 = [&]() { asm volatile("{.reg .b32 a, b; shl.b32 a, %2, 3; shl.b32 b, %3, 6; lop3.b32 a, %1, a, 0x38383838, 0xD8; lop3.b32 a, a, b, 0xC0C0C0C0, 0xD8; sub.rn.bf16x2 %0, %4, a;}" : "=r"(dpk) : "r"(x0), "r"(x1), "r"(x2), "r"(own)); };
      auto ex2 = [&]() { asm volatile("{.reg .b32 a, b, d, u; .reg .b16 l, h; shl.b32 a, %2, 16; and.b32 b, %2, 0xFFFF0000; cvt.rn.f16x2.f32 d, b, a; mul.rn.f16x2 %0, d, d; mov.b32 {l, h}, d; mov.b32 u, {h, h}; mul.rn.f16x2 %1, u, u;}" : "=&r"(q0), "=&r"(q1) : "r"(dpk)); };
      auto pf = [&]() { asm volatile("fma.rn.f32 %0, %1, %2, %0; fma.rn.f32 %0, %3, %4, %0;" : "+f"(pacc) : "f"(cs[0]), "f"(e0_), "f"(cs[2]), "f"(e1_)); };
#define FX(k) if (FM >> k & 1) asm volatile("pmevent 1;" ::: "memory")
      if (mode == 2) {
        hc(0); mu(3); fi(2); un(); ad(0); ad(1); mu(4); fi(3); hc(1); mu(5); fi(4); ad(2); mu(6); fi(5); ad(3); hc(2); mu(7); fi(6); fi(7); ad(4); ad(5); hc(3); ad(6); ad(7); pf();
        return;
      }
      asm volatile("cp.async.wait_group %0;" :: "n"(NST - 1) : "memory");
      __syncwarp();
      if (mode == 1) STAMP(8);
      ldsm4(ef, eadr + so); ldsm4(T, qa0 + so); ldsm4(T + 4, qa1 + so); ldsm4(T + 8, qa2 + so); ldsm4(T + 12, qa3 + so);
      tl_();
      if (mode == 1) {
        issue();
        cv(0); cv(1); cv(2); cv(3); ex0(); ex1(); ex2();
#pragma unroll
        for (int j = 0; j < 8; j++) { he(j); hs(j); }
        mu(0); mu(1); fi(0); mu(2); fi(1);
        return;
      }
      hc(0); mu(3); fi(2); un(); ad(0); ad(1);
      FX(0);
      mu(4); fi(3); cv(0); cv(1); cv(2); cv(3); ex0(); ex1();
      FX(1);
      he(0); he(1); hc(1); mu(5); fi(4); ex2(); ad(2);
      FX(2);
      hs(0); he(2); mu(6); fi(5); issue(); ad(3);
      FX(3);
      hs(1); he(3); hc(2); mu(7); fi(6);
      FX(4);
      hs(2); hs(3); he(4); he(5); mu(0); fi(7); ad(4); ad(5);
      FX(5);
      hc(3); hs(4); he(6); he(7); mu(1); fi(0); ad(6);
      FX(6);
      hs(5); hs(6); hs(7); mu(2); fi(1); ad(7); pf();
      FX(7);
    };
#pragma unroll
    for (int j = 0; j < 8; j++) sum[j] = 0;
    body(IC<1>());
    int cnt = (lens & 255) - 1;
#pragma unroll 1
    for (int t = 0; t < 8; t++) {
#pragma unroll 1
      for (; cnt > 0; cnt--) { body(IC<0>());
      }
      if (!(t & 1)) {
        ownp = own;
        if (t < 6) {
          a_g += 64; own = lds16(a_g) * 0x10001u;
          if (t == 0) {
#pragma unroll
            for (int j = 0; j < 8; j++) bp[2 * j + 1] = sp[j];
          } else bload((a_g & 16) ? (t & 4) * 256 : 0);
          lens >>= 8; cnt = 1;
          continue;
        }
        body(IC<2>()); t++; a_g += 64;
        STAMP(9);
      }
      cnt = (lens & 255) - 1;
      asm volatile("{.reg .pred p; setp.ne.u32 p, %2, 6; @p st.shared.u16 [%0+-64], %1;}" :: "r"(a_g), "h"((uint16_t)pack_bf16(bf_hi(ownp) + pacc, 0.f)), "r"(a_g & 6) : "memory");
      chk = fmaf(pacc, 0.f, chk); pacc = 0.f;
      if (t & 2) {
        uint32_t hf[16]; float acc[32];
        const uint32_t nd = lds16(a_n);
        const uint32_t hrow = hload(hf, nd);
        a_n += 128;
        __syncwarp();
        mbar_arrive(sb + BAR_X, (a_g & 62) == 0);
        const uint64_t b1 = DHI | ((sb + OFF_W) >> 4), b2_ = b1 + 512;
        mbar_wait(sb + BAR_WH);
        wg_fence();
        rs64h<0>(acc, sp[0], sum[0], sp[1], sum[1], b2_); rs64h<1>(acc, sp[2], sum[2], sp[3], sum[3], b2_ + 128); rs64h<1>(acc, sp[4], sum[4], sp[5], sum[5], b2_ + 256); rs64h<1>(acc, sp[6], sum[6], sp[7], sum[7], b2_ + 384);
        rs64b<1>(acc, hf[0], hf[1], hf[2], hf[3], b1); rs64b<1>(acc, hf[4], hf[5], hf[6], hf[7], b1 + 128); rs64b<1>(acc, hf[8], hf[9], hf[10], hf[11], b1 + 256); rs64b<1>(acc, hf[12], hf[13], hf[14], hf[15], b1 + 384);
        wg_commit();
        uint32_t nr[4];
#pragma unroll
        for (int j = 0; j < 4; j++) nr[j] = __shfl_sync(~0u, nd, 4 * j + ((a_g >> 4) & 3)) * 128 + ((a_g << 3) & 0x70);
        wg_wait0(); fence_regs(acc);
        if (t == 7) STAMP(10);
        chk = fmaf(acc[0], 0.f, fmaf(acc[2], 0.f, chk));
        auto fin = [&](uint32_t x, float y0, float y1) { return u2(__hadd2(b2(x), b2(pack_bf16(silu_h(y0), silu_h(y1))))); };
#pragma unroll
        for (int j = 0; j < 4; j++) stsm4(hrow ^ (j << 5), fin(hf[4 * j], acc[8 * j], acc[8 * j + 1]), fin(hf[4 * j + 1], acc[8 * j + 2], acc[8 * j + 3]), fin(hf[4 * j + 2], acc[8 * j + 4], acc[8 * j + 5]), fin(hf[4 * j + 3], acc[8 * j + 6], acc[8 * j + 7]));
        __syncwarp();
        if (DEFO && t == 3) mbar_arrive(sb + BAR_M, (a_g & 62) == 0);
        else {
          uint32_t v[16];
#pragma unroll
          for (int j = 0; j < 4; j++) lds128(v + 4 * j, sb + OFF_H + (nr[j] ^ ((nr[j] >> 3) & 0x70)));
#pragma unroll
          for (int j = 0; j < 4; j++) asm volatile("{.reg .pred p; setp.lt.u32 p, %5, %6; @p st.global" OCS ".v4.b32 [%0], {%1,%2,%3,%4};}" :: "l"(outh + nr[j]), "r"(v[4 * j]), "r"(v[4 * j + 1]), "r"(v[4 * j + 2]), "r"(v[4 * j + 3]), "r"(nr[j]), "r"(nl * 128) : "memory");
          if (DEFO) break;
        }
        wload();
      }
#pragma unroll
      for (int j = 0; j < 8; j++) { sp[j] = sum[j]; asm volatile("mov.b32 %0, 0;" : "=r"(sum[j])); }
    }
    asm volatile("{.reg .pred p, q; setp.neu.f32 p, %1, 0f00000000; setp.ne.or.u32 p, %2, 0, p; bar.red.or.pred q, 5, %3, p; selp.u32 %0, 1, 0, q;}" : "=r"(bad) : "f"(chk), "r"(lds32(sb + OFF_MISC + 12)), "n"(DEFO ? 512 : 384) : "memory");
    STAMP(11);
   } else { asm volatile("cp.async.wait_all;" ::: "memory"); bar_sync(5, 384); }
  }
  if (bad) slow_path(p, wid, lane, node0, nloc);
}

}

typedef CUresult (*EncodeFn)(CUtensorMap*, CUtensorMapDataType, cuuint32_t, void*, const cuuint64_t*, const cuuint64_t*, const cuuint32_t*, const cuuint32_t*,
                             CUtensorMapInterleave, CUtensorMapSwizzle, CUtensorMapL2promotion, CUtensorMapFloatOOBfill);

extern "C" void kernel_launch(void* const* d_in, const int* in_sizes, int n_in, void* d_out, int out_size) {
  Params p; Maps maps;
  p.h = (const uint4*)d_in[0]; p.pos = (const uint16_t*)d_in[1]; p.ea = (const uint4*)d_in[2];
  p.src = (const int*)d_in[3]; p.dst = (const int*)d_in[4];
  p.we = (const uint16_t*)d_in[5]; p.wx = (const uint16_t*)d_in[6]; p.wh = (const uint16_t*)d_in[7];
  p.out = (uint16_t*)d_out;
  p.N = in_sizes[0] / 64; p.E = in_sizes[3];
  p.EPC = ((p.E + G * 4 - 1) / (G * 4)) * 4;
  p.magic = (uint32_t)(((uint64_t)G << 24) / (uint64_t)p.N);
  p.inv = (1ull << 56) / p.magic;
  const uint64_t ea0 = (uint64_t)d_in[2], ea1 = ea0 + (uint64_t)p.E * 32 - 1;
  p.force_slow = ((ea0 >> 32) != (ea1 >> 32)) || (ea0 & 31) || (p.E & 3);
  void* qp = nullptr;
  cudaGetSymbolAddress(&qp, g_q);
  p.q = (char*)qp;
  if (((uint64_t)p.q >> 32) != (((uint64_t)p.q + QBYTES) >> 32)) p.q += QBYTES;
  cudaGetSymbolAddress((void**)&p.sync, g_sync); cudaGetSymbolAddress((void**)&p.xe, g_xe);
  cudaGetSymbolAddress((void**)&p.xa, g_xa); cudaGetSymbolAddress((void**)&p.xb, g_xb);
  void* fn = nullptr; cudaDriverEntryPointQueryResult qr;
  cudaGetDriverEntryPoint("cuTensorMapEncodeTiled", &fn, cudaEnableDefault, &qr);
  auto mk = [&](CUtensorMap* tm, void* base, int rows, int box = 64) {
    const cuuint64_t dim[2] = {64, (cuuint64_t)rows}, str[1] = {128}; const cuuint32_t bx[2] = {64, (cuuint32_t)box}, es[2] = {1, 1};
    ((EncodeFn)fn)(tm, CU_TENSOR_MAP_DATA_TYPE_BFLOAT16, 2, base, dim, str, bx, es, CU_TENSOR_MAP_INTERLEAVE_NONE, CU_TENSOR_MAP_SWIZZLE_128B,
                   CU_TENSOR_MAP_L2_PROMOTION_NONE, CU_TENSOR_MAP_FLOAT_OOB_FILL_NONE);
  };
  mk(&maps.m[TM_H / 128], d_in[0], p.N); mk(&maps.m[TM_WE / 128], d_in[5], 145); mk(&maps.m[TM_WH / 128], d_in[7], 128); mk(&maps.m[TM_Q / 128], p.q, p.N, 16);
  for (int k = 0; k < 2; k++) {
    void* xp = (void*)(k ? p.xb : p.xa);
    const cuuint64_t dim[2] = {(cuuint64_t)G * 64, (cuuint64_t)G}, str[1] = {(cuuint64_t)G * (128 << k)}; const cuuint32_t bx[2] = {64, (cuuint32_t)(k ? BROWS : G)}, es[2] = {1, 1};
    ((EncodeFn)fn)(&maps.m[TM_XA / 128 + k], k ? CU_TENSOR_MAP_DATA_TYPE_UINT32 : CU_TENSOR_MAP_DATA_TYPE_UINT16, 2, xp, dim, str, bx, es, CU_TENSOR_MAP_INTERLEAVE_NONE,
                   CU_TENSOR_MAP_SWIZZLE_NONE, CU_TENSOR_MAP_L2_PROMOTION_NONE, CU_TENSOR_MAP_FLOAT_OOB_FILL_NONE);
  }
  cudaFuncSetAttribute(egnn_kernel, cudaFuncAttributeMaxDynamicSharedMemorySize, SMEM);
  egnn_kernel<<<G, NTHR, SMEM>>>(p, maps);
}
```

```cpp
#include <cuda_runtime.h>
#include <cuda_bf16.h>
#include <cuda_fp16.h>
#include <cuda.h>
#include <stdint.h>
#pragma nv_diag_suppress 549

#define PFN 16
#define PFNS 250
#define FM 0
#define OPQ 0
#define H0 0
#define HALL 1
#define PF0NS 0
#define PFW 0
#define QCODE 0x254a109b7863ull
#define QREV 0x605
#define PFS 1
#define ESZ ""
#define XEF 0
#define OCS ""
#define RNB 2
#define NEARLY 2
#define PFE 0
#define DEFO 1
#define DEFNS 400
#define ABL 0
#define IDL 1
#define FIN 1
#define HW 3
#define BROWS 132
#define B_HOLD 1
#define LSEQ 0x231200ull
#define HE 0
namespace {

constexpr int G = 132;
constexpr int NTHR = 512, NWK = 352, NCH = 5;
constexpr int NST = 3, STG = 2560;
constexpr int SCAP = 448;

constexpr int OFF_H = 0;
constexpr int OFF_W = 49152;
constexpr int OFF_WD = OFF_W + 16384;
constexpr int OFF_W3 = OFF_WD + 1024;
constexpr int OFF_P2 = OFF_W3 + 2048;
constexpr int OFF_RING = OFF_P2 + 24576;
constexpr int OFF_TE = OFF_RING + 12 * NST * STG;
constexpr int OFF_TS = OFF_TE + SCAP * 64;
constexpr int OFF_GP = OFF_TS + SCAP * 32;
constexpr int OFF_WX = OFF_GP + 3072;
constexpr int OFF_LEN = OFF_WX + 128;
constexpr int OFF_MISC = OFF_LEN + 128;
constexpr int OFF_BAR = OFF_MISC + 48;
constexpr int SMEM = OFF_BAR + 256;
static_assert(SMEM <= 232448, "smem");
constexpr uint32_t sb = 1024;
constexpr int OFF_SRCI = OFF_TE;
constexpr int OFF_SB = OFF_RING, OFF_SA = OFF_SB + 34816, OFF_AX = OFF_SA + 32768, OFF_DST = OFF_H + 24576;
constexpr int OFF_WS = OFF_AX + 17408;
constexpr int OFF_BC = OFF_WS + 2304;
constexpr int OFF_CNT = OFF_P2;
constexpr int OFF_DH = OFF_CNT + 2176;
constexpr int OFF_POS = OFF_DH + 128;
constexpr int OFF_EXT = OFF_POS + 3072;
constexpr int OFF_XB = OFF_EXT + 1024, XPAD = G * 256;
static_assert(OFF_XB + XPAD + 1028 <= OFF_RING + 12 * STG && OFF_XB % 128 == 0 && OFF_BC + 544 <= OFF_TE && OFF_P2 % 1024 == 0 && OFF_SA % 1024 == 0 && SCAP * 64 >= 24576, "staging");
constexpr int BAR_DST = OFF_BAR, BAR_SRC = BAR_DST + 40, BAR_T = BAR_SRC + 24, BAR_W = BAR_T + 48, BAR_XA = BAR_W + 8, BAR_PS = BAR_XA + 8, BAR_AW = BAR_PS + 8,
              BAR_QP = BAR_AW + 8, BAR_QR = BAR_QP + 8, BAR_HA = BAR_QR + 8, BAR_EP = BAR_HA + 8, BAR_AX = BAR_EP + 8, BAR_AI = BAR_AX + 8, BAR_HB = BAR_AI + 8, BAR_U = BAR_HB + 8, BAR_WH = BAR_U + 8, BAR_M = BAR_WH + 8, BAR_X = BAR_M + 8, BAR_END = BAR_X + 8;
static_assert(BAR_END <= OFF_BAR + 256, "barriers");
constexpr uint32_t QBYTES = 8u << 20;

__device__ __align__(256) uint4 g_xa[G * G * 8];
__device__ __align__(256) uint4 g_xb[G * G * 16];
__device__ __align__(256) uint2 g_xe[G * G * 32];
__device__ __align__(256) uint4 g_q[2 * QBYTES / 16];
__device__ __align__(256) uint32_t g_sync[8];
#define STAMP(k)

struct Maps { CUtensorMap m[6]; };
constexpr int TM_H = 0, TM_WE = 128, TM_WH = 256, TM_Q = 384, TM_XA = 512, TM_XB = 640;
struct Params {
  const int* dst; uint32_t* sync; int E, EPC, N; uint32_t magic; unsigned long long inv;
  const int* src; const uint16_t* pos; const uint4* ea; const uint16_t* we; const uint16_t* wx; char* q; int force_slow;
  const uint4* xa; const uint4* xb; uint2* xe; uint16_t* out; const uint4* h; const uint16_t* wh;
};
template<int V> struct IC { static constexpr int value = V; };

#define R32(d) "+f"(d[0]),"+f"(d[1]),"+f"(d[2]),"+f"(d[3]),"+f"(d[4]),"+f"(d[5]),"+f"(d[6]),"+f"(d[7]),"+f"(d[8]),"+f"(d[9]),"+f"(d[10]),"+f"(d[11]),"+f"(d[12]),"+f"(d[13]),"+f"(d[14]),"+f"(d[15]),"+f"(d[16]),"+f"(d[17]),"+f"(d[18]),"+f"(d[19]),"+f"(d[20]),"+f"(d[21]),"+f"(d[22]),"+f"(d[23]),"+f"(d[24]),"+f"(d[25]),"+f"(d[26]),"+f"(d[27]),"+f"(d[28]),"+f"(d[29]),"+f"(d[30]),"+f"(d[31])
#define S32 "{%0,%1,%2,%3,%4,%5,%6,%7,%8,%9,%10,%11,%12,%13,%14,%15,%16,%17,%18,%19,%20,%21,%22,%23,%24,%25,%26,%27,%28,%29,%30,%31}"
#define DI __device__ __forceinline__

constexpr uint64_t DHI = ((uint64_t)(1024 >> 4) << 32) | (1ull << 62);
template<int SD> DI void rs64b(float (&d)[32], uint32_t a0, uint32_t a1, uint32_t a2, uint32_t a3, uint64_t db) {
  asm volatile("wgmma.mma_async.sync.aligned.m64n64k16.f32.bf16.bf16 " S32 ", {%32,%33,%34,%35}, %36, %37, 1, 1, 1;" : R32(d) : "r"(a0), "r"(a1), "r"(a2), "r"(a3), "l"(db), "n"(SD)); }
template<int SD> DI void rs64h(float (&d)[32], uint32_t a0, uint32_t a1, uint32_t a2, uint32_t a3, uint64_t db) {
  asm volatile("wgmma.mma_async.sync.aligned.m64n64k16.f32.f16.f16 " S32 ", {%32,%33,%34,%35}, %36, %37, 1, 1, 1;" : R32(d) : "r"(a0), "r"(a1), "r"(a2), "r"(a3), "l"(db), "n"(SD)); }
template<int SD> DI void ss64(float (&d)[32], uint64_t da, uint64_t db) {
  asm volatile("wgmma.mma_async.sync.aligned.m64n64k16.f32.bf16.bf16 " S32 ", %32, %33, %34, 1, 1, 0, 1;" : R32(d) : "l"(da), "l"(db), "n"(SD)); }
DI void trap_if(bool c) { asm volatile("{.reg .pred p; setp.eq.u32 p, %0, 0; @p bra.uni LT_%=; trap; LT_%=:}" :: "r"((uint32_t)c)); }
DI void wg_fence() { asm volatile("wgmma.fence.sync.aligned;" ::: "memory"); }
DI void wg_commit() { asm volatile("wgmma.commit_group.sync.aligned;" ::: "memory"); }
DI void wg_wait0() { asm volatile("wgmma.wait_group.sync.aligned 0;" ::: "memory"); }
DI void fence_regs(float (&d)[32]) { asm volatile("" : R32(d) :: "memory"); }
DI void proxy_fence() { asm volatile("fence.proxy.async.shared::cta;" ::: "memory"); }
DI uint64_t pol_first() { uint64_t r; asm("createpolicy.fractional.L2::evict_first.b64 %0, 1.0;" : "=l"(r)); return r; }
DI float tanh_ap(float x) { float y; asm("tanh.approx.f32 %0, %1;" : "=f"(y) : "f"(x)); return y; }
DI float silu_h(float y) { return fmaf(y, tanh_ap(y), y); }
DI uint32_t pack_bf16(float lo, float hi) { uint32_t r; asm("cvt.rn.bf16x2.f32 %0, %1, %2;" : "=r"(r) : "f"(hi), "f"(lo)); return r; }
DI uint32_t pack_f16(float lo, float hi) { uint32_t r; asm("cvt.rn.f16x2.f32 %0, %1, %2;" : "=r"(r) : "f"(hi), "f"(lo)); return r; }
DI float bf_lo(uint32_t v) { return __uint_as_float(v << 16); }
DI float bf_hi(uint32_t v) { return __uint_as_float(v & 0xFFFF0000u); }
DI uint32_t b2h(uint32_t v, float s) { return pack_f16(s * bf_lo(v), s * bf_hi(v)); }
DI void mbar_wait(uint32_t bar, uint32_t parity = 0) {
  asm volatile("{.reg .pred p, q; .reg .u32 c; mov.u32 c, 0;\n"
    "LW_%=: mbarrier.try_wait.parity.shared::cta.b64 p, [%0], %1;\n add.u32 c, c, 1; setp.lt.and.u32 q, c, 0x200000, !p;\n @q bra.uni LW_%=;}" :: "r"(bar), "r"(parity) : "memory");
}
DI void mbar_arrive(uint32_t bar, int p = 1) { asm volatile("{.reg .pred p; setp.ne.b32 p, %1, 0; @p mbarrier.arrive.shared::cta.b64 _, [%0];}" :: "r"(bar), "r"(p) : "memory"); }
DI void bar_sync(int id, int n) { asm volatile("bar.sync %0, %1;" :: "r"(id), "r"(n) : "memory"); }
DI void bar_arrive(int id, int n) { asm volatile("bar.arrive %0, %1;" :: "r"(id), "r"(n) : "memory"); }
DI __nv_bfloat162 b2(uint32_t v) { return *(__nv_bfloat162*)&v; }
DI uint32_t u2(__nv_bfloat162 v) { return *(uint32_t*)&v; }
DI uint32_t hsq(uint32_t v) { return u2(__hmul2(b2(v), b2(v))); }
DI uint32_t hsub(uint32_t a, uint32_t b) { return u2(__hsub2(b2(a), b2(b))); }
DI uint32_t hhalf(uint32_t v) { return u2(__hmul2(b2(v), __floats2bfloat162_rn(0.5f, 0.5f))); }
DI uint32_t mag2(uint32_t m, uint32_t v) { return __vmaxu2(m, v & 0x7FFF7FFFu); }
DI uint32_t hmag(uint32_t m, uint32_t v) { const __half2 r = __hmax2(*(const __half2*)&m, __habs2(*(const __half2*)&v)); return *(const uint32_t*)&r; }
DI uint32_t magr(uint32_t m) { return max(m & 0xFFFF, m >> 16); }
DI void sts128(uint32_t a, uint32_t x, uint32_t y, uint32_t z, uint32_t w) { asm volatile("st.shared.v4.u32 [%0], {%1,%2,%3,%4};" :: "r"(a), "r"(x), "r"(y), "r"(z), "r"(w) : "memory"); }
DI void sts64(uint32_t a, uint32_t x, uint32_t y) { asm volatile("st.shared.v2.u32 [%0], {%1,%2};" :: "r"(a), "r"(x), "r"(y) : "memory"); }
DI void sts32(uint32_t a, uint32_t x) { asm volatile("st.shared.u32 [%0], %1;" :: "r"(a), "r"(x) : "memory"); }
DI void sts16(uint32_t a, uint32_t x) { asm volatile("st.shared.u16 [%0], %1;" :: "r"(a), "h"((uint16_t)x) : "memory"); }
DI void lds128(uint32_t* v, uint32_t a) { asm volatile("ld.shared.v4.u32 {%0, %1, %2, %3}, [%4];" : "=r"(v[0]), "=r"(v[1]), "=r"(v[2]), "=r"(v[3]) : "r"(a) : "memory"); }
DI void lds64(uint32_t& x, uint32_t& y, uint32_t a) { asm volatile("ld.shared.v2.u32 {%0, %1}, [%2];" : "=r"(x), "=r"(y) : "r"(a) : "memory"); }
DI uint32_t lds32(uint32_t a) { uint32_t x; asm volatile("ld.shared.u32 %0, [%1];" : "=r"(x) : "r"(a) : "memory"); return x; }
DI uint32_t lds16(uint32_t a) { uint32_t x; asm volatile("ld.shared.u16 %0, [%1];" : "=r"(x) : "r"(a) : "memory"); return x; }
DI uint32_t atoms_add(uint32_t a, uint32_t v) { uint32_t r; asm volatile("atom.shared.add.u32 %0, [%1], %2;" : "=r"(r) : "r"(a), "r"(v) : "memory"); return r; }
DI void bulk_load(uint32_t dst, const void* src, uint32_t bytes, uint32_t bar) {
  asm volatile("cp.async.bulk.shared::cluster.global.mbarrier::complete_tx::bytes.L2::cache_hint [%0], [%1], %2, [%3], %4;" :: "r"(dst), "l"(src), "r"(bytes), "r"(bar), "l"(pol_first()) : "memory"); }
DI void bulk_store(void* dst, uint32_t src, uint32_t bytes) { asm volatile("cp.async.bulk.global.shared::cta.bulk_group [%0], [%1], %2;" :: "l"(dst), "r"(src), "r"(bytes) : "memory"); }
DI void mbar_expect(uint32_t bar, uint32_t bytes) { asm volatile("mbarrier.arrive.expect_tx.shared::cta.b64 _, [%0], %1;" :: "r"(bar), "r"(bytes) : "memory"); }
DI void mbar_init(uint32_t bar, int n) { asm volatile("mbarrier.init.shared::cta.b64 [%0], %1;" :: "r"(bar), "r"(n) : "memory"); }
DI void tma_load(uint32_t dst, uint64_t tm, int row, uint32_t bar) {
  asm volatile("cp.async.bulk.tensor.2d.shared::cluster.global.mbarrier::complete_tx::bytes.L2::cache_hint [%0], [%1, {%3, %4}], [%2], %5;" :: "r"(dst), "l"(tm), "r"(bar), "r"(0), "r"(row), "l"(pol_first()) : "memory"); }
DI void tma_store(uint64_t tm, int col, int row, uint32_t src) {
  asm volatile("cp.async.bulk.tensor.2d.global.shared::cta.bulk_group [%0, {%2, %3}], [%1];" :: "l"(tm), "r"(src), "r"(col), "r"(row) : "memory"); }
DI void tma_store_ef(uint64_t tm, int col, int row, uint32_t src) {
  if (XEF) asm volatile("cp.async.bulk.tensor.2d.global.shared::cta.bulk_group.L2::cache_hint [%0, {%2, %3}], [%1], %4;" :: "l"(tm), "r"(src), "r"(col), "r"(row), "l"(pol_first()) : "memory");
  else tma_store(tm, col, row, src); }
DI void bulk_commit() { asm volatile("cp.async.bulk.commit_group;" ::: "memory"); }
DI void bulk_wait_read() { asm volatile("cp.async.bulk.wait_group.read 0;" ::: "memory"); }
DI uint2 ld_poll2(const void* a) { uint2 v; asm volatile("ld.relaxed.gpu.global.v2.u32 {%0, %1}, [%2];" : "=r"(v.x), "=r"(v.y) : "l"(a) : "memory"); return v; }
DI void st_ext(uint2* a, uint32_t v, uint32_t ep) { asm volatile("st.relaxed.gpu.global.v2.u32 [%0], {%1, %2};" :: "l"(a), "r"(v), "r"(ep) : "memory"); }
DI uint32_t ext_get(const uint2* a, uint32_t ep) { uint2 v; int spin = 0; do { v = ld_poll2(a); trap_if(++spin > 4000000); } while (__any_sync(~0u, v.y != ep)); return v.x; }
DI void bulk_wait() { asm volatile("cp.async.bulk.wait_group 0;" ::: "memory"); }
DI void hint_signal(uint32_t* c) { asm volatile("red.relaxed.gpu.global.add.u32 [%0], 1;" :: "l"(c) : "memory"); }
DI void hint_wait(const uint32_t* c, uint32_t target) { uint32_t v; int spin = 0;
  do { asm volatile("ld.relaxed.gpu.global.u32 %0, [%1];" : "=r"(v) : "l"(c) : "memory"); trap_if(++spin > 4000000); } while (__any_sync(~0u, (int)(v - target) < 0)); }
DI void stsm4(uint32_t a, uint32_t x, uint32_t y, uint32_t z, uint32_t w) { asm volatile("stmatrix.sync.aligned.m8n8.x4.shared.b16 [%0], {%1,%2,%3,%4};" :: "r"(a), "r"(x), "r"(y), "r"(z), "r"(w) : "memory"); }
DI void ldsm4(uint32_t* v, uint32_t a) { asm volatile("ldmatrix.sync.aligned.m8n8.x4.shared.b16 {%0,%1,%2,%3}, [%4];" : "=r"(v[0]), "=r"(v[1]), "=r"(v[2]), "=r"(v[3]) : "r"(a) : "memory"); }
DI void ldsm4t(uint32_t* v, uint32_t a) { asm volatile("ldmatrix.sync.aligned.m8n8.x4.trans.shared.b16 {%0,%1,%2,%3}, [%4];" : "=r"(v[0]), "=r"(v[1]), "=r"(v[2]), "=r"(v[3]) : "r"(a) : "memory"); }
DI uint32_t mad16(uint32_t x, uint32_t m, uint32_t c) { uint32_t r; asm("dp2a.lo.u32.u32 %0, %1, %2, %3;" : "=r"(r) : "r"(x), "r"(m), "r"(c)); return r; }
DI bool wbad(uint32_t m, uint32_t hi) { return m > hi || (m && m < 0x3980); }

__device__ __noinline__ void slow_path(const Params& p, int wid, int lane, int node0, int nloc) {
  const uint32_t ab = sb + OFF_P2 + wid * 8704;
  for (int i = lane; i < 32 * 68; i += 32) sts32(ab + i * 4, 0);
  __syncwarp();
  const uint32_t wdv = __ldg((const uint32_t*)(p.we + 128 * 64) + lane), wxv = __ldg((const uint32_t*)p.wx + lane);
  const int nb0 = node0 + wid * 32, cntn = max(0, min(32, nloc - wid * 32));
  auto dot = [&](uint32_t hv, const uint16_t* w, int K2, float& y0, float& y1) {
#pragma unroll 4
    for (int k = 0; k < K2; k++) {
      const uint32_t hk = __shfl_sync(~0u, hv, k), wa = __ldg((const uint32_t*)(w + 2 * k * 64) + lane), wb = __ldg((const uint32_t*)(w + (2 * k + 1) * 64) + lane);
      y0 = fmaf(bf_lo(hk), bf_lo(wa), fmaf(bf_hi(hk), bf_lo(wb), y0)); y1 = fmaf(bf_lo(hk), bf_hi(wa), fmaf(bf_hi(hk), bf_hi(wb), y1));
    }
  };
  auto silu = [](float x) { return x / (1.f + __expf(-x)); };
#pragma unroll 1
  for (int base = 0; base < p.E; base += 32) {
    const int e = base + lane;
    const uint32_t dl = e < p.E ? (uint32_t)(__ldg(p.dst + e) - nb0) : 0xFFFFFFFFu;
    uint32_t mk = __ballot_sync(~0u, dl < (uint32_t)cntn);
    while (mk) {
      const int l = __ffs(mk) - 1; mk &= mk - 1;
      const int ee = base + l, n = __shfl_sync(~0u, dl, l), s = __ldg(p.src + ee);
      const uint16_t *po = p.pos + (size_t)(nb0 + n) * 3, *pp = p.pos + (size_t)s * 3;
      const uint32_t dxy = hsub(__ldg(po) | (__ldg(po + 1) << 16), __ldg(pp) | (__ldg(pp + 1) << 16)), dz = hsub(__ldg(po + 2), __ldg(pp + 2));
      const uint32_t sq = hsq(dxy); const float d2 = bf_lo(sq) + bf_hi(sq) + bf_lo(hsq(dz));
      float y0 = d2 * bf_lo(wdv), y1 = d2 * bf_hi(wdv);
      dot(__ldg((const uint32_t*)(p.h + (size_t)(nb0 + n) * 8) + lane), p.we, 32, y0, y1);
      dot(__ldg((const uint32_t*)(p.h + (size_t)s * 8) + lane), p.we + 64 * 64, 32, y0, y1);
      dot(__ldg((const uint32_t*)(p.ea + (size_t)ee * 2) + (lane & 7)), p.we + 129 * 64, 8, y0, y1);
      const uint32_t mm = pack_bf16(silu(y0), silu(y1));
      float c = bf_lo(mm) * bf_lo(wxv) + bf_hi(mm) * bf_hi(wxv);
#pragma unroll
      for (int o = 16; o; o >>= 1) c += __shfl_xor_sync(~0u, c, o);
      const uint32_t a = ab + n * 272;
      uint32_t x0, x1; lds64(x0, x1, a + lane * 8);
      sts64(a + lane * 8, __float_as_uint(__uint_as_float(x0) + bf_lo(mm)), __float_as_uint(__uint_as_float(x1) + bf_hi(mm)));
      if (lane < 3) { const float df = lane == 0 ? bf_lo(dxy) : lane == 1 ? bf_hi(dxy) : bf_lo(dz); sts32(a + 256 + lane * 4, __float_as_uint(fmaf(c, df, __uint_as_float(lds32(a + 256 + lane * 4))))); }
    }
  }
  __syncwarp();
#pragma unroll 1
  for (int n = 0; n < cntn; n++) {
    uint32_t x0, x1; lds64(x0, x1, ab + n * 272 + lane * 8);
    const uint32_t hv = __ldg((const uint32_t*)(p.h + (size_t)(nb0 + n) * 8) + lane);
    float y0 = 0.f, y1 = 0.f;
    dot(hv, p.wh, 32, y0, y1); dot(pack_bf16(__uint_as_float(x0), __uint_as_float(x1)), p.wh + 64 * 64, 32, y0, y1);
    ((uint32_t*)p.out)[(size_t)(nb0 + n) * 32 + lane] = u2(__hadd2(b2(hv), b2(pack_bf16(silu(y0), silu(y1)))));
    if (lane < 3) p.out[(size_t)p.N * 64 + (size_t)(nb0 + n) * 3 + lane] = (uint16_t)pack_bf16(bf_lo(__ldg(p.pos + (size_t)(nb0 + n) * 3 + lane)) + __uint_as_float(lds32(ab + n * 272 + 256 + lane * 4)), 0.f);
  }
}

__global__ void __launch_bounds__(NTHR, 1) egnn_kernel(const __grid_constant__ Params p, const __grid_constant__ Maps maps) {
  const uint64_t tmb = (uint64_t)&maps;
  extern __shared__ __align__(1024) unsigned char smraw[];
  const int tid = threadIdx.x, cta = blockIdx.x;
  const int e0 = cta * p.EPC, n4 = max(0, min(p.EPC, p.E - e0)) >> 2;
  STAMP(0);
  if (tid == NWK) {
#pragma unroll 1
    for (int k = 0; k < NCH; k++) { const int nb = max(0, min(NWK, n4 - k * NWK)) * 16;
      mbar_init(sb + BAR_DST + k * 8, 1);
      asm volatile("fence.mbarrier_init.release.cluster;" ::: "memory");
      mbar_expect(sb + BAR_DST + k * 8, nb);
      if (nb) bulk_load(sb + OFF_DST + k * NWK * 16, (const char*)(p.dst + e0) + k * NWK * 16, nb, sb + BAR_DST + k * 8); }
  }
  const int lane = tid & 31, wid = __shfl_sync(~0u, tid >> 5, 0), w = wid & 3;
  asm volatile("{.reg .pred p; setp.eq.u32 p, %2, 384; @p cp.async.cg.shared.global [%0], [%1], 16;}" :: "r"(sb + OFF_LEN - 192 + (tid >> 1)), "l"(p.sync), "r"(tid & 415) : "memory");

  auto first_node = [&](int c) { return (int)((c * p.inv + 0xFFFFFFFFull) >> 32); };
  const int node0 = first_node(cta), nloc = min(first_node(cta + 1), p.N) - node0;
  const uint32_t ealo = (uint32_t)(uint64_t)p.ea;
  const int epad = min(e0, p.E - 1);
  auto load_h = [&](int b) { mbar_expect(sb + BAR_T + b * 8, 8192); tma_load(sb + OFF_H + b * 8192, tmb + TM_H, node0 + b * 64, sb + BAR_T + b * 8); };
  auto prefetch_e = [&](int i) {
    const uint32_t nb = (p.E / G) & ~15u;
    if (nb && i < PFN) asm volatile("cp.async.bulk.prefetch.L2.global [%0], %1;" :: "l"((const char*)p.ea + (size_t)(((i * PFS + i * PFS / 32 * (~PFS & 1)) & 31) * G + cta) * nb), "r"(nb) : "memory");
  };
  if (wid >= 12) {
    const int t = tid - 384;
    uint32_t pv[9], ev = 0;
#pragma unroll
    for (int i = 0; i < 3; i++) { const uint16_t* pp = p.pos + (size_t)(node0 + t + 128 * i) * 3;
      pv[3 * i] = pv[3 * i + 1] = pv[3 * i + 2] = 0;
      asm volatile("{.reg .pred p; setp.lt.s32 p, %4, %5;\n @p ld.global.nc.u16 %0, [%3];\n @p ld.global.nc.u16 %1, [%3+2];\n @p ld.global.nc.u16 %2, [%3+4];}"
        : "+r"(pv[3 * i]), "+r"(pv[3 * i + 1]), "+r"(pv[3 * i + 2]) : "l"(pp), "r"(t + 128 * i), "r"(p.N - node0)); }
    asm volatile("{.reg .pred p; setp.lt.u32 p, %3, 8; @p ld.global.nc.u32 %0, [%1]; @p st.global.v4.u32 [%2], {%4, %4, %4, %4};}"
      : "+r"(ev) : "l"((const uint32_t*)(p.ea + (size_t)epad * 2) + t), "l"(p.q + (size_t)(p.N + cta) * 128 + t * 16), "r"(t), "r"(0xF700F700u) : "memory");
    asm volatile("cp.async.wait_all;" ::: "memory");
    __syncwarp();
    const uint32_t e = lds32(sb + OFF_LEN + 8 + w * 16) + 1;
    {
      const uint32_t tg = (1 + e % 3) << 30, v = ((tg >> 16) + 512 + (lane & 7) * 4) * 0x10001u;
      if (t == 0) sts32(sb + OFF_MISC + 32, e);
#pragma unroll
      for (int i = 0; i < 9; i++) sts128(sb + OFF_SA + t * 16 + i * 2048, v, v + 0x10001u, v + 0x20002u, v + 0x30003u);
      bar_sync(6, NTHR);
      mbar_arrive(sb + BAR_EP, lane == 0);
#pragma unroll
      for (int i = 0; i < 17; i++) sts128(sb + OFF_SB + t * 16 + i * 2048, tg, tg, tg, tg); }
    uint32_t mp = 0;
#pragma unroll
    for (int i = 0; i < 3; i++) { sts64(sb + OFF_POS + (t + 128 * i) * 8, pv[3 * i] | (pv[3 * i + 1] << 16), pv[3 * i + 2]); mp = mag2(mag2(mp, pv[3 * i] | (pv[3 * i + 1] << 16)), pv[3 * i + 2]); }
    proxy_fence();
    __syncwarp();
    mbar_arrive(sb + BAR_PS, lane == 0);
    mbar_wait(sb + BAR_W);
    {
      uint32_t v[4], u[4]; const int r = t >> 3, c = t & 7;
      lds128(v, sb + OFF_WS + 128 + t * 16); lds128(u, sb + OFF_WS + c * 16);
      const uint32_t x = lds32(sb + OFF_WS + 2176 + lane * 4);
      sts128(sb + OFF_W3 + r * 128 + ((c ^ (r & 7)) << 4), b2h(v[0], .5f), b2h(v[1], .5f), b2h(v[2], .5f), b2h(v[3], .5f));
      const float s = ((r & 1) || r == 6) ? 0.f : .5f;
      if (t < 64) sts128(sb + OFF_WD + r * 128 + ((c ^ r) << 4), b2h(u[0], s), b2h(u[1], s), b2h(u[2], s), b2h(u[3], s));
      if (t < 32) sts32(sb + OFF_WX + (t & 3) * 32 + (t >> 2) * 4, b2h(x, 1.f));
      const uint32_t m3 = __reduce_max_sync(~0u, magr(mag2(mag2(mag2(mag2(0, v[0]), v[1]), v[2]), v[3]))), md = __reduce_max_sync(~0u, magr(mag2(mag2(mag2(mag2(0, u[0]), u[1]), u[2]), u[3])));
      if (wbad(m3, 0x4000) || wbad(md, 0x4000) || wbad(__reduce_max_sync(~0u, magr(mag2(0, x))), 0x4700) || magr(mp) >= 0x4200 || magr(mag2(0, ev)) >= 0x4380) sts32(sb + OFF_MISC + 8, 1);
    }
    if (w == 1) {
#pragma unroll 1
      for (int b = HE; b < HW; b++) { mbar_wait(sb + BAR_SRC + max(0, H0 + b) * 8); if (lane == 0) load_h(b); }
    }
    bar_sync(3, 128);
    const uint32_t frag = (w * 16 + (lane & 15)) * 128 + (((lane >> 4) ^ (lane & 7)) << 4);
    uint32_t mq = 0;
#pragma unroll 1
    for (int b = 0; b < 6; b++) {
      float acc[32];
      const uint64_t da = DHI | (((sb + OFF_H) >> 4) + b * 512), db = DHI | ((sb + OFF_W) >> 4);
      const uint32_t v0 = lds16(sb + OFF_POS + b * 512 + w * 128 + lane * 2), v1 = lds16(sb + OFF_POS + 64 + b * 512 + w * 128 + lane * 2);
      mbar_wait(sb + BAR_T + b * 8);
      if (b == 0) STAMP(25);
      if (b == 5) STAMP(26);
      wg_fence();
      ss64<0>(acc, da, db); ss64<1>(acc, da + 2, db + 128); ss64<1>(acc, da + 4, db + 256); ss64<1>(acc, da + 6, db + 384);
      wg_commit();
      if (b == 0) mbar_wait(sb + BAR_AW);
      if (t == 32) { if (HALL) { if (b == 0) for (int k = HW; k < 6; k++) load_h(k); } else if (b + HW < 6) load_h(b + HW); }
      __syncwarp();
      uint32_t ff[6], fg[6];
#pragma unroll
      for (int j = 0; j < 6; j++) { ff[j] = (__byte_perm((j & 1) ? v1 : v0, 0, 0x4140) >> (3 * (j >> 1))) & 0x00070007u; fg[j] = __vsub2(0x00040004u, ff[j]);
        asm volatile("" : "+r"(ff[j]), "+r"(fg[j])); }
      wg_wait0(); fence_regs(acc);
      uint32_t o[16];
#pragma unroll
      for (int j = 0; j < 16; j++) o[j] = pack_f16(.5f * acc[2 * j], .5f * acc[2 * j + 1]);
#pragma unroll
      for (int j = 0; j < 6; j++) {
        const uint32_t m = o[j] & 0x7FFF7FFFu; mq = __vmaxu2(mq, m);
        o[j] = (__viaddmax_s16x2(m, fg[j], 0) & 0xFFF8FFF8u) | ff[j] | (o[j] & 0x80008000u); }
      if (b == 4) mbar_wait(sb + BAR_AX);
      const uint32_t qs = sb + OFF_SA + b * 8192;
#pragma unroll
      for (int j = 0; j < 4; j++) stsm4((qs + frag) ^ (j << 5), o[4 * j], o[4 * j + 1], o[4 * j + 2], o[4 * j + 3]);
      proxy_fence();
      __syncwarp();
      if (lane == 0 && b * 64 + w * 16 < nloc) tma_store(tmb + TM_Q, 0, node0 + b * 64 + w * 16, qs + w * 2048);
    }
    if (lane == 0) bulk_commit();
    { const uint32_t m = __reduce_max_sync(~0u, magr(mq)); if (lane == 0) sts32(sb + OFF_MISC + 16 + w * 4, m); }
    asm volatile("setmaxnreg.dec.sync.aligned.u32 32;");
    bulk_wait();
    bar_sync(3, 128);
    if (w == 0) {
      STAMP(18);
      uint32_t mv[4]; lds128(mv, sb + OFF_MISC + 16);
      const uint32_t mx = max(max(mv[0], mv[1]), max(mv[2], mv[3]));
      mbar_arrive(sb + BAR_QR, lane == 0);
      STAMP(19);
      if (lane == 0) {
        if (nloc > 0 && (mx >= 0x7BF0 || mx < 0x1400)) asm volatile("st.relaxed.gpu.global.u32 [%0+4], %1;" :: "l"(p.sync), "r"(e) : "memory");
        asm volatile("red.release.gpu.global.add.u32 [%0], 1;" :: "l"(p.sync) : "memory");
      }
      __syncwarp();
      uint32_t c, f; int spin = 0;
      do { asm volatile("ld.acquire.gpu.global.v2.u32 {%0, %1}, [%2];" : "=r"(c), "=r"(f) : "l"(p.sync) : "memory"); trap_if(++spin > 4000000); } while (__any_sync(~0u, (int)(c - e * G) < 0));
      if (f == e) sts32(sb + OFF_MISC + 8, 1);
      if (cta == 0 && lane == 0) asm volatile("st.relaxed.gpu.global.u32 [%0+8], %1;" :: "l"(p.sync), "r"(e) : "memory");
      STAMP(20);
      __syncwarp();
      mbar_arrive(sb + BAR_QP, lane == 0);
    }
    if (w == 2) {
      const uint32_t tg = (1 + e % 3) << 30;
      hint_wait(p.sync + 5, e * G);
      if (lane == 0) { mbar_expect(sb + BAR_HB, XPAD);
#pragma unroll 1
        for (int o = 0; o < 4; o++) bulk_load(sb + OFF_XB + o * (G * 64), (const char*)p.xb + (size_t)(cta * 4 + o) * (G * 64), G * 64, sb + BAR_HB); }
      STAMP(21);
      bar_sync(7, 384);
      sts32(sb + OFF_XB + XPAD, tg + p.N + cta);
      const uint32_t nx = __shfl_sync(~0u, lds32(sb + OFF_MISC + 8) ? 0 : lds32(sb + OFF_MISC + 4), 0);
#pragma unroll 1
      for (uint32_t k = 0; k < nx; k += 32) {
        const uint32_t i = min(k + lane, nx - 1), xr = lds32(sb + OFF_EXT + i * 4), row = (xr >> 9) & 255;
        const uint32_t v = ext_get(p.xe + (cta * G + row) * 32 + ((xr >> 17) & 31), e), x = lds32(sb + OFF_CNT + (xr & 511) * 4) + (xr >> 22) * 16;
        sts32(sb + OFF_XB + XPAD + 4 + i * 4, v); sts16(sb + OFF_TS + x, XPAD + 4 + i * 4);
        sts32(sb + OFF_TE + x * 2, mad16(v, 0x2000u, ealo - (tg >> 11) + row * p.EPC * 32));
      }
      __syncwarp();
      mbar_arrive(sb + BAR_HB, lane == 0);
    }
    if (w == 1) {
      if (PFW) mbar_wait(sb + PFW);
      __nanosleep(PF0NS);
#pragma unroll 1
      for (int i = PFE; i < PFN; i++) { if (lane == 0) prefetch_e(i); __nanosleep(PFNS); }
    }
    if (w == 3) {
      if (lane == 0) { mbar_expect(sb + BAR_U, 16384); tma_load(sb + OFF_W, tmb + TM_WH, 0, sb + BAR_U); }
      __syncwarp();
      bar_sync(4, 416);
      if (lane == 0) tma_load(sb + OFF_W + 8192, tmb + TM_WH, 64, sb + BAR_U);
    }
    bar_sync(3, 128);
    mbar_wait(sb + BAR_U);
    uint32_t mh = 0;
#pragma unroll 1
    for (int i = t; i < 512; i += 128) { uint32_t v[4]; const uint32_t a = sb + OFF_W + i * 16;
      lds128(v, a); sts128(a, hhalf(v[0]), hhalf(v[1]), hhalf(v[2]), hhalf(v[3]));
      lds128(v, a + 8192); sts128(a + 8192, b2h(v[0], .5f), b2h(v[1], .5f), b2h(v[2], .5f), b2h(v[3], .5f));
      mh = mag2(mag2(mag2(mag2(mh, v[0]), v[1]), v[2]), v[3]); }
    if (wbad(__reduce_max_sync(~0u, magr(mh)), 0x4700)) sts32(sb + OFF_MISC + 12, 1);
    proxy_fence();
    __syncwarp();
    mbar_arrive(sb + BAR_WH, lane == 0);
    if (DEFO) { if (!__shfl_sync(~0u, lds32(sb + OFF_MISC + 8), 0)) {
      mbar_wait(sb + BAR_M);
      __nanosleep(DEFO);
#pragma unroll 1
      for (int i = 0; i < 12; i++) { uint32_t v[4]; const uint32_t n = lds16(sb + OFF_GP + i * 256 + (t >> 3) * 8 + 6);
        lds128(v, sb + OFF_H + n * 128 + (((n ^ t) & 7) << 4));
        if (n < nloc) ((uint4*)p.out)[(size_t)(node0 + n) * 8 + (t & 7)] = make_uint4(v[0], v[1], v[2], v[3]);
        __nanosleep(DEFNS); }
      mbar_wait(sb + BAR_X);
#pragma unroll 1
      for (int i = t; i < 384; i += 128) { uint32_t x, y; lds64(x, y, sb + OFF_GP + i * 8); const uint32_t a = sb + OFF_P2 + (y >> 16) * 6; sts16(a, x); sts16(a + 2, x >> 16); sts16(a + 4, y); }
      bar_sync(3, 128);
#pragma unroll 3
      for (int i = t; i < nloc * 3; i += 128) p.out[(size_t)p.N * 64 + node0 * 3 + i] = lds16(sb + OFF_P2 + i * 2);
      asm volatile("{.reg .pred p, q; setp.ne.u32 p, 0, 0; bar.red.or.pred q, 5, 512, p;}" ::: "memory"); } }
    return;
  }

  if (tid == 320) {
    mbar_init(sb + BAR_W, 1);
    asm volatile("fence.mbarrier_init.release.cluster;" ::: "memory");
    mbar_expect(sb + BAR_W, 2 * 8192 + 2304);
    tma_load(sb + OFF_W, tmb + TM_WE, 64, sb + BAR_W); tma_load(sb + OFF_W + 8192, tmb + TM_WE, 0, sb + BAR_W);
    bulk_load(sb + OFF_WS, p.we + 128 * 64, 2176, sb + BAR_W); bulk_load(sb + OFF_WS + 2176, p.wx, 128, sb + BAR_W);
  }
  if (tid == 288) {
#pragma unroll
    for (int a = BAR_SRC; a < BAR_END; a += 8) if (a != BAR_W) mbar_init(sb + a, a == BAR_WH || a == BAR_PS || a == BAR_EP ? 4 : a == BAR_XA ? 11 : a == BAR_HB ? 2 : a >= BAR_M ? 12 : 1);
    asm volatile("fence.mbarrier_init.release.cluster;" ::: "memory");
    asm volatile("prefetch.tensormap [%0];" :: "l"(tmb + TM_XA)); asm volatile("prefetch.tensormap [%0];" :: "l"(tmb + TM_H));
    asm volatile("prefetch.tensormap [%0];" :: "l"(tmb + TM_XB)); asm volatile("prefetch.tensormap [%0];" :: "l"(tmb + TM_Q));
  }
  {
    if (tid < 144) { const uint32_t z = (tid >> 3) == 16 ? 0x8000u : 0u; sts128(sb + OFF_CNT + tid * 16, z, z, z, z); }
    else if (tid <= 144 + G) sts32(sb + OFF_BC + (tid - 144) * 4, ((tid - 144) & 31) * 4);
    const uint32_t sp = XPAD * 0x10001u, em = first_node(G);
    if (wid < 7) {
#pragma unroll
      for (int i = 0; i < 4; i++) sts128(sb + OFF_TS + tid * 16 + i * 3584, sp, sp, sp, sp);
    }
    static_assert(SCAP * 32 == 4 * 3584, "fill");
#pragma unroll 1
    for (int i = n4 + tid; i < 1536; i += 384) sts128(sb + OFF_DST + i * 16, em, em, em, em);
    if (tid == 321) sts128(sb + OFF_MISC, 0, 0, p.force_slow, 0);
  }
  bar_arrive(6, NTHR);
  bar_sync(0, 384);
  uint32_t ep, tag, eb0, pk[12], r0[12], r1[12], cb;
  uint2 vb[12];
  auto get_tag = [&]() { mbar_wait(sb + BAR_EP); ep = lds32(sb + OFF_MISC + 32); tag = (1 + ep % 3) << 30; eb0 = ealo - (tag >> 11); };
  if (wid == 11) {
    trap_if(sb != (uint32_t)__cvta_generic_to_shared(smraw));
#pragma unroll 1
    for (unsigned long long q = LSEQ; q; q >>= 8) { const int k = (q >> 4) & 7, nb = max(0, min(8192, n4 * 16 - k * 8192));
      if (!(q & 8)) mbar_wait(sb + BAR_DST + ((uint32_t)q & 7) * 8);
      if (lane == 0) {
        if (k >= 3) load_h(k - 3);
        else { mbar_expect(sb + BAR_SRC + k * 8, nb);
          if (nb) bulk_load(sb + OFF_SRCI + k * 8192, (const char*)(p.src + e0) + k * 8192, nb, sb + BAR_SRC + k * 8); } } }
    get_tag();
    mbar_wait(sb + BAR_PS);
    bar_sync(12, 384);
    uint32_t xm = 0;
#pragma unroll
    for (int k = 0; k < 5; k++) xm |= (lds32(sb + OFF_BC + min(lane + 32 * k, G - 1) * 4) >= (65 << 9) && lane + 32 * k < G) << k;
    auto ext_send = [&](int pl) {
      uint32_t x = xm;
      for (uint32_t m; (m = __ballot_sync(~0u, x));) {
        const uint32_t l = __ffs(m) - 1, j = l + 32 * (__ffs(__shfl_sync(~0u, x, l)) - 1);
        if (lane == l) x &= x - 1;
        const uint32_t e = min(lds16(sb + OFF_AX + j * 128 + ((4 * l + 2 * lane) & 126)), 6143u);
        if (pl) st_ext(p.xe + (j * G + cta) * 32 + lane, lds32(sb + OFF_SRCI + e * 4) + tag + (e << 16), ep);
        else { const uint32_t cn = lds32(sb + OFF_BC + j * 4) >> 9, v = cn > 96 ? 1 : lane + 64 < cn ? 512 | (lds32(sb + OFF_DST + e * 4) & 511) : 0;
          asm volatile("red.shared.xor.b32 [%0], %1;" :: "r"(sb + OFF_SA + j * 128 + ((l + lane) & 31) * 4), "r"(((v & 63) << 10) | ((v >> 6) << 26)) : "memory"); }
      }
    };
    if (__any_sync(~0u, xm)) { ext_send(0); proxy_fence(); __syncwarp(); }
    if (lane == 0) { tma_store_ef(tmb + TM_XA, cta * 64, 0, sb + OFF_SA); bulk_commit(); mbar_arrive(sb + BAR_AI); bulk_wait(); hint_signal(p.sync + 4); mbar_arrive(sb + BAR_AW); STAMP(16); }
    __syncwarp();
    bar_sync(13, 384);
    if (!B_HOLD && lane == 0) { tma_store_ef(tmb + TM_XB, cta * 64, 0, sb + OFF_SB); bulk_commit(); }
    __syncwarp();
    ext_send(1);
    mbar_arrive(sb + BAR_AX, lane == 0);
    if (B_HOLD) mbar_wait(sb + (B_HOLD == 1 ? BAR_HA : BAR_XA));
    if (lane == 0) {
      bulk_wait();
#pragma unroll 1
      for (int r = B_HOLD ? 0 : BROWS; r < G; r += BROWS) { tma_store_ef(tmb + TM_XB, cta * 64, r, sb + OFF_SB + r * 256); bulk_commit(); bulk_wait(); }
      hint_signal(p.sync + 5);
#pragma unroll 1
      for (int i = 0; i < PFE; i++) prefetch_e(i);
      STAMP(17);
    }
    __syncwarp();
  } else {
    {
      uint32_t d[4 * NCH], jj[4 * NCH], rr[4 * NCH];
      auto count = [&](int k) {
        mbar_wait(sb + BAR_DST + k * 8);
        lds128(d + 4 * k, sb + OFF_DST + (tid + NWK * k) * 16);
#pragma unroll
        for (int i = 4 * k; i < 4 * k + 4; i++) { jj[i] = d[i] * p.magic; rr[i] = atoms_add(__dp4a(jj[i], 0x04000000u, sb + OFF_BC), 0x202u); }
      };
      auto place = [&](int k) {
#pragma unroll
        for (int i = 4 * k; i < 4 * k + 4; i++) {
          const uint32_t o = __dp4a(jj[i], 0x80000000u, rr[i] & 0x807Eu);
          d[i] = (d[i] & 511) | (tag >> 16);
          asm("{.reg .pred p; setp.ge.u32 p, %1, 0x8000; @p add.u32 %0, %2, %3;}" : "+r"(d[i]) : "r"(o), "r"(tid * 4), "r"(NWK * k * 4 + (i & 3)));
          sts16(sb + OFF_SA + o, d[i]); jj[i] = __viaddmin_u32(o, o, G * 256);
        }
      };
      count(0); STAMP(1); count(1); get_tag(); place(0); count(2); place(1); count(3); place(2);
      if (wid < 4) { count(4); STAMP(15); place(3); place(4); } else place(3);
      proxy_fence();
      bar_arrive(12, 384);
      STAMP(2);
      mbar_wait(sb + BAR_AI);
      mbar_wait(sb + BAR_SRC); mbar_wait(sb + BAR_SRC + 8); mbar_wait(sb + BAR_SRC + 16);
      STAMP(12);
#pragma unroll
      for (int k = 0; k < NCH; k++) lds128(d + 4 * k, sb + OFF_SRCI + (tid + NWK * k) * 16);
      const uint32_t tb = tag + (tid << 18);
#pragma unroll
      for (int i = 0; i < 4 * NCH; i++) if (i < 4 * NCH - 4 || wid < 4) sts32(sb + OFF_SB + jj[i], d[i] + tb + ((NWK * (i >> 2) * 4 + (i & 3)) << 16));
      proxy_fence();
      bar_arrive(13, 384);
      STAMP(3);
    }
    const uint32_t rot = (lane + cta) & 31;
    cb = sb + OFF_CNT - (tag >> 14);
    {
      const uint32_t* xa = (const uint32_t*)(p.xa + (cta * G + wid) * 8) + rot;
      if (wid < 8) { const uint32_t e_ = ealo + epad * 32;
        mbar_wait(sb + BAR_AX);
#pragma unroll
        for (int i = 0; i < 7; i++) sts128(sb + OFF_TE + tid * 16 + i * 4096, e_, e_, e_, e_); }
      static_assert(SCAP * 64 == 7 * 4096, "fill");
      if (wid == 10) { hint_wait(p.sync + 4, ep * G); mbar_arrive(sb + BAR_HA, lane == 0); }
      mbar_wait(sb + BAR_HA);
      STAMP(14);
      const uint32_t tp = tag | (tag >> 16);
      uint32_t st;
#pragma unroll 1
      for (int spin = 0;; spin++) {
        st = 0;
#pragma unroll
        for (int k = 0; k < 12; k++) asm volatile("ld.relaxed.gpu.global.u32 %0, [%1];" : "=r"(pk[k]) : "l"(xa + k * 352) : "memory");
#pragma unroll
        for (int k = 0; k < 12; k++) st |= pk[k] ^ tp;
        st = __reduce_or_sync(~0u, st);
        if (!(st >> 30)) break;
        trap_if(spin > 2000000);
      }
      if (st & 0x3C00FC00u) {
#pragma unroll 1
        for (;;) {
          uint32_t x = 0, row = 0;
#pragma unroll
          for (int k = 0; k < 12; k++) { const uint32_t y = (pk[k] ^ tp) & 0x3C00FC00u; if (!x && y) { x = y; row = wid + 11 * k; pk[k] ^= y; } }
          if (!__any_sync(~0u, x)) break;
          const uint32_t n = ((x >> 10) & 63) | ((x >> 20) & 0x1C0);
          if (x >> 29) {
            const uint32_t r = atoms_add(sb + OFF_CNT + n * 4, 16), idx = atoms_add(sb + OFF_MISC + 4, 1);
            if (idx < 256) sts32(sb + OFF_EXT + idx * 4, n | (row << 9) | (lane << 17) | (min(r >> 4, 255u) << 22));
            else x = 1;
          }
          if (x && !(x >> 29)) sts32(sb + OFF_MISC + 8, 1);
          __syncwarp();
        }
      }
#pragma unroll
      for (int k = 0; k < 12; k++) { r0[k] = mad16(pk[k], 0x0004u, cb); r1[k] = mad16(pk[k], 0x0400u, cb); vb[k].x = atoms_add(r0[k], 16); vb[k].y = atoms_add(r1[k], 16); }
      if (B_HOLD == 2) mbar_arrive(sb + BAR_XA, lane == 0);
    }
    STAMP(4);
    if (wid >= 6) bar_arrive(11, NWK);
    if (wid < 6) {
      uint32_t ca[2], ky[2], dr[2], sq[2], ps[4];
#pragma unroll
      for (int i = 0; i < 2; i++) { ca[i] = sb + OFF_CNT + ((node0 + tid + 192 * i) & 511) * 4; lds64(ps[2 * i], ps[2 * i + 1], sb + OFF_POS + (tid + 192 * i) * 8); ps[2 * i + 1] |= (tid + 192 * i) << 16; }
      bar_sync(11, NWK);
      STAMP(5);
#pragma unroll
      for (int i = 0; i < 2; i++) ky[i] = (lds32(ca[i]) + 16) >> 5;
      if (max(ky[0], ky[1]) > 31) sts32(sb + OFF_MISC + 8, 1);
#pragma unroll
      for (int i = 0; i < 2; i++) { ky[i] = min(ky[i], 31u); dr[i] = atoms_add(sb + OFF_DH + ky[i] * 4, 1); }
      bar_sync(10, 192);
      const uint32_t hv = lds32(sb + OFF_DH + lane * 4);
      uint32_t inc = hv;
#pragma unroll
      for (int o = 1; o < 32; o <<= 1) asm("{.reg .pred p; .reg .b32 y; shfl.sync.down.b32 y|p, %0, %1, 31, -1; @p add.u32 %0, %0, y;}" : "+r"(inc) : "r"(o));
#pragma unroll
      for (int i = 0; i < 2; i++) {
        const uint32_t pos = __shfl_sync(~0u, inc - hv, ky[i]) + dr[i];
        const uint32_t ak = (uint32_t)(QCODE >> ((pos >> 5) * 4)) & 15, l = (pos >> 3) & 3;
        sq[i] = (ak >> 2) * 16 + ((QREV >> (pos >> 5) & 1) ? 3 - l : l) * 4 + (ak & 3);
        dr[i] = pos & 7;
        asm volatile("{.reg .pred p; setp.eq.u32 p, %2, 0; @p st.shared.u8 [%0], %1;}" :: "r"(sb + OFF_LEN + sq[i]), "r"(max(ky[i], 1u)), "r"(dr[i]) : "memory");
        sts64(sb + OFF_GP + sq[i] * 64 + dr[i] * 8, ps[2 * i], ps[2 * i + 1]);
      }
      bar_sync(10, 192);
      const uint32_t ln = lds32(sb + OFF_LEN + min(lane, 11) * 4), tot = __dp4a(ln, 0x01010101u, 0u);
      inc = tot;
#pragma unroll
      for (int o = 1; o < 16; o <<= 1) asm("{.reg .pred p; .reg .b32 y; shfl.sync.up.b32 y|p, %0, %1, 0, -1; @p add.u32 %0, %0, y;}" : "+r"(inc) : "r"(o));
      if (wid == 1) sts32(sb + OFF_CNT + 2048 + lane * 4, 0);
      if (tid < 12) { sts32(sb + OFF_LEN + 64 + tid * 4, inc - tot); if (inc > SCAP) sts32(sb + OFF_MISC + 8, 1); }
#pragma unroll
      for (int i = 0; i < 2; i++) sts32(ca[i], __dp4a(__shfl_sync(~0u, ln, sq[i] >> 2), 0x00010101u >> (24 - 8 * (sq[i] & 3)), __shfl_sync(~0u, inc - tot, sq[i] >> 2)) * 32 + dr[i] * 2);
    }
    bar_arrive(7, 384);
  }
  bar_sync(1, 384);
  STAMP(6);
  if (wid != 11 && !__shfl_sync(~0u, lds32(sb + OFF_MISC + 8), 0)) {
#pragma unroll
    for (int k = 0; k < 12; k++) { r0[k] = lds32(r0[k]); r1[k] = lds32(r1[k]); }
#pragma unroll
    for (int k = 0; k < 12; k++) { r0[k] += vb[k].x; r1[k] += vb[k].y; }
  } else {
#pragma unroll
    for (int k = 0; k < 12; k++) r0[k] = r1[k] = 0x8000;
  }
  auto put_ids = [&]() {
    const uint32_t id = wid * 256 + ((lane + cta) & 31) * 8;
    auto put = [&](uint32_t x, uint32_t v) { asm volatile("{.reg .pred p; setp.lt.u32 p, %0, 0x8000; @p st.shared.u16 [%0+%2], %1;}" :: "r"(x), "h"((uint16_t)v), "n"(sb + OFF_TS) : "memory"); };
#pragma unroll
    for (int k = 0; k < 12; k++) { put(IDL ? pk[k] & 0xFFFF : r0[k], id + k * 2816); put(IDL ? pk[k] >> 16 : r1[k], id + k * 2816 + 4); }
  };
  if (!IDL) put_ids();
  STAMP(7);
  mbar_wait(sb + BAR_QR);
  asm volatile("setmaxnreg.inc.sync.aligned.u32 160;");
  if (IDL) {
#pragma unroll
    for (int k = 0; k < 12; k++) asm volatile("prmt.b32 %0, %1, %2, 0x5410;" : "=r"(pk[k]) : "r"(r0[k]), "r"(r1[k]));
  }
  uint32_t pa[8], sp[8], pq[16]; float chk = 0.f;
  {
    uint32_t hf[32], mp = 0; float a0[32], a1[32];
    const uint32_t an = sb + OFF_GP + wid * 256 + (lane & 15) * 8 + 6, n0 = lds16(an), n1 = lds16(an + 128);
#pragma unroll
    for (int j = 0; j < 8; j++) { const uint32_t nd = j < 4 ? n0 : n1; ldsm4(hf + 4 * j, (sb + OFF_H + nd * 128 + (((nd & 7) << 4) ^ (lane & 16))) ^ ((j & 3) << 5)); }
    const uint64_t db = DHI | ((sb + OFF_W + 8192) >> 4);
    wg_fence();
    rs64b<0>(a0, hf[0], hf[1], hf[2], hf[3], db); rs64b<1>(a0, hf[4], hf[5], hf[6], hf[7], db + 128); rs64b<1>(a0, hf[8], hf[9], hf[10], hf[11], db + 256); rs64b<1>(a0, hf[12], hf[13], hf[14], hf[15], db + 384);
    wg_commit();
    rs64b<0>(a1, hf[16], hf[17], hf[18], hf[19], db); rs64b<1>(a1, hf[20], hf[21], hf[22], hf[23], db + 128); rs64b<1>(a1, hf[24], hf[25], hf[26], hf[27], db + 256); rs64b<1>(a1, hf[28], hf[29], hf[30], hf[31], db + 384);
    wg_commit();
    if (IDL) put_ids();
    asm volatile("wgmma.wait_group.sync.aligned 1;" ::: "memory"); fence_regs(a0);
#pragma unroll
    for (int j = 0; j < 8; j++) { const uint32_t x = pack_f16(.5f * a0[4 * j], .5f * a0[4 * j + 1]), y = pack_f16(.5f * a0[4 * j + 2], .5f * a0[4 * j + 3]); mp = hmag(hmag(mp, x), y);
      asm volatile("movmatrix.sync.aligned.m8n8.trans.b16 %0, %1;" : "=r"(pa[j]) : "r"(x)); asm volatile("movmatrix.sync.aligned.m8n8.trans.b16 %0, %1;" : "=r"(sp[j]) : "r"(y)); }
    wg_wait0(); fence_regs(a1);
    bar_arrive(4, 416);
#pragma unroll
    for (int j = 0; j < 16; j++) { pq[j] = pack_f16(.5f * a1[2 * j], .5f * a1[2 * j + 1]); mp = hmag(mp, pq[j]); }
    if (magr(mp) >= 0x7000) chk = __int_as_float(0x7FC00000);
  }
  if (wid == 0) STAMP(23);
  uint32_t bad;
  {
    const uint32_t ring = sb + OFF_RING + wid * STG, p2 = sb + OFF_P2 + wid * 2048;
    uint32_t lens = __shfl_sync(~0u, lds32(sb + OFF_LEN + wid * 4), 0);
    uint32_t rem = __dp4a(lens, 0x20202020u, 0u);
    const uint32_t base = min(lds32(sb + OFF_LEN + 64 + wid * 4), SCAP);
    uint32_t a_s = sb + OFF_TS + base * 32 + (lane >> 3) * 8, a_e = sb + OFF_TE + base * 64 + (lane >> 1) * 4;
    uint32_t k0 = (uint32_t)(uint64_t)p.q + (((lane & 7) ^ ((lane >> 1) & 4)) << 4), k1 = k0 ^ 16, k2 = k0 ^ 32, k3 = k0 ^ 48, ke = ((lane ^ (lane >> 3)) & 1) << 4;
    uint32_t dst0 = ring + (lane >> 3) * 640 + (lane & 7) * 16;
    const uint32_t qhi = (uint32_t)((uint64_t)p.q >> 32), ehi = (uint32_t)((uint64_t)p.ea >> 32);
    uint32_t s0, s1, ev, to = 0, so = 12 * STG;
    auto tl_ = [&]() { lds64(s0, s1, a_s + to); asm volatile("ld.shared.u32 %0, [%1]; add.u32 %1, %1, 64;" : "=&r"(ev), "+r"(a_e) :: "memory"); to += 32; };
#define CPQ(LH, x, k, off) "dp2a." LH ".u32.u32 lo, " x ", 0x80000080, " k "; mov.b64 a, {lo, %7}; @p cp.async.cg.shared.global [%0+" #off "], [a], 16;\n"
#define CPE "or.b32 lo, %10, %11; mov.b64 a, {lo, %12}; @p cp.async.cg.shared.global" ESZ " [%0+512], [a], 16;\n"
#define CPA(BODY) asm volatile("{.reg .b32 lo; .reg .b64 a; .reg .pred p; setp.le.u32 p, %8, %9;\n" BODY "}" \
      :: "r"(dst0 + so), "r"(s0), "r"(s1), "r"(k0), "r"(k1), "r"(k2), "r"(k3), "r"(qhi), "r"(to), "r"(rem), "r"(ev), "r"(ke), "r"(ehi) : "memory")
#define CPQ4 CPQ("lo", "%1", "%3", 0) CPQ("hi", "%1", "%4", 128) CPQ("lo", "%2", "%5", 256) CPQ("hi", "%2", "%6", 384) "cp.async.commit_group;"
    auto issue = [&]() { CPA(CPE CPQ4); so = so == (NST - 1) * 12 * STG ? 0 : so + 12 * STG; };
    const int g = lane >> 2, qd = lane & 3;
    const uint32_t sw = ((lane >> 4) ^ (lane & 7)) << 4, fr = (lane & 15) * 128 + sw;
    uint32_t qa0 = ring + (g & 3) * 640 + qd * 128 + sw, qa1 = qa0 ^ 32, qa2 = qa0 ^ 64, qa3 = qa0 ^ 96;
    uint32_t eadr = ring + 512 + (g & 3) * 640 + qd * 32 + ((((lane >> 4) ^ g) & 1) << 4);
    uint32_t oh0 = g == 2 * qd ? 0x3C00u : g == 2 * qd + 1 ? 0x3C000000u : 0u, oh1 = oh0;
    uint32_t a_g = sb + OFF_GP + wid * 256 + lane * 2;
    uint32_t a_n = sb + OFF_GP + wid * 256 + (lane & 15) * 8 + 6;
    uint32_t a_p = ((lane & 8) ? p2 : sb + OFF_WD) + (lane & 7) * 128 + ((((lane >> 4) ^ lane) & 7) << 4);
    uint32_t a_w = sb + OFF_W3 + fr;
#define OPQ4(A, B, C, D) asm volatile("shfl.sync.bfly.b32 %0, %0, 0, 31, -1; shfl.sync.bfly.b32 %1, %1, 0, 31, -1; shfl.sync.bfly.b32 %2, %2, 0, 31, -1; shfl.sync.bfly.b32 %3, %3, 0, 31, -1;" : "+r"(A), "+r"(B), "+r"(C), "+r"(D))
    asm volatile("shfl.sync.idx.b32 %0, %0, %1, 31, -1;" : "+r"(oh1) : "r"(lane));
    if (OPQ & 1) OPQ4(a_w, oh0, ke, dst0);
    if (OPQ & 2) OPQ4(qa0, qa1, qa2, qa3);
    if (OPQ & 4) OPQ4(k0, k1, k2, k3);
    if (OPQ & 8) OPQ4(a_g, a_n, a_p, eadr);
    uint32_t w3[16], wv[8], bp[16], sum[8], Y[16], M[16], own, ownp, dpk; uint16_t tl[16], th[16];
    float pacc = 0.f;
    auto wload = [&]() {
#pragma unroll
      for (int j = 0; j < 4; j++) ldsm4t(w3 + 4 * j, a_w ^ (j << 5));
      lds128(wv, sb + OFF_WX + (a_g & 6) * 16); lds128(wv + 4, sb + OFF_WX + 16 + (a_g & 6) * 16);
    };
    auto hload = [&](uint32_t (&hf)[16], uint32_t nd) {
      const uint32_t hrow = sb + OFF_H + nd * 128 + (((nd & 7) << 4) ^ ((a_g >> 1) & 16));
#pragma unroll
      for (int j = 0; j < 4; j++) ldsm4(hf + 4 * j, hrow ^ (j << 5));
      return hrow;
    };
    auto bload = [&](uint32_t o) {
#pragma unroll
      for (int j = 0; j < 4; j++) ldsm4t(bp + 4 * j, (a_p ^ (j << 5)) + o);
    };
    { uint32_t wd[8]; const uint32_t a = sb + OFF_WD + (lane & 7) * 128 + ((((lane >> 3) ^ lane) & 7) << 4);
      ldsm4t(wd, a); ldsm4t(wd + 4, a ^ 64);
#pragma unroll
      for (int j = 0; j < 8; j++) { bp[2 * j] = wd[j]; bp[2 * j + 1] = pa[j]; } }
    own = lds16(a_g) * 0x10001u;
    wload();
    if (__shfl_sync(~0u, lds32(sb + OFF_MISC + 8), 0)) rem = 0;
    auto resolve = [&](auto NBK, uint32_t o) {
      constexpr int NB = decltype(NBK)::value;
      uint32_t id[NB], c0[NB], c1[NB]; const uint32_t a = base * 32 + o + lane * 4;
#pragma unroll
      for (int i = 0; i < NB; i++) { id[i] = lds32(sb + OFF_TS + a + i * 128); if (o + lane * 4 + i * 128 >= rem) id[i] = XPAD * 0x10001u; }
      uint32_t st = 0;
#pragma unroll
      for (int i = 0; i < NB; i++) { c0[i] = lds32(sb + OFF_XB + (id[i] & 0xFFFF)); c1[i] = lds32(sb + OFF_XB + (id[i] >> 16)); }
#pragma unroll
      for (int i = 0; i < NB; i++) st |= (c0[i] ^ tag) | (c1[i] ^ tag);
      for (int spin = 0; __any_sync(~0u, st >> 30); spin++) {
        st = 0; trap_if(spin > 2000000);
#pragma unroll
        for (int i = 0; i < NB; i++) {
          asm volatile("{.reg .pred p, q; setp.lt.u32 p, %4, %6; setp.lt.u32 q, %5, %6; @p ld.relaxed.gpu.global.u32 %0, [%2]; @q ld.relaxed.gpu.global.u32 %1, [%3];}"
            : "+r"(c0[i]), "+r"(c1[i]) : "l"((const char*)p.xb + cta * XPAD + (id[i] & 0xFFFF)), "l"((const char*)p.xb + cta * XPAD + (id[i] >> 16)), "r"(id[i] & 0xFFFF), "r"(id[i] >> 16), "n"(XPAD) : "memory");
          st |= (c0[i] ^ tag) | (c1[i] ^ tag); }
      }
#pragma unroll
      for (int i = 0; i < NB; i++) { const uint32_t j0 = (id[i] >> 8) & 255, j1 = id[i] >> 24;
        if (ABL & 2) { c0[i] &= 0xFFFF0FFFu; c1[i] &= 0xFFFF0FFFu; }
        asm volatile("{.reg .pred p, q, r; setp.lt.u32 p, %5, %9; setp.lt.u32 q, %6, %9; setp.lt.u32 r, %7, %8;\n"
          "@p st.shared.u32 [%0], %2; @q st.shared.u32 [%0+4], %3; @r st.shared.u32 [%1], %4;}"
          :: "r"(sb + OFF_TE + 2 * a + i * 256), "r"(sb + OFF_TS + a + i * 128), "r"(mad16(c0[i], 0x2000u, eb0 + ((ABL & 1) ? j0 & 7 : j0) * p.EPC * 32)), "r"(mad16(c1[i], 0x2000u, eb0 + ((ABL & 1) ? j1 & 7 : j1) * p.EPC * 32)),
             "r"(__byte_perm(c0[i], c1[i], 0x5410)), "r"(j0), "r"(j1), "r"(o + lane * 4 + i * 128), "r"(rem), "n"(G) : "memory"); }
    };
    bar_sync(2, 384);
    if (wid == 0) STAMP(27);
    mbar_wait(sb + BAR_HB);
    if (wid == 0) STAMP(22);
#pragma unroll 1
    for (uint32_t o = 0, go = 0; go < 32 * NST; o += 128 * RNB) {
      if (o < rem) { resolve(IC<RNB>(), o);
        asm volatile("{.reg .pred p; mbarrier.test_wait.parity.shared::cta.b64 p, [%1], 0; vote.sync.all.pred p, p, -1; selp.u32 %0, %2, 0, p;}" : "=r"(go) : "r"(sb + BAR_QP), "n"(32 * NEARLY) : "memory"); }
      else { bar_sync(8, 384); mbar_wait(sb + BAR_QP); go = 32 * NST; if (wid == 0) STAMP(24); }
      __syncwarp();
#pragma unroll 1
      while (to < go) { tl_(); issue(); if (to == 32) STAMP(13); }
    }
    bad = __shfl_sync(~0u, lds32(sb + OFF_MISC + 8), 0);
   if (!bad) {
#pragma unroll
    for (int j = 0; j < 4; j++) stsm4((p2 + fr) ^ (j << 5), pq[4 * j], pq[4 * j + 1], pq[4 * j + 2], pq[4 * j + 3]);
    auto body = [&](auto MODE) {
      constexpr int mode = decltype(MODE)::value;
      uint32_t T[16], ef[4], q0, q1, x0, x1, x2; float e0_, e1_, cs[4];
      auto mu = [&](int j) {
#pragma unroll
        for (int i = 2 * j; i < 2 * j + 2; i++) asm volatile("{.reg .b16 l, h; mov.b32 {l, h}, %2; tanh.approx.f16 %0, l; tanh.approx.f16 %1, h;}" : "=h"(tl[i]), "=h"(th[i]) : "r"(Y[i])); };
      auto fi = [&](int j) {
#pragma unroll
        for (int i = 2 * j; i < 2 * j + 2; i++) asm volatile("{.reg .b32 t; mov.b32 t, {%2, %3}; fma.rn.f16x2 %0, %1, t, %1;}" : "=r"(M[i]) : "r"(Y[i]), "h"(tl[i]), "h"(th[i])); };
      auto ad = [&](int j) { asm volatile("add.rn.f16x2 %0, %0, %1; add.rn.f16x2 %0, %0, %2;" : "+r"(sum[j]) : "r"(M[2 * j]), "r"(M[2 * j + 1])); };
      auto he = [&](int j) { asm volatile("mma.sync.aligned.m16n8k16.row.col.f16.f16.f16.f16 {%0,%1}, {%2,%3,%4,%5}, {%6,%7}, {%0,%1};" : "+r"(T[2 * j]), "+r"(T[2 * j + 1]) : "r"(ef[0]), "r"(ef[1]), "r"(ef[2]), "r"(ef[3]), "r"(w3[2 * j]), "r"(w3[2 * j + 1])); };
      auto hs = [&](int j) { asm volatile("mma.sync.aligned.m16n8k16.row.col.f16.f16.f16.f16 {%0,%1}, {%2,%3,%4,%5}, {%6,%7}, {%8,%9};" : "=r"(Y[2 * j]), "=r"(Y[2 * j + 1]) : "r"(q0), "r"(q1), "r"(oh0), "r"(oh1), "r"(bp[2 * j]), "r"(bp[2 * j + 1]), "r"(T[2 * j]), "r"(T[2 * j + 1])); };
      auto hc = [&](int j) {
        if (j) asm volatile("mma.sync.aligned.m16n8k16.row.col.f32.f16.f16.f32 {%0,%1,%2,%3}, {%4,%5,%6,%7}, {%8,%9}, {%0,%1,%2,%3};" : "+f"(cs[0]), "+f"(cs[1]), "+f"(cs[2]), "+f"(cs[3]) : "r"(M[4 * j]), "r"(M[4 * j + 1]), "r"(M[4 * j + 2]), "r"(M[4 * j + 3]), "r"(wv[2 * j]), "r"(wv[2 * j + 1]));
        else asm volatile("mma.sync.aligned.m16n8k16.row.col.f32.f16.f16.f32 {%0,%1,%2,%3}, {%4,%5,%6,%7}, {%8,%9}, {%10,%10,%10,%10};" : "=f"(cs[0]), "=f"(cs[1]), "=f"(cs[2]), "=f"(cs[3]) : "r"(M[0]), "r"(M[1]), "r"(M[2]), "r"(M[3]), "r"(wv[0]), "r"(wv[1]), "f"(0.f)); };
      auto cv = [&](int i) { asm volatile("{.reg .b32 a, b; shl.b32 a, %0, 16; and.b32 b, %0, 0xFFFF0000; cvt.rn.f16x2.f32 %0, b, a;}" : "+r"(ef[i])); };
      auto un = [&]() { asm volatile("shl.b32 %0, %2, 16; and.b32 %1, %2, 0xFFFF0000;" : "=&f"(e0_), "=&f"(e1_) : "r"(dpk)); };
      auto ex0 = [&]() { asm volatile("prmt.b32 %0, %3, %4, 0x6420; prmt.b32 %1, %5, %6, 0x6420; prmt.b32 %2, %7, %8, 0x6420;" : "=&r"(x0), "=&r"(x1), "=&r"(x2) : "r"(T[0]), "r"(T[1]), "r"(T[2]), "r"(T[3]), "r"(T[4]), "r"(T[5])); };
      auto ex1 = [&]() { asm volatile("{.reg .b32 a, b; shl.b32 a, %2, 3; shl.b32 b, %3, 6; lop3.b32 a, %1, a, 0x38383838, 0xD8; lop3.b32 a, a, b, 0xC0C0C0C0, 0xD8; sub.rn.bf16x2 %0, %4, a;}" : "=r"(dpk) : "r"(x0), "r"(x1), "r"(x2), "r"(own)); };
      auto ex2 = [&]() { asm volatile("{.reg .b32 a, b, d, u; .reg .b16 l, h; shl.b32 a, %2, 16; and.b32 b, %2, 0xFFFF0000; cvt.rn.f16x2.f32 d, b, a; mul.rn.f16x2 %0, d, d; mov.b32 {l, h}, d; mov.b32 u, {h, h}; mul.rn.f16x2 %1, u, u;}" : "=&r"(q0), "=&r"(q1) : "r"(dpk)); };
      auto pf = [&]() { asm volatile("fma.rn.f32 %0, %1, %2, %0; fma.rn.f32 %0, %3, %4, %0;" : "+f"(pacc) : "f"(cs[0]), "f"(e0_), "f"(cs[2]), "f"(e1_)); };
#define FX(k) if (FM >> k & 1) asm volatile("pmevent 1;" ::: "memory")
      if (mode == 2) {
        hc(0); mu(3); fi(2); un(); ad(0); ad(1); mu(4); fi(3); hc(1); mu(5); fi(4); ad(2); mu(6); fi(5); ad(3); hc(2); mu(7); fi(6); fi(7); ad(4); ad(5); hc(3); ad(6); ad(7); pf();
        return;
      }
      asm volatile("cp.async.wait_group %0;" :: "n"(NST - 1) : "memory");
      __syncwarp();
      if (mode == 1) STAMP(8);
      ldsm4(ef, eadr + so); ldsm4(T, qa0 + so); ldsm4(T + 4, qa1 + so); ldsm4(T + 8, qa2 + so); ldsm4(T + 12, qa3 + so);
      tl_();
      if (mode == 1) {
        issue();
        cv(0); cv(1); cv(2); cv(3); ex0(); ex1(); ex2();
#pragma unroll
        for (int j = 0; j < 8; j++) { he(j); hs(j); }
        mu(0); mu(1); fi(0); mu(2); fi(1);
        return;
      }
      hc(0); mu(3); fi(2); un(); ad(0); ad(1);
      FX(0);
      mu(4); fi(3); cv(0); cv(1); cv(2); cv(3); ex0(); ex1();
      FX(1);
      he(0); he(1); hc(1); mu(5); fi(4); ex2(); ad(2);
      FX(2);
      hs(0); he(2); mu(6); fi(5); issue(); ad(3);
      FX(3);
      hs(1); he(3); hc(2); mu(7); fi(6);
      FX(4);
      hs(2); hs(3); he(4); he(5); mu(0); fi(7); ad(4); ad(5);
      FX(5);
      hc(3); hs(4); he(6); he(7); mu(1); fi(0); ad(6);
      FX(6);
      hs(5); hs(6); hs(7); mu(2); fi(1); ad(7); pf();
      FX(7);
    };
#pragma unroll
    for (int j = 0; j < 8; j++) sum[j] = 0;
    body(IC<1>());
    int cnt = (lens & 255) - 1;
    auto flush = [&]() {
      asm volatile("{.reg .pred p; setp.ne.u32 p, %2, 6; @p st.shared.u16 [%0+-64], %1;}" :: "r"(a_g), "h"((uint16_t)pack_bf16(bf_hi(ownp) + pacc, 0.f)), "r"(a_g & 6) : "memory");
      chk = fmaf(pacc, 0.f, chk); pacc = 0.f; };
    constexpr uint64_t b1 = DHI | ((sb + OFF_W) >> 4), b2_ = b1 + 512;
    auto mma_h = [&](float (&acc)[32], uint32_t (&hf)[16]) {
      rs64b<0>(acc, hf[0], hf[1], hf[2], hf[3], b1); rs64b<1>(acc, hf[4], hf[5], hf[6], hf[7], b1 + 128); rs64b<1>(acc, hf[8], hf[9], hf[10], hf[11], b1 + 256); rs64b<1>(acc, hf[12], hf[13], hf[14], hf[15], b1 + 384); };
    auto finish = [&](float (&acc)[32], uint32_t (&hf)[16], uint32_t hrow) {
      rs64h<1>(acc, sp[0], sum[0], sp[1], sum[1], b2_); rs64h<1>(acc, sp[2], sum[2], sp[3], sum[3], b2_ + 128); rs64h<1>(acc, sp[4], sum[4], sp[5], sum[5], b2_ + 256); rs64h<1>(acc, sp[6], sum[6], sp[7], sum[7], b2_ + 384);
      wg_commit(); wg_wait0(); fence_regs(acc);
      STAMP(10);
      chk = fmaf(acc[0], 0.f, fmaf(acc[2], 0.f, chk));
      auto fin = [&](uint32_t x, float y0, float y1) { return u2(__hadd2(b2(x), b2(pack_bf16(silu_h(y0), silu_h(y1))))); };
#pragma unroll
      for (int j = 0; j < 4; j++) stsm4(hrow ^ (j << 5), fin(hf[4 * j], acc[8 * j], acc[8 * j + 1]), fin(hf[4 * j + 1], acc[8 * j + 2], acc[8 * j + 3]), fin(hf[4 * j + 2], acc[8 * j + 4], acc[8 * j + 5]), fin(hf[4 * j + 3], acc[8 * j + 6], acc[8 * j + 7]));
      __syncwarp();
    };
#pragma unroll 1
    for (int t = 0;; t++) {
#pragma unroll 1
      for (; cnt > 0; cnt--) { body(IC<0>());
      }
      if (!(t & 1)) {
        ownp = own; a_g += 64;
        if (t == 6) break;
        own = lds16(a_g) * 0x10001u;
        if (t == 0) {
#pragma unroll
          for (int j = 0; j < 8; j++) bp[2 * j + 1] = sp[j];
        } else bload((a_g & 16) ? (t & 4) * 256 : 0);
        lens >>= 8; cnt = 1;
        continue;
      }
      cnt = (lens & 255) - 1;
      flush();
      if (t == 3) {
        uint32_t hf[16]; float acc[32];
        const uint32_t hrow = hload(hf, lds16(a_n));
        mbar_wait(sb + BAR_WH);
        wg_fence();
        mma_h(acc, hf); finish(acc, hf, hrow);
        mbar_arrive(sb + BAR_M, (a_g & 62) == 0);
        wload();
      }
#pragma unroll
      for (int j = 0; j < 8; j++) { sp[j] = sum[j]; asm volatile("mov.b32 %0, 0;" : "=r"(sum[j])); }
    }
    {
      uint32_t hf[16], nr[4], v[16]; float acc[32];
      const uint32_t nd = lds16(a_n + 128), hrow = hload(hf, nd);
#pragma unroll
      for (int j = 0; j < 4; j++) nr[j] = __shfl_sync(~0u, nd, 4 * j + (lane >> 3)) * 128 + (lane & 7) * 16;
      if (FIN) { wg_fence(); mma_h(acc, hf); wg_commit(); }
      body(IC<2>());
      STAMP(9);
      flush();
      __syncwarp();
      mbar_arrive(sb + BAR_X, lane == 0);
      if (FIN == 2) { wg_wait0(); fence_regs(acc); }
      wg_fence();
      if (!FIN) mma_h(acc, hf);
      finish(acc, hf, hrow);
#pragma unroll
      for (int j = 0; j < 4; j++) lds128(v + 4 * j, sb + OFF_H + (nr[j] ^ ((nr[j] >> 3) & 0x70)));
#pragma unroll
      for (int j = 0; j < 4; j++) asm volatile("{.reg .pred p; setp.lt.u32 p, %5, %6; @p st.global" OCS ".v4.b32 [%0], {%1,%2,%3,%4};}" :: "l"((const char*)p.out + (size_t)node0 * 128 + nr[j]), "r"(v[4 * j]), "r"(v[4 * j + 1]), "r"(v[4 * j + 2]), "r"(v[4 * j + 3]), "r"(nr[j]), "r"(nloc * 128) : "memory");
    }
    asm volatile("{.reg .pred p, q; setp.neu.f32 p, %1, 0f00000000; setp.ne.or.u32 p, %2, 0, p; bar.red.or.pred q, 5, %3, p; selp.u32 %0, 1, 0, q;}" : "=r"(bad) : "f"(chk), "r"(lds32(sb + OFF_MISC + 12)), "n"(DEFO ? 512 : 384) : "memory");
    STAMP(11);
   } else { asm volatile("cp.async.wait_all;" ::: "memory"); bar_sync(5, 384); }
  }
  if (bad) slow_path(p, wid, lane, node0, nloc);
}

}

typedef CUresult (*EncodeFn)(CUtensorMap*, CUtensorMapDataType, cuuint32_t, void*, const cuuint64_t*, const cuuint64_t*, const cuuint32_t*, const cuuint32_t*,
                             CUtensorMapInterleave, CUtensorMapSwizzle, CUtensorMapL2promotion, CUtensorMapFloatOOBfill);

extern "C" void kernel_launch(void* const* d_in, const int* in_sizes, int n_in, void* d_out, int out_size) {
  Params p; Maps maps;
  p.h = (const uint4*)d_in[0]; p.pos = (const uint16_t*)d_in[1]; p.ea = (const uint4*)d_in[2];
  p.src = (const int*)d_in[3]; p.dst = (const int*)d_in[4];
  p.we = (const uint16_t*)d_in[5]; p.wx = (const uint16_t*)d_in[6]; p.wh = (const uint16_t*)d_in[7];
  p.out = (uint16_t*)d_out;
  p.N = in_sizes[0] / 64; p.E = in_sizes[3];
  p.EPC = ((p.E + G * 4 - 1) / (G * 4)) * 4;
  p.magic = (uint32_t)(((uint64_t)G << 24) / (uint64_t)p.N);
  p.inv = (1ull << 56) / p.magic;
  const uint64_t ea0 = (uint64_t)d_in[2], ea1 = ea0 + (uint64_t)p.E * 32 - 1;
  p.force_slow = ((ea0 >> 32) != (ea1 >> 32)) || (ea0 & 31) || (p.E & 3);
  void* qp = nullptr;
  cudaGetSymbolAddress(&qp, g_q);
  p.q = (char*)qp;
  if (((uint64_t)p.q >> 32) != (((uint64_t)p.q + QBYTES) >> 32)) p.q += QBYTES;
  cudaGetSymbolAddress((void**)&p.sync, g_sync); cudaGetSymbolAddress((void**)&p.xe, g_xe);
  cudaGetSymbolAddress((void**)&p.xa, g_xa); cudaGetSymbolAddress((void**)&p.xb, g_xb);
  void* fn = nullptr; cudaDriverEntryPointQueryResult qr;
  cudaGetDriverEntryPoint("cuTensorMapEncodeTiled", &fn, cudaEnableDefault, &qr);
  auto mk = [&](CUtensorMap* tm, void* base, int rows, int box = 64) {
    const cuuint64_t dim[2] = {64, (cuuint64_t)rows}, str[1] = {128}; const cuuint32_t bx[2] = {64, (cuuint32_t)box}, es[2] = {1, 1};
    ((EncodeFn)fn)(tm, CU_TENSOR_MAP_DATA_TYPE_BFLOAT16, 2, base, dim, str, bx, es, CU_TENSOR_MAP_INTERLEAVE_NONE, CU_TENSOR_MAP_SWIZZLE_128B,
                   CU_TENSOR_MAP_L2_PROMOTION_NONE, CU_TENSOR_MAP_FLOAT_OOB_FILL_NONE);
  };
  mk(&maps.m[TM_H / 128], d_in[0], p.N); mk(&maps.m[TM_WE / 128], d_in[5], 145); mk(&maps.m[TM_WH / 128], d_in[7], 128); mk(&maps.m[TM_Q / 128], p.q, p.N, 16);
  for (int k = 0; k < 2; k++) {
    void* xp = (void*)(k ? p.xb : p.xa);
    const cuuint64_t dim[2] = {(cuuint64_t)G * 64, (cuuint64_t)G}, str[1] = {(cuuint64_t)G * (128 << k)}; const cuuint32_t bx[2] = {64, (cuuint32_t)(k ? BROWS : G)}, es[2] = {1, 1};
    ((EncodeFn)fn)(&maps.m[TM_XA / 128 + k], k ? CU_TENSOR_MAP_DATA_TYPE_UINT32 : CU_TENSOR_MAP_DATA_TYPE_UINT16, 2, xp, dim, str, bx, es, CU_TENSOR_MAP_INTERLEAVE_NONE,
                   CU_TENSOR_MAP_SWIZZLE_NONE, CU_TENSOR_MAP_L2_PROMOTION_NONE, CU_TENSOR_MAP_FLOAT_OOB_FILL_NONE);
  }
  cudaFuncSetAttribute(egnn_kernel, cudaFuncAttributeMaxDynamicSharedMemorySize, SMEM);
  egnn_kernel<<<G, NTHR, SMEM>>>(p, maps);
}
```

```cpp
#include <cuda_runtime.h>
#include <cuda_bf16.h>
#include <cuda_fp16.h>
#include <cuda.h>
#include <stdint.h>
#pragma nv_diag_suppress 549

#define PFN 16
#define PFNS 250
#define FM 0
#define OPQ 0
#define H0 0
#define HALL 1
#define PF0NS 0
#define PFW 0
#define QCODE 0x254a109b7863ull
#define QREV 0x605
#define PFS 1
#define ESZ ""
#define XEF 0
#define OCS ""
#define RNB 2
#define NEARLY 2
#define PFE 0
#define DEFO 1
#define DEFNS 400
#define ABL 0
#define IDL 1
#define BDEL 400
#define HW 3
#define BROWS 44
#define B_HOLD 1
#define LSEQ 0x231200ull
#define HE 0
namespace {

constexpr int G = 132;
constexpr int NTHR = 512, NWK = 352, NCH = 5;
constexpr int NST = 3, STG = 2560;
constexpr int SCAP = 448;

constexpr int OFF_H = 0;
constexpr int OFF_W = 49152;
constexpr int OFF_WD = OFF_W + 16384;
constexpr int OFF_W3 = OFF_WD + 1024;
constexpr int OFF_P2 = OFF_W3 + 2048;
constexpr int OFF_RING = OFF_P2 + 24576;
constexpr int OFF_TE = OFF_RING + 12 * NST * STG;
constexpr int OFF_TS = OFF_TE + SCAP * 64;
constexpr int OFF_INV = OFF_TS - 768;
constexpr int OFF_GP = OFF_TS + SCAP * 32;
constexpr int OFF_WX = OFF_GP + 3072;
constexpr int OFF_LEN = OFF_WX + 128;
constexpr int OFF_MISC = OFF_LEN + 128;
constexpr int OFF_BAR = OFF_MISC + 48;
constexpr int SMEM = OFF_BAR + 256;
static_assert(SMEM <= 232448, "smem");
constexpr uint32_t sb = 1024;
constexpr int OFF_SRCI = OFF_TE;
constexpr int OFF_SB = OFF_RING, OFF_SA = OFF_SB + 34816, OFF_AX = OFF_SA + 32768, OFF_DST = OFF_H + 24576;
constexpr int OFF_WS = OFF_AX + 17408;
constexpr int OFF_BC = OFF_WS + 2304;
constexpr int OFF_CNT = OFF_P2;
constexpr int OFF_DH = OFF_CNT + 2176;
constexpr int OFF_POS = OFF_DH + 128;
constexpr int OFF_EXT = OFF_POS + 3072;
constexpr int OFF_XB = OFF_EXT + 1024, XPAD = G * 256;
static_assert(OFF_XB + XPAD + 1028 <= OFF_RING + 12 * STG && OFF_XB % 128 == 0 && OFF_BC + 544 <= OFF_TE && OFF_P2 % 1024 == 0 && OFF_SA % 1024 == 0 && SCAP * 64 >= 24576, "staging");
constexpr int BAR_DST = OFF_BAR, BAR_SRC = BAR_DST + 40, BAR_T = BAR_SRC + 24, BAR_W = BAR_T + 48, BAR_XA = BAR_W + 8, BAR_PS = BAR_XA + 8, BAR_AW = BAR_PS + 8,
              BAR_QP = BAR_AW + 8, BAR_QR = BAR_QP + 8, BAR_HA = BAR_QR + 8, BAR_EP = BAR_HA + 8, BAR_AX = BAR_EP + 8, BAR_AI = BAR_AX + 8, BAR_HB = BAR_AI + 8, BAR_U = BAR_HB + 8, BAR_WH = BAR_U + 8, BAR_M = BAR_WH + 8, BAR_X = BAR_M + 8, BAR_END = BAR_X + 8;
static_assert(BAR_END <= OFF_BAR + 256, "barriers");
constexpr uint32_t QBYTES = 8u << 20;

__device__ __align__(256) uint4 g_xa[G * G * 8];
__device__ __align__(256) uint4 g_xb[G * G * 16];
__device__ __align__(256) uint2 g_xe[G * G * 32];
__device__ __align__(256) uint4 g_q[2 * QBYTES / 16];
__device__ __align__(256) uint32_t g_sync[8];
#define STAMP(k)

struct Maps { CUtensorMap m[6]; };
constexpr int TM_H = 0, TM_WE = 128, TM_WH = 256, TM_Q = 384, TM_XA = 512, TM_XB = 640;
struct Params {
  const int* dst; uint32_t* sync; int E, EPC, N; uint32_t magic; unsigned long long inv;
  const int* src; const uint16_t* pos; const uint4* ea; const uint16_t* we; const uint16_t* wx; char* q; int force_slow;
  const uint4* xa; const uint4* xb; uint2* xe; uint16_t* out; const uint4* h; const uint16_t* wh;
};
template<int V> struct IC { static constexpr int value = V; };

#define R32(d) "+f"(d[0]),"+f"(d[1]),"+f"(d[2]),"+f"(d[3]),"+f"(d[4]),"+f"(d[5]),"+f"(d[6]),"+f"(d[7]),"+f"(d[8]),"+f"(d[9]),"+f"(d[10]),"+f"(d[11]),"+f"(d[12]),"+f"(d[13]),"+f"(d[14]),"+f"(d[15]),"+f"(d[16]),"+f"(d[17]),"+f"(d[18]),"+f"(d[19]),"+f"(d[20]),"+f"(d[21]),"+f"(d[22]),"+f"(d[23]),"+f"(d[24]),"+f"(d[25]),"+f"(d[26]),"+f"(d[27]),"+f"(d[28]),"+f"(d[29]),"+f"(d[30]),"+f"(d[31])
#define S32 "{%0,%1,%2,%3,%4,%5,%6,%7,%8,%9,%10,%11,%12,%13,%14,%15,%16,%17,%18,%19,%20,%21,%22,%23,%24,%25,%26,%27,%28,%29,%30,%31}"
#define DI __device__ __forceinline__

constexpr uint64_t DHI = ((uint64_t)(1024 >> 4) << 32) | (1ull << 62);
template<int SD> DI void rs64b(float (&d)[32], uint32_t a0, uint32_t a1, uint32_t a2, uint32_t a3, uint64_t db) {
  asm volatile("wgmma.mma_async.sync.aligned.m64n64k16.f32.bf16.bf16 " S32 ", {%32,%33,%34,%35}, %36, %37, 1, 1, 1;" : R32(d) : "r"(a0), "r"(a1), "r"(a2), "r"(a3), "l"(db), "n"(SD)); }
template<int SD> DI void rs64h(float (&d)[32], uint32_t a0, uint32_t a1, uint32_t a2, uint32_t a3, uint64_t db) {
  asm volatile("wgmma.mma_async.sync.aligned.m64n64k16.f32.f16.f16 " S32 ", {%32,%33,%34,%35}, %36, %37, 1, 1, 1;" : R32(d) : "r"(a0), "r"(a1), "r"(a2), "r"(a3), "l"(db), "n"(SD)); }
template<int SD> DI void ss64(float (&d)[32], uint64_t da, uint64_t db) {
  asm volatile("wgmma.mma_async.sync.aligned.m64n64k16.f32.bf16.bf16 " S32 ", %32, %33, %34, 1, 1, 0, 1;" : R32(d) : "l"(da), "l"(db), "n"(SD)); }
DI void trap_if(bool c) { asm volatile("{.reg .pred p; setp.eq.u32 p, %0, 0; @p bra.uni LT_%=; trap; LT_%=:}" :: "r"((uint32_t)c)); }
DI void wg_fence() { asm volatile("wgmma.fence.sync.aligned;" ::: "memory"); }
DI void wg_commit() { asm volatile("wgmma.commit_group.sync.aligned;" ::: "memory"); }
DI void wg_wait0() { asm volatile("wgmma.wait_group.sync.aligned 0;" ::: "memory"); }
DI void fence_regs(float (&d)[32]) { asm volatile("" : R32(d) :: "memory"); }
DI void proxy_fence() { asm volatile("fence.proxy.async.shared::cta;" ::: "memory"); }
DI uint64_t pol_first() { uint64_t r; asm("createpolicy.fractional.L2::evict_first.b64 %0, 1.0;" : "=l"(r)); return r; }
DI float tanh_ap(float x) { float y; asm("tanh.approx.f32 %0, %1;" : "=f"(y) : "f"(x)); return y; }
DI float silu_h(float y) { return fmaf(y, tanh_ap(y), y); }
DI uint32_t pack_bf16(float lo, float hi) { uint32_t r; asm("cvt.rn.bf16x2.f32 %0, %1, %2;" : "=r"(r) : "f"(hi), "f"(lo)); return r; }
DI uint32_t pack_f16(float lo, float hi) { uint32_t r; asm("cvt.rn.f16x2.f32 %0, %1, %2;" : "=r"(r) : "f"(hi), "f"(lo)); return r; }
DI float bf_lo(uint32_t v) { return __uint_as_float(v << 16); }
DI float bf_hi(uint32_t v) { return __uint_as_float(v & 0xFFFF0000u); }
DI uint32_t b2h(uint32_t v, float s) { return pack_f16(s * bf_lo(v), s * bf_hi(v)); }
DI void mbar_wait(uint32_t bar, uint32_t parity = 0) {
  asm volatile("{.reg .pred p, q; .reg .u32 c; mov.u32 c, 0;\n"
    "LW_%=: mbarrier.try_wait.parity.shared::cta.b64 p, [%0], %1;\n add.u32 c, c, 1; setp.lt.and.u32 q, c, 0x200000, !p;\n @q bra.uni LW_%=;}" :: "r"(bar), "r"(parity) : "memory");
}
DI void mbar_arrive(uint32_t bar, int p = 1) { asm volatile("{.reg .pred p; setp.ne.b32 p, %1, 0; @p mbarrier.arrive.shared::cta.b64 _, [%0];}" :: "r"(bar), "r"(p) : "memory"); }
DI void bar_sync(int id, int n) { asm volatile("bar.sync %0, %1;" :: "r"(id), "r"(n) : "memory"); }
DI void bar_arrive(int id, int n) { asm volatile("bar.arrive %0, %1;" :: "r"(id), "r"(n) : "memory"); }
DI __nv_bfloat162 b2(uint32_t v) { return *(__nv_bfloat162*)&v; }
DI uint32_t u2(__nv_bfloat162 v) { return *(uint32_t*)&v; }
DI uint32_t hsq(uint32_t v) { return u2(__hmul2(b2(v), b2(v))); }
DI uint32_t hsub(uint32_t a, uint32_t b) { return u2(__hsub2(b2(a), b2(b))); }
DI uint32_t hhalf(uint32_t v) { return u2(__hmul2(b2(v), __floats2bfloat162_rn(0.5f, 0.5f))); }
DI uint32_t mag2(uint32_t m, uint32_t v) { return __vmaxu2(m, v & 0x7FFF7FFFu); }
DI uint32_t hmag(uint32_t m, uint32_t v) { const __half2 r = __hmax2(*(const __half2*)&m, __habs2(*(const __half2*)&v)); return *(const uint32_t*)&r; }
DI uint32_t magr(uint32_t m) { return max(m & 0xFFFF, m >> 16); }
DI void sts128(uint32_t a, uint32_t x, uint32_t y, uint32_t z, uint32_t w) { asm volatile("st.shared.v4.u32 [%0], {%1,%2,%3,%4};" :: "r"(a), "r"(x), "r"(y), "r"(z), "r"(w) : "memory"); }
DI void sts64(uint32_t a, uint32_t x, uint32_t y) { asm volatile("st.shared.v2.u32 [%0], {%1,%2};" :: "r"(a), "r"(x), "r"(y) : "memory"); }
DI void sts32(uint32_t a, uint32_t x) { asm volatile("st.shared.u32 [%0], %1;" :: "r"(a), "r"(x) : "memory"); }
DI void sts16(uint32_t a, uint32_t x) { asm volatile("st.shared.u16 [%0], %1;" :: "r"(a), "h"((uint16_t)x) : "memory"); }
DI void lds128(uint32_t* v, uint32_t a) { asm volatile("ld.shared.v4.u32 {%0, %1, %2, %3}, [%4];" : "=r"(v[0]), "=r"(v[1]), "=r"(v[2]), "=r"(v[3]) : "r"(a) : "memory"); }
DI void lds64(uint32_t& x, uint32_t& y, uint32_t a) { asm volatile("ld.shared.v2.u32 {%0, %1}, [%2];" : "=r"(x), "=r"(y) : "r"(a) : "memory"); }
DI uint32_t lds32(uint32_t a) { uint32_t x; asm volatile("ld.shared.u32 %0, [%1];" : "=r"(x) : "r"(a) : "memory"); return x; }
DI uint32_t lds16(uint32_t a) { uint32_t x; asm volatile("ld.shared.u16 %0, [%1];" : "=r"(x) : "r"(a) : "memory"); return x; }
DI uint32_t atoms_add(uint32_t a, uint32_t v) { uint32_t r; asm volatile("atom.shared.add.u32 %0, [%1], %2;" : "=r"(r) : "r"(a), "r"(v) : "memory"); return r; }
DI void bulk_load(uint32_t dst, const void* src, uint32_t bytes, uint32_t bar) {
  asm volatile("cp.async.bulk.shared::cluster.global.mbarrier::complete_tx::bytes.L2::cache_hint [%0], [%1], %2, [%3], %4;" :: "r"(dst), "l"(src), "r"(bytes), "r"(bar), "l"(pol_first()) : "memory"); }
DI void bulk_store(void* dst, uint32_t src, uint32_t bytes) { asm volatile("cp.async.bulk.global.shared::cta.bulk_group [%0], [%1], %2;" :: "l"(dst), "r"(src), "r"(bytes) : "memory"); }
DI void mbar_expect(uint32_t bar, uint32_t bytes) { asm volatile("mbarrier.arrive.expect_tx.shared::cta.b64 _, [%0], %1;" :: "r"(bar), "r"(bytes) : "memory"); }
DI void mbar_init(uint32_t bar, int n) { asm volatile("mbarrier.init.shared::cta.b64 [%0], %1;" :: "r"(bar), "r"(n) : "memory"); }
DI void tma_load(uint32_t dst, uint64_t tm, int row, uint32_t bar) {
  asm volatile("cp.async.bulk.tensor.2d.shared::cluster.global.mbarrier::complete_tx::bytes.L2::cache_hint [%0], [%1, {%3, %4}], [%2], %5;" :: "r"(dst), "l"(tm), "r"(bar), "r"(0), "r"(row), "l"(pol_first()) : "memory"); }
DI void tma_store(uint64_t tm, int col, int row, uint32_t src) {
  asm volatile("cp.async.bulk.tensor.2d.global.shared::cta.bulk_group [%0, {%2, %3}], [%1];" :: "l"(tm), "r"(src), "r"(col), "r"(row) : "memory"); }
DI void tma_store_ef(uint64_t tm, int col, int row, uint32_t src) {
  if (XEF) asm volatile("cp.async.bulk.tensor.2d.global.shared::cta.bulk_group.L2::cache_hint [%0, {%2, %3}], [%1], %4;" :: "l"(tm), "r"(src), "r"(col), "r"(row), "l"(pol_first()) : "memory");
  else tma_store(tm, col, row, src); }
DI void bulk_commit() { asm volatile("cp.async.bulk.commit_group;" ::: "memory"); }
DI void bulk_wait_read() { asm volatile("cp.async.bulk.wait_group.read 0;" ::: "memory"); }
DI uint2 ld_poll2(const void* a) { uint2 v; asm volatile("ld.relaxed.gpu.global.v2.u32 {%0, %1}, [%2];" : "=r"(v.x), "=r"(v.y) : "l"(a) : "memory"); return v; }
DI void st_ext(uint2* a, uint32_t v, uint32_t ep) { asm volatile("st.relaxed.gpu.global.v2.u32 [%0], {%1, %2};" :: "l"(a), "r"(v), "r"(ep) : "memory"); }
DI uint32_t ext_get(const uint2* a, uint32_t ep) { uint2 v; int spin = 0; do { v = ld_poll2(a); trap_if(++spin > 4000000); } while (__any_sync(~0u, v.y != ep)); return v.x; }
DI void bulk_wait() { asm volatile("cp.async.bulk.wait_group 0;" ::: "memory"); }
DI void hint_signal(uint32_t* c) { asm volatile("red.relaxed.gpu.global.add.u32 [%0], 1;" :: "l"(c) : "memory"); }
DI void hint_wait(const uint32_t* c, uint32_t target) { uint32_t v; int spin = 0;
  do { asm volatile("ld.relaxed.gpu.global.u32 %0, [%1];" : "=r"(v) : "l"(c) : "memory"); trap_if(++spin > 4000000); } while (__any_sync(~0u, (int)(v - target) < 0)); }
DI void stsm4(uint32_t a, uint32_t x, uint32_t y, uint32_t z, uint32_t w) { asm volatile("stmatrix.sync.aligned.m8n8.x4.shared.b16 [%0], {%1,%2,%3,%4};" :: "r"(a), "r"(x), "r"(y), "r"(z), "r"(w) : "memory"); }
DI void ldsm4(uint32_t* v, uint32_t a) { asm volatile("ldmatrix.sync.aligned.m8n8.x4.shared.b16 {%0,%1,%2,%3}, [%4];" : "=r"(v[0]), "=r"(v[1]), "=r"(v[2]), "=r"(v[3]) : "r"(a) : "memory"); }
DI void ldsm4t(uint32_t* v, uint32_t a) { asm volatile("ldmatrix.sync.aligned.m8n8.x4.trans.shared.b16 {%0,%1,%2,%3}, [%4];" : "=r"(v[0]), "=r"(v[1]), "=r"(v[2]), "=r"(v[3]) : "r"(a) : "memory"); }
DI uint32_t mad16(uint32_t x, uint32_t m, uint32_t c) { uint32_t r; asm("dp2a.lo.u32.u32 %0, %1, %2, %3;" : "=r"(r) : "r"(x), "r"(m), "r"(c)); return r; }
DI bool wbad(uint32_t m, uint32_t hi) { return m > hi || (m && m < 0x3980); }

__device__ __noinline__ void slow_path(const Params& p, int wid, int lane, int node0, int nloc) {
  const uint32_t ab = sb + OFF_P2 + wid * 8704;
  for (int i = lane; i < 32 * 68; i += 32) sts32(ab + i * 4, 0);
  __syncwarp();
  const uint32_t wdv = __ldg((const uint32_t*)(p.we + 128 * 64) + lane), wxv = __ldg((const uint32_t*)p.wx + lane);
  const int nb0 = node0 + wid * 32, cntn = max(0, min(32, nloc - wid * 32));
  auto dot = [&](uint32_t hv, const uint16_t* w, int K2, float& y0, float& y1) {
#pragma unroll 4
    for (int k = 0; k < K2; k++) {
      const uint32_t hk = __shfl_sync(~0u, hv, k), wa = __ldg((const uint32_t*)(w + 2 * k * 64) + lane), wb = __ldg((const uint32_t*)(w + (2 * k + 1) * 64) + lane);
      y0 = fmaf(bf_lo(hk), bf_lo(wa), fmaf(bf_hi(hk), bf_lo(wb), y0)); y1 = fmaf(bf_lo(hk), bf_hi(wa), fmaf(bf_hi(hk), bf_hi(wb), y1));
    }
  };
  auto silu = [](float x) { return x / (1.f + __expf(-x)); };
#pragma unroll 1
  for (int base = 0; base < p.E; base += 32) {
    const int e = base + lane;
    const uint32_t dl = e < p.E ? (uint32_t)(__ldg(p.dst + e) - nb0) : 0xFFFFFFFFu;
    uint32_t mk = __ballot_sync(~0u, dl < (uint32_t)cntn);
    while (mk) {
      const int l = __ffs(mk) - 1; mk &= mk - 1;
      const int ee = base + l, n = __shfl_sync(~0u, dl, l), s = __ldg(p.src + ee);
      const uint16_t *po = p.pos + (size_t)(nb0 + n) * 3, *pp = p.pos + (size_t)s * 3;
      const uint32_t dxy = hsub(__ldg(po) | (__ldg(po + 1) << 16), __ldg(pp) | (__ldg(pp + 1) << 16)), dz = hsub(__ldg(po + 2), __ldg(pp + 2));
      const uint32_t sq = hsq(dxy); const float d2 = bf_lo(sq) + bf_hi(sq) + bf_lo(hsq(dz));
      float y0 = d2 * bf_lo(wdv), y1 = d2 * bf_hi(wdv);
      dot(__ldg((const uint32_t*)(p.h + (size_t)(nb0 + n) * 8) + lane), p.we, 32, y0, y1);
      dot(__ldg((const uint32_t*)(p.h + (size_t)s * 8) + lane), p.we + 64 * 64, 32, y0, y1);
      dot(__ldg((const uint32_t*)(p.ea + (size_t)ee * 2) + (lane & 7)), p.we + 129 * 64, 8, y0, y1);
      const uint32_t mm = pack_bf16(silu(y0), silu(y1));
      float c = bf_lo(mm) * bf_lo(wxv) + bf_hi(mm) * bf_hi(wxv);
#pragma unroll
      for (int o = 16; o; o >>= 1) c += __shfl_xor_sync(~0u, c, o);
      const uint32_t a = ab + n * 272;
      uint32_t x0, x1; lds64(x0, x1, a + lane * 8);
      sts64(a + lane * 8, __float_as_uint(__uint_as_float(x0) + bf_lo(mm)), __float_as_uint(__uint_as_float(x1) + bf_hi(mm)));
      if (lane < 3) { const float df = lane == 0 ? bf_lo(dxy) : lane == 1 ? bf_hi(dxy) : bf_lo(dz); sts32(a + 256 + lane * 4, __float_as_uint(fmaf(c, df, __uint_as_float(lds32(a + 256 + lane * 4))))); }
    }
  }
  __syncwarp();
#pragma unroll 1
  for (int n = 0; n < cntn; n++) {
    uint32_t x0, x1; lds64(x0, x1, ab + n * 272 + lane * 8);
    const uint32_t hv = __ldg((const uint32_t*)(p.h + (size_t)(nb0 + n) * 8) + lane);
    float y0 = 0.f, y1 = 0.f;
    dot(hv, p.wh, 32, y0, y1); dot(pack_bf16(__uint_as_float(x0), __uint_as_float(x1)), p.wh + 64 * 64, 32, y0, y1);
    ((uint32_t*)p.out)[(size_t)(nb0 + n) * 32 + lane] = u2(__hadd2(b2(hv), b2(pack_bf16(silu(y0), silu(y1)))));
    if (lane < 3) p.out[(size_t)p.N * 64 + (size_t)(nb0 + n) * 3 + lane] = (uint16_t)pack_bf16(bf_lo(__ldg(p.pos + (size_t)(nb0 + n) * 3 + lane)) + __uint_as_float(lds32(ab + n * 272 + 256 + lane * 4)), 0.f);
  }
}

__global__ void __launch_bounds__(NTHR, 1) egnn_kernel(const __grid_constant__ Params p, const __grid_constant__ Maps maps) {
  const uint64_t tmb = (uint64_t)&maps;
  extern __shared__ __align__(1024) unsigned char smraw[];
  const int tid = threadIdx.x, cta = blockIdx.x;
  const int e0 = cta * p.EPC, n4 = max(0, min(p.EPC, p.E - e0)) >> 2;
  STAMP(0);
  if (tid == NWK) {
#pragma unroll 1
    for (int k = 0; k < NCH; k++) { const int nb = max(0, min(NWK, n4 - k * NWK)) * 16;
      mbar_init(sb + BAR_DST + k * 8, 1);
      asm volatile("fence.mbarrier_init.release.cluster;" ::: "memory");
      mbar_expect(sb + BAR_DST + k * 8, nb);
      if (nb) bulk_load(sb + OFF_DST + k * NWK * 16, (const char*)(p.dst + e0) + k * NWK * 16, nb, sb + BAR_DST + k * 8); }
  }
  const int lane = tid & 31, wid = __shfl_sync(~0u, tid >> 5, 0), w = wid & 3;
  asm volatile("{.reg .pred p; setp.eq.u32 p, %2, 384; @p cp.async.cg.shared.global [%0], [%1], 16;}" :: "r"(sb + OFF_LEN - 192 + (tid >> 1)), "l"(p.sync), "r"(tid & 415) : "memory");

  auto first_node = [&](int c) { return (int)((c * p.inv + 0xFFFFFFFFull) >> 32); };
  const int node0 = first_node(cta), nloc = min(first_node(cta + 1), p.N) - node0;
  const uint32_t ealo = (uint32_t)(uint64_t)p.ea;
  const int epad = min(e0, p.E - 1);
  auto load_h = [&](int b) { mbar_expect(sb + BAR_T + b * 8, 8192); tma_load(sb + OFF_H + b * 8192, tmb + TM_H, node0 + b * 64, sb + BAR_T + b * 8); };
  auto prefetch_e = [&](int i) {
    const uint32_t nb = (p.E / G) & ~15u;
    if (nb && i < PFN) asm volatile("cp.async.bulk.prefetch.L2.global [%0], %1;" :: "l"((const char*)p.ea + (size_t)(((i * PFS + i * PFS / 32 * (~PFS & 1)) & 31) * G + cta) * nb), "r"(nb) : "memory");
  };
  if (wid >= 12) {
    const int t = tid - 384;
    uint32_t pv[9], ev = 0;
#pragma unroll
    for (int i = 0; i < 3; i++) { const uint16_t* pp = p.pos + (size_t)(node0 + t + 128 * i) * 3;
      pv[3 * i] = pv[3 * i + 1] = pv[3 * i + 2] = 0;
      asm volatile("{.reg .pred p; setp.lt.s32 p, %4, %5;\n @p ld.global.nc.u16 %0, [%3];\n @p ld.global.nc.u16 %1, [%3+2];\n @p ld.global.nc.u16 %2, [%3+4];}"
        : "+r"(pv[3 * i]), "+r"(pv[3 * i + 1]), "+r"(pv[3 * i + 2]) : "l"(pp), "r"(t + 128 * i), "r"(p.N - node0)); }
    asm volatile("{.reg .pred p; setp.lt.u32 p, %3, 8; @p ld.global.nc.u32 %0, [%1]; @p st.global.v4.u32 [%2], {%4, %4, %4, %4};}"
      : "+r"(ev) : "l"((const uint32_t*)(p.ea + (size_t)epad * 2) + t), "l"(p.q + (size_t)(p.N + cta) * 128 + t * 16), "r"(t), "r"(0xF700F700u) : "memory");
    asm volatile("cp.async.wait_all;" ::: "memory");
    __syncwarp();
    const uint32_t e = lds32(sb + OFF_LEN + 8 + w * 16) + 1;
    {
      const uint32_t tg = (1 + e % 3) << 30, v = ((tg >> 16) + 512 + (lane & 7) * 4) * 0x10001u;
      if (t == 0) sts32(sb + OFF_MISC + 32, e);
#pragma unroll
      for (int i = 0; i < 9; i++) sts128(sb + OFF_SA + t * 16 + i * 2048, v, v + 0x10001u, v + 0x20002u, v + 0x30003u);
      bar_sync(6, NTHR);
      mbar_arrive(sb + BAR_EP, lane == 0);
#pragma unroll
      for (int i = 0; i < 17; i++) sts128(sb + OFF_SB + t * 16 + i * 2048, tg, tg, tg, tg); }
    uint32_t mp = 0;
#pragma unroll
    for (int i = 0; i < 3; i++) { sts64(sb + OFF_POS + (t + 128 * i) * 8, pv[3 * i] | (pv[3 * i + 1] << 16), pv[3 * i + 2]); mp = mag2(mag2(mp, pv[3 * i] | (pv[3 * i + 1] << 16)), pv[3 * i + 2]); }
    proxy_fence();
    __syncwarp();
    mbar_arrive(sb + BAR_PS, lane == 0);
    mbar_wait(sb + BAR_W);
    {
      uint32_t v[4], u[4]; const int r = t >> 3, c = t & 7;
      lds128(v, sb + OFF_WS + 128 + t * 16); lds128(u, sb + OFF_WS + c * 16);
      const uint32_t x = lds32(sb + OFF_WS + 2176 + lane * 4);
      sts128(sb + OFF_W3 + r * 128 + ((c ^ (r & 7)) << 4), b2h(v[0], .5f), b2h(v[1], .5f), b2h(v[2], .5f), b2h(v[3], .5f));
      const float s = ((r & 1) || r == 6) ? 0.f : .5f;
      if (t < 64) sts128(sb + OFF_WD + r * 128 + ((c ^ r) << 4), b2h(u[0], s), b2h(u[1], s), b2h(u[2], s), b2h(u[3], s));
      if (t < 32) sts32(sb + OFF_WX + (t & 3) * 32 + (t >> 2) * 4, b2h(x, 1.f));
      const uint32_t m3 = __reduce_max_sync(~0u, magr(mag2(mag2(mag2(mag2(0, v[0]), v[1]), v[2]), v[3]))), md = __reduce_max_sync(~0u, magr(mag2(mag2(mag2(mag2(0, u[0]), u[1]), u[2]), u[3])));
      if (wbad(m3, 0x4000) || wbad(md, 0x4000) || wbad(__reduce_max_sync(~0u, magr(mag2(0, x))), 0x4700) || magr(mp) >= 0x4200 || magr(mag2(0, ev)) >= 0x4380) sts32(sb + OFF_MISC + 8, 1);
    }
    if (w == 1) {
#pragma unroll 1
      for (int b = HE; b < HW; b++) { mbar_wait(sb + BAR_SRC + max(0, H0 + b) * 8); if (lane == 0) load_h(b); }
    }
    bar_sync(3, 128);
    const uint32_t frag = (w * 16 + (lane & 15)) * 128 + (((lane >> 4) ^ (lane & 7)) << 4);
    uint32_t mq = 0;
#pragma unroll 1
    for (int b = 0; b < 6; b++) {
      float acc[32];
      const uint64_t da = DHI | (((sb + OFF_H) >> 4) + b * 512), db = DHI | ((sb + OFF_W) >> 4);
      const uint32_t v0 = lds16(sb + OFF_POS + b * 512 + w * 128 + lane * 2), v1 = lds16(sb + OFF_POS + 64 + b * 512 + w * 128 + lane * 2);
      mbar_wait(sb + BAR_T + b * 8);
      if (b == 0) STAMP(25);
      if (b == 5) STAMP(26);
      wg_fence();
      ss64<0>(acc, da, db); ss64<1>(acc, da + 2, db + 128); ss64<1>(acc, da + 4, db + 256); ss64<1>(acc, da + 6, db + 384);
      wg_commit();
      if (b == 0) mbar_wait(sb + BAR_AW);
      if (t == 32) { if (HALL) { if (b == 0) for (int k = HW; k < 6; k++) load_h(k); } else if (b + HW < 6) load_h(b + HW); }
      __syncwarp();
      uint32_t ff[6], fg[6];
#pragma unroll
      for (int j = 0; j < 6; j++) { ff[j] = (__byte_perm((j & 1) ? v1 : v0, 0, 0x4140) >> (3 * (j >> 1))) & 0x00070007u; fg[j] = __vsub2(0x00040004u, ff[j]);
        asm volatile("" : "+r"(ff[j]), "+r"(fg[j])); }
      wg_wait0(); fence_regs(acc);
      uint32_t o[16];
#pragma unroll
      for (int j = 0; j < 16; j++) o[j] = pack_f16(.5f * acc[2 * j], .5f * acc[2 * j + 1]);
#pragma unroll
      for (int j = 0; j < 6; j++) {
        const uint32_t m = o[j] & 0x7FFF7FFFu; mq = __vmaxu2(mq, m);
        o[j] = (__viaddmax_s16x2(m, fg[j], 0) & 0xFFF8FFF8u) | ff[j] | (o[j] & 0x80008000u); }
      if (b == 4) mbar_wait(sb + BAR_AX);
      const uint32_t qs = sb + OFF_SA + b * 8192;
#pragma unroll
      for (int j = 0; j < 4; j++) stsm4((qs + frag) ^ (j << 5), o[4 * j], o[4 * j + 1], o[4 * j + 2], o[4 * j + 3]);
      proxy_fence();
      __syncwarp();
      if (lane == 0 && b * 64 + w * 16 < nloc) tma_store(tmb + TM_Q, 0, node0 + b * 64 + w * 16, qs + w * 2048);
    }
    if (lane == 0) bulk_commit();
    { const uint32_t m = __reduce_max_sync(~0u, magr(mq)); if (lane == 0) sts32(sb + OFF_MISC + 16 + w * 4, m); }
    asm volatile("setmaxnreg.dec.sync.aligned.u32 32;");
    bulk_wait();
    bar_sync(3, 128);
    if (w == 0) {
      STAMP(18);
      uint32_t mv[4]; lds128(mv, sb + OFF_MISC + 16);
      const uint32_t mx = max(max(mv[0], mv[1]), max(mv[2], mv[3]));
      mbar_arrive(sb + BAR_QR, lane == 0);
      STAMP(19);
      if (lane == 0) {
        if (nloc > 0 && (mx >= 0x7BF0 || mx < 0x1400)) asm volatile("st.relaxed.gpu.global.u32 [%0+4], %1;" :: "l"(p.sync), "r"(e) : "memory");
        asm volatile("red.release.gpu.global.add.u32 [%0], 1;" :: "l"(p.sync) : "memory");
      }
      __syncwarp();
      uint32_t c, f; int spin = 0;
      do { asm volatile("ld.acquire.gpu.global.v2.u32 {%0, %1}, [%2];" : "=r"(c), "=r"(f) : "l"(p.sync) : "memory"); trap_if(++spin > 4000000); } while (__any_sync(~0u, (int)(c - e * G) < 0));
      if (f == e) sts32(sb + OFF_MISC + 8, 1);
      if (cta == 0 && lane == 0) asm volatile("st.relaxed.gpu.global.u32 [%0+8], %1;" :: "l"(p.sync), "r"(e) : "memory");
      STAMP(20);
      __syncwarp();
      mbar_arrive(sb + BAR_QP, lane == 0);
    }
    if (w == 2) {
      const uint32_t tg = (1 + e % 3) << 30;
      hint_wait(p.sync + 5, e * G);
      if (lane == 0) { mbar_expect(sb + BAR_HB, XPAD);
#pragma unroll 1
        for (int o = 0; o < 4; o++) bulk_load(sb + OFF_XB + o * (G * 64), (const char*)p.xb + (size_t)(cta * 4 + o) * (G * 64), G * 64, sb + BAR_HB); }
      STAMP(21);
      bar_sync(7, 384);
      sts32(sb + OFF_XB + XPAD, tg + p.N + cta);
      const uint32_t nx = __shfl_sync(~0u, lds32(sb + OFF_MISC + 8) ? 0 : lds32(sb + OFF_MISC + 4), 0);
#pragma unroll 1
      for (uint32_t k = 0; k < nx; k += 32) {
        const uint32_t i = min(k + lane, nx - 1), xr = lds32(sb + OFF_EXT + i * 4), row = (xr >> 9) & 255;
        const uint32_t v = ext_get(p.xe + (cta * G + row) * 32 + ((xr >> 17) & 31), e), x = lds32(sb + OFF_CNT + (xr & 511) * 4) + (xr >> 22) * 16;
        sts32(sb + OFF_XB + XPAD + 4 + i * 4, v); sts16(sb + OFF_TS + x, XPAD + 4 + i * 4);
        sts32(sb + OFF_TE + x * 2, mad16(v, 0x2000u, ealo - (tg >> 11) + row * p.EPC * 32));
      }
      __syncwarp();
      mbar_arrive(sb + BAR_HB, lane == 0);
    }
    if (w == 1) {
      if (PFW) mbar_wait(sb + PFW);
      __nanosleep(PF0NS);
#pragma unroll 1
      for (int i = PFE; i < PFN; i++) { if (lane == 0) prefetch_e(i); __nanosleep(PFNS); }
    }
    if (w == 3) {
      if (lane == 0) { mbar_expect(sb + BAR_U, 16384); tma_load(sb + OFF_W, tmb + TM_WH, 0, sb + BAR_U); }
      __syncwarp();
      bar_sync(4, 416);
      if (lane == 0) tma_load(sb + OFF_W + 8192, tmb + TM_WH, 64, sb + BAR_U);
    }
    bar_sync(3, 128);
    mbar_wait(sb + BAR_U);
    uint32_t mh = 0;
#pragma unroll 1
    for (int i = t; i < 1024; i += 128) {
      uint32_t v[4]; const uint32_t r = (i >> 3) & 7, j = (i ^ r) & 7;
#pragma unroll
      for (int k = 0; k < 4; k++) v[k] = lds32(sb + OFF_W + (i >> 3) * 128 + ((((j & 4) + k) ^ r) << 4) + (j & 3) * 4);
      __syncwarp();
      if (i < 512) sts128(sb + OFF_W + i * 16, hhalf(v[0]), hhalf(v[1]), hhalf(v[2]), hhalf(v[3]));
      else { sts128(sb + OFF_W + i * 16, b2h(v[0], .5f), b2h(v[1], .5f), b2h(v[2], .5f), b2h(v[3], .5f)); mh = mag2(mag2(mag2(mag2(mh, v[0]), v[1]), v[2]), v[3]); } }
    if (wbad(__reduce_max_sync(~0u, magr(mh)), 0x4700)) sts32(sb + OFF_MISC + 12, 1);
    proxy_fence();
    __syncwarp();
    mbar_arrive(sb + BAR_WH, lane == 0);
    if (DEFO) { if (!__shfl_sync(~0u, lds32(sb + OFF_MISC + 8), 0)) {
      mbar_wait(sb + BAR_M);
      __nanosleep(DEFO);
#pragma unroll 1
      for (int i = 0; i < 12; i++) { uint32_t v[4]; const uint32_t n = lds16(sb + OFF_GP + i * 256 + (t >> 3) * 8 + 6);
        lds128(v, sb + OFF_H + n * 128 + (((n ^ t) & 7) << 4));
        if (n < nloc) ((uint4*)p.out)[(size_t)(node0 + n) * 8 + (t & 7)] = make_uint4(v[0], v[1], v[2], v[3]);
        __nanosleep(DEFNS); }
      uint32_t pa_[9];
#pragma unroll
      for (int k = 0; k < 9; k++) { const uint32_t i = t + 128 * k, n = (i * 43691u) >> 17; pa_[k] = lds16(sb + OFF_INV + n * 2) + (i - 3 * n) * 2; }
      uint16_t* po = p.out + (size_t)p.N * 64 + node0 * 3 + t;
      mbar_wait(sb + BAR_X);
#pragma unroll
      for (int k = 0; k < 9; k++) pa_[k] = lds16(sb + OFF_GP + pa_[k]);
#pragma unroll
      for (int k = 0; k < 9; k++) if (t + 128 * k < nloc * 3) po[128 * k] = pa_[k];
      asm volatile("{.reg .pred p, q; setp.ne.u32 p, 0, 0; bar.red.or.pred q, 5, 512, p;}" ::: "memory"); } }
    return;
  }

  if (tid == 320) {
    mbar_init(sb + BAR_W, 1);
    asm volatile("fence.mbarrier_init.release.cluster;" ::: "memory");
    mbar_expect(sb + BAR_W, 2 * 8192 + 2304);
    tma_load(sb + OFF_W, tmb + TM_WE, 64, sb + BAR_W); tma_load(sb + OFF_W + 8192, tmb + TM_WE, 0, sb + BAR_W);
    bulk_load(sb + OFF_WS, p.we + 128 * 64, 2176, sb + BAR_W); bulk_load(sb + OFF_WS + 2176, p.wx, 128, sb + BAR_W);
  }
  if (tid == 288) {
#pragma unroll
    for (int a = BAR_SRC; a < BAR_END; a += 8) if (a != BAR_W) mbar_init(sb + a, a == BAR_WH || a == BAR_PS || a == BAR_EP ? 4 : a == BAR_XA ? 11 : a == BAR_HB ? 2 : a >= BAR_M ? 12 : 1);
    asm volatile("fence.mbarrier_init.release.cluster;" ::: "memory");
    asm volatile("prefetch.tensormap [%0];" :: "l"(tmb + TM_XA)); asm volatile("prefetch.tensormap [%0];" :: "l"(tmb + TM_H));
    asm volatile("prefetch.tensormap [%0];" :: "l"(tmb + TM_XB)); asm volatile("prefetch.tensormap [%0];" :: "l"(tmb + TM_Q));
  }
  {
    if (tid < 144) { const uint32_t z = (tid >> 3) == 16 ? 0x8000u : 0u; sts128(sb + OFF_CNT + tid * 16, z, z, z, z); }
    else if (tid <= 144 + G) sts32(sb + OFF_BC + (tid - 144) * 4, ((tid - 144) & 31) * 4);
    const uint32_t sp = XPAD * 0x10001u, em = first_node(G);
    if (wid < 7) {
#pragma unroll
      for (int i = 0; i < 4; i++) sts128(sb + OFF_TS + tid * 16 + i * 3584, sp, sp, sp, sp);
    }
    static_assert(SCAP * 32 == 4 * 3584, "fill");
#pragma unroll 1
    for (int i = n4 + tid; i < 1536; i += 384) sts128(sb + OFF_DST + i * 16, em, em, em, em);
    if (tid == 321) sts128(sb + OFF_MISC, 0, 0, p.force_slow, 0);
  }
  bar_arrive(6, NTHR);
  bar_sync(0, 384);
  uint32_t ep, tag, eb0, pk[12], r0[12], r1[12], cb;
  uint2 vb[12];
  auto get_tag = [&]() { mbar_wait(sb + BAR_EP); ep = lds32(sb + OFF_MISC + 32); tag = (1 + ep % 3) << 30; eb0 = ealo - (tag >> 11); };
  if (wid == 11) {
    trap_if(sb != (uint32_t)__cvta_generic_to_shared(smraw));
#pragma unroll 1
    for (unsigned long long q = LSEQ; q; q >>= 8) { const int k = (q >> 4) & 7, nb = max(0, min(8192, n4 * 16 - k * 8192));
      if (!(q & 8)) mbar_wait(sb + BAR_DST + ((uint32_t)q & 7) * 8);
      if (lane == 0) {
        if (k >= 3) load_h(k - 3);
        else { mbar_expect(sb + BAR_SRC + k * 8, nb);
          if (nb) bulk_load(sb + OFF_SRCI + k * 8192, (const char*)(p.src + e0) + k * 8192, nb, sb + BAR_SRC + k * 8); } } }
    get_tag();
    mbar_wait(sb + BAR_PS);
    bar_sync(12, 384);
    uint32_t xm = 0;
#pragma unroll
    for (int k = 0; k < 5; k++) xm |= (lds32(sb + OFF_BC + min(lane + 32 * k, G - 1) * 4) >= (65 << 9) && lane + 32 * k < G) << k;
    auto ext_send = [&](int pl) {
      uint32_t x = xm;
      for (uint32_t m; (m = __ballot_sync(~0u, x));) {
        const uint32_t l = __ffs(m) - 1, j = l + 32 * (__ffs(__shfl_sync(~0u, x, l)) - 1);
        if (lane == l) x &= x - 1;
        const uint32_t e = min(lds16(sb + OFF_AX + j * 128 + ((4 * l + 2 * lane) & 126)), 6143u);
        if (pl) st_ext(p.xe + (j * G + cta) * 32 + lane, lds32(sb + OFF_SRCI + e * 4) + tag + (e << 16), ep);
        else { const uint32_t cn = lds32(sb + OFF_BC + j * 4) >> 9, v = cn > 96 ? 1 : lane + 64 < cn ? 512 | (lds32(sb + OFF_DST + e * 4) & 511) : 0;
          asm volatile("red.shared.xor.b32 [%0], %1;" :: "r"(sb + OFF_SA + j * 128 + ((l + lane) & 31) * 4), "r"(((v & 63) << 10) | ((v >> 6) << 26)) : "memory"); }
      }
    };
    if (__any_sync(~0u, xm)) { ext_send(0); proxy_fence(); __syncwarp(); }
    if (lane == 0) { tma_store_ef(tmb + TM_XA, cta * 64, 0, sb + OFF_SA); bulk_commit(); mbar_arrive(sb + BAR_AI); bulk_wait(); hint_signal(p.sync + 4); mbar_arrive(sb + BAR_AW); STAMP(16); }
    __syncwarp();
    bar_sync(13, 384);
    if (!B_HOLD && lane == 0) { tma_store_ef(tmb + TM_XB, cta * 64, 0, sb + OFF_SB); bulk_commit(); }
    __syncwarp();
    ext_send(1);
    mbar_arrive(sb + BAR_AX, lane == 0);
    if (B_HOLD) mbar_wait(sb + (B_HOLD == 1 ? BAR_HA : BAR_XA));
    if (BDEL) __nanosleep(BDEL);
    if (lane == 0) {
      bulk_wait();
#pragma unroll 1
      for (int r = B_HOLD ? 0 : BROWS; r < G; r += BROWS) { tma_store_ef(tmb + TM_XB, cta * 64, r, sb + OFF_SB + r * 256); bulk_commit(); bulk_wait(); }
      hint_signal(p.sync + 5);
#pragma unroll 1
      for (int i = 0; i < PFE; i++) prefetch_e(i);
      STAMP(17);
    }
    __syncwarp();
  } else {
    {
      uint32_t d[4 * NCH], jj[4 * NCH], rr[4 * NCH];
      auto count = [&](int k) {
        mbar_wait(sb + BAR_DST + k * 8);
        lds128(d + 4 * k, sb + OFF_DST + (tid + NWK * k) * 16);
#pragma unroll
        for (int i = 4 * k; i < 4 * k + 4; i++) { jj[i] = d[i] * p.magic; rr[i] = atoms_add(__dp4a(jj[i], 0x04000000u, sb + OFF_BC), 0x202u); }
      };
      auto place = [&](int k) {
#pragma unroll
        for (int i = 4 * k; i < 4 * k + 4; i++) {
          const uint32_t o = __dp4a(jj[i], 0x80000000u, rr[i] & 0x807Eu);
          d[i] = (d[i] & 511) | (tag >> 16);
          asm("{.reg .pred p; setp.ge.u32 p, %1, 0x8000; @p add.u32 %0, %2, %3;}" : "+r"(d[i]) : "r"(o), "r"(tid * 4), "r"(NWK * k * 4 + (i & 3)));
          sts16(sb + OFF_SA + o, d[i]); jj[i] = __viaddmin_u32(o, o, G * 256);
        }
      };
      count(0); STAMP(1); count(1); get_tag(); place(0); count(2); place(1); count(3); place(2);
      if (wid < 4) { count(4); STAMP(15); place(3); place(4); } else place(3);
      proxy_fence();
      bar_arrive(12, 384);
      STAMP(2);
      mbar_wait(sb + BAR_AI);
      mbar_wait(sb + BAR_SRC); mbar_wait(sb + BAR_SRC + 8); mbar_wait(sb + BAR_SRC + 16);
      STAMP(12);
#pragma unroll
      for (int k = 0; k < NCH; k++) lds128(d + 4 * k, sb + OFF_SRCI + (tid + NWK * k) * 16);
      const uint32_t tb = tag + (tid << 18);
#pragma unroll
      for (int i = 0; i < 4 * NCH; i++) if (i < 4 * NCH - 4 || wid < 4) sts32(sb + OFF_SB + jj[i], d[i] + tb + ((NWK * (i >> 2) * 4 + (i & 3)) << 16));
      proxy_fence();
      bar_arrive(13, 384);
      STAMP(3);
    }
    const uint32_t rot = (lane + cta) & 31;
    cb = sb + OFF_CNT - (tag >> 14);
    {
      const uint32_t* xa = (const uint32_t*)(p.xa + (cta * G + wid) * 8) + rot;
      if (wid < 8) { const uint32_t e_ = ealo + epad * 32;
        mbar_wait(sb + BAR_AX);
#pragma unroll
        for (int i = 0; i < 7; i++) sts128(sb + OFF_TE + tid * 16 + i * 4096, e_, e_, e_, e_); }
      static_assert(SCAP * 64 == 7 * 4096, "fill");
      if (wid == 10) { hint_wait(p.sync + 4, ep * G); mbar_arrive(sb + BAR_HA, lane == 0); }
      mbar_wait(sb + BAR_HA);
      STAMP(14);
      const uint32_t tp = tag | (tag >> 16);
      uint32_t st;
#pragma unroll 1
      for (int spin = 0;; spin++) {
        st = 0;
#pragma unroll
        for (int k = 0; k < 12; k++) asm volatile("ld.relaxed.gpu.global.u32 %0, [%1];" : "=r"(pk[k]) : "l"(xa + k * 352) : "memory");
#pragma unroll
        for (int k = 0; k < 12; k++) st |= pk[k] ^ tp;
        st = __reduce_or_sync(~0u, st);
        if (!(st >> 30)) break;
        trap_if(spin > 2000000);
      }
      if (st & 0x3C00FC00u) {
#pragma unroll 1
        for (;;) {
          uint32_t x = 0, row = 0;
#pragma unroll
          for (int k = 0; k < 12; k++) { const uint32_t y = (pk[k] ^ tp) & 0x3C00FC00u; if (!x && y) { x = y; row = wid + 11 * k; pk[k] ^= y; } }
          if (!__any_sync(~0u, x)) break;
          const uint32_t n = ((x >> 10) & 63) | ((x >> 20) & 0x1C0);
          if (x >> 29) {
            const uint32_t r = atoms_add(sb + OFF_CNT + n * 4, 16), idx = atoms_add(sb + OFF_MISC + 4, 1);
            if (idx < 256) sts32(sb + OFF_EXT + idx * 4, n | (row << 9) | (lane << 17) | (min(r >> 4, 255u) << 22));
            else x = 1;
          }
          if (x && !(x >> 29)) sts32(sb + OFF_MISC + 8, 1);
          __syncwarp();
        }
      }
#pragma unroll
      for (int k = 0; k < 12; k++) { r0[k] = mad16(pk[k], 0x0004u, cb); r1[k] = mad16(pk[k], 0x0400u, cb); vb[k].x = atoms_add(r0[k], 16); vb[k].y = atoms_add(r1[k], 16); }
      if (B_HOLD == 2) mbar_arrive(sb + BAR_XA, lane == 0);
    }
    STAMP(4);
    if (wid >= 6) bar_arrive(11, NWK);
    if (wid < 6) {
      uint32_t ca[2], ky[2], dr[2], sq[2], ps[4];
#pragma unroll
      for (int i = 0; i < 2; i++) { ca[i] = sb + OFF_CNT + ((node0 + tid + 192 * i) & 511) * 4; lds64(ps[2 * i], ps[2 * i + 1], sb + OFF_POS + (tid + 192 * i) * 8); ps[2 * i + 1] |= (tid + 192 * i) << 16; }
      bar_sync(11, NWK);
      STAMP(5);
#pragma unroll
      for (int i = 0; i < 2; i++) ky[i] = (lds32(ca[i]) + 16) >> 5;
      if (max(ky[0], ky[1]) > 31) sts32(sb + OFF_MISC + 8, 1);
#pragma unroll
      for (int i = 0; i < 2; i++) { ky[i] = min(ky[i], 31u); dr[i] = atoms_add(sb + OFF_DH + ky[i] * 4, 1); }
      bar_sync(10, 192);
      const uint32_t hv = lds32(sb + OFF_DH + lane * 4);
      uint32_t inc = hv;
#pragma unroll
      for (int o = 1; o < 32; o <<= 1) asm("{.reg .pred p; .reg .b32 y; shfl.sync.down.b32 y|p, %0, %1, 31, -1; @p add.u32 %0, %0, y;}" : "+r"(inc) : "r"(o));
#pragma unroll
      for (int i = 0; i < 2; i++) {
        const uint32_t pos = __shfl_sync(~0u, inc - hv, ky[i]) + dr[i];
        const uint32_t ak = (uint32_t)(QCODE >> ((pos >> 5) * 4)) & 15, l = (pos >> 3) & 3;
        sq[i] = (ak >> 2) * 16 + ((QREV >> (pos >> 5) & 1) ? 3 - l : l) * 4 + (ak & 3);
        dr[i] = pos & 7;
        asm volatile("{.reg .pred p; setp.eq.u32 p, %2, 0; @p st.shared.u8 [%0], %1;}" :: "r"(sb + OFF_LEN + sq[i]), "r"(max(ky[i], 1u)), "r"(dr[i]) : "memory");
        sts64(sb + OFF_GP + sq[i] * 64 + dr[i] * 8, ps[2 * i], ps[2 * i + 1]);
        sts16(sb + OFF_INV + (tid + 192 * i) * 2, sq[i] * 64 + dr[i] * 8);
      }
      bar_sync(10, 192);
      const uint32_t ln = lds32(sb + OFF_LEN + min(lane, 11) * 4), tot = __dp4a(ln, 0x01010101u, 0u);
      inc = tot;
#pragma unroll
      for (int o = 1; o < 16; o <<= 1) asm("{.reg .pred p; .reg .b32 y; shfl.sync.up.b32 y|p, %0, %1, 0, -1; @p add.u32 %0, %0, y;}" : "+r"(inc) : "r"(o));
      if (wid == 1) sts32(sb + OFF_CNT + 2048 + lane * 4, 0);
      if (tid < 12) { sts32(sb + OFF_LEN + 64 + tid * 4, inc - tot); if (inc > SCAP - 12) sts32(sb + OFF_MISC + 8, 1); }
#pragma unroll
      for (int i = 0; i < 2; i++) sts32(ca[i], __dp4a(__shfl_sync(~0u, ln, sq[i] >> 2), 0x00010101u >> (24 - 8 * (sq[i] & 3)), __shfl_sync(~0u, inc - tot, sq[i] >> 2)) * 32 + dr[i] * 2);
    }
    bar_arrive(7, 384);
  }
  bar_sync(1, 384);
  STAMP(6);
  if (wid != 11 && !__shfl_sync(~0u, lds32(sb + OFF_MISC + 8), 0)) {
#pragma unroll
    for (int k = 0; k < 12; k++) { r0[k] = lds32(r0[k]); r1[k] = lds32(r1[k]); }
#pragma unroll
    for (int k = 0; k < 12; k++) { r0[k] += vb[k].x; r1[k] += vb[k].y; }
  } else {
#pragma unroll
    for (int k = 0; k < 12; k++) r0[k] = r1[k] = 0x8000;
  }
  auto put_ids = [&]() {
    const uint32_t id = wid * 256 + ((lane + cta) & 31) * 8;
    auto put = [&](uint32_t x, uint32_t v) { asm volatile("{.reg .pred p; setp.lt.u32 p, %0, 0x8000; @p st.shared.u16 [%0+%2], %1;}" :: "r"(x), "h"((uint16_t)v), "n"(sb + OFF_TS) : "memory"); };
#pragma unroll
    for (int k = 0; k < 12; k++) { put(IDL ? pk[k] & 0xFFFF : r0[k], id + k * 2816); put(IDL ? pk[k] >> 16 : r1[k], id + k * 2816 + 4); }
  };
  if (!IDL) put_ids();
  STAMP(7);
  mbar_wait(sb + BAR_QR);
  asm volatile("setmaxnreg.inc.sync.aligned.u32 160;");
  if (IDL) {
#pragma unroll
    for (int k = 0; k < 12; k++) asm volatile("prmt.b32 %0, %1, %2, 0x5410;" : "=r"(pk[k]) : "r"(r0[k]), "r"(r1[k]));
  }
  uint32_t pa[8], sp[8], pq[16]; float chk = 0.f;
  {
    uint32_t hf[32], mp = 0; float a0[32], a1[32];
    const uint32_t an = sb + OFF_GP + wid * 256 + (lane & 15) * 8 + 6, n0 = lds16(an), n1 = lds16(an + 128);
#pragma unroll
    for (int j = 0; j < 8; j++) { const uint32_t nd = j < 4 ? n0 : n1; ldsm4(hf + 4 * j, (sb + OFF_H + nd * 128 + (((nd & 7) << 4) ^ (lane & 16))) ^ ((j & 3) << 5)); }
    const uint64_t db = DHI | ((sb + OFF_W + 8192) >> 4);
    wg_fence();
    rs64b<0>(a0, hf[0], hf[1], hf[2], hf[3], db); rs64b<1>(a0, hf[4], hf[5], hf[6], hf[7], db + 128); rs64b<1>(a0, hf[8], hf[9], hf[10], hf[11], db + 256); rs64b<1>(a0, hf[12], hf[13], hf[14], hf[15], db + 384);
    wg_commit();
    rs64b<0>(a1, hf[16], hf[17], hf[18], hf[19], db); rs64b<1>(a1, hf[20], hf[21], hf[22], hf[23], db + 128); rs64b<1>(a1, hf[24], hf[25], hf[26], hf[27], db + 256); rs64b<1>(a1, hf[28], hf[29], hf[30], hf[31], db + 384);
    wg_commit();
    if (IDL) put_ids();
    asm volatile("wgmma.wait_group.sync.aligned 1;" ::: "memory"); fence_regs(a0);
#pragma unroll
    for (int j = 0; j < 8; j++) { const uint32_t x = pack_f16(.5f * a0[4 * j], .5f * a0[4 * j + 1]), y = pack_f16(.5f * a0[4 * j + 2], .5f * a0[4 * j + 3]); mp = hmag(hmag(mp, x), y);
      asm volatile("movmatrix.sync.aligned.m8n8.trans.b16 %0, %1;" : "=r"(pa[j]) : "r"(x)); asm volatile("movmatrix.sync.aligned.m8n8.trans.b16 %0, %1;" : "=r"(sp[j]) : "r"(y)); }
    wg_wait0(); fence_regs(a1);
    bar_arrive(4, 416);
#pragma unroll
    for (int j = 0; j < 16; j++) { pq[j] = pack_f16(.5f * a1[2 * j], .5f * a1[2 * j + 1]); mp = hmag(mp, pq[j]); }
    if (magr(mp) >= 0x7000) chk = __int_as_float(0x7FC00000);
  }
  if (wid == 0) STAMP(23);
  uint32_t bad;
  {
    const uint32_t ring = sb + OFF_RING + wid * STG, p2 = sb + OFF_P2 + wid * 2048;
    uint32_t lens = __shfl_sync(~0u, lds32(sb + OFF_LEN + wid * 4), 0);
    uint32_t rem = __dp4a(lens, 0x20202020u, 0u);
    const uint32_t base = min(lds32(sb + OFF_LEN + 64 + wid * 4), SCAP);
    uint32_t a_s = sb + OFF_TS + base * 32 + (lane >> 3) * 8, a_e = sb + OFF_TE + base * 64 + (lane >> 1) * 4;
    uint32_t k0 = (uint32_t)(uint64_t)p.q + (((lane & 7) ^ ((lane >> 1) & 4)) << 4), k1 = k0 ^ 16, k2 = k0 ^ 32, k3 = k0 ^ 48, ke = ((lane ^ (lane >> 3)) & 1) << 4;
    uint32_t dst0 = ring + (lane >> 3) * 640 + (lane & 7) * 16;
    const uint32_t qhi = (uint32_t)((uint64_t)p.q >> 32), ehi = (uint32_t)((uint64_t)p.ea >> 32);
    uint32_t s0, s1, ev, to = 0, so = 12 * STG;
    auto tl_ = [&]() { lds64(s0, s1, a_s + to); asm volatile("ld.shared.u32 %0, [%1]; add.u32 %1, %1, 64;" : "=&r"(ev), "+r"(a_e) :: "memory"); to += 32; };
#define CPQ(LH, x, k, off) "dp2a." LH ".u32.u32 lo, " x ", 0x80000080, " k "; mov.b64 a, {lo, %7}; @p cp.async.cg.shared.global [%0+" #off "], [a], 16;\n"
#define CPE "or.b32 lo, %10, %11; mov.b64 a, {lo, %12}; @p cp.async.cg.shared.global" ESZ " [%0+512], [a], 16;\n"
#define CPA(BODY) asm volatile("{.reg .b32 lo; .reg .b64 a; .reg .pred p; setp.le.u32 p, %8, %9;\n" BODY "}" \
      :: "r"(dst0 + so), "r"(s0), "r"(s1), "r"(k0), "r"(k1), "r"(k2), "r"(k3), "r"(qhi), "r"(to), "r"(rem), "r"(ev), "r"(ke), "r"(ehi) : "memory")
#define CPQ4 CPQ("lo", "%1", "%3", 0) CPQ("hi", "%1", "%4", 128) CPQ("lo", "%2", "%5", 256) CPQ("hi", "%2", "%6", 384) "cp.async.commit_group;"
    auto issue = [&]() { CPA(CPE CPQ4); so = so == (NST - 1) * 12 * STG ? 0 : so + 12 * STG; };
    const int g = lane >> 2, qd = lane & 3;
    const uint32_t sw = ((lane >> 4) ^ (lane & 7)) << 4, fr = (lane & 15) * 128 + sw;
    uint32_t qa0 = ring + (g & 3) * 640 + qd * 128 + sw, qa1 = qa0 ^ 32, qa2 = qa0 ^ 64, qa3 = qa0 ^ 96;
    uint32_t eadr = ring + 512 + (g & 3) * 640 + qd * 32 + ((((lane >> 4) ^ g) & 1) << 4);
    uint32_t oh0 = g == 2 * qd ? 0x3C00u : g == 2 * qd + 1 ? 0x3C000000u : 0u, oh1 = oh0;
    uint32_t a_g = sb + OFF_GP + wid * 256 + lane * 2;
    uint32_t a_n = sb + OFF_GP + wid * 256 + (lane & 15) * 8 + 6;
    uint32_t a_p = ((lane & 8) ? p2 : sb + OFF_WD) + (lane & 7) * 128 + ((((lane >> 4) ^ lane) & 7) << 4);
    uint32_t a_w = sb + OFF_W3 + fr;
#define OPQ4(A, B, C, D) asm volatile("shfl.sync.bfly.b32 %0, %0, 0, 31, -1; shfl.sync.bfly.b32 %1, %1, 0, 31, -1; shfl.sync.bfly.b32 %2, %2, 0, 31, -1; shfl.sync.bfly.b32 %3, %3, 0, 31, -1;" : "+r"(A), "+r"(B), "+r"(C), "+r"(D))
    asm volatile("shfl.sync.idx.b32 %0, %0, %1, 31, -1;" : "+r"(oh1) : "r"(lane));
    if (OPQ & 1) OPQ4(a_w, oh0, ke, dst0);
    if (OPQ & 2) OPQ4(qa0, qa1, qa2, qa3);
    if (OPQ & 4) OPQ4(k0, k1, k2, k3);
    if (OPQ & 8) OPQ4(a_g, a_n, a_p, eadr);
    uint32_t w3[16], wv[8], bp[16], sum[8], Y[16], M[16], own, ownp, dpk; uint16_t tl[16], th[16];
    float pacc = 0.f;
    auto wload = [&]() {
#pragma unroll
      for (int j = 0; j < 4; j++) ldsm4t(w3 + 4 * j, a_w ^ (j << 5));
      lds128(wv, sb + OFF_WX + (a_g & 6) * 16); lds128(wv + 4, sb + OFF_WX + 16 + (a_g & 6) * 16);
    };
    auto hload = [&](uint32_t (&hf)[16], uint32_t nd) {
      const uint32_t hrow = sb + OFF_H + nd * 128 + (((nd & 7) << 4) ^ ((a_g >> 1) & 16));
#pragma unroll
      for (int j = 0; j < 4; j++) ldsm4(hf + 4 * j, hrow ^ (j << 5));
      return hrow;
    };
    auto bload = [&](uint32_t o) {
#pragma unroll
      for (int j = 0; j < 4; j++) ldsm4t(bp + 4 * j, (a_p ^ (j << 5)) + o);
    };
    { uint32_t wd[8]; const uint32_t a = sb + OFF_WD + (lane & 7) * 128 + ((((lane >> 3) ^ lane) & 7) << 4);
      ldsm4t(wd, a); ldsm4t(wd + 4, a ^ 64);
#pragma unroll
      for (int j = 0; j < 8; j++) { bp[2 * j] = wd[j]; bp[2 * j + 1] = pa[j]; } }
    own = lds16(a_g) * 0x10001u;
    wload();
    if (__shfl_sync(~0u, lds32(sb + OFF_MISC + 8), 0)) rem = 0;
    auto resolve = [&](auto NBK, uint32_t o) {
      constexpr int NB = decltype(NBK)::value;
      uint32_t id[NB], c0[NB], c1[NB]; const uint32_t a = base * 32 + o + lane * 4;
#pragma unroll
      for (int i = 0; i < NB; i++) { id[i] = lds32(sb + OFF_TS + a + i * 128); if (o + lane * 4 + i * 128 >= rem) id[i] = XPAD * 0x10001u; }
      uint32_t st = 0;
#pragma unroll
      for (int i = 0; i < NB; i++) { c0[i] = lds32(sb + OFF_XB + (id[i] & 0xFFFF)); c1[i] = lds32(sb + OFF_XB + (id[i] >> 16)); }
#pragma unroll
      for (int i = 0; i < NB; i++) st |= (c0[i] ^ tag) | (c1[i] ^ tag);
      for (int spin = 0; __any_sync(~0u, st >> 30); spin++) {
        st = 0; trap_if(spin > 2000000);
#pragma unroll
        for (int i = 0; i < NB; i++) {
          asm volatile("{.reg .pred p, q; setp.lt.u32 p, %4, %6; setp.lt.u32 q, %5, %6; @p ld.relaxed.gpu.global.u32 %0, [%2]; @q ld.relaxed.gpu.global.u32 %1, [%3];}"
            : "+r"(c0[i]), "+r"(c1[i]) : "l"((const char*)p.xb + cta * XPAD + (id[i] & 0xFFFF)), "l"((const char*)p.xb + cta * XPAD + (id[i] >> 16)), "r"(id[i] & 0xFFFF), "r"(id[i] >> 16), "n"(XPAD) : "memory");
          st |= (c0[i] ^ tag) | (c1[i] ^ tag); }
      }
#pragma unroll
      for (int i = 0; i < NB; i++) { const uint32_t j0 = (id[i] >> 8) & 255, j1 = id[i] >> 24;
        if (ABL & 2) { c0[i] &= 0xFFFF0FFFu; c1[i] &= 0xFFFF0FFFu; }
        asm volatile("{.reg .pred p, q, r; setp.lt.u32 p, %5, %9; setp.lt.u32 q, %6, %9; setp.lt.u32 r, %7, %8;\n"
          "@p st.shared.u32 [%0], %2; @q st.shared.u32 [%0+4], %3; @r st.shared.u32 [%1], %4;}"
          :: "r"(sb + OFF_TE + 2 * a + i * 256), "r"(sb + OFF_TS + a + i * 128), "r"(mad16(c0[i], 0x2000u, eb0 + ((ABL & 1) ? j0 & 7 : j0) * p.EPC * 32)), "r"(mad16(c1[i], 0x2000u, eb0 + ((ABL & 1) ? j1 & 7 : j1) * p.EPC * 32)),
             "r"(__byte_perm(c0[i], c1[i], 0x5410)), "r"(j0), "r"(j1), "r"(o + lane * 4 + i * 128), "r"(rem), "n"(G) : "memory"); }
    };
    bar_sync(2, 384);
    if (wid == 0) STAMP(27);
    mbar_wait(sb + BAR_HB);
    if (wid == 0) STAMP(22);
#pragma unroll 1
    for (uint32_t o = 0, go = 0; go < 32 * NST; o += 128 * RNB) {
      if (o < rem) { resolve(IC<RNB>(), o);
        asm volatile("{.reg .pred p; mbarrier.test_wait.parity.shared::cta.b64 p, [%1], 0; vote.sync.all.pred p, p, -1; selp.u32 %0, %2, 0, p;}" : "=r"(go) : "r"(sb + BAR_QP), "n"(32 * NEARLY) : "memory"); }
      else { bar_sync(8, 384); mbar_wait(sb + BAR_QP); go = 32 * NST; if (wid == 0) STAMP(24); }
      __syncwarp();
#pragma unroll 1
      while (to < go) { tl_(); issue(); if (to == 32) STAMP(13); }
    }
    bad = __shfl_sync(~0u, lds32(sb + OFF_MISC + 8), 0);
   if (!bad) {
#pragma unroll
    for (int j = 0; j < 4; j++) stsm4((p2 + fr) ^ (j << 5), pq[4 * j], pq[4 * j + 1], pq[4 * j + 2], pq[4 * j + 3]);
    auto body = [&](auto MODE) {
      constexpr int mode = decltype(MODE)::value;
      uint32_t T[16], ef[4], q0, q1, x0, x1, x2; float e0_, e1_, cs[4];
      auto mu = [&](int j) {
#pragma unroll
        for (int i = 2 * j; i < 2 * j + 2; i++) asm volatile("{.reg .b16 l, h; mov.b32 {l, h}, %2; tanh.approx.f16 %0, l; tanh.approx.f16 %1, h;}" : "=h"(tl[i]), "=h"(th[i]) : "r"(Y[i])); };
      auto fi = [&](int j) {
#pragma unroll
        for (int i = 2 * j; i < 2 * j + 2; i++) asm volatile("{.reg .b32 t; mov.b32 t, {%2, %3}; fma.rn.f16x2 %0, %1, t, %1;}" : "=r"(M[i]) : "r"(Y[i]), "h"(tl[i]), "h"(th[i])); };
      auto ad = [&](int j) { asm volatile("add.rn.f16x2 %0, %0, %1; add.rn.f16x2 %0, %0, %2;" : "+r"(sum[j]) : "r"(M[2 * j]), "r"(M[2 * j + 1])); };
      auto he = [&](int j) { asm volatile("mma.sync.aligned.m16n8k16.row.col.f16.f16.f16.f16 {%0,%1}, {%2,%3,%4,%5}, {%6,%7}, {%0,%1};" : "+r"(T[2 * j]), "+r"(T[2 * j + 1]) : "r"(ef[0]), "r"(ef[1]), "r"(ef[2]), "r"(ef[3]), "r"(w3[2 * j]), "r"(w3[2 * j + 1])); };
      auto hs = [&](int j) { asm volatile("mma.sync.aligned.m16n8k16.row.col.f16.f16.f16.f16 {%0,%1}, {%2,%3,%4,%5}, {%6,%7}, {%8,%9};" : "=r"(Y[2 * j]), "=r"(Y[2 * j + 1]) : "r"(q0), "r"(q1), "r"(oh0), "r"(oh1), "r"(bp[2 * j]), "r"(bp[2 * j + 1]), "r"(T[2 * j]), "r"(T[2 * j + 1])); };
      auto hc = [&](int j) {
        if (j) asm volatile("mma.sync.aligned.m16n8k16.row.col.f32.f16.f16.f32 {%0,%1,%2,%3}, {%4,%5,%6,%7}, {%8,%9}, {%0,%1,%2,%3};" : "+f"(cs[0]), "+f"(cs[1]), "+f"(cs[2]), "+f"(cs[3]) : "r"(M[4 * j]), "r"(M[4 * j + 1]), "r"(M[4 * j + 2]), "r"(M[4 * j + 3]), "r"(wv[2 * j]), "r"(wv[2 * j + 1]));
        else asm volatile("mma.sync.aligned.m16n8k16.row.col.f32.f16.f16.f32 {%0,%1,%2,%3}, {%4,%5,%6,%7}, {%8,%9}, {%10,%10,%10,%10};" : "=f"(cs[0]), "=f"(cs[1]), "=f"(cs[2]), "=f"(cs[3]) : "r"(M[0]), "r"(M[1]), "r"(M[2]), "r"(M[3]), "r"(wv[0]), "r"(wv[1]), "f"(0.f)); };
      auto cv = [&](int i) { asm volatile("{.reg .b32 a, b; shl.b32 a, %0, 16; and.b32 b, %0, 0xFFFF0000; cvt.rn.f16x2.f32 %0, b, a;}" : "+r"(ef[i])); };
      auto un = [&]() { asm volatile("shl.b32 %0, %2, 16; and.b32 %1, %2, 0xFFFF0000;" : "=&f"(e0_), "=&f"(e1_) : "r"(dpk)); };
      auto ex0 = [&]() { asm volatile("prmt.b32 %0, %3, %4, 0x6420; prmt.b32 %1, %5, %6, 0x6420; prmt.b32 %2, %7, %8, 0x6420;" : "=&r"(x0), "=&r"(x1), "=&r"(x2) : "r"(T[0]), "r"(T[1]), "r"(T[2]), "r"(T[3]), "r"(T[4]), "r"(T[5])); };
      auto ex1 = [&]() { asm volatile("{.reg .b32 a, b; shl.b32 a, %2, 3; shl.b32 b, %3, 6; lop3.b32 a, %1, a, 0x38383838, 0xD8; lop3.b32 a, a, b, 0xC0C0C0C0, 0xD8; sub.rn.bf16x2 %0, %4, a;}" : "=r"(dpk) : "r"(x0), "r"(x1), "r"(x2), "r"(own)); };
      auto ex2 = [&]() { asm volatile("{.reg .b32 a, b, d, u; .reg .b16 l, h; shl.b32 a, %2, 16; and.b32 b, %2, 0xFFFF0000; cvt.rn.f16x2.f32 d, b, a; mul.rn.f16x2 %0, d, d; mov.b32 {l, h}, d; mov.b32 u, {h, h}; mul.rn.f16x2 %1, u, u;}" : "=&r"(q0), "=&r"(q1) : "r"(dpk)); };
      auto pf = [&]() { asm volatile("fma.rn.f32 %0, %1, %2, %0; fma.rn.f32 %0, %3, %4, %0;" : "+f"(pacc) : "f"(cs[0]), "f"(e0_), "f"(cs[2]), "f"(e1_)); };
#define FX(k) if (FM >> k & 1) asm volatile("pmevent 1;" ::: "memory")
      if (mode == 2) {
        hc(0); mu(3); fi(2); un(); ad(0); ad(1); mu(4); fi(3); hc(1); mu(5); fi(4); ad(2); mu(6); fi(5); ad(3); hc(2); mu(7); fi(6); fi(7); ad(4); ad(5); hc(3); ad(6); ad(7); pf();
        return;
      }
      asm volatile("cp.async.wait_group %0;" :: "n"(NST - 1) : "memory");
      __syncwarp();
      if (mode == 1) STAMP(8);
      ldsm4(ef, eadr + so); ldsm4(T, qa0 + so); ldsm4(T + 4, qa1 + so); ldsm4(T + 8, qa2 + so); ldsm4(T + 12, qa3 + so);
      tl_();
      if (mode == 1) {
        issue();
        cv(0); cv(1); cv(2); cv(3); ex0(); ex1(); ex2();
#pragma unroll
        for (int j = 0; j < 8; j++) { he(j); hs(j); }
        mu(0); mu(1); fi(0); mu(2); fi(1);
        return;
      }
      hc(0); mu(3); fi(2); un(); ad(0); ad(1);
      FX(0);
      mu(4); fi(3); cv(0); cv(1); cv(2); cv(3); ex0(); ex1();
      FX(1);
      he(0); he(1); hc(1); mu(5); fi(4); ex2(); ad(2);
      FX(2);
      hs(0); he(2); mu(6); fi(5); issue(); ad(3);
      FX(3);
      hs(1); he(3); hc(2); mu(7); fi(6);
      FX(4);
      hs(2); hs(3); he(4); he(5); mu(0); fi(7); ad(4); ad(5);
      FX(5);
      hc(3); hs(4); he(6); he(7); mu(1); fi(0); ad(6);
      FX(6);
      hs(5); hs(6); hs(7); mu(2); fi(1); ad(7); pf();
      FX(7);
    };
#pragma unroll
    for (int j = 0; j < 8; j++) sum[j] = 0;
    body(IC<1>());
    int cnt = (lens & 255) - 1;
    auto flush = [&]() {
      asm volatile("{.reg .pred p; setp.ne.u32 p, %2, 6; @p st.shared.u16 [%0+-64], %1;}" :: "r"(a_g), "h"((uint16_t)pack_bf16(bf_hi(ownp) + pacc, 0.f)), "r"(a_g & 6) : "memory");
      chk = fmaf(pacc, 0.f, chk); pacc = 0.f; };
    constexpr uint64_t b1 = DHI | ((sb + OFF_W) >> 4), b2_ = b1 + 512;
    auto mma_h = [&](float (&acc)[32], uint32_t (&hf)[16]) {
      rs64b<0>(acc, hf[0], hf[1], hf[2], hf[3], b1); rs64b<1>(acc, hf[4], hf[5], hf[6], hf[7], b1 + 128); rs64b<1>(acc, hf[8], hf[9], hf[10], hf[11], b1 + 256); rs64b<1>(acc, hf[12], hf[13], hf[14], hf[15], b1 + 384); };
    auto mma_m = [&](float (&acc)[32]) {
      rs64h<1>(acc, sp[0], sum[0], sp[1], sum[1], b2_); rs64h<1>(acc, sp[2], sum[2], sp[3], sum[3], b2_ + 128); rs64h<1>(acc, sp[4], sum[4], sp[5], sum[5], b2_ + 256); rs64h<1>(acc, sp[6], sum[6], sp[7], sum[7], b2_ + 384);
      wg_commit(); wg_wait0(); fence_regs(acc);
      STAMP(10);
      chk = fmaf(acc[0], 0.f, fmaf(acc[2], 0.f, chk)); };
    auto roff = [&](uint32_t nd, int r) { return __shfl_sync(~0u, nd, ((a_g >> 3) & 7) + 8 * r) * 128 + (a_g & 6) * 8; };
    auto radr = [&](uint32_t o, int k) { return sb + OFF_H + (o ^ ((o >> 3) & 0x70) ^ ((k >> 1) << 6)); };
    auto fin = [&](float (&acc)[32], uint32_t* x, int k) {
#pragma unroll
      for (int i = 0; i < 4; i++) { const int c = 16 * (k >> 1) + 4 * i + 2 * (k & 1); x[i] = u2(__hadd2(b2(x[i]), b2(pack_bf16(silu_h(acc[c]), silu_h(acc[c + 1]))))); } };
#pragma unroll 1
    for (int t = 0;; t++) {
#pragma unroll 1
      for (; cnt > 0; cnt--) { body(IC<0>());
      }
      if (!(t & 1)) {
        ownp = own; a_g += 64;
        if (t == 6) break;
        own = lds16(a_g) * 0x10001u;
        if (t == 0) {
#pragma unroll
          for (int j = 0; j < 8; j++) bp[2 * j + 1] = sp[j];
        } else bload((a_g & 16) ? (t & 4) * 256 : 0);
        lens >>= 8; cnt = 1;
        continue;
      }
      cnt = (lens & 255) - 1;
      flush();
      if (t == 3) {
        uint32_t hf[16]; float acc[32];
        const uint32_t nd = lds16(a_n), o[2] = {roff(nd, 0), roff(nd, 1)};
        hload(hf, nd);
        mbar_wait(sb + BAR_WH);
        wg_fence();
        mma_h(acc, hf); mma_m(acc);
#pragma unroll
        for (int k = 0; k < 4; k++) lds128(hf + 4 * k, radr(o[k & 1], k));
#pragma unroll
        for (int k = 0; k < 4; k++) { fin(acc, hf + 4 * k, k); sts128(radr(o[k & 1], k), hf[4 * k], hf[4 * k + 1], hf[4 * k + 2], hf[4 * k + 3]); }
        __syncwarp();
        mbar_arrive(sb + BAR_M, (a_g & 62) == 0);
        wload();
      }
#pragma unroll
      for (int j = 0; j < 8; j++) { sp[j] = sum[j]; asm volatile("mov.b32 %0, 0;" : "=r"(sum[j])); }
    }
    {
      uint32_t hf[16], v[16]; float acc[32];
      const uint32_t nd = lds16(a_n + 128), o[2] = {roff(nd, 0), roff(nd, 1)};
      hload(hf, nd);
#pragma unroll
      for (int k = 0; k < 4; k++) lds128(v + 4 * k, radr(o[k & 1], k));
      wg_fence(); mma_h(acc, hf); wg_commit();
      body(IC<2>());
      STAMP(9);
      flush();
      __syncwarp();
      mbar_arrive(sb + BAR_X, lane == 0);
      wg_fence();
      mma_m(acc);
#pragma unroll
      for (int k = 0; k < 4; k++) { fin(acc, v + 4 * k, k);
        asm volatile("{.reg .pred p; setp.lt.u32 p, %5, %6; @p st.global" OCS ".v4.b32 [%0], {%1,%2,%3,%4};}" :: "l"((const char*)p.out + (size_t)node0 * 128 + o[k & 1] + (k >> 1) * 64), "r"(v[4 * k]), "r"(v[4 * k + 1]), "r"(v[4 * k + 2]), "r"(v[4 * k + 3]), "r"(o[k & 1]), "r"(nloc * 128) : "memory"); }
    }
    asm volatile("{.reg .pred p, q; setp.neu.f32 p, %1, 0f00000000; setp.ne.or.u32 p, %2, 0, p; bar.red.or.pred q, 5, %3, p; selp.u32 %0, 1, 0, q;}" : "=r"(bad) : "f"(chk), "r"(lds32(sb + OFF_MISC + 12)), "n"(DEFO ? 512 : 384) : "memory");
    STAMP(11);
   } else { asm volatile("cp.async.wait_all;" ::: "memory"); bar_sync(5, 384); }
  }
  if (bad) slow_path(p, wid, lane, node0, nloc);
}

}

typedef CUresult (*EncodeFn)(CUtensorMap*, CUtensorMapDataType, cuuint32_t, void*, const cuuint64_t*, const cuuint64_t*, const cuuint32_t*, const cuuint32_t*,
                             CUtensorMapInterleave, CUtensorMapSwizzle, CUtensorMapL2promotion, CUtensorMapFloatOOBfill);

extern "C" void kernel_launch(void* const* d_in, const int* in_sizes, int n_in, void* d_out, int out_size) {
  Params p; Maps maps;
  p.h = (const uint4*)d_in[0]; p.pos = (const uint16_t*)d_in[1]; p.ea = (const uint4*)d_in[2];
  p.src = (const int*)d_in[3]; p.dst = (const int*)d_in[4];
  p.we = (const uint16_t*)d_in[5]; p.wx = (const uint16_t*)d_in[6]; p.wh = (const uint16_t*)d_in[7];
  p.out = (uint16_t*)d_out;
  p.N = in_sizes[0] / 64; p.E = in_sizes[3];
  p.EPC = ((p.E + G * 4 - 1) / (G * 4)) * 4;
  p.magic = (uint32_t)(((uint64_t)G << 24) / (uint64_t)p.N);
  p.inv = (1ull << 56) / p.magic;
  const uint64_t ea0 = (uint64_t)d_in[2], ea1 = ea0 + (uint64_t)p.E * 32 - 1;
  p.force_slow = ((ea0 >> 32) != (ea1 >> 32)) || (ea0 & 31) || (p.E & 3);
  void* qp = nullptr;
  cudaGetSymbolAddress(&qp, g_q);
  p.q = (char*)qp;
  if (((uint64_t)p.q >> 32) != (((uint64_t)p.q + QBYTES) >> 32)) p.q += QBYTES;
  cudaGetSymbolAddress((void**)&p.sync, g_sync); cudaGetSymbolAddress((void**)&p.xe, g_xe);
  cudaGetSymbolAddress((void**)&p.xa, g_xa); cudaGetSymbolAddress((void**)&p.xb, g_xb);
  void* fn = nullptr; cudaDriverEntryPointQueryResult qr;
  cudaGetDriverEntryPoint("cuTensorMapEncodeTiled", &fn, cudaEnableDefault, &qr);
  auto mk = [&](CUtensorMap* tm, void* base, int rows, int box = 64) {
    const cuuint64_t dim[2] = {64, (cuuint64_t)rows}, str[1] = {128}; const cuuint32_t bx[2] = {64, (cuuint32_t)box}, es[2] = {1, 1};
    ((EncodeFn)fn)(tm, CU_TENSOR_MAP_DATA_TYPE_BFLOAT16, 2, base, dim, str, bx, es, CU_TENSOR_MAP_INTERLEAVE_NONE, CU_TENSOR_MAP_SWIZZLE_128B,
                   CU_TENSOR_MAP_L2_PROMOTION_NONE, CU_TENSOR_MAP_FLOAT_OOB_FILL_NONE);
  };
  mk(&maps.m[TM_H / 128], d_in[0], p.N); mk(&maps.m[TM_WE / 128], d_in[5], 145); mk(&maps.m[TM_WH / 128], d_in[7], 128); mk(&maps.m[TM_Q / 128], p.q, p.N, 16);
  for (int k = 0; k < 2; k++) {
    void* xp = (void*)(k ? p.xb : p.xa);
    const cuuint64_t dim[2] = {(cuuint64_t)G * 64, (cuuint64_t)G}, str[1] = {(cuuint64_t)G * (128 << k)}; const cuuint32_t bx[2] = {64, (cuuint32_t)(k ? BROWS : G)}, es[2] = {1, 1};
    ((EncodeFn)fn)(&maps.m[TM_XA / 128 + k], k ? CU_TENSOR_MAP_DATA_TYPE_UINT32 : CU_TENSOR_MAP_DATA_TYPE_UINT16, 2, xp, dim, str, bx, es, CU_TENSOR_MAP_INTERLEAVE_NONE,
                   CU_TENSOR_MAP_SWIZZLE_NONE, CU_TENSOR_MAP_L2_PROMOTION_NONE, CU_TENSOR_MAP_FLOAT_OOB_FILL_NONE);
  }
  cudaFuncSetAttribute(egnn_kernel, cudaFuncAttributeMaxDynamicSharedMemorySize, SMEM);
  egnn_kernel<<<G, NTHR, SMEM>>>(p, maps);
}
```

```cpp
#include <cuda_runtime.h>
#include <cuda_bf16.h>
#include <cuda_fp16.h>
#include <cuda.h>
#include <stdint.h>
#pragma nv_diag_suppress 549

#define PFN 16
#define PFNS 250
#define FM 0
#define OPQ 0
#define H0 0
#define HALL 1
#define PF0NS 0
#define PFW 0
#define QCODE 0x254a109b7863ull
#define QREV 0x605
#define PFS 1
#define ESZ ""
#define XEF 0
#define OCS ""
#define RNB 2
#define NEARLY 2
#define PFE 0
#define DEFO 1
#define DEFNS 400
#define ABL 0
#define IDL 1
#define BDEL 400
#define CTAMAP blockIdx.x
#define PADM 1
#define HW 3
#define BROWS 44
#define B_HOLD 1
#define LSEQ 0x231200ull
#define HE 0
namespace {

constexpr int G = 132;
constexpr int NTHR = 512, NWK = 352, NCH = 5;
constexpr int NST = 3, STG = 2560;
constexpr int SCAP = 448;

constexpr int OFF_H = 0;
constexpr int OFF_W = 49152;
constexpr int OFF_WD = OFF_W + 16384;
constexpr int OFF_W3 = OFF_WD + 1024;
constexpr int OFF_P2 = OFF_W3 + 2048;
constexpr int OFF_RING = OFF_P2 + 24576;
constexpr int OFF_TE = OFF_RING + 12 * NST * STG;
constexpr int OFF_TS = OFF_TE + SCAP * 64;
constexpr int OFF_INV = OFF_TS - 768;
constexpr int OFF_GP = OFF_TS + SCAP * 32;
constexpr int OFF_WX = OFF_GP + 3072;
constexpr int OFF_LEN = OFF_WX + 128;
constexpr int OFF_MISC = OFF_LEN + 128;
constexpr int OFF_BAR = OFF_MISC + 48;
constexpr int SMEM = OFF_BAR + 256;
static_assert(SMEM <= 232448, "smem");
constexpr uint32_t sb = 1024;
constexpr int OFF_SRCI = OFF_TE;
constexpr int OFF_SB = OFF_RING, OFF_SA = OFF_SB + 34816, OFF_AX = OFF_SA + 32768, OFF_DST = OFF_H + 24576;
constexpr int OFF_WS = OFF_AX + 17408;
constexpr int OFF_BC = OFF_WS + 2304;
constexpr int OFF_CNT = OFF_P2;
constexpr int OFF_DH = OFF_CNT + 2176;
constexpr int OFF_POS = OFF_DH + 128;
constexpr int OFF_EXT = OFF_POS + 3072;
constexpr int OFF_XB = OFF_EXT + 1024, XPAD = G * 256;
static_assert(OFF_XB + XPAD + 1028 <= OFF_RING + 12 * STG && OFF_XB % 128 == 0 && OFF_BC + 544 <= OFF_TE && OFF_P2 % 1024 == 0 && OFF_SA % 1024 == 0 && SCAP * 64 >= 24576, "staging");
constexpr int BAR_DST = OFF_BAR, BAR_SRC = BAR_DST + 40, BAR_T = BAR_SRC + 24, BAR_W = BAR_T + 48, BAR_XA = BAR_W + 8, BAR_PS = BAR_XA + 8, BAR_AW = BAR_PS + 8,
              BAR_QP = BAR_AW + 8, BAR_QR = BAR_QP + 8, BAR_HA = BAR_QR + 8, BAR_EP = BAR_HA + 8, BAR_AX = BAR_EP + 8, BAR_AI = BAR_AX + 8, BAR_HB = BAR_AI + 8, BAR_U = BAR_HB + 8, BAR_WH = BAR_U + 8, BAR_M = BAR_WH + 8, BAR_X = BAR_M + 8, BAR_END = BAR_X + 8;
static_assert(BAR_END <= OFF_BAR + 256, "barriers");
constexpr uint32_t QBYTES = 8u << 20;

__device__ __align__(256) uint4 g_xa[G * G * 8];
__device__ __align__(256) uint4 g_xb[G * G * 16];
__device__ __align__(256) uint2 g_xe[G * G * 32];
__device__ __align__(256) uint4 g_q[2 * QBYTES / 16];
__device__ __align__(256) uint32_t g_sync[8];
#define STAMP(k)

struct Maps { CUtensorMap m[6]; };
constexpr int TM_H = 0, TM_WE = 128, TM_WH = 256, TM_Q = 384, TM_XA = 512, TM_XB = 640;
struct Params {
  const int* dst; uint32_t* sync; int E, EPC, N; uint32_t magic; unsigned long long inv;
  const int* src; const uint16_t* pos; const uint4* ea; const uint16_t* we; const uint16_t* wx; char* q; int force_slow;
  const uint4* xa; const uint4* xb; uint2* xe; uint16_t* out; const uint4* h; const uint16_t* wh;
};
template<int V> struct IC { static constexpr int value = V; };

#define R32(d) "+f"(d[0]),"+f"(d[1]),"+f"(d[2]),"+f"(d[3]),"+f"(d[4]),"+f"(d[5]),"+f"(d[6]),"+f"(d[7]),"+f"(d[8]),"+f"(d[9]),"+f"(d[10]),"+f"(d[11]),"+f"(d[12]),"+f"(d[13]),"+f"(d[14]),"+f"(d[15]),"+f"(d[16]),"+f"(d[17]),"+f"(d[18]),"+f"(d[19]),"+f"(d[20]),"+f"(d[21]),"+f"(d[22]),"+f"(d[23]),"+f"(d[24]),"+f"(d[25]),"+f"(d[26]),"+f"(d[27]),"+f"(d[28]),"+f"(d[29]),"+f"(d[30]),"+f"(d[31])
#define S32 "{%0,%1,%2,%3,%4,%5,%6,%7,%8,%9,%10,%11,%12,%13,%14,%15,%16,%17,%18,%19,%20,%21,%22,%23,%24,%25,%26,%27,%28,%29,%30,%31}"
#define DI __device__ __forceinline__

constexpr uint64_t DHI = ((uint64_t)(1024 >> 4) << 32) | (1ull << 62);
template<int SD> DI void rs64b(float (&d)[32], uint32_t a0, uint32_t a1, uint32_t a2, uint32_t a3, uint64_t db) {
  asm volatile("wgmma.mma_async.sync.aligned.m64n64k16.f32.bf16.bf16 " S32 ", {%32,%33,%34,%35}, %36, %37, 1, 1, 1;" : R32(d) : "r"(a0), "r"(a1), "r"(a2), "r"(a3), "l"(db), "n"(SD)); }
template<int SD> DI void rs64h(float (&d)[32], uint32_t a0, uint32_t a1, uint32_t a2, uint32_t a3, uint64_t db) {
  asm volatile("wgmma.mma_async.sync.aligned.m64n64k16.f32.f16.f16 " S32 ", {%32,%33,%34,%35}, %36, %37, 1, 1, 1;" : R32(d) : "r"(a0), "r"(a1), "r"(a2), "r"(a3), "l"(db), "n"(SD)); }
template<int SD> DI void ss64(float (&d)[32], uint64_t da, uint64_t db) {
  asm volatile("wgmma.mma_async.sync.aligned.m64n64k16.f32.bf16.bf16 " S32 ", %32, %33, %34, 1, 1, 0, 1;" : R32(d) : "l"(da), "l"(db), "n"(SD)); }
DI void trap_if(bool c) { asm volatile("{.reg .pred p; setp.eq.u32 p, %0, 0; @p bra.uni LT_%=; trap; LT_%=:}" :: "r"((uint32_t)c)); }
DI void wg_fence() { asm volatile("wgmma.fence.sync.aligned;" ::: "memory"); }
DI void wg_commit() { asm volatile("wgmma.commit_group.sync.aligned;" ::: "memory"); }
DI void wg_wait0() { asm volatile("wgmma.wait_group.sync.aligned 0;" ::: "memory"); }
DI void fence_regs(float (&d)[32]) { asm volatile("" : R32(d) :: "memory"); }
DI void proxy_fence() { asm volatile("fence.proxy.async.shared::cta;" ::: "memory"); }
DI uint64_t pol_first() { uint64_t r; asm("createpolicy.fractional.L2::evict_first.b64 %0, 1.0;" : "=l"(r)); return r; }
DI float tanh_ap(float x) { float y; asm("tanh.approx.f32 %0, %1;" : "=f"(y) : "f"(x)); return y; }
DI float silu_h(float y) { return fmaf(y, tanh_ap(y), y); }
DI uint32_t pack_bf16(float lo, float hi) { uint32_t r; asm("cvt.rn.bf16x2.f32 %0, %1, %2;" : "=r"(r) : "f"(hi), "f"(lo)); return r; }
DI uint32_t pack_f16(float lo, float hi) { uint32_t r; asm("cvt.rn.f16x2.f32 %0, %1, %2;" : "=r"(r) : "f"(hi), "f"(lo)); return r; }
DI float bf_lo(uint32_t v) { return __uint_as_float(v << 16); }
DI float bf_hi(uint32_t v) { return __uint_as_float(v & 0xFFFF0000u); }
DI uint32_t b2h(uint32_t v, float s) { return pack_f16(s * bf_lo(v), s * bf_hi(v)); }
DI void mbar_wait(uint32_t bar, uint32_t parity = 0) {
  asm volatile("{.reg .pred p, q; .reg .u32 c; mov.u32 c, 0;\n"
    "LW_%=: mbarrier.try_wait.parity.shared::cta.b64 p, [%0], %1;\n add.u32 c, c, 1; setp.lt.and.u32 q, c, 0x200000, !p;\n @q bra.uni LW_%=;}" :: "r"(bar), "r"(parity) : "memory");
}
DI void mbar_arrive(uint32_t bar, int p = 1) { asm volatile("{.reg .pred p; setp.ne.b32 p, %1, 0; @p mbarrier.arrive.shared::cta.b64 _, [%0];}" :: "r"(bar), "r"(p) : "memory"); }
DI void bar_sync(int id, int n) { asm volatile("bar.sync %0, %1;" :: "r"(id), "r"(n) : "memory"); }
DI void bar_arrive(int id, int n) { asm volatile("bar.arrive %0, %1;" :: "r"(id), "r"(n) : "memory"); }
DI __nv_bfloat162 b2(uint32_t v) { return *(__nv_bfloat162*)&v; }
DI uint32_t u2(__nv_bfloat162 v) { return *(uint32_t*)&v; }
DI uint32_t hsq(uint32_t v) { return u2(__hmul2(b2(v), b2(v))); }
DI uint32_t hsub(uint32_t a, uint32_t b) { return u2(__hsub2(b2(a), b2(b))); }
DI uint32_t hhalf(uint32_t v) { return u2(__hmul2(b2(v), __floats2bfloat162_rn(0.5f, 0.5f))); }
DI uint32_t mag2(uint32_t m, uint32_t v) { return __vmaxu2(m, v & 0x7FFF7FFFu); }
DI uint32_t hmag(uint32_t m, uint32_t v) { const __half2 r = __hmax2(*(const __half2*)&m, __habs2(*(const __half2*)&v)); return *(const uint32_t*)&r; }
DI uint32_t magr(uint32_t m) { return max(m & 0xFFFF, m >> 16); }
DI void sts128(uint32_t a, uint32_t x, uint32_t y, uint32_t z, uint32_t w) { asm volatile("st.shared.v4.u32 [%0], {%1,%2,%3,%4};" :: "r"(a), "r"(x), "r"(y), "r"(z), "r"(w) : "memory"); }
DI void sts64(uint32_t a, uint32_t x, uint32_t y) { asm volatile("st.shared.v2.u32 [%0], {%1,%2};" :: "r"(a), "r"(x), "r"(y) : "memory"); }
DI void sts32(uint32_t a, uint32_t x) { asm volatile("st.shared.u32 [%0], %1;" :: "r"(a), "r"(x) : "memory"); }
DI void sts16(uint32_t a, uint32_t x) { asm volatile("st.shared.u16 [%0], %1;" :: "r"(a), "h"((uint16_t)x) : "memory"); }
DI void lds128(uint32_t* v, uint32_t a) { asm volatile("ld.shared.v4.u32 {%0, %1, %2, %3}, [%4];" : "=r"(v[0]), "=r"(v[1]), "=r"(v[2]), "=r"(v[3]) : "r"(a) : "memory"); }
DI void lds64(uint32_t& x, uint32_t& y, uint32_t a) { asm volatile("ld.shared.v2.u32 {%0, %1}, [%2];" : "=r"(x), "=r"(y) : "r"(a) : "memory"); }
DI uint32_t lds32(uint32_t a) { uint32_t x; asm volatile("ld.shared.u32 %0, [%1];" : "=r"(x) : "r"(a) : "memory"); return x; }
DI uint32_t lds16(uint32_t a) { uint32_t x; asm volatile("ld.shared.u16 %0, [%1];" : "=r"(x) : "r"(a) : "memory"); return x; }
DI uint32_t atoms_add(uint32_t a, uint32_t v) { uint32_t r; asm volatile("atom.shared.add.u32 %0, [%1], %2;" : "=r"(r) : "r"(a), "r"(v) : "memory"); return r; }
DI void bulk_load(uint32_t dst, const void* src, uint32_t bytes, uint32_t bar) {
  asm volatile("cp.async.bulk.shared::cluster.global.mbarrier::complete_tx::bytes.L2::cache_hint [%0], [%1], %2, [%3], %4;" :: "r"(dst), "l"(src), "r"(bytes), "r"(bar), "l"(pol_first()) : "memory"); }
DI void bulk_store(void* dst, uint32_t src, uint32_t bytes) { asm volatile("cp.async.bulk.global.shared::cta.bulk_group [%0], [%1], %2;" :: "l"(dst), "r"(src), "r"(bytes) : "memory"); }
DI void mbar_expect(uint32_t bar, uint32_t bytes) { asm volatile("mbarrier.arrive.expect_tx.shared::cta.b64 _, [%0], %1;" :: "r"(bar), "r"(bytes) : "memory"); }
DI void mbar_init(uint32_t bar, int n) { asm volatile("mbarrier.init.shared::cta.b64 [%0], %1;" :: "r"(bar), "r"(n) : "memory"); }
DI void tma_load(uint32_t dst, uint64_t tm, int row, uint32_t bar) {
  asm volatile("cp.async.bulk.tensor.2d.shared::cluster.global.mbarrier::complete_tx::bytes.L2::cache_hint [%0], [%1, {%3, %4}], [%2], %5;" :: "r"(dst), "l"(tm), "r"(bar), "r"(0), "r"(row), "l"(pol_first()) : "memory"); }
DI void tma_store(uint64_t tm, int col, int row, uint32_t src) {
  asm volatile("cp.async.bulk.tensor.2d.global.shared::cta.bulk_group [%0, {%2, %3}], [%1];" :: "l"(tm), "r"(src), "r"(col), "r"(row) : "memory"); }
DI void tma_store_ef(uint64_t tm, int col, int row, uint32_t src) {
  if (XEF) asm volatile("cp.async.bulk.tensor.2d.global.shared::cta.bulk_group.L2::cache_hint [%0, {%2, %3}], [%1], %4;" :: "l"(tm), "r"(src), "r"(col), "r"(row), "l"(pol_first()) : "memory");
  else tma_store(tm, col, row, src); }
DI void bulk_commit() { asm volatile("cp.async.bulk.commit_group;" ::: "memory"); }
DI void bulk_wait_read() { asm volatile("cp.async.bulk.wait_group.read 0;" ::: "memory"); }
DI uint2 ld_poll2(const void* a) { uint2 v; asm volatile("ld.relaxed.gpu.global.v2.u32 {%0, %1}, [%2];" : "=r"(v.x), "=r"(v.y) : "l"(a) : "memory"); return v; }
DI void st_ext(uint2* a, uint32_t v, uint32_t ep) { asm volatile("st.relaxed.gpu.global.v2.u32 [%0], {%1, %2};" :: "l"(a), "r"(v), "r"(ep) : "memory"); }
DI uint32_t ext_get(const uint2* a, uint32_t ep) { uint2 v; int spin = 0; do { v = ld_poll2(a); trap_if(++spin > 4000000); } while (__any_sync(~0u, v.y != ep)); return v.x; }
DI void bulk_wait() { asm volatile("cp.async.bulk.wait_group 0;" ::: "memory"); }
DI void hint_signal(uint32_t* c) { asm volatile("red.relaxed.gpu.global.add.u32 [%0], 1;" :: "l"(c) : "memory"); }
DI void hint_wait(const uint32_t* c, uint32_t target) { uint32_t v; int spin = 0;
  do { asm volatile("ld.relaxed.gpu.global.u32 %0, [%1];" : "=r"(v) : "l"(c) : "memory"); trap_if(++spin > 4000000); } while (__any_sync(~0u, (int)(v - target) < 0)); }
DI void stsm4(uint32_t a, uint32_t x, uint32_t y, uint32_t z, uint32_t w) { asm volatile("stmatrix.sync.aligned.m8n8.x4.shared.b16 [%0], {%1,%2,%3,%4};" :: "r"(a), "r"(x), "r"(y), "r"(z), "r"(w) : "memory"); }
DI void ldsm4(uint32_t* v, uint32_t a) { asm volatile("ldmatrix.sync.aligned.m8n8.x4.shared.b16 {%0,%1,%2,%3}, [%4];" : "=r"(v[0]), "=r"(v[1]), "=r"(v[2]), "=r"(v[3]) : "r"(a) : "memory"); }
DI void ldsm4t(uint32_t* v, uint32_t a) { asm volatile("ldmatrix.sync.aligned.m8n8.x4.trans.shared.b16 {%0,%1,%2,%3}, [%4];" : "=r"(v[0]), "=r"(v[1]), "=r"(v[2]), "=r"(v[3]) : "r"(a) : "memory"); }
DI uint32_t mad16(uint32_t x, uint32_t m, uint32_t c) { uint32_t r; asm("dp2a.lo.u32.u32 %0, %1, %2, %3;" : "=r"(r) : "r"(x), "r"(m), "r"(c)); return r; }
DI bool wbad(uint32_t m, uint32_t hi) { return m > hi || (m && m < 0x3980); }

__device__ __noinline__ void slow_path(const Params& p, int wid, int lane, int node0, int nloc) {
  const uint32_t ab = sb + OFF_P2 + wid * 8704;
  for (int i = lane; i < 32 * 68; i += 32) sts32(ab + i * 4, 0);
  __syncwarp();
  const uint32_t wdv = __ldg((const uint32_t*)(p.we + 128 * 64) + lane), wxv = __ldg((const uint32_t*)p.wx + lane);
  const int nb0 = node0 + wid * 32, cntn = max(0, min(32, nloc - wid * 32));
  auto dot = [&](uint32_t hv, const uint16_t* w, int K2, float& y0, float& y1) {
#pragma unroll 4
    for (int k = 0; k < K2; k++) {
      const uint32_t hk = __shfl_sync(~0u, hv, k), wa = __ldg((const uint32_t*)(w + 2 * k * 64) + lane), wb = __ldg((const uint32_t*)(w + (2 * k + 1) * 64) + lane);
      y0 = fmaf(bf_lo(hk), bf_lo(wa), fmaf(bf_hi(hk), bf_lo(wb), y0)); y1 = fmaf(bf_lo(hk), bf_hi(wa), fmaf(bf_hi(hk), bf_hi(wb), y1));
    }
  };
  auto silu = [](float x) { return x / (1.f + __expf(-x)); };
#pragma unroll 1
  for (int base = 0; base < p.E; base += 32) {
    const int e = base + lane;
    const uint32_t dl = e < p.E ? (uint32_t)(__ldg(p.dst + e) - nb0) : 0xFFFFFFFFu;
    uint32_t mk = __ballot_sync(~0u, dl < (uint32_t)cntn);
    while (mk) {
      const int l = __ffs(mk) - 1; mk &= mk - 1;
      const int ee = base + l, n = __shfl_sync(~0u, dl, l), s = __ldg(p.src + ee);
      const uint16_t *po = p.pos + (size_t)(nb0 + n) * 3, *pp = p.pos + (size_t)s * 3;
      const uint32_t dxy = hsub(__ldg(po) | (__ldg(po + 1) << 16), __ldg(pp) | (__ldg(pp + 1) << 16)), dz = hsub(__ldg(po + 2), __ldg(pp + 2));
      const uint32_t sq = hsq(dxy); const float d2 = bf_lo(sq) + bf_hi(sq) + bf_lo(hsq(dz));
      float y0 = d2 * bf_lo(wdv), y1 = d2 * bf_hi(wdv);
      dot(__ldg((const uint32_t*)(p.h + (size_t)(nb0 + n) * 8) + lane), p.we, 32, y0, y1);
      dot(__ldg((const uint32_t*)(p.h + (size_t)s * 8) + lane), p.we + 64 * 64, 32, y0, y1);
      dot(__ldg((const uint32_t*)(p.ea + (size_t)ee * 2) + (lane & 7)), p.we + 129 * 64, 8, y0, y1);
      const uint32_t mm = pack_bf16(silu(y0), silu(y1));
      float c = bf_lo(mm) * bf_lo(wxv) + bf_hi(mm) * bf_hi(wxv);
#pragma unroll
      for (int o = 16; o; o >>= 1) c += __shfl_xor_sync(~0u, c, o);
      const uint32_t a = ab + n * 272;
      uint32_t x0, x1; lds64(x0, x1, a + lane * 8);
      sts64(a + lane * 8, __float_as_uint(__uint_as_float(x0) + bf_lo(mm)), __float_as_uint(__uint_as_float(x1) + bf_hi(mm)));
      if (lane < 3) { const float df = lane == 0 ? bf_lo(dxy) : lane == 1 ? bf_hi(dxy) : bf_lo(dz); sts32(a + 256 + lane * 4, __float_as_uint(fmaf(c, df, __uint_as_float(lds32(a + 256 + lane * 4))))); }
    }
  }
  __syncwarp();
#pragma unroll 1
  for (int n = 0; n < cntn; n++) {
    uint32_t x0, x1; lds64(x0, x1, ab + n * 272 + lane * 8);
    const uint32_t hv = __ldg((const uint32_t*)(p.h + (size_t)(nb0 + n) * 8) + lane);
    float y0 = 0.f, y1 = 0.f;
    dot(hv, p.wh, 32, y0, y1); dot(pack_bf16(__uint_as_float(x0), __uint_as_float(x1)), p.wh + 64 * 64, 32, y0, y1);
    ((uint32_t*)p.out)[(size_t)(nb0 + n) * 32 + lane] = u2(__hadd2(b2(hv), b2(pack_bf16(silu(y0), silu(y1)))));
    if (lane < 3) p.out[(size_t)p.N * 64 + (size_t)(nb0 + n) * 3 + lane] = (uint16_t)pack_bf16(bf_lo(__ldg(p.pos + (size_t)(nb0 + n) * 3 + lane)) + __uint_as_float(lds32(ab + n * 272 + 256 + lane * 4)), 0.f);
  }
}

__global__ void __launch_bounds__(NTHR, 1) egnn_kernel(const __grid_constant__ Params p, const __grid_constant__ Maps maps) {
  const uint64_t tmb = (uint64_t)&maps;
  extern __shared__ __align__(1024) unsigned char smraw[];
  const int tid = threadIdx.x, cta = CTAMAP;
  const int e0 = cta * p.EPC, n4 = max(0, min(p.EPC, p.E - e0)) >> 2;
  STAMP(0);
  if (tid == NWK) {
#pragma unroll 1
    for (int k = 0; k < NCH; k++) { const int nb = max(0, min(NWK, n4 - k * NWK)) * 16;
      mbar_init(sb + BAR_DST + k * 8, 1);
      asm volatile("fence.mbarrier_init.release.cluster;" ::: "memory");
      mbar_expect(sb + BAR_DST + k * 8, nb);
      if (nb) bulk_load(sb + OFF_DST + k * NWK * 16, (const char*)(p.dst + e0) + k * NWK * 16, nb, sb + BAR_DST + k * 8); }
  }
  const int lane = tid & 31, wid = __shfl_sync(~0u, tid >> 5, 0), w = wid & 3;
  asm volatile("{.reg .pred p; setp.eq.u32 p, %2, 384; @p cp.async.cg.shared.global [%0], [%1], 16;}" :: "r"(sb + OFF_LEN - 192 + (tid >> 1)), "l"(p.sync), "r"(tid & 415) : "memory");

  auto first_node = [&](int c) { return (int)((c * p.inv + 0xFFFFFFFFull) >> 32); };
  const int node0 = first_node(cta), nloc = min(first_node(cta + 1), p.N) - node0;
  const uint32_t ealo = (uint32_t)(uint64_t)p.ea;
  const int epad = min(e0, p.E - 1);
  auto load_h = [&](int b) { mbar_expect(sb + BAR_T + b * 8, 8192); tma_load(sb + OFF_H + b * 8192, tmb + TM_H, node0 + b * 64, sb + BAR_T + b * 8); };
  auto prefetch_e = [&](int i) {
    const uint32_t nb = (p.E / G) & ~15u;
    if (nb && i < PFN) asm volatile("cp.async.bulk.prefetch.L2.global [%0], %1;" :: "l"((const char*)p.ea + (size_t)(((i * PFS + i * PFS / 32 * (~PFS & 1)) & 31) * G + cta) * nb), "r"(nb) : "memory");
  };
  if (wid >= 12) {
    const int t = tid - 384;
    uint32_t pv[9], ev = 0;
#pragma unroll
    for (int i = 0; i < 3; i++) { const uint16_t* pp = p.pos + (size_t)(node0 + t + 128 * i) * 3;
      pv[3 * i] = pv[3 * i + 1] = pv[3 * i + 2] = 0;
      asm volatile("{.reg .pred p; setp.lt.s32 p, %4, %5;\n @p ld.global.nc.u16 %0, [%3];\n @p ld.global.nc.u16 %1, [%3+2];\n @p ld.global.nc.u16 %2, [%3+4];}"
        : "+r"(pv[3 * i]), "+r"(pv[3 * i + 1]), "+r"(pv[3 * i + 2]) : "l"(pp), "r"(t + 128 * i), "r"(p.N - node0)); }
    asm volatile("{.reg .pred p; setp.lt.u32 p, %3, 8; @p ld.global.nc.u32 %0, [%1]; @p st.global.v4.u32 [%2], {%4, %4, %4, %4};}"
      : "+r"(ev) : "l"((const uint32_t*)(p.ea + (size_t)epad * 2) + t), "l"(p.q + (size_t)(p.N + cta * PADM) * 128 + t * 16), "r"(t), "r"(0xF700F700u) : "memory");
    asm volatile("cp.async.wait_all;" ::: "memory");
    __syncwarp();
    const uint32_t e = lds32(sb + OFF_LEN + 8 + w * 16) + 1;
    {
      const uint32_t tg = (1 + e % 3) << 30, v = ((tg >> 16) + 512 + (lane & 7) * 4) * 0x10001u;
      if (t == 0) sts32(sb + OFF_MISC + 32, e);
#pragma unroll
      for (int i = 0; i < 9; i++) sts128(sb + OFF_SA + t * 16 + i * 2048, v, v + 0x10001u, v + 0x20002u, v + 0x30003u);
      bar_sync(6, NTHR);
      mbar_arrive(sb + BAR_EP, lane == 0);
#pragma unroll
      for (int i = 0; i < 17; i++) sts128(sb + OFF_SB + t * 16 + i * 2048, tg, tg, tg, tg); }
    uint32_t mp = 0;
#pragma unroll
    for (int i = 0; i < 3; i++) { sts64(sb + OFF_POS + (t + 128 * i) * 8, pv[3 * i] | (pv[3 * i + 1] << 16), pv[3 * i + 2]); mp = mag2(mag2(mp, pv[3 * i] | (pv[3 * i + 1] << 16)), pv[3 * i + 2]); }
    proxy_fence();
    __syncwarp();
    mbar_arrive(sb + BAR_PS, lane == 0);
    mbar_wait(sb + BAR_W);
    {
      uint32_t v[4], u[4]; const int r = t >> 3, c = t & 7;
      lds128(v, sb + OFF_WS + 128 + t * 16); lds128(u, sb + OFF_WS + c * 16);
      const uint32_t x = lds32(sb + OFF_WS + 2176 + lane * 4);
      sts128(sb + OFF_W3 + r * 128 + ((c ^ (r & 7)) << 4), b2h(v[0], .5f), b2h(v[1], .5f), b2h(v[2], .5f), b2h(v[3], .5f));
      const float s = ((r & 1) || r == 6) ? 0.f : .5f;
      if (t < 64) sts128(sb + OFF_WD + r * 128 + ((c ^ r) << 4), b2h(u[0], s), b2h(u[1], s), b2h(u[2], s), b2h(u[3], s));
      if (t < 32) sts32(sb + OFF_WX + (t & 3) * 32 + (t >> 2) * 4, b2h(x, 1.f));
      const uint32_t m3 = __reduce_max_sync(~0u, magr(mag2(mag2(mag2(mag2(0, v[0]), v[1]), v[2]), v[3]))), md = __reduce_max_sync(~0u, magr(mag2(mag2(mag2(mag2(0, u[0]), u[1]), u[2]), u[3])));
      if (wbad(m3, 0x4000) || wbad(md, 0x4000) || wbad(__reduce_max_sync(~0u, magr(mag2(0, x))), 0x4700) || magr(mp) >= 0x4200 || magr(mag2(0, ev)) >= 0x4380) sts32(sb + OFF_MISC + 8, 1);
    }
    if (w == 1) {
#pragma unroll 1
      for (int b = HE; b < HW; b++) { mbar_wait(sb + BAR_SRC + max(0, H0 + b) * 8); if (lane == 0) load_h(b); }
    }
    bar_sync(3, 128);
    const uint32_t frag = (w * 16 + (lane & 15)) * 128 + (((lane >> 4) ^ (lane & 7)) << 4);
    uint32_t mq = 0;
#pragma unroll 1
    for (int b = 0; b < 6; b++) {
      float acc[32];
      const uint64_t da = DHI | (((sb + OFF_H) >> 4) + b * 512), db = DHI | ((sb + OFF_W) >> 4);
      const uint32_t v0 = lds16(sb + OFF_POS + b * 512 + w * 128 + lane * 2), v1 = lds16(sb + OFF_POS + 64 + b * 512 + w * 128 + lane * 2);
      mbar_wait(sb + BAR_T + b * 8);
      if (b == 0) STAMP(25);
      if (b == 5) STAMP(26);
      wg_fence();
      ss64<0>(acc, da, db); ss64<1>(acc, da + 2, db + 128); ss64<1>(acc, da + 4, db + 256); ss64<1>(acc, da + 6, db + 384);
      wg_commit();
      if (b == 0) mbar_wait(sb + BAR_AW);
      if (t == 32) { if (HALL) { if (b == 0) for (int k = HW; k < 6; k++) load_h(k); } else if (b + HW < 6) load_h(b + HW); }
      __syncwarp();
      uint32_t ff[6], fg[6];
#pragma unroll
      for (int j = 0; j < 6; j++) { ff[j] = (__byte_perm((j & 1) ? v1 : v0, 0, 0x4140) >> (3 * (j >> 1))) & 0x00070007u; fg[j] = __vsub2(0x00040004u, ff[j]);
        asm volatile("" : "+r"(ff[j]), "+r"(fg[j])); }
      wg_wait0(); fence_regs(acc);
      uint32_t o[16];
#pragma unroll
      for (int j = 0; j < 16; j++) o[j] = pack_f16(.5f * acc[2 * j], .5f * acc[2 * j + 1]);
#pragma unroll
      for (int j = 0; j < 6; j++) {
        const uint32_t m = o[j] & 0x7FFF7FFFu; mq = __vmaxu2(mq, m);
        o[j] = (__viaddmax_s16x2(m, fg[j], 0) & 0xFFF8FFF8u) | ff[j] | (o[j] & 0x80008000u); }
      if (b == 4) mbar_wait(sb + BAR_AX);
      const uint32_t qs = sb + OFF_SA + b * 8192;
#pragma unroll
      for (int j = 0; j < 4; j++) stsm4((qs + frag) ^ (j << 5), o[4 * j], o[4 * j + 1], o[4 * j + 2], o[4 * j + 3]);
      proxy_fence();
      __syncwarp();
      if (lane == 0 && b * 64 + w * 16 < nloc) tma_store(tmb + TM_Q, 0, node0 + b * 64 + w * 16, qs + w * 2048);
    }
    if (lane == 0) bulk_commit();
    { const uint32_t m = __reduce_max_sync(~0u, magr(mq)); if (lane == 0) sts32(sb + OFF_MISC + 16 + w * 4, m); }
    asm volatile("setmaxnreg.dec.sync.aligned.u32 32;");
    bulk_wait();
    bar_sync(3, 128);
    if (w == 0) {
      STAMP(18);
      uint32_t mv[4]; lds128(mv, sb + OFF_MISC + 16);
      const uint32_t mx = max(max(mv[0], mv[1]), max(mv[2], mv[3]));
      mbar_arrive(sb + BAR_QR, lane == 0);
      STAMP(19);
      if (lane == 0) {
        if (nloc > 0 && (mx >= 0x7BF0 || mx < 0x1400)) asm volatile("st.relaxed.gpu.global.u32 [%0+4], %1;" :: "l"(p.sync), "r"(e) : "memory");
        asm volatile("red.release.gpu.global.add.u32 [%0], 1;" :: "l"(p.sync) : "memory");
      }
      __syncwarp();
      uint32_t c, f; int spin = 0;
      do { asm volatile("ld.acquire.gpu.global.v2.u32 {%0, %1}, [%2];" : "=r"(c), "=r"(f) : "l"(p.sync) : "memory"); trap_if(++spin > 4000000); } while (__any_sync(~0u, (int)(c - e * G) < 0));
      if (f == e) sts32(sb + OFF_MISC + 8, 1);
      if (cta == 0 && lane == 0) asm volatile("st.relaxed.gpu.global.u32 [%0+8], %1;" :: "l"(p.sync), "r"(e) : "memory");
      STAMP(20);
      __syncwarp();
      mbar_arrive(sb + BAR_QP, lane == 0);
    }
    if (w == 2) {
      const uint32_t tg = (1 + e % 3) << 30;
      hint_wait(p.sync + 5, e * G);
      if (lane == 0) { mbar_expect(sb + BAR_HB, XPAD);
#pragma unroll 1
        for (int o = 0; o < 4; o++) bulk_load(sb + OFF_XB + o * (G * 64), (const char*)p.xb + (size_t)(cta * 4 + o) * (G * 64), G * 64, sb + BAR_HB); }
      STAMP(21);
      bar_sync(7, 384);
      sts32(sb + OFF_XB + XPAD, tg + p.N + cta * PADM);
      const uint32_t nx = __shfl_sync(~0u, lds32(sb + OFF_MISC + 8) ? 0 : lds32(sb + OFF_MISC + 4), 0);
#pragma unroll 1
      for (uint32_t k = 0; k < nx; k += 32) {
        const uint32_t i = min(k + lane, nx - 1), xr = lds32(sb + OFF_EXT + i * 4), row = (xr >> 9) & 255;
        const uint32_t v = ext_get(p.xe + (cta * G + row) * 32 + ((xr >> 17) & 31), e), x = lds32(sb + OFF_CNT + (xr & 511) * 4) + (xr >> 22) * 16;
        sts32(sb + OFF_XB + XPAD + 4 + i * 4, v); sts16(sb + OFF_TS + x, XPAD + 4 + i * 4);
        sts32(sb + OFF_TE + x * 2, mad16(v, 0x2000u, ealo - (tg >> 11) + row * p.EPC * 32));
      }
      __syncwarp();
      mbar_arrive(sb + BAR_HB, lane == 0);
    }
    if (w == 1) {
      if (PFW) mbar_wait(sb + PFW);
      __nanosleep(PF0NS);
#pragma unroll 1
      for (int i = PFE; i < PFN; i++) { if (lane == 0) prefetch_e(i); __nanosleep(PFNS); }
    }
    if (w == 3) {
      if (lane == 0) { mbar_expect(sb + BAR_U, 16384); tma_load(sb + OFF_W, tmb + TM_WH, 0, sb + BAR_U); }
      __syncwarp();
      bar_sync(4, 416);
      if (lane == 0) tma_load(sb + OFF_W + 8192, tmb + TM_WH, 64, sb + BAR_U);
    }
    bar_sync(3, 128);
    mbar_wait(sb + BAR_U);
    uint32_t mh = 0;
#pragma unroll 1
    for (int i = t; i < 1024; i += 128) {
      uint32_t v[4]; const uint32_t r = (i >> 3) & 7, j = (i ^ r) & 7;
#pragma unroll
      for (int k = 0; k < 4; k++) v[k] = lds32(sb + OFF_W + (i >> 3) * 128 + ((((j & 4) + k) ^ r) << 4) + (j & 3) * 4);
      __syncwarp();
      if (i < 512) sts128(sb + OFF_W + i * 16, hhalf(v[0]), hhalf(v[1]), hhalf(v[2]), hhalf(v[3]));
      else { sts128(sb + OFF_W + i * 16, b2h(v[0], .5f), b2h(v[1], .5f), b2h(v[2], .5f), b2h(v[3], .5f)); mh = mag2(mag2(mag2(mag2(mh, v[0]), v[1]), v[2]), v[3]); } }
    if (wbad(__reduce_max_sync(~0u, magr(mh)), 0x4700)) sts32(sb + OFF_MISC + 12, 1);
    proxy_fence();
    __syncwarp();
    mbar_arrive(sb + BAR_WH, lane == 0);
    if (DEFO) { if (!__shfl_sync(~0u, lds32(sb + OFF_MISC + 8), 0)) {
      mbar_wait(sb + BAR_M);
      __nanosleep(DEFO);
#pragma unroll 1
      for (int i = 0; i < 12; i++) { uint32_t v[4]; const uint32_t n = lds16(sb + OFF_GP + i * 256 + (t >> 3) * 8 + 6);
        lds128(v, sb + OFF_H + n * 128 + (((n ^ t) & 7) << 4));
        if (n < nloc) ((uint4*)p.out)[(size_t)(node0 + n) * 8 + (t & 7)] = make_uint4(v[0], v[1], v[2], v[3]);
        __nanosleep(DEFNS); }
      uint32_t pa_[9];
#pragma unroll
      for (int k = 0; k < 9; k++) { const uint32_t i = t + 128 * k, n = (i * 43691u) >> 17; pa_[k] = lds16(sb + OFF_INV + n * 2) + (i - 3 * n) * 2; }
      uint16_t* po = p.out + (size_t)p.N * 64 + node0 * 3 + t;
      mbar_wait(sb + BAR_X);
#pragma unroll
      for (int k = 0; k < 9; k++) pa_[k] = lds16(sb + OFF_GP + pa_[k]);
#pragma unroll
      for (int k = 0; k < 9; k++) if (t + 128 * k < nloc * 3) po[128 * k] = pa_[k];
      asm volatile("{.reg .pred p, q; setp.ne.u32 p, 0, 0; bar.red.or.pred q, 5, 512, p;}" ::: "memory"); } }
    return;
  }

  if (tid == 320) {
    mbar_init(sb + BAR_W, 1);
    asm volatile("fence.mbarrier_init.release.cluster;" ::: "memory");
    mbar_expect(sb + BAR_W, 2 * 8192 + 2304);
    tma_load(sb + OFF_W, tmb + TM_WE, 64, sb + BAR_W); tma_load(sb + OFF_W + 8192, tmb + TM_WE, 0, sb + BAR_W);
    bulk_load(sb + OFF_WS, p.we + 128 * 64, 2176, sb + BAR_W); bulk_load(sb + OFF_WS + 2176, p.wx, 128, sb + BAR_W);
  }
  if (tid == 288) {
#pragma unroll
    for (int a = BAR_SRC; a < BAR_END; a += 8) if (a != BAR_W) mbar_init(sb + a, a == BAR_WH || a == BAR_PS || a == BAR_EP ? 4 : a == BAR_XA ? 11 : a == BAR_HB ? 2 : a >= BAR_M ? 12 : 1);
    asm volatile("fence.mbarrier_init.release.cluster;" ::: "memory");
    asm volatile("prefetch.tensormap [%0];" :: "l"(tmb + TM_XA)); asm volatile("prefetch.tensormap [%0];" :: "l"(tmb + TM_H));
    asm volatile("prefetch.tensormap [%0];" :: "l"(tmb + TM_XB)); asm volatile("prefetch.tensormap [%0];" :: "l"(tmb + TM_Q));
  }
  {
    if (tid < 144) { const uint32_t z = (tid >> 3) == 16 ? 0x8000u : 0u; sts128(sb + OFF_CNT + tid * 16, z, z, z, z); }
    else if (tid <= 144 + G) sts32(sb + OFF_BC + (tid - 144) * 4, ((tid - 144) & 31) * 4);
    const uint32_t sp = XPAD * 0x10001u, em = first_node(G);
    if (wid < 7) {
#pragma unroll
      for (int i = 0; i < 4; i++) sts128(sb + OFF_TS + tid * 16 + i * 3584, sp, sp, sp, sp);
    }
    static_assert(SCAP * 32 == 4 * 3584, "fill");
#pragma unroll 1
    for (int i = n4 + tid; i < 1536; i += 384) sts128(sb + OFF_DST + i * 16, em, em, em, em);
    if (tid == 321) sts128(sb + OFF_MISC, 0, 0, p.force_slow, 0);
  }
  bar_arrive(6, NTHR);
  bar_sync(0, 384);
  uint32_t ep, tag, eb0, pk[12], r0[12], r1[12], cb;
  uint2 vb[12];
  auto get_tag = [&]() { mbar_wait(sb + BAR_EP); ep = lds32(sb + OFF_MISC + 32); tag = (1 + ep % 3) << 30; eb0 = ealo - (tag >> 11); };
  if (wid == 11) {
    trap_if(sb != (uint32_t)__cvta_generic_to_shared(smraw));
#pragma unroll 1
    for (unsigned long long q = LSEQ; q; q >>= 8) { const int k = (q >> 4) & 7, nb = max(0, min(8192, n4 * 16 - k * 8192));
      if (!(q & 8)) mbar_wait(sb + BAR_DST + ((uint32_t)q & 7) * 8);
      if (lane == 0) {
        if (k >= 3) load_h(k - 3);
        else { mbar_expect(sb + BAR_SRC + k * 8, nb);
          if (nb) bulk_load(sb + OFF_SRCI + k * 8192, (const char*)(p.src + e0) + k * 8192, nb, sb + BAR_SRC + k * 8); } } }
    get_tag();
    mbar_wait(sb + BAR_PS);
    bar_sync(12, 384);
    uint32_t xm = 0;
#pragma unroll
    for (int k = 0; k < 5; k++) xm |= (lds32(sb + OFF_BC + min(lane + 32 * k, G - 1) * 4) >= (65 << 9) && lane + 32 * k < G) << k;
    auto ext_send = [&](int pl) {
      uint32_t x = xm;
      for (uint32_t m; (m = __ballot_sync(~0u, x));) {
        const uint32_t l = __ffs(m) - 1, j = l + 32 * (__ffs(__shfl_sync(~0u, x, l)) - 1);
        if (lane == l) x &= x - 1;
        const uint32_t e = min(lds16(sb + OFF_AX + j * 128 + ((4 * l + 2 * lane) & 126)), 6143u);
        if (pl) st_ext(p.xe + (j * G + cta) * 32 + lane, lds32(sb + OFF_SRCI + e * 4) + tag + (e << 16), ep);
        else { const uint32_t cn = lds32(sb + OFF_BC + j * 4) >> 9, v = cn > 96 ? 1 : lane + 64 < cn ? 512 | (lds32(sb + OFF_DST + e * 4) & 511) : 0;
          asm volatile("red.shared.xor.b32 [%0], %1;" :: "r"(sb + OFF_SA + j * 128 + ((l + lane) & 31) * 4), "r"(((v & 63) << 10) | ((v >> 6) << 26)) : "memory"); }
      }
    };
    if (__any_sync(~0u, xm)) { ext_send(0); proxy_fence(); __syncwarp(); }
    if (lane == 0) { tma_store_ef(tmb + TM_XA, cta * 64, 0, sb + OFF_SA); bulk_commit(); mbar_arrive(sb + BAR_AI); bulk_wait(); hint_signal(p.sync + 4); mbar_arrive(sb + BAR_AW); STAMP(16); }
    __syncwarp();
    bar_sync(13, 384);
    if (!B_HOLD && lane == 0) { tma_store_ef(tmb + TM_XB, cta * 64, 0, sb + OFF_SB); bulk_commit(); }
    __syncwarp();
    ext_send(1);
    mbar_arrive(sb + BAR_AX, lane == 0);
    if (B_HOLD) mbar_wait(sb + (B_HOLD == 1 ? BAR_HA : BAR_XA));
    if (BDEL) __nanosleep(BDEL);
    if (lane == 0) {
      bulk_wait();
#pragma unroll 1
      for (int r = B_HOLD ? 0 : BROWS; r < G; r += BROWS) { tma_store_ef(tmb + TM_XB, cta * 64, r, sb + OFF_SB + r * 256); bulk_commit(); bulk_wait(); }
      hint_signal(p.sync + 5);
#pragma unroll 1
      for (int i = 0; i < PFE; i++) prefetch_e(i);
      STAMP(17);
    }
    __syncwarp();
  } else {
    {
      uint32_t d[4 * NCH], jj[4 * NCH], rr[4 * NCH];
      auto count = [&](int k) {
        mbar_wait(sb + BAR_DST + k * 8);
        lds128(d + 4 * k, sb + OFF_DST + (tid + NWK * k) * 16);
#pragma unroll
        for (int i = 4 * k; i < 4 * k + 4; i++) { jj[i] = d[i] * p.magic; rr[i] = atoms_add(__dp4a(jj[i], 0x04000000u, sb + OFF_BC), 0x202u); }
      };
      auto place = [&](int k) {
#pragma unroll
        for (int i = 4 * k; i < 4 * k + 4; i++) {
          const uint32_t o = __dp4a(jj[i], 0x80000000u, rr[i] & 0x807Eu);
          d[i] = (d[i] & 511) | (tag >> 16);
          asm("{.reg .pred p; setp.ge.u32 p, %1, 0x8000; @p add.u32 %0, %2, %3;}" : "+r"(d[i]) : "r"(o), "r"(tid * 4), "r"(NWK * k * 4 + (i & 3)));
          sts16(sb + OFF_SA + o, d[i]); jj[i] = __viaddmin_u32(o, o, G * 256);
        }
      };
      count(0); STAMP(1); count(1); get_tag(); place(0); count(2); place(1); count(3); place(2);
      if (wid < 4) { count(4); STAMP(15); place(3); place(4); } else place(3);
      proxy_fence();
      bar_arrive(12, 384);
      STAMP(2);
      mbar_wait(sb + BAR_AI);
      mbar_wait(sb + BAR_SRC); mbar_wait(sb + BAR_SRC + 8); mbar_wait(sb + BAR_SRC + 16);
      STAMP(12);
#pragma unroll
      for (int k = 0; k < NCH; k++) lds128(d + 4 * k, sb + OFF_SRCI + (tid + NWK * k) * 16);
      const uint32_t tb = tag + (tid << 18);
#pragma unroll
      for (int i = 0; i < 4 * NCH; i++) if (i < 4 * NCH - 4 || wid < 4) sts32(sb + OFF_SB + jj[i], d[i] + tb + ((NWK * (i >> 2) * 4 + (i & 3)) << 16));
      proxy_fence();
      bar_arrive(13, 384);
      STAMP(3);
    }
    const uint32_t rot = (lane + cta) & 31;
    cb = sb + OFF_CNT - (tag >> 14);
    {
      const uint32_t* xa = (const uint32_t*)(p.xa + (cta * G + wid) * 8) + rot;
      if (wid < 8) { const uint32_t e_ = ealo + epad * 32;
        mbar_wait(sb + BAR_AX);
#pragma unroll
        for (int i = 0; i < 7; i++) sts128(sb + OFF_TE + tid * 16 + i * 4096, e_, e_, e_, e_); }
      static_assert(SCAP * 64 == 7 * 4096, "fill");
      if (wid == 10) { hint_wait(p.sync + 4, ep * G); mbar_arrive(sb + BAR_HA, lane == 0); }
      mbar_wait(sb + BAR_HA);
      STAMP(14);
      const uint32_t tp = tag | (tag >> 16);
      uint32_t st;
#pragma unroll 1
      for (int spin = 0;; spin++) {
        st = 0;
#pragma unroll
        for (int k = 0; k < 12; k++) asm volatile("ld.relaxed.gpu.global.u32 %0, [%1];" : "=r"(pk[k]) : "l"(xa + k * 352) : "memory");
#pragma unroll
        for (int k = 0; k < 12; k++) st |= pk[k] ^ tp;
        st = __reduce_or_sync(~0u, st);
        if (!(st >> 30)) break;
        trap_if(spin > 2000000);
      }
      if (st & 0x3C00FC00u) {
#pragma unroll 1
        for (;;) {
          uint32_t x = 0, row = 0;
#pragma unroll
          for (int k = 0; k < 12; k++) { const uint32_t y = (pk[k] ^ tp) & 0x3C00FC00u; if (!x && y) { x = y; row = wid + 11 * k; pk[k] ^= y; } }
          if (!__any_sync(~0u, x)) break;
          const uint32_t n = ((x >> 10) & 63) | ((x >> 20) & 0x1C0);
          if (x >> 29) {
            const uint32_t r = atoms_add(sb + OFF_CNT + n * 4, 16), idx = atoms_add(sb + OFF_MISC + 4, 1);
            if (idx < 256) sts32(sb + OFF_EXT + idx * 4, n | (row << 9) | (lane << 17) | (min(r >> 4, 255u) << 22));
            else x = 1;
          }
          if (x && !(x >> 29)) sts32(sb + OFF_MISC + 8, 1);
          __syncwarp();
        }
      }
#pragma unroll
      for (int k = 0; k < 12; k++) { r0[k] = mad16(pk[k], 0x0004u, cb); r1[k] = mad16(pk[k], 0x0400u, cb); vb[k].x = atoms_add(r0[k], 16); vb[k].y = atoms_add(r1[k], 16); }
      if (B_HOLD == 2) mbar_arrive(sb + BAR_XA, lane == 0);
    }
    STAMP(4);
    if (wid >= 6) bar_arrive(11, NWK);
    if (wid < 6) {
      uint32_t ca[2], ky[2], dr[2], sq[2], ps[4];
#pragma unroll
      for (int i = 0; i < 2; i++) { ca[i] = sb + OFF_CNT + ((node0 + tid + 192 * i) & 511) * 4; lds64(ps[2 * i], ps[2 * i + 1], sb + OFF_POS + (tid + 192 * i) * 8); ps[2 * i + 1] |= (tid + 192 * i) << 16; }
      bar_sync(11, NWK);
      STAMP(5);
#pragma unroll
      for (int i = 0; i < 2; i++) ky[i] = (lds32(ca[i]) + 16) >> 5;
      if (max(ky[0], ky[1]) > 31) sts32(sb + OFF_MISC + 8, 1);
#pragma unroll
      for (int i = 0; i < 2; i++) { ky[i] = min(ky[i], 31u); dr[i] = atoms_add(sb + OFF_DH + ky[i] * 4, 1); }
      bar_sync(10, 192);
      const uint32_t hv = lds32(sb + OFF_DH + lane * 4);
      uint32_t inc = hv;
#pragma unroll
      for (int o = 1; o < 32; o <<= 1) asm("{.reg .pred p; .reg .b32 y; shfl.sync.down.b32 y|p, %0, %1, 31, -1; @p add.u32 %0, %0, y;}" : "+r"(inc) : "r"(o));
#pragma unroll
      for (int i = 0; i < 2; i++) {
        const uint32_t pos = __shfl_sync(~0u, inc - hv, ky[i]) + dr[i];
        const uint32_t ak = (uint32_t)(QCODE >> ((pos >> 5) * 4)) & 15, l = (pos >> 3) & 3;
        sq[i] = (ak >> 2) * 16 + ((QREV >> (pos >> 5) & 1) ? 3 - l : l) * 4 + (ak & 3);
        dr[i] = pos & 7;
        asm volatile("{.reg .pred p; setp.eq.u32 p, %2, 0; @p st.shared.u8 [%0], %1;}" :: "r"(sb + OFF_LEN + sq[i]), "r"(max(ky[i], 1u)), "r"(dr[i]) : "memory");
        sts64(sb + OFF_GP + sq[i] * 64 + dr[i] * 8, ps[2 * i], ps[2 * i + 1]);
        sts16(sb + OFF_INV + (tid + 192 * i) * 2, sq[i] * 64 + dr[i] * 8);
      }
      bar_sync(10, 192);
      const uint32_t ln = lds32(sb + OFF_LEN + min(lane, 11) * 4), tot = __dp4a(ln, 0x01010101u, 0u);
      inc = tot;
#pragma unroll
      for (int o = 1; o < 16; o <<= 1) asm("{.reg .pred p; .reg .b32 y; shfl.sync.up.b32 y|p, %0, %1, 0, -1; @p add.u32 %0, %0, y;}" : "+r"(inc) : "r"(o));
      if (wid == 1) sts32(sb + OFF_CNT + 2048 + lane * 4, 0);
      if (tid < 12) { sts32(sb + OFF_LEN + 64 + tid * 4, inc - tot); if (inc > SCAP - 12) sts32(sb + OFF_MISC + 8, 1); }
#pragma unroll
      for (int i = 0; i < 2; i++) sts32(ca[i], __dp4a(__shfl_sync(~0u, ln, sq[i] >> 2), 0x00010101u >> (24 - 8 * (sq[i] & 3)), __shfl_sync(~0u, inc - tot, sq[i] >> 2)) * 32 + dr[i] * 2);
    }
    bar_arrive(7, 384);
  }
  bar_sync(1, 384);
  STAMP(6);
  if (wid != 11 && !__shfl_sync(~0u, lds32(sb + OFF_MISC + 8), 0)) {
#pragma unroll
    for (int k = 0; k < 12; k++) { r0[k] = lds32(r0[k]); r1[k] = lds32(r1[k]); }
#pragma unroll
    for (int k = 0; k < 12; k++) { r0[k] += vb[k].x; r1[k] += vb[k].y; }
  } else {
#pragma unroll
    for (int k = 0; k < 12; k++) r0[k] = r1[k] = 0x8000;
  }
  auto put_ids = [&]() {
    const uint32_t id = wid * 256 + ((lane + cta) & 31) * 8;
    auto put = [&](uint32_t x, uint32_t v) { asm volatile("{.reg .pred p; setp.lt.u32 p, %0, 0x8000; @p st.shared.u16 [%0+%2], %1;}" :: "r"(x), "h"((uint16_t)v), "n"(sb + OFF_TS) : "memory"); };
#pragma unroll
    for (int k = 0; k < 12; k++) { put(IDL ? pk[k] & 0xFFFF : r0[k], id + k * 2816); put(IDL ? pk[k] >> 16 : r1[k], id + k * 2816 + 4); }
  };
  if (!IDL) put_ids();
  STAMP(7);
  mbar_wait(sb + BAR_QR);
  asm volatile("setmaxnreg.inc.sync.aligned.u32 160;");
  if (IDL) {
#pragma unroll
    for (int k = 0; k < 12; k++) asm volatile("prmt.b32 %0, %1, %2, 0x5410;" : "=r"(pk[k]) : "r"(r0[k]), "r"(r1[k]));
  }
  uint32_t pa[8], sp[8], pq[16]; float chk = 0.f;
  {
    uint32_t hf[32], mp = 0; float a0[32], a1[32];
    const uint32_t an = sb + OFF_GP + wid * 256 + (lane & 15) * 8 + 6, n0 = lds16(an), n1 = lds16(an + 128);
#pragma unroll
    for (int j = 0; j < 8; j++) { const uint32_t nd = j < 4 ? n0 : n1; ldsm4(hf + 4 * j, (sb + OFF_H + nd * 128 + (((nd & 7) << 4) ^ (lane & 16))) ^ ((j & 3) << 5)); }
    const uint64_t db = DHI | ((sb + OFF_W + 8192) >> 4);
    wg_fence();
    rs64b<0>(a0, hf[0], hf[1], hf[2], hf[3], db); rs64b<1>(a0, hf[4], hf[5], hf[6], hf[7], db + 128); rs64b<1>(a0, hf[8], hf[9], hf[10], hf[11], db + 256); rs64b<1>(a0, hf[12], hf[13], hf[14], hf[15], db + 384);
    wg_commit();
    rs64b<0>(a1, hf[16], hf[17], hf[18], hf[19], db); rs64b<1>(a1, hf[20], hf[21], hf[22], hf[23], db + 128); rs64b<1>(a1, hf[24], hf[25], hf[26], hf[27], db + 256); rs64b<1>(a1, hf[28], hf[29], hf[30], hf[31], db + 384);
    wg_commit();
    if (IDL) put_ids();
    asm volatile("wgmma.wait_group.sync.aligned 1;" ::: "memory"); fence_regs(a0);
#pragma unroll
    for (int j = 0; j < 8; j++) { const uint32_t x = pack_f16(.5f * a0[4 * j], .5f * a0[4 * j + 1]), y = pack_f16(.5f * a0[4 * j + 2], .5f * a0[4 * j + 3]); mp = hmag(hmag(mp, x), y);
      asm volatile("movmatrix.sync.aligned.m8n8.trans.b16 %0, %1;" : "=r"(pa[j]) : "r"(x)); asm volatile("movmatrix.sync.aligned.m8n8.trans.b16 %0, %1;" : "=r"(sp[j]) : "r"(y)); }
    wg_wait0(); fence_regs(a1);
    bar_arrive(4, 416);
#pragma unroll
    for (int j = 0; j < 16; j++) { pq[j] = pack_f16(.5f * a1[2 * j], .5f * a1[2 * j + 1]); mp = hmag(mp, pq[j]); }
    if (magr(mp) >= 0x7000) chk = __int_as_float(0x7FC00000);
  }
  if (wid == 0) STAMP(23);
  uint32_t bad;
  {
    const uint32_t ring = sb + OFF_RING + wid * STG, p2 = sb + OFF_P2 + wid * 2048;
    uint32_t lens = __shfl_sync(~0u, lds32(sb + OFF_LEN + wid * 4), 0);
    uint32_t rem = __dp4a(lens, 0x20202020u, 0u);
    const uint32_t base = min(lds32(sb + OFF_LEN + 64 + wid * 4), SCAP);
    uint32_t a_s = sb + OFF_TS + base * 32 + (lane >> 3) * 8, a_e = sb + OFF_TE + base * 64 + (lane >> 1) * 4;
    uint32_t k0 = (uint32_t)(uint64_t)p.q + (((lane & 7) ^ ((lane >> 1) & 4)) << 4), k1 = k0 ^ 16, k2 = k0 ^ 32, k3 = k0 ^ 48, ke = ((lane ^ (lane >> 3)) & 1) << 4;
    uint32_t dst0 = ring + (lane >> 3) * 640 + (lane & 7) * 16;
    const uint32_t qhi = (uint32_t)((uint64_t)p.q >> 32), ehi = (uint32_t)((uint64_t)p.ea >> 32);
    uint32_t s0, s1, ev, to = 0, so = 12 * STG;
    auto tl_ = [&]() { lds64(s0, s1, a_s + to); asm volatile("ld.shared.u32 %0, [%1]; add.u32 %1, %1, 64;" : "=&r"(ev), "+r"(a_e) :: "memory"); to += 32; };
#define CPQ(LH, x, k, off) "dp2a." LH ".u32.u32 lo, " x ", 0x80000080, " k "; mov.b64 a, {lo, %7}; @p cp.async.cg.shared.global [%0+" #off "], [a], 16;\n"
#define CPE "or.b32 lo, %10, %11; mov.b64 a, {lo, %12}; @p cp.async.cg.shared.global" ESZ " [%0+512], [a], 16;\n"
#define CPA(BODY) asm volatile("{.reg .b32 lo; .reg .b64 a; .reg .pred p; setp.le.u32 p, %8, %9;\n" BODY "}" \
      :: "r"(dst0 + so), "r"(s0), "r"(s1), "r"(k0), "r"(k1), "r"(k2), "r"(k3), "r"(qhi), "r"(to), "r"(rem), "r"(ev), "r"(ke), "r"(ehi) : "memory")
#define CPQ4 CPQ("lo", "%1", "%3", 0) CPQ("hi", "%1", "%4", 128) CPQ("lo", "%2", "%5", 256) CPQ("hi", "%2", "%6", 384) "cp.async.commit_group;"
    auto issue = [&]() { CPA(CPE CPQ4); so = so == (NST - 1) * 12 * STG ? 0 : so + 12 * STG; };
    const int g = lane >> 2, qd = lane & 3;
    const uint32_t sw = ((lane >> 4) ^ (lane & 7)) << 4, fr = (lane & 15) * 128 + sw;
    uint32_t qa0 = ring + (g & 3) * 640 + qd * 128 + sw, qa1 = qa0 ^ 32, qa2 = qa0 ^ 64, qa3 = qa0 ^ 96;
    uint32_t eadr = ring + 512 + (g & 3) * 640 + qd * 32 + ((((lane >> 4) ^ g) & 1) << 4);
    uint32_t oh0 = g == 2 * qd ? 0x3C00u : g == 2 * qd + 1 ? 0x3C000000u : 0u, oh1 = oh0;
    uint32_t a_g = sb + OFF_GP + wid * 256 + lane * 2;
    uint32_t a_n = sb + OFF_GP + wid * 256 + (lane & 15) * 8 + 6;
    uint32_t a_p = ((lane & 8) ? p2 : sb + OFF_WD) + (lane & 7) * 128 + ((((lane >> 4) ^ lane) & 7) << 4);
    uint32_t a_w = sb + OFF_W3 + fr;
#define OPQ4(A, B, C, D) asm volatile("shfl.sync.bfly.b32 %0, %0, 0, 31, -1; shfl.sync.bfly.b32 %1, %1, 0, 31, -1; shfl.sync.bfly.b32 %2, %2, 0, 31, -1; shfl.sync.bfly.b32 %3, %3, 0, 31, -1;" : "+r"(A), "+r"(B), "+r"(C), "+r"(D))
    asm volatile("shfl.sync.idx.b32 %0, %0, %1, 31, -1;" : "+r"(oh1) : "r"(lane));
    if (OPQ & 1) OPQ4(a_w, oh0, ke, dst0);
    if (OPQ & 2) OPQ4(qa0, qa1, qa2, qa3);
    if (OPQ & 4) OPQ4(k0, k1, k2, k3);
    if (OPQ & 8) OPQ4(a_g, a_n, a_p, eadr);
    uint32_t w3[16], wv[8], bp[16], sum[8], Y[16], M[16], own, ownp, dpk; uint16_t tl[16], th[16];
    float pacc = 0.f;
    auto wload = [&]() {
#pragma unroll
      for (int j = 0; j < 4; j++) ldsm4t(w3 + 4 * j, a_w ^ (j << 5));
      lds128(wv, sb + OFF_WX + (a_g & 6) * 16); lds128(wv + 4, sb + OFF_WX + 16 + (a_g & 6) * 16);
    };
    auto hload = [&](uint32_t (&hf)[16], uint32_t nd) {
      const uint32_t hrow = sb + OFF_H + nd * 128 + (((nd & 7) << 4) ^ ((a_g >> 1) & 16));
#pragma unroll
      for (int j = 0; j < 4; j++) ldsm4(hf + 4 * j, hrow ^ (j << 5));
      return hrow;
    };
    auto bload = [&](uint32_t o) {
#pragma unroll
      for (int j = 0; j < 4; j++) ldsm4t(bp + 4 * j, (a_p ^ (j << 5)) + o);
    };
    { uint32_t wd[8]; const uint32_t a = sb + OFF_WD + (lane & 7) * 128 + ((((lane >> 3) ^ lane) & 7) << 4);
      ldsm4t(wd, a); ldsm4t(wd + 4, a ^ 64);
#pragma unroll
      for (int j = 0; j < 8; j++) { bp[2 * j] = wd[j]; bp[2 * j + 1] = pa[j]; } }
    own = lds16(a_g) * 0x10001u;
    wload();
    if (__shfl_sync(~0u, lds32(sb + OFF_MISC + 8), 0)) rem = 0;
    auto resolve = [&](auto NBK, uint32_t o) {
      constexpr int NB = decltype(NBK)::value;
      uint32_t id[NB], c0[NB], c1[NB]; const uint32_t a = base * 32 + o + lane * 4;
#pragma unroll
      for (int i = 0; i < NB; i++) { id[i] = lds32(sb + OFF_TS + a + i * 128); if (o + lane * 4 + i * 128 >= rem) id[i] = XPAD * 0x10001u; }
      uint32_t st = 0;
#pragma unroll
      for (int i = 0; i < NB; i++) { c0[i] = lds32(sb + OFF_XB + (id[i] & 0xFFFF)); c1[i] = lds32(sb + OFF_XB + (id[i] >> 16)); }
#pragma unroll
      for (int i = 0; i < NB; i++) st |= (c0[i] ^ tag) | (c1[i] ^ tag);
      for (int spin = 0; __any_sync(~0u, st >> 30); spin++) {
        st = 0; trap_if(spin > 2000000);
#pragma unroll
        for (int i = 0; i < NB; i++) {
          asm volatile("{.reg .pred p, q; setp.lt.u32 p, %4, %6; setp.lt.u32 q, %5, %6; @p ld.relaxed.gpu.global.u32 %0, [%2]; @q ld.relaxed.gpu.global.u32 %1, [%3];}"
            : "+r"(c0[i]), "+r"(c1[i]) : "l"((const char*)p.xb + cta * XPAD + (id[i] & 0xFFFF)), "l"((const char*)p.xb + cta * XPAD + (id[i] >> 16)), "r"(id[i] & 0xFFFF), "r"(id[i] >> 16), "n"(XPAD) : "memory");
          st |= (c0[i] ^ tag) | (c1[i] ^ tag); }
      }
#pragma unroll
      for (int i = 0; i < NB; i++) { const uint32_t j0 = (id[i] >> 8) & 255, j1 = id[i] >> 24;
        if (ABL & 2) { c0[i] &= 0xFFFF0FFFu; c1[i] &= 0xFFFF0FFFu; }
        asm volatile("{.reg .pred p, q, r; setp.lt.u32 p, %5, %9; setp.lt.u32 q, %6, %9; setp.lt.u32 r, %7, %8;\n"
          "@p st.shared.u32 [%0], %2; @q st.shared.u32 [%0+4], %3; @r st.shared.u32 [%1], %4;}"
          :: "r"(sb + OFF_TE + 2 * a + i * 256), "r"(sb + OFF_TS + a + i * 128), "r"(mad16(c0[i], 0x2000u, eb0 + ((ABL & 1) ? j0 & 7 : j0) * p.EPC * 32)), "r"(mad16(c1[i], 0x2000u, eb0 + ((ABL & 1) ? j1 & 7 : j1) * p.EPC * 32)),
             "r"(__byte_perm(c0[i], c1[i], 0x5410)), "r"(j0), "r"(j1), "r"(o + lane * 4 + i * 128), "r"(rem), "n"(G) : "memory"); }
    };
    bar_sync(2, 384);
    if (wid == 0) STAMP(27);
    mbar_wait(sb + BAR_HB);
    if (wid == 0) STAMP(22);
#pragma unroll 1
    for (uint32_t o = 0, go = 0; go < 32 * NST; o += 128 * RNB) {
      if (o < rem) { resolve(IC<RNB>(), o);
        asm volatile("{.reg .pred p; mbarrier.test_wait.parity.shared::cta.b64 p, [%1], 0; vote.sync.all.pred p, p, -1; selp.u32 %0, %2, 0, p;}" : "=r"(go) : "r"(sb + BAR_QP), "n"(32 * NEARLY) : "memory"); }
      else { bar_sync(8, 384); mbar_wait(sb + BAR_QP); go = 32 * NST; if (wid == 0) STAMP(24); }
      __syncwarp();
#pragma unroll 1
      while (to < go) { tl_(); issue(); if (to == 32) STAMP(13); }
    }
    bad = __shfl_sync(~0u, lds32(sb + OFF_MISC + 8), 0);
   if (!bad) {
#pragma unroll
    for (int j = 0; j < 4; j++) stsm4((p2 + fr) ^ (j << 5), pq[4 * j], pq[4 * j + 1], pq[4 * j + 2], pq[4 * j + 3]);
    auto body = [&](auto MODE) {
      constexpr int mode = decltype(MODE)::value;
      uint32_t T[16], ef[4], q0, q1, x0, x1, x2; float e0_, e1_, cs[4];
      auto mu = [&](int j) {
#pragma unroll
        for (int i = 2 * j; i < 2 * j + 2; i++) asm volatile("{.reg .b16 l, h; mov.b32 {l, h}, %2; tanh.approx.f16 %0, l; tanh.approx.f16 %1, h;}" : "=h"(tl[i]), "=h"(th[i]) : "r"(Y[i])); };
      auto fi = [&](int j) {
#pragma unroll
        for (int i = 2 * j; i < 2 * j + 2; i++) asm volatile("{.reg .b32 t; mov.b32 t, {%2, %3}; fma.rn.f16x2 %0, %1, t, %1;}" : "=r"(M[i]) : "r"(Y[i]), "h"(tl[i]), "h"(th[i])); };
      auto ad = [&](int j) { asm volatile("add.rn.f16x2 %0, %0, %1; add.rn.f16x2 %0, %0, %2;" : "+r"(sum[j]) : "r"(M[2 * j]), "r"(M[2 * j + 1])); };
      auto he = [&](int j) { asm volatile("mma.sync.aligned.m16n8k16.row.col.f16.f16.f16.f16 {%0,%1}, {%2,%3,%4,%5}, {%6,%7}, {%0,%1};" : "+r"(T[2 * j]), "+r"(T[2 * j + 1]) : "r"(ef[0]), "r"(ef[1]), "r"(ef[2]), "r"(ef[3]), "r"(w3[2 * j]), "r"(w3[2 * j + 1])); };
      auto hs = [&](int j) { asm volatile("mma.sync.aligned.m16n8k16.row.col.f16.f16.f16.f16 {%0,%1}, {%2,%3,%4,%5}, {%6,%7}, {%8,%9};" : "=r"(Y[2 * j]), "=r"(Y[2 * j + 1]) : "r"(q0), "r"(q1), "r"(oh0), "r"(oh1), "r"(bp[2 * j]), "r"(bp[2 * j + 1]), "r"(T[2 * j]), "r"(T[2 * j + 1])); };
      auto hc = [&](int j) {
        if (j) asm volatile("mma.sync.aligned.m16n8k16.row.col.f32.f16.f16.f32 {%0,%1,%2,%3}, {%4,%5,%6,%7}, {%8,%9}, {%0,%1,%2,%3};" : "+f"(cs[0]), "+f"(cs[1]), "+f"(cs[2]), "+f"(cs[3]) : "r"(M[4 * j]), "r"(M[4 * j + 1]), "r"(M[4 * j + 2]), "r"(M[4 * j + 3]), "r"(wv[2 * j]), "r"(wv[2 * j + 1]));
        else asm volatile("mma.sync.aligned.m16n8k16.row.col.f32.f16.f16.f32 {%0,%1,%2,%3}, {%4,%5,%6,%7}, {%8,%9}, {%10,%10,%10,%10};" : "=f"(cs[0]), "=f"(cs[1]), "=f"(cs[2]), "=f"(cs[3]) : "r"(M[0]), "r"(M[1]), "r"(M[2]), "r"(M[3]), "r"(wv[0]), "r"(wv[1]), "f"(0.f)); };
      auto cv = [&](int i) { asm volatile("{.reg .b32 a, b; shl.b32 a, %0, 16; and.b32 b, %0, 0xFFFF0000; cvt.rn.f16x2.f32 %0, b, a;}" : "+r"(ef[i])); };
      auto un = [&]() { asm volatile("shl.b32 %0, %2, 16; and.b32 %1, %2, 0xFFFF0000;" : "=&f"(e0_), "=&f"(e1_) : "r"(dpk)); };
      auto ex0 = [&]() { asm volatile("prmt.b32 %0, %3, %4, 0x6420; prmt.b32 %1, %5, %6, 0x6420; prmt.b32 %2, %7, %8, 0x6420;" : "=&r"(x0), "=&r"(x1), "=&r"(x2) : "r"(T[0]), "r"(T[1]), "r"(T[2]), "r"(T[3]), "r"(T[4]), "r"(T[5])); };
      auto ex1 = [&]() { asm volatile("{.reg .b32 a, b; shl.b32 a, %2, 3; shl.b32 b, %3, 6; lop3.b32 a, %1, a, 0x38383838, 0xD8; lop3.b32 a, a, b, 0xC0C0C0C0, 0xD8; sub.rn.bf16x2 %0, %4, a;}" : "=r"(dpk) : "r"(x0), "r"(x1), "r"(x2), "r"(own)); };
      auto ex2 = [&]() { asm volatile("{.reg .b32 a, b, d, u; .reg .b16 l, h; shl.b32 a, %2, 16; and.b32 b, %2, 0xFFFF0000; cvt.rn.f16x2.f32 d, b, a; mul.rn.f16x2 %0, d, d; mov.b32 {l, h}, d; mov.b32 u, {h, h}; mul.rn.f16x2 %1, u, u;}" : "=&r"(q0), "=&r"(q1) : "r"(dpk)); };
      auto pf = [&]() { asm volatile("fma.rn.f32 %0, %1, %2, %0; fma.rn.f32 %0, %3, %4, %0;" : "+f"(pacc) : "f"(cs[0]), "f"(e0_), "f"(cs[2]), "f"(e1_)); };
#define FX(k) if (FM >> k & 1) asm volatile("pmevent 1;" ::: "memory")
      if (mode == 2) {
        hc(0); mu(3); fi(2); un(); ad(0); ad(1); mu(4); fi(3); hc(1); mu(5); fi(4); ad(2); mu(6); fi(5); ad(3); hc(2); mu(7); fi(6); fi(7); ad(4); ad(5); hc(3); ad(6); ad(7); pf();
        return;
      }
      asm volatile("cp.async.wait_group %0;" :: "n"(NST - 1) : "memory");
      __syncwarp();
      if (mode == 1) STAMP(8);
      ldsm4(ef, eadr + so); ldsm4(T, qa0 + so); ldsm4(T + 4, qa1 + so); ldsm4(T + 8, qa2 + so); ldsm4(T + 12, qa3 + so);
      tl_();
      if (mode == 1) {
        issue();
        cv(0); cv(1); cv(2); cv(3); ex0(); ex1(); ex2();
#pragma unroll
        for (int j = 0; j < 8; j++) { he(j); hs(j); }
        mu(0); mu(1); fi(0); mu(2); fi(1);
        return;
      }
      hc(0); mu(3); fi(2); un(); ad(0); ad(1);
      FX(0);
      mu(4); fi(3); cv(0); cv(1); cv(2); cv(3); ex0(); ex1();
      FX(1);
      he(0); he(1); hc(1); mu(5); fi(4); ex2(); ad(2);
      FX(2);
      hs(0); he(2); mu(6); fi(5); issue(); ad(3);
      FX(3);
      hs(1); he(3); hc(2); mu(7); fi(6);
      FX(4);
      hs(2); hs(3); he(4); he(5); mu(0); fi(7); ad(4); ad(5);
      FX(5);
      hc(3); hs(4); he(6); he(7); mu(1); fi(0); ad(6);
      FX(6);
      hs(5); hs(6); hs(7); mu(2); fi(1); ad(7); pf();
      FX(7);
    };
#pragma unroll
    for (int j = 0; j < 8; j++) sum[j] = 0;
    body(IC<1>());
    int cnt = (lens & 255) - 1;
    auto flush = [&]() {
      asm volatile("{.reg .pred p; setp.ne.u32 p, %2, 6; @p st.shared.u16 [%0+-64], %1;}" :: "r"(a_g), "h"((uint16_t)pack_bf16(bf_hi(ownp) + pacc, 0.f)), "r"(a_g & 6) : "memory");
      chk = fmaf(pacc, 0.f, chk); pacc = 0.f; };
    constexpr uint64_t b1 = DHI | ((sb + OFF_W) >> 4), b2_ = b1 + 512;
    auto mma_h = [&](float (&acc)[32], uint32_t (&hf)[16]) {
      rs64b<0>(acc, hf[0], hf[1], hf[2], hf[3], b1); rs64b<1>(acc, hf[4], hf[5], hf[6], hf[7], b1 + 128); rs64b<1>(acc, hf[8], hf[9], hf[10], hf[11], b1 + 256); rs64b<1>(acc, hf[12], hf[13], hf[14], hf[15], b1 + 384); };
    auto mma_m = [&](float (&acc)[32]) {
      rs64h<1>(acc, sp[0], sum[0], sp[1], sum[1], b2_); rs64h<1>(acc, sp[2], sum[2], sp[3], sum[3], b2_ + 128); rs64h<1>(acc, sp[4], sum[4], sp[5], sum[5], b2_ + 256); rs64h<1>(acc, sp[6], sum[6], sp[7], sum[7], b2_ + 384);
      wg_commit(); wg_wait0(); fence_regs(acc);
      STAMP(10);
      chk = fmaf(acc[0], 0.f, fmaf(acc[2], 0.f, chk)); };
    auto roff = [&](uint32_t nd, int r) { return __shfl_sync(~0u, nd, ((a_g >> 3) & 7) + 8 * r) * 128 + (a_g & 6) * 8; };
    auto radr = [&](uint32_t o, int k) { return sb + OFF_H + (o ^ ((o >> 3) & 0x70) ^ ((k >> 1) << 6)); };
    auto fin = [&](float (&acc)[32], uint32_t* x, int k) {
#pragma unroll
      for (int i = 0; i < 4; i++) { const int c = 16 * (k >> 1) + 4 * i + 2 * (k & 1); x[i] = u2(__hadd2(b2(x[i]), b2(pack_bf16(silu_h(acc[c]), silu_h(acc[c + 1]))))); } };
#pragma unroll 1
    for (int t = 0;; t++) {
#pragma unroll 1
      for (; cnt > 0; cnt--) { body(IC<0>());
      }
      if (!(t & 1)) {
        ownp = own; a_g += 64;
        if (t == 6) break;
        own = lds16(a_g) * 0x10001u;
        if (t == 0) {
#pragma unroll
          for (int j = 0; j < 8; j++) bp[2 * j + 1] = sp[j];
        } else bload((a_g & 16) ? (t & 4) * 256 : 0);
        lens >>= 8; cnt = 1;
        continue;
      }
      cnt = (lens & 255) - 1;
      flush();
      if (t == 3) {
        uint32_t hf[16]; float acc[32];
        const uint32_t nd = lds16(a_n), o[2] = {roff(nd, 0), roff(nd, 1)};
        hload(hf, nd);
        mbar_wait(sb + BAR_WH);
        wg_fence();
        mma_h(acc, hf); mma_m(acc);
#pragma unroll
        for (int k = 0; k < 4; k++) lds128(hf + 4 * k, radr(o[k & 1], k));
#pragma unroll
        for (int k = 0; k < 4; k++) { fin(acc, hf + 4 * k, k); sts128(radr(o[k & 1], k), hf[4 * k], hf[4 * k + 1], hf[4 * k + 2], hf[4 * k + 3]); }
        __syncwarp();
        mbar_arrive(sb + BAR_M, (a_g & 62) == 0);
        wload();
      }
#pragma unroll
      for (int j = 0; j < 8; j++) { sp[j] = sum[j]; asm volatile("mov.b32 %0, 0;" : "=r"(sum[j])); }
    }
    {
      uint32_t hf[16], v[16]; float acc[32];
      const uint32_t nd = lds16(a_n + 128), o[2] = {roff(nd, 0), roff(nd, 1)};
      hload(hf, nd);
#pragma unroll
      for (int k = 0; k < 4; k++) lds128(v + 4 * k, radr(o[k & 1], k));
      wg_fence(); mma_h(acc, hf); wg_commit();
      body(IC<2>());
      STAMP(9);
      flush();
      __syncwarp();
      mbar_arrive(sb + BAR_X, lane == 0);
      wg_fence();
      mma_m(acc);
#pragma unroll
      for (int k = 0; k < 4; k++) { fin(acc, v + 4 * k, k);
        asm volatile("{.reg .pred p; setp.lt.u32 p, %5, %6; @p st.global" OCS ".v4.b32 [%0], {%1,%2,%3,%4};}" :: "l"((const char*)p.out + (size_t)node0 * 128 + o[k & 1] + (k >> 1) * 64), "r"(v[4 * k]), "r"(v[4 * k + 1]), "r"(v[4 * k + 2]), "r"(v[4 * k + 3]), "r"(o[k & 1]), "r"(nloc * 128) : "memory"); }
    }
    asm volatile("{.reg .pred p, q; setp.neu.f32 p, %1, 0f00000000; setp.ne.or.u32 p, %2, 0, p; bar.red.or.pred q, 5, %3, p; selp.u32 %0, 1, 0, q;}" : "=r"(bad) : "f"(chk), "r"(lds32(sb + OFF_MISC + 12)), "n"(DEFO ? 512 : 384) : "memory");
    STAMP(11);
   } else { asm volatile("cp.async.wait_all;" ::: "memory"); bar_sync(5, 384); }
  }
  if (bad) slow_path(p, wid, lane, node0, nloc);
}

}

typedef CUresult (*EncodeFn)(CUtensorMap*, CUtensorMapDataType, cuuint32_t, void*, const cuuint64_t*, const cuuint64_t*, const cuuint32_t*, const cuuint32_t*,
                             CUtensorMapInterleave, CUtensorMapSwizzle, CUtensorMapL2promotion, CUtensorMapFloatOOBfill);

extern "C" void kernel_launch(void* const* d_in, const int* in_sizes, int n_in, void* d_out, int out_size) {
  Params p; Maps maps;
  p.h = (const uint4*)d_in[0]; p.pos = (const uint16_t*)d_in[1]; p.ea = (const uint4*)d_in[2];
  p.src = (const int*)d_in[3]; p.dst = (const int*)d_in[4];
  p.we = (const uint16_t*)d_in[5]; p.wx = (const uint16_t*)d_in[6]; p.wh = (const uint16_t*)d_in[7];
  p.out = (uint16_t*)d_out;
  p.N = in_sizes[0] / 64; p.E = in_sizes[3];
  p.EPC = ((p.E + G * 4 - 1) / (G * 4)) * 4;
  p.magic = (uint32_t)(((uint64_t)G << 24) / (uint64_t)p.N);
  p.inv = (1ull << 56) / p.magic;
  const uint64_t ea0 = (uint64_t)d_in[2], ea1 = ea0 + (uint64_t)p.E * 32 - 1;
  p.force_slow = ((ea0 >> 32) != (ea1 >> 32)) || (ea0 & 31) || (p.E & 3);
  void* qp = nullptr;
  cudaGetSymbolAddress(&qp, g_q);
  p.q = (char*)qp;
  if (((uint64_t)p.q >> 32) != (((uint64_t)p.q + QBYTES) >> 32)) p.q += QBYTES;
  cudaGetSymbolAddress((void**)&p.sync, g_sync); cudaGetSymbolAddress((void**)&p.xe, g_xe);
  cudaGetSymbolAddress((void**)&p.xa, g_xa); cudaGetSymbolAddress((void**)&p.xb, g_xb);
  void* fn = nullptr; cudaDriverEntryPointQueryResult qr;
  cudaGetDriverEntryPoint("cuTensorMapEncodeTiled", &fn, cudaEnableDefault, &qr);
  auto mk = [&](CUtensorMap* tm, void* base, int rows, int box = 64) {
    const cuuint64_t dim[2] = {64, (cuuint64_t)rows}, str[1] = {128}; const cuuint32_t bx[2] = {64, (cuuint32_t)box}, es[2] = {1, 1};
    ((EncodeFn)fn)(tm, CU_TENSOR_MAP_DATA_TYPE_BFLOAT16, 2, base, dim, str, bx, es, CU_TENSOR_MAP_INTERLEAVE_NONE, CU_TENSOR_MAP_SWIZZLE_128B,
                   CU_TENSOR_MAP_L2_PROMOTION_NONE, CU_TENSOR_MAP_FLOAT_OOB_FILL_NONE);
  };
  mk(&maps.m[TM_H / 128], d_in[0], p.N); mk(&maps.m[TM_WE / 128], d_in[5], 145); mk(&maps.m[TM_WH / 128], d_in[7], 128); mk(&maps.m[TM_Q / 128], p.q, p.N, 16);
  for (int k = 0; k < 2; k++) {
    void* xp = (void*)(k ? p.xb : p.xa);
    const cuuint64_t dim[2] = {(cuuint64_t)G * 64, (cuuint64_t)G}, str[1] = {(cuuint64_t)G * (128 << k)}; const cuuint32_t bx[2] = {64, (cuuint32_t)(k ? BROWS : G)}, es[2] = {1, 1};
    ((EncodeFn)fn)(&maps.m[TM_XA / 128 + k], k ? CU_TENSOR_MAP_DATA_TYPE_UINT32 : CU_TENSOR_MAP_DATA_TYPE_UINT16, 2, xp, dim, str, bx, es, CU_TENSOR_MAP_INTERLEAVE_NONE,
                   CU_TENSOR_MAP_SWIZZLE_NONE, CU_TENSOR_MAP_L2_PROMOTION_NONE, CU_TENSOR_MAP_FLOAT_OOB_FILL_NONE);
  }
  cudaFuncSetAttribute(egnn_kernel, cudaFuncAttributeMaxDynamicSharedMemorySize, SMEM);
  egnn_kernel<<<G, NTHR, SMEM>>>(p, maps);
}
```

```cpp
#include <cuda_runtime.h>
#include <cuda_bf16.h>
#include <cuda_fp16.h>
#include <cuda.h>
#include <stdint.h>
#pragma nv_diag_suppress 549

#define PFN 16
#define PFNS 250
#define FM 0
#define OPQ 0
#define H0 0
#define HALL 1
#define PF0NS 0
#define PFW 0
#define QCODE 0x254a109b7863ull
#define QREV 0x605
#define PFS 1
#define ESZ ""
#define XEF 0
#define OCS ""
#define RNB 2
#define NEARLY 2
#define PFE 0
#define DEFO 1
#define DEFNS 400
#define ABL 0
#define IDL 1
#define BDEL 400
#define CTAMAP (blockIdx.x * 59 % G)
#define PADM 33
#define NPAD 1
#define PADS 1
#define NPE 1
#define HW 3
#define BROWS 44
#define B_HOLD 1
#define LSEQ 0x231200ull
#define HE 0
namespace {

constexpr int G = 132;
constexpr int NTHR = 512, NWK = 352, NCH = 5;
constexpr int NST = 3, STG = 2560;
constexpr int SCAP = 448;

constexpr int OFF_H = 0;
constexpr int OFF_W = 49152;
constexpr int OFF_WD = OFF_W + 16384;
constexpr int OFF_W3 = OFF_WD + 1024;
constexpr int OFF_P2 = OFF_W3 + 2048;
constexpr int OFF_RING = OFF_P2 + 24576;
constexpr int OFF_TE = OFF_RING + 12 * NST * STG;
constexpr int OFF_TS = OFF_TE + SCAP * 64;
constexpr int OFF_INV = OFF_TS - 768;
constexpr int OFF_GP = OFF_TS + SCAP * 32;
constexpr int OFF_WX = OFF_GP + 3072;
constexpr int OFF_LEN = OFF_WX + 128;
constexpr int OFF_MISC = OFF_LEN + 128;
constexpr int OFF_BAR = OFF_MISC + 48;
constexpr int SMEM = OFF_BAR + 256;
static_assert(SMEM <= 232448, "smem");
constexpr uint32_t sb = 1024;
constexpr int OFF_SRCI = OFF_TE;
constexpr int OFF_SB = OFF_RING, OFF_SA = OFF_SB + 34816, OFF_AX = OFF_SA + 32768, OFF_DST = OFF_H + 24576;
constexpr int OFF_WS = OFF_AX + 17408;
constexpr int OFF_BC = OFF_WS + 2304;
constexpr int OFF_CNT = OFF_P2;
constexpr int OFF_DH = OFF_CNT + 2176;
constexpr int OFF_POS = OFF_DH + 128;
constexpr int OFF_EXT = OFF_POS + 3072;
constexpr int OFF_XB = OFF_EXT + 1024, XPAD = G * 256;
static_assert(OFF_XB + XPAD + 1088 <= OFF_RING + 12 * STG && OFF_XB % 128 == 0 && OFF_BC + 544 <= OFF_TE && OFF_P2 % 1024 == 0 && OFF_SA % 1024 == 0 && SCAP * 64 >= 24576, "staging");
constexpr int BAR_DST = OFF_BAR, BAR_SRC = BAR_DST + 40, BAR_T = BAR_SRC + 24, BAR_W = BAR_T + 48, BAR_XA = BAR_W + 8, BAR_PS = BAR_XA + 8, BAR_AW = BAR_PS + 8,
              BAR_QP = BAR_AW + 8, BAR_QR = BAR_QP + 8, BAR_HA = BAR_QR + 8, BAR_EP = BAR_HA + 8, BAR_AX = BAR_EP + 8, BAR_AI = BAR_AX + 8, BAR_HB = BAR_AI + 8, BAR_U = BAR_HB + 8, BAR_WH = BAR_U + 8, BAR_M = BAR_WH + 8, BAR_X = BAR_M + 8, BAR_END = BAR_X + 8;
static_assert(BAR_END <= OFF_BAR + 256, "barriers");
constexpr uint32_t QBYTES = 8u << 20;

__device__ __align__(256) uint4 g_xa[G * G * 8];
__device__ __align__(256) uint4 g_xb[G * G * 16];
__device__ __align__(256) uint2 g_xe[G * G * 32];
__device__ __align__(256) uint4 g_q[2 * QBYTES / 16];
__device__ __align__(256) uint32_t g_sync[8];
#define STAMP(k)

struct Maps { CUtensorMap m[6]; };
constexpr int TM_H = 0, TM_WE = 128, TM_WH = 256, TM_Q = 384, TM_XA = 512, TM_XB = 640;
struct Params {
  const int* dst; uint32_t* sync; int E, EPC, N; uint32_t magic; unsigned long long inv;
  const int* src; const uint16_t* pos; const uint4* ea; const uint16_t* we; const uint16_t* wx; char* q; int force_slow;
  const uint4* xa; const uint4* xb; uint2* xe; uint16_t* out; const uint4* h; const uint16_t* wh;
};
template<int V> struct IC { static constexpr int value = V; };

#define R32(d) "+f"(d[0]),"+f"(d[1]),"+f"(d[2]),"+f"(d[3]),"+f"(d[4]),"+f"(d[5]),"+f"(d[6]),"+f"(d[7]),"+f"(d[8]),"+f"(d[9]),"+f"(d[10]),"+f"(d[11]),"+f"(d[12]),"+f"(d[13]),"+f"(d[14]),"+f"(d[15]),"+f"(d[16]),"+f"(d[17]),"+f"(d[18]),"+f"(d[19]),"+f"(d[20]),"+f"(d[21]),"+f"(d[22]),"+f"(d[23]),"+f"(d[24]),"+f"(d[25]),"+f"(d[26]),"+f"(d[27]),"+f"(d[28]),"+f"(d[29]),"+f"(d[30]),"+f"(d[31])
#define S32 "{%0,%1,%2,%3,%4,%5,%6,%7,%8,%9,%10,%11,%12,%13,%14,%15,%16,%17,%18,%19,%20,%21,%22,%23,%24,%25,%26,%27,%28,%29,%30,%31}"
#define DI __device__ __forceinline__

constexpr uint64_t DHI = ((uint64_t)(1024 >> 4) << 32) | (1ull << 62);
template<int SD> DI void rs64b(float (&d)[32], uint32_t a0, uint32_t a1, uint32_t a2, uint32_t a3, uint64_t db) {
  asm volatile("wgmma.mma_async.sync.aligned.m64n64k16.f32.bf16.bf16 " S32 ", {%32,%33,%34,%35}, %36, %37, 1, 1, 1;" : R32(d) : "r"(a0), "r"(a1), "r"(a2), "r"(a3), "l"(db), "n"(SD)); }
template<int SD> DI void rs64h(float (&d)[32], uint32_t a0, uint32_t a1, uint32_t a2, uint32_t a3, uint64_t db) {
  asm volatile("wgmma.mma_async.sync.aligned.m64n64k16.f32.f16.f16 " S32 ", {%32,%33,%34,%35}, %36, %37, 1, 1, 1;" : R32(d) : "r"(a0), "r"(a1), "r"(a2), "r"(a3), "l"(db), "n"(SD)); }
template<int SD> DI void ss64(float (&d)[32], uint64_t da, uint64_t db) {
  asm volatile("wgmma.mma_async.sync.aligned.m64n64k16.f32.bf16.bf16 " S32 ", %32, %33, %34, 1, 1, 0, 1;" : R32(d) : "l"(da), "l"(db), "n"(SD)); }
DI void trap_if(bool c) { asm volatile("{.reg .pred p; setp.eq.u32 p, %0, 0; @p bra.uni LT_%=; trap; LT_%=:}" :: "r"((uint32_t)c)); }
DI void wg_fence() { asm volatile("wgmma.fence.sync.aligned;" ::: "memory"); }
DI void wg_commit() { asm volatile("wgmma.commit_group.sync.aligned;" ::: "memory"); }
DI void wg_wait0() { asm volatile("wgmma.wait_group.sync.aligned 0;" ::: "memory"); }
DI void fence_regs(float (&d)[32]) { asm volatile("" : R32(d) :: "memory"); }
DI void proxy_fence() { asm volatile("fence.proxy.async.shared::cta;" ::: "memory"); }
DI uint64_t pol_first() { uint64_t r; asm("createpolicy.fractional.L2::evict_first.b64 %0, 1.0;" : "=l"(r)); return r; }
DI float tanh_ap(float x) { float y; asm("tanh.approx.f32 %0, %1;" : "=f"(y) : "f"(x)); return y; }
DI float silu_h(float y) { return fmaf(y, tanh_ap(y), y); }
DI uint32_t pack_bf16(float lo, float hi) { uint32_t r; asm("cvt.rn.bf16x2.f32 %0, %1, %2;" : "=r"(r) : "f"(hi), "f"(lo)); return r; }
DI uint32_t pack_f16(float lo, float hi) { uint32_t r; asm("cvt.rn.f16x2.f32 %0, %1, %2;" : "=r"(r) : "f"(hi), "f"(lo)); return r; }
DI float bf_lo(uint32_t v) { return __uint_as_float(v << 16); }
DI float bf_hi(uint32_t v) { return __uint_as_float(v & 0xFFFF0000u); }
DI uint32_t b2h(uint32_t v, float s) { return pack_f16(s * bf_lo(v), s * bf_hi(v)); }
DI void mbar_wait(uint32_t bar, uint32_t parity = 0) {
  asm volatile("{.reg .pred p, q; .reg .u32 c; mov.u32 c, 0;\n"
    "LW_%=: mbarrier.try_wait.parity.shared::cta.b64 p, [%0], %1;\n add.u32 c, c, 1; setp.lt.and.u32 q, c, 0x200000, !p;\n @q bra.uni LW_%=;}" :: "r"(bar), "r"(parity) : "memory");
}
DI void mbar_arrive(uint32_t bar, int p = 1) { asm volatile("{.reg .pred p; setp.ne.b32 p, %1, 0; @p mbarrier.arrive.shared::cta.b64 _, [%0];}" :: "r"(bar), "r"(p) : "memory"); }
DI void bar_sync(int id, int n) { asm volatile("bar.sync %0, %1;" :: "r"(id), "r"(n) : "memory"); }
DI void bar_arrive(int id, int n) { asm volatile("bar.arrive %0, %1;" :: "r"(id), "r"(n) : "memory"); }
DI __nv_bfloat162 b2(uint32_t v) { return *(__nv_bfloat162*)&v; }
DI uint32_t u2(__nv_bfloat162 v) { return *(uint32_t*)&v; }
DI uint32_t hsq(uint32_t v) { return u2(__hmul2(b2(v), b2(v))); }
DI uint32_t hsub(uint32_t a, uint32_t b) { return u2(__hsub2(b2(a), b2(b))); }
DI uint32_t hhalf(uint32_t v) { return u2(__hmul2(b2(v), __floats2bfloat162_rn(0.5f, 0.5f))); }
DI uint32_t mag2(uint32_t m, uint32_t v) { return __vmaxu2(m, v & 0x7FFF7FFFu); }
DI uint32_t hmag(uint32_t m, uint32_t v) { const __half2 r = __hmax2(*(const __half2*)&m, __habs2(*(const __half2*)&v)); return *(const uint32_t*)&r; }
DI uint32_t magr(uint32_t m) { return max(m & 0xFFFF, m >> 16); }
DI void sts128(uint32_t a, uint32_t x, uint32_t y, uint32_t z, uint32_t w) { asm volatile("st.shared.v4.u32 [%0], {%1,%2,%3,%4};" :: "r"(a), "r"(x), "r"(y), "r"(z), "r"(w) : "memory"); }
DI void sts64(uint32_t a, uint32_t x, uint32_t y) { asm volatile("st.shared.v2.u32 [%0], {%1,%2};" :: "r"(a), "r"(x), "r"(y) : "memory"); }
DI void sts32(uint32_t a, uint32_t x) { asm volatile("st.shared.u32 [%0], %1;" :: "r"(a), "r"(x) : "memory"); }
DI void sts16(uint32_t a, uint32_t x) { asm volatile("st.shared.u16 [%0], %1;" :: "r"(a), "h"((uint16_t)x) : "memory"); }
DI void lds128(uint32_t* v, uint32_t a) { asm volatile("ld.shared.v4.u32 {%0, %1, %2, %3}, [%4];" : "=r"(v[0]), "=r"(v[1]), "=r"(v[2]), "=r"(v[3]) : "r"(a) : "memory"); }
DI void lds64(uint32_t& x, uint32_t& y, uint32_t a) { asm volatile("ld.shared.v2.u32 {%0, %1}, [%2];" : "=r"(x), "=r"(y) : "r"(a) : "memory"); }
DI uint32_t lds32(uint32_t a) { uint32_t x; asm volatile("ld.shared.u32 %0, [%1];" : "=r"(x) : "r"(a) : "memory"); return x; }
DI uint32_t lds16(uint32_t a) { uint32_t x; asm volatile("ld.shared.u16 %0, [%1];" : "=r"(x) : "r"(a) : "memory"); return x; }
DI uint32_t atoms_add(uint32_t a, uint32_t v) { uint32_t r; asm volatile("atom.shared.add.u32 %0, [%1], %2;" : "=r"(r) : "r"(a), "r"(v) : "memory"); return r; }
DI void bulk_load(uint32_t dst, const void* src, uint32_t bytes, uint32_t bar) {
  asm volatile("cp.async.bulk.shared::cluster.global.mbarrier::complete_tx::bytes.L2::cache_hint [%0], [%1], %2, [%3], %4;" :: "r"(dst), "l"(src), "r"(bytes), "r"(bar), "l"(pol_first()) : "memory"); }
DI void bulk_store(void* dst, uint32_t src, uint32_t bytes) { asm volatile("cp.async.bulk.global.shared::cta.bulk_group [%0], [%1], %2;" :: "l"(dst), "r"(src), "r"(bytes) : "memory"); }
DI void mbar_expect(uint32_t bar, uint32_t bytes) { asm volatile("mbarrier.arrive.expect_tx.shared::cta.b64 _, [%0], %1;" :: "r"(bar), "r"(bytes) : "memory"); }
DI void mbar_init(uint32_t bar, int n) { asm volatile("mbarrier.init.shared::cta.b64 [%0], %1;" :: "r"(bar), "r"(n) : "memory"); }
DI void tma_load(uint32_t dst, uint64_t tm, int row, uint32_t bar) {
  asm volatile("cp.async.bulk.tensor.2d.shared::cluster.global.mbarrier::complete_tx::bytes.L2::cache_hint [%0], [%1, {%3, %4}], [%2], %5;" :: "r"(dst), "l"(tm), "r"(bar), "r"(0), "r"(row), "l"(pol_first()) : "memory"); }
DI void tma_store(uint64_t tm, int col, int row, uint32_t src) {
  asm volatile("cp.async.bulk.tensor.2d.global.shared::cta.bulk_group [%0, {%2, %3}], [%1];" :: "l"(tm), "r"(src), "r"(col), "r"(row) : "memory"); }
DI void tma_store_ef(uint64_t tm, int col, int row, uint32_t src) {
  if (XEF) asm volatile("cp.async.bulk.tensor.2d.global.shared::cta.bulk_group.L2::cache_hint [%0, {%2, %3}], [%1], %4;" :: "l"(tm), "r"(src), "r"(col), "r"(row), "l"(pol_first()) : "memory");
  else tma_store(tm, col, row, src); }
DI void bulk_commit() { asm volatile("cp.async.bulk.commit_group;" ::: "memory"); }
DI void bulk_wait_read() { asm volatile("cp.async.bulk.wait_group.read 0;" ::: "memory"); }
DI uint2 ld_poll2(const void* a) { uint2 v; asm volatile("ld.relaxed.gpu.global.v2.u32 {%0, %1}, [%2];" : "=r"(v.x), "=r"(v.y) : "l"(a) : "memory"); return v; }
DI void st_ext(uint2* a, uint32_t v, uint32_t ep) { asm volatile("st.relaxed.gpu.global.v2.u32 [%0], {%1, %2};" :: "l"(a), "r"(v), "r"(ep) : "memory"); }
DI uint32_t ext_get(const uint2* a, uint32_t ep) { uint2 v; int spin = 0; do { v = ld_poll2(a); trap_if(++spin > 4000000); } while (__any_sync(~0u, v.y != ep)); return v.x; }
DI void bulk_wait() { asm volatile("cp.async.bulk.wait_group 0;" ::: "memory"); }
DI void hint_signal(uint32_t* c) { asm volatile("red.relaxed.gpu.global.add.u32 [%0], 1;" :: "l"(c) : "memory"); }
DI void hint_wait(const uint32_t* c, uint32_t target) { uint32_t v; int spin = 0;
  do { asm volatile("ld.relaxed.gpu.global.u32 %0, [%1];" : "=r"(v) : "l"(c) : "memory"); trap_if(++spin > 4000000); } while (__any_sync(~0u, (int)(v - target) < 0)); }
DI void stsm4(uint32_t a, uint32_t x, uint32_t y, uint32_t z, uint32_t w) { asm volatile("stmatrix.sync.aligned.m8n8.x4.shared.b16 [%0], {%1,%2,%3,%4};" :: "r"(a), "r"(x), "r"(y), "r"(z), "r"(w) : "memory"); }
DI void ldsm4(uint32_t* v, uint32_t a) { asm volatile("ldmatrix.sync.aligned.m8n8.x4.shared.b16 {%0,%1,%2,%3}, [%4];" : "=r"(v[0]), "=r"(v[1]), "=r"(v[2]), "=r"(v[3]) : "r"(a) : "memory"); }
DI void ldsm4t(uint32_t* v, uint32_t a) { asm volatile("ldmatrix.sync.aligned.m8n8.x4.trans.shared.b16 {%0,%1,%2,%3}, [%4];" : "=r"(v[0]), "=r"(v[1]), "=r"(v[2]), "=r"(v[3]) : "r"(a) : "memory"); }
DI uint32_t mad16(uint32_t x, uint32_t m, uint32_t c) { uint32_t r; asm("dp2a.lo.u32.u32 %0, %1, %2, %3;" : "=r"(r) : "r"(x), "r"(m), "r"(c)); return r; }
DI bool wbad(uint32_t m, uint32_t hi) { return m > hi || (m && m < 0x3980); }

__device__ __noinline__ void slow_path(const Params& p, int wid, int lane, int node0, int nloc) {
  const uint32_t ab = sb + OFF_P2 + wid * 8704;
  for (int i = lane; i < 32 * 68; i += 32) sts32(ab + i * 4, 0);
  __syncwarp();
  const uint32_t wdv = __ldg((const uint32_t*)(p.we + 128 * 64) + lane), wxv = __ldg((const uint32_t*)p.wx + lane);
  const int nb0 = node0 + wid * 32, cntn = max(0, min(32, nloc - wid * 32));
  auto dot = [&](uint32_t hv, const uint16_t* w, int K2, float& y0, float& y1) {
#pragma unroll 4
    for (int k = 0; k < K2; k++) {
      const uint32_t hk = __shfl_sync(~0u, hv, k), wa = __ldg((const uint32_t*)(w + 2 * k * 64) + lane), wb = __ldg((const uint32_t*)(w + (2 * k + 1) * 64) + lane);
      y0 = fmaf(bf_lo(hk), bf_lo(wa), fmaf(bf_hi(hk), bf_lo(wb), y0)); y1 = fmaf(bf_lo(hk), bf_hi(wa), fmaf(bf_hi(hk), bf_hi(wb), y1));
    }
  };
  auto silu = [](float x) { return x / (1.f + __expf(-x)); };
#pragma unroll 1
  for (int base = 0; base < p.E; base += 32) {
    const int e = base + lane;
    const uint32_t dl = e < p.E ? (uint32_t)(__ldg(p.dst + e) - nb0) : 0xFFFFFFFFu;
    uint32_t mk = __ballot_sync(~0u, dl < (uint32_t)cntn);
    while (mk) {
      const int l = __ffs(mk) - 1; mk &= mk - 1;
      const int ee = base + l, n = __shfl_sync(~0u, dl, l), s = __ldg(p.src + ee);
      const uint16_t *po = p.pos + (size_t)(nb0 + n) * 3, *pp = p.pos + (size_t)s * 3;
      const uint32_t dxy = hsub(__ldg(po) | (__ldg(po + 1) << 16), __ldg(pp) | (__ldg(pp + 1) << 16)), dz = hsub(__ldg(po + 2), __ldg(pp + 2));
      const uint32_t sq = hsq(dxy); const float d2 = bf_lo(sq) + bf_hi(sq) + bf_lo(hsq(dz));
      float y0 = d2 * bf_lo(wdv), y1 = d2 * bf_hi(wdv);
      dot(__ldg((const uint32_t*)(p.h + (size_t)(nb0 + n) * 8) + lane), p.we, 32, y0, y1);
      dot(__ldg((const uint32_t*)(p.h + (size_t)s * 8) + lane), p.we + 64 * 64, 32, y0, y1);
      dot(__ldg((const uint32_t*)(p.ea + (size_t)ee * 2) + (lane & 7)), p.we + 129 * 64, 8, y0, y1);
      const uint32_t mm = pack_bf16(silu(y0), silu(y1));
      float c = bf_lo(mm) * bf_lo(wxv) + bf_hi(mm) * bf_hi(wxv);
#pragma unroll
      for (int o = 16; o; o >>= 1) c += __shfl_xor_sync(~0u, c, o);
      const uint32_t a = ab + n * 272;
      uint32_t x0, x1; lds64(x0, x1, a + lane * 8);
      sts64(a + lane * 8, __float_as_uint(__uint_as_float(x0) + bf_lo(mm)), __float_as_uint(__uint_as_float(x1) + bf_hi(mm)));
      if (lane < 3) { const float df = lane == 0 ? bf_lo(dxy) : lane == 1 ? bf_hi(dxy) : bf_lo(dz); sts32(a + 256 + lane * 4, __float_as_uint(fmaf(c, df, __uint_as_float(lds32(a + 256 + lane * 4))))); }
    }
  }
  __syncwarp();
#pragma unroll 1
  for (int n = 0; n < cntn; n++) {
    uint32_t x0, x1; lds64(x0, x1, ab + n * 272 + lane * 8);
    const uint32_t hv = __ldg((const uint32_t*)(p.h + (size_t)(nb0 + n) * 8) + lane);
    float y0 = 0.f, y1 = 0.f;
    dot(hv, p.wh, 32, y0, y1); dot(pack_bf16(__uint_as_float(x0), __uint_as_float(x1)), p.wh + 64 * 64, 32, y0, y1);
    ((uint32_t*)p.out)[(size_t)(nb0 + n) * 32 + lane] = u2(__hadd2(b2(hv), b2(pack_bf16(silu(y0), silu(y1)))));
    if (lane < 3) p.out[(size_t)p.N * 64 + (size_t)(nb0 + n) * 3 + lane] = (uint16_t)pack_bf16(bf_lo(__ldg(p.pos + (size_t)(nb0 + n) * 3 + lane)) + __uint_as_float(lds32(ab + n * 272 + 256 + lane * 4)), 0.f);
  }
}

__global__ void __launch_bounds__(NTHR, 1) egnn_kernel(const __grid_constant__ Params p, const __grid_constant__ Maps maps) {
  const uint64_t tmb = (uint64_t)&maps;
  extern __shared__ __align__(1024) unsigned char smraw[];
  const int tid = threadIdx.x, cta = CTAMAP;
  const int e0 = cta * p.EPC, n4 = max(0, min(p.EPC, p.E - e0)) >> 2;
  STAMP(0);
  if (tid == NWK) {
#pragma unroll 1
    for (int k = 0; k < NCH; k++) { const int nb = max(0, min(NWK, n4 - k * NWK)) * 16;
      mbar_init(sb + BAR_DST + k * 8, 1);
      asm volatile("fence.mbarrier_init.release.cluster;" ::: "memory");
      mbar_expect(sb + BAR_DST + k * 8, nb);
      if (nb) bulk_load(sb + OFF_DST + k * NWK * 16, (const char*)(p.dst + e0) + k * NWK * 16, nb, sb + BAR_DST + k * 8); }
  }
  const int lane = tid & 31, wid = __shfl_sync(~0u, tid >> 5, 0), w = wid & 3;
  asm volatile("{.reg .pred p; setp.eq.u32 p, %2, 384; @p cp.async.cg.shared.global [%0], [%1], 16;}" :: "r"(sb + OFF_LEN - 192 + (tid >> 1)), "l"(p.sync), "r"(tid & 415) : "memory");

  auto first_node = [&](int c) { return (int)((c * p.inv + 0xFFFFFFFFull) >> 32); };
  const int node0 = first_node(cta), nloc = min(first_node(cta + 1), p.N) - node0;
  const uint32_t ealo = (uint32_t)(uint64_t)p.ea;
  const int epad = max(0, min(e0, p.E - 16));
  auto load_h = [&](int b) { mbar_expect(sb + BAR_T + b * 8, 8192); tma_load(sb + OFF_H + b * 8192, tmb + TM_H, node0 + b * 64, sb + BAR_T + b * 8); };
  auto prefetch_e = [&](int i) {
    const uint32_t nb = (p.E / G) & ~15u;
    if (nb && i < PFN) asm volatile("cp.async.bulk.prefetch.L2.global [%0], %1;" :: "l"((const char*)p.ea + (size_t)(((i * PFS + i * PFS / 32 * (~PFS & 1)) & 31) * G + cta) * nb), "r"(nb) : "memory");
  };
  if (wid >= 12) {
    const int t = tid - 384;
    uint32_t pv[9], ev = 0;
#pragma unroll
    for (int i = 0; i < 3; i++) { const uint16_t* pp = p.pos + (size_t)(node0 + t + 128 * i) * 3;
      pv[3 * i] = pv[3 * i + 1] = pv[3 * i + 2] = 0;
      asm volatile("{.reg .pred p; setp.lt.s32 p, %4, %5;\n @p ld.global.nc.u16 %0, [%3];\n @p ld.global.nc.u16 %1, [%3+2];\n @p ld.global.nc.u16 %2, [%3+4];}"
        : "+r"(pv[3 * i]), "+r"(pv[3 * i + 1]), "+r"(pv[3 * i + 2]) : "l"(pp), "r"(t + 128 * i), "r"(p.N - node0)); }
    asm volatile("{.reg .pred p; setp.lt.u32 p, %3, %5; @p ld.global.nc.u32 %0, [%1]; @p st.global.v4.u32 [%2], {%4, %4, %4, %4};}"
      : "+r"(ev) : "l"((const uint32_t*)(p.ea + (size_t)epad * 2) + t), "l"(p.q + (size_t)(p.N + cta * PADM + (t >> 3) * PADS) * 128 + (t & 7) * 16), "r"(t), "r"(0xF700F700u), "n"(8 * NPAD) : "memory");
    asm volatile("cp.async.wait_all;" ::: "memory");
    __syncwarp();
    const uint32_t e = lds32(sb + OFF_LEN + 8 + w * 16) + 1;
    {
      const uint32_t tg = (1 + e % 3) << 30, v = ((tg >> 16) + 512 + (lane & 7) * 4) * 0x10001u;
      if (t == 0) sts32(sb + OFF_MISC + 32, e);
#pragma unroll
      for (int i = 0; i < 9; i++) sts128(sb + OFF_SA + t * 16 + i * 2048, v, v + 0x10001u, v + 0x20002u, v + 0x30003u);
      bar_sync(6, NTHR);
      mbar_arrive(sb + BAR_EP, lane == 0);
#pragma unroll
      for (int i = 0; i < 17; i++) sts128(sb + OFF_SB + t * 16 + i * 2048, tg, tg, tg, tg); }
    uint32_t mp = 0;
#pragma unroll
    for (int i = 0; i < 3; i++) { sts64(sb + OFF_POS + (t + 128 * i) * 8, pv[3 * i] | (pv[3 * i + 1] << 16), pv[3 * i + 2]); mp = mag2(mag2(mp, pv[3 * i] | (pv[3 * i + 1] << 16)), pv[3 * i + 2]); }
    proxy_fence();
    __syncwarp();
    mbar_arrive(sb + BAR_PS, lane == 0);
    mbar_wait(sb + BAR_W);
    {
      uint32_t v[4], u[4]; const int r = t >> 3, c = t & 7;
      lds128(v, sb + OFF_WS + 128 + t * 16); lds128(u, sb + OFF_WS + c * 16);
      const uint32_t x = lds32(sb + OFF_WS + 2176 + lane * 4);
      sts128(sb + OFF_W3 + r * 128 + ((c ^ (r & 7)) << 4), b2h(v[0], .5f), b2h(v[1], .5f), b2h(v[2], .5f), b2h(v[3], .5f));
      const float s = ((r & 1) || r == 6) ? 0.f : .5f;
      if (t < 64) sts128(sb + OFF_WD + r * 128 + ((c ^ r) << 4), b2h(u[0], s), b2h(u[1], s), b2h(u[2], s), b2h(u[3], s));
      if (t < 32) sts32(sb + OFF_WX + (t & 3) * 32 + (t >> 2) * 4, b2h(x, 1.f));
      const uint32_t m3 = __reduce_max_sync(~0u, magr(mag2(mag2(mag2(mag2(0, v[0]), v[1]), v[2]), v[3]))), md = __reduce_max_sync(~0u, magr(mag2(mag2(mag2(mag2(0, u[0]), u[1]), u[2]), u[3])));
      if (wbad(m3, 0x4000) || wbad(md, 0x4000) || wbad(__reduce_max_sync(~0u, magr(mag2(0, x))), 0x4700) || magr(mp) >= 0x4200 || magr(mag2(0, ev)) >= 0x4380) sts32(sb + OFF_MISC + 8, 1);
    }
    if (w == 1) {
#pragma unroll 1
      for (int b = HE; b < HW; b++) { mbar_wait(sb + BAR_SRC + max(0, H0 + b) * 8); if (lane == 0) load_h(b); }
    }
    bar_sync(3, 128);
    const uint32_t frag = (w * 16 + (lane & 15)) * 128 + (((lane >> 4) ^ (lane & 7)) << 4);
    uint32_t mq = 0;
#pragma unroll 1
    for (int b = 0; b < 6; b++) {
      float acc[32];
      const uint64_t da = DHI | (((sb + OFF_H) >> 4) + b * 512), db = DHI | ((sb + OFF_W) >> 4);
      const uint32_t v0 = lds16(sb + OFF_POS + b * 512 + w * 128 + lane * 2), v1 = lds16(sb + OFF_POS + 64 + b * 512 + w * 128 + lane * 2);
      mbar_wait(sb + BAR_T + b * 8);
      if (b == 0) STAMP(25);
      if (b == 5) STAMP(26);
      wg_fence();
      ss64<0>(acc, da, db); ss64<1>(acc, da + 2, db + 128); ss64<1>(acc, da + 4, db + 256); ss64<1>(acc, da + 6, db + 384);
      wg_commit();
      if (b == 0) mbar_wait(sb + BAR_AW);
      if (t == 32) { if (HALL) { if (b == 0) for (int k = HW; k < 6; k++) load_h(k); } else if (b + HW < 6) load_h(b + HW); }
      __syncwarp();
      uint32_t ff[6], fg[6];
#pragma unroll
      for (int j = 0; j < 6; j++) { ff[j] = (__byte_perm((j & 1) ? v1 : v0, 0, 0x4140) >> (3 * (j >> 1))) & 0x00070007u; fg[j] = __vsub2(0x00040004u, ff[j]);
        asm volatile("" : "+r"(ff[j]), "+r"(fg[j])); }
      wg_wait0(); fence_regs(acc);
      uint32_t o[16];
#pragma unroll
      for (int j = 0; j < 16; j++) o[j] = pack_f16(.5f * acc[2 * j], .5f * acc[2 * j + 1]);
#pragma unroll
      for (int j = 0; j < 6; j++) {
        const uint32_t m = o[j] & 0x7FFF7FFFu; mq = __vmaxu2(mq, m);
        o[j] = (__viaddmax_s16x2(m, fg[j], 0) & 0xFFF8FFF8u) | ff[j] | (o[j] & 0x80008000u); }
      if (b == 4) mbar_wait(sb + BAR_AX);
      const uint32_t qs = sb + OFF_SA + b * 8192;
#pragma unroll
      for (int j = 0; j < 4; j++) stsm4((qs + frag) ^ (j << 5), o[4 * j], o[4 * j + 1], o[4 * j + 2], o[4 * j + 3]);
      proxy_fence();
      __syncwarp();
      if (lane == 0 && b * 64 + w * 16 < nloc) tma_store(tmb + TM_Q, 0, node0 + b * 64 + w * 16, qs + w * 2048);
    }
    if (lane == 0) bulk_commit();
    { const uint32_t m = __reduce_max_sync(~0u, magr(mq)); if (lane == 0) sts32(sb + OFF_MISC + 16 + w * 4, m); }
    asm volatile("setmaxnreg.dec.sync.aligned.u32 32;");
    bulk_wait();
    bar_sync(3, 128);
    if (w == 0) {
      STAMP(18);
      uint32_t mv[4]; lds128(mv, sb + OFF_MISC + 16);
      const uint32_t mx = max(max(mv[0], mv[1]), max(mv[2], mv[3]));
      mbar_arrive(sb + BAR_QR, lane == 0);
      STAMP(19);
      if (lane == 0) {
        if (nloc > 0 && (mx >= 0x7BF0 || mx < 0x1400)) asm volatile("st.relaxed.gpu.global.u32 [%0+4], %1;" :: "l"(p.sync), "r"(e) : "memory");
        asm volatile("red.release.gpu.global.add.u32 [%0], 1;" :: "l"(p.sync) : "memory");
      }
      __syncwarp();
      uint32_t c, f; int spin = 0;
      do { asm volatile("ld.acquire.gpu.global.v2.u32 {%0, %1}, [%2];" : "=r"(c), "=r"(f) : "l"(p.sync) : "memory"); trap_if(++spin > 4000000); } while (__any_sync(~0u, (int)(c - e * G) < 0));
      if (f == e) sts32(sb + OFF_MISC + 8, 1);
      if (cta == 0 && lane == 0) asm volatile("st.relaxed.gpu.global.u32 [%0+8], %1;" :: "l"(p.sync), "r"(e) : "memory");
      STAMP(20);
      __syncwarp();
      mbar_arrive(sb + BAR_QP, lane == 0);
    }
    if (w == 2) {
      const uint32_t tg = (1 + e % 3) << 30;
      hint_wait(p.sync + 5, e * G);
      if (lane == 0) { mbar_expect(sb + BAR_HB, XPAD);
#pragma unroll 1
        for (int o = 0; o < 4; o++) bulk_load(sb + OFF_XB + o * (G * 64), (const char*)p.xb + (size_t)(cta * 4 + o) * (G * 64), G * 64, sb + BAR_HB); }
      STAMP(21);
      bar_sync(7, 384);
      if (lane < 16) sts32(sb + OFF_XB + XPAD + lane * 4, tg + p.N + cta * PADM + (lane & (NPAD - 1)) * PADS);
      const uint32_t nx = __shfl_sync(~0u, lds32(sb + OFF_MISC + 8) ? 0 : lds32(sb + OFF_MISC + 4), 0);
#pragma unroll 1
      for (uint32_t k = 0; k < nx; k += 32) {
        const uint32_t i = min(k + lane, nx - 1), xr = lds32(sb + OFF_EXT + i * 4), row = (xr >> 9) & 255;
        const uint32_t v = ext_get(p.xe + (cta * G + row) * 32 + ((xr >> 17) & 31), e), x = lds32(sb + OFF_CNT + (xr & 511) * 4) + (xr >> 22) * 16;
        sts32(sb + OFF_XB + XPAD + 64 + i * 4, v); sts16(sb + OFF_TS + x, XPAD + 64 + i * 4);
        sts32(sb + OFF_TE + x * 2, mad16(v, 0x2000u, ealo - (tg >> 11) + row * p.EPC * 32));
      }
      __syncwarp();
      mbar_arrive(sb + BAR_HB, lane == 0);
    }
    if (w == 1) {
      if (PFW) mbar_wait(sb + PFW);
      __nanosleep(PF0NS);
#pragma unroll 1
      for (int i = PFE; i < PFN; i++) { if (lane == 0) prefetch_e(i); __nanosleep(PFNS); }
    }
    if (w == 3) {
      if (lane == 0) { mbar_expect(sb + BAR_U, 16384); tma_load(sb + OFF_W, tmb + TM_WH, 0, sb + BAR_U); }
      __syncwarp();
      bar_sync(4, 416);
      if (lane == 0) tma_load(sb + OFF_W + 8192, tmb + TM_WH, 64, sb + BAR_U);
    }
    bar_sync(3, 128);
    mbar_wait(sb + BAR_U);
    uint32_t mh = 0;
#pragma unroll 1
    for (int i = t; i < 1024; i += 128) {
      uint32_t v[4]; const uint32_t r = (i >> 3) & 7, j = (i ^ r) & 7;
#pragma unroll
      for (int k = 0; k < 4; k++) v[k] = lds32(sb + OFF_W + (i >> 3) * 128 + ((((j & 4) + k) ^ r) << 4) + (j & 3) * 4);
      __syncwarp();
      if (i < 512) sts128(sb + OFF_W + i * 16, hhalf(v[0]), hhalf(v[1]), hhalf(v[2]), hhalf(v[3]));
      else { sts128(sb + OFF_W + i * 16, b2h(v[0], .5f), b2h(v[1], .5f), b2h(v[2], .5f), b2h(v[3], .5f)); mh = mag2(mag2(mag2(mag2(mh, v[0]), v[1]), v[2]), v[3]); } }
    if (wbad(__reduce_max_sync(~0u, magr(mh)), 0x4700)) sts32(sb + OFF_MISC + 12, 1);
    proxy_fence();
    __syncwarp();
    mbar_arrive(sb + BAR_WH, lane == 0);
    if (DEFO) { if (!__shfl_sync(~0u, lds32(sb + OFF_MISC + 8), 0)) {
      mbar_wait(sb + BAR_M);
      __nanosleep(DEFO);
#pragma unroll 1
      for (int i = 0; i < 12; i++) { uint32_t v[4]; const uint32_t n = lds16(sb + OFF_GP + i * 256 + (t >> 3) * 8 + 6);
        lds128(v, sb + OFF_H + n * 128 + (((n ^ t) & 7) << 4));
        if (n < nloc) ((uint4*)p.out)[(size_t)(node0 + n) * 8 + (t & 7)] = make_uint4(v[0], v[1], v[2], v[3]);
        __nanosleep(DEFNS); }
      uint32_t pa_[9];
#pragma unroll
      for (int k = 0; k < 9; k++) { const uint32_t i = t + 128 * k, n = (i * 43691u) >> 17; pa_[k] = lds16(sb + OFF_INV + n * 2) + (i - 3 * n) * 2; }
      uint16_t* po = p.out + (size_t)p.N * 64 + node0 * 3 + t;
      mbar_wait(sb + BAR_X);
#pragma unroll
      for (int k = 0; k < 9; k++) pa_[k] = lds16(sb + OFF_GP + pa_[k]);
#pragma unroll
      for (int k = 0; k < 9; k++) if (t + 128 * k < nloc * 3) po[128 * k] = pa_[k];
      asm volatile("{.reg .pred p, q; setp.ne.u32 p, 0, 0; bar.red.or.pred q, 5, 512, p;}" ::: "memory"); } }
    return;
  }

  if (tid == 320) {
    mbar_init(sb + BAR_W, 1);
    asm volatile("fence.mbarrier_init.release.cluster;" ::: "memory");
    mbar_expect(sb + BAR_W, 2 * 8192 + 2304);
    tma_load(sb + OFF_W, tmb + TM_WE, 64, sb + BAR_W); tma_load(sb + OFF_W + 8192, tmb + TM_WE, 0, sb + BAR_W);
    bulk_load(sb + OFF_WS, p.we + 128 * 64, 2176, sb + BAR_W); bulk_load(sb + OFF_WS + 2176, p.wx, 128, sb + BAR_W);
  }
  if (tid == 288) {
#pragma unroll
    for (int a = BAR_SRC; a < BAR_END; a += 8) if (a != BAR_W) mbar_init(sb + a, a == BAR_WH || a == BAR_PS || a == BAR_EP ? 4 : a == BAR_XA ? 11 : a == BAR_HB ? 2 : a >= BAR_M ? 12 : 1);
    asm volatile("fence.mbarrier_init.release.cluster;" ::: "memory");
    asm volatile("prefetch.tensormap [%0];" :: "l"(tmb + TM_XA)); asm volatile("prefetch.tensormap [%0];" :: "l"(tmb + TM_H));
    asm volatile("prefetch.tensormap [%0];" :: "l"(tmb + TM_XB)); asm volatile("prefetch.tensormap [%0];" :: "l"(tmb + TM_Q));
  }
  {
    if (tid < 144) { const uint32_t z = (tid >> 3) == 16 ? 0x8000u : 0u; sts128(sb + OFF_CNT + tid * 16, z, z, z, z); }
    else if (tid <= 144 + G) sts32(sb + OFF_BC + (tid - 144) * 4, ((tid - 144) & 31) * 4);
    const uint32_t sp = (XPAD + (tid & 1) * 32) * 0x10001u + 0x40000u, em = first_node(G);
    if (wid < 7) {
#pragma unroll
      for (int i = 0; i < 4; i++) sts128(sb + OFF_TS + tid * 16 + i * 3584, sp, sp + 0x80008u, sp + 0x100010u, sp + 0x180018u);
    }
    static_assert(SCAP * 32 == 4 * 3584, "fill");
#pragma unroll 1
    for (int i = n4 + tid; i < 1536; i += 384) sts128(sb + OFF_DST + i * 16, em, em, em, em);
    if (tid == 321) sts128(sb + OFF_MISC, 0, 0, p.force_slow, 0);
  }
  bar_arrive(6, NTHR);
  bar_sync(0, 384);
  uint32_t ep, tag, eb0, pk[12], r0[12], r1[12], cb;
  uint2 vb[12];
  auto get_tag = [&]() { mbar_wait(sb + BAR_EP); ep = lds32(sb + OFF_MISC + 32); tag = (1 + ep % 3) << 30; eb0 = ealo - (tag >> 11); };
  if (wid == 11) {
    trap_if(sb != (uint32_t)__cvta_generic_to_shared(smraw));
#pragma unroll 1
    for (unsigned long long q = LSEQ; q; q >>= 8) { const int k = (q >> 4) & 7, nb = max(0, min(8192, n4 * 16 - k * 8192));
      if (!(q & 8)) mbar_wait(sb + BAR_DST + ((uint32_t)q & 7) * 8);
      if (lane == 0) {
        if (k >= 3) load_h(k - 3);
        else { mbar_expect(sb + BAR_SRC + k * 8, nb);
          if (nb) bulk_load(sb + OFF_SRCI + k * 8192, (const char*)(p.src + e0) + k * 8192, nb, sb + BAR_SRC + k * 8); } } }
    get_tag();
    mbar_wait(sb + BAR_PS);
    bar_sync(12, 384);
    uint32_t xm = 0;
#pragma unroll
    for (int k = 0; k < 5; k++) xm |= (lds32(sb + OFF_BC + min(lane + 32 * k, G - 1) * 4) >= (65 << 9) && lane + 32 * k < G) << k;
    auto ext_send = [&](int pl) {
      uint32_t x = xm;
      for (uint32_t m; (m = __ballot_sync(~0u, x));) {
        const uint32_t l = __ffs(m) - 1, j = l + 32 * (__ffs(__shfl_sync(~0u, x, l)) - 1);
        if (lane == l) x &= x - 1;
        const uint32_t e = min(lds16(sb + OFF_AX + j * 128 + ((4 * l + 2 * lane) & 126)), 6143u);
        if (pl) st_ext(p.xe + (j * G + cta) * 32 + lane, lds32(sb + OFF_SRCI + e * 4) + tag + (e << 16), ep);
        else { const uint32_t cn = lds32(sb + OFF_BC + j * 4) >> 9, v = cn > 96 ? 1 : lane + 64 < cn ? 512 | (lds32(sb + OFF_DST + e * 4) & 511) : 0;
          asm volatile("red.shared.xor.b32 [%0], %1;" :: "r"(sb + OFF_SA + j * 128 + ((l + lane) & 31) * 4), "r"(((v & 63) << 10) | ((v >> 6) << 26)) : "memory"); }
      }
    };
    if (__any_sync(~0u, xm)) { ext_send(0); proxy_fence(); __syncwarp(); }
    if (lane == 0) { tma_store_ef(tmb + TM_XA, cta * 64, 0, sb + OFF_SA); bulk_commit(); mbar_arrive(sb + BAR_AI); bulk_wait(); hint_signal(p.sync + 4); mbar_arrive(sb + BAR_AW); STAMP(16); }
    __syncwarp();
    bar_sync(13, 384);
    if (!B_HOLD && lane == 0) { tma_store_ef(tmb + TM_XB, cta * 64, 0, sb + OFF_SB); bulk_commit(); }
    __syncwarp();
    ext_send(1);
    mbar_arrive(sb + BAR_AX, lane == 0);
    if (B_HOLD) mbar_wait(sb + (B_HOLD == 1 ? BAR_HA : BAR_XA));
    if (BDEL) __nanosleep(BDEL);
    if (lane == 0) {
      bulk_wait();
#pragma unroll 1
      for (int r = B_HOLD ? 0 : BROWS; r < G; r += BROWS) { tma_store_ef(tmb + TM_XB, cta * 64, r, sb + OFF_SB + r * 256); bulk_commit(); bulk_wait(); }
      hint_signal(p.sync + 5);
#pragma unroll 1
      for (int i = 0; i < PFE; i++) prefetch_e(i);
      STAMP(17);
    }
    __syncwarp();
  } else {
    {
      uint32_t d[4 * NCH], jj[4 * NCH], rr[4 * NCH];
      auto count = [&](int k) {
        mbar_wait(sb + BAR_DST + k * 8);
        lds128(d + 4 * k, sb + OFF_DST + (tid + NWK * k) * 16);
#pragma unroll
        for (int i = 4 * k; i < 4 * k + 4; i++) { jj[i] = d[i] * p.magic; rr[i] = atoms_add(__dp4a(jj[i], 0x04000000u, sb + OFF_BC), 0x202u); }
      };
      auto place = [&](int k) {
#pragma unroll
        for (int i = 4 * k; i < 4 * k + 4; i++) {
          const uint32_t o = __dp4a(jj[i], 0x80000000u, rr[i] & 0x807Eu);
          d[i] = (d[i] & 511) | (tag >> 16);
          asm("{.reg .pred p; setp.ge.u32 p, %1, 0x8000; @p add.u32 %0, %2, %3;}" : "+r"(d[i]) : "r"(o), "r"(tid * 4), "r"(NWK * k * 4 + (i & 3)));
          sts16(sb + OFF_SA + o, d[i]); jj[i] = __viaddmin_u32(o, o, G * 256);
        }
      };
      count(0); STAMP(1); count(1); get_tag(); place(0); count(2); place(1); count(3); place(2);
      if (wid < 4) { count(4); STAMP(15); place(3); place(4); } else place(3);
      proxy_fence();
      bar_arrive(12, 384);
      STAMP(2);
      mbar_wait(sb + BAR_AI);
      mbar_wait(sb + BAR_SRC); mbar_wait(sb + BAR_SRC + 8); mbar_wait(sb + BAR_SRC + 16);
      STAMP(12);
#pragma unroll
      for (int k = 0; k < NCH; k++) lds128(d + 4 * k, sb + OFF_SRCI + (tid + NWK * k) * 16);
      const uint32_t tb = tag + (tid << 18);
#pragma unroll
      for (int i = 0; i < 4 * NCH; i++) if (i < 4 * NCH - 4 || wid < 4) sts32(sb + OFF_SB + jj[i], d[i] + tb + ((NWK * (i >> 2) * 4 + (i & 3)) << 16));
      proxy_fence();
      bar_arrive(13, 384);
      STAMP(3);
    }
    const uint32_t rot = (lane + cta) & 31;
    cb = sb + OFF_CNT - (tag >> 14);
    {
      const uint32_t* xa = (const uint32_t*)(p.xa + (cta * G + wid) * 8) + rot;
      if (wid < 8) { const uint32_t e_ = ealo + (epad + (tid * 4 & (NPE - 1))) * 32, d_ = NPE > 1 ? 32 : 0;
        mbar_wait(sb + BAR_AX);
#pragma unroll
        for (int i = 0; i < 7; i++) sts128(sb + OFF_TE + tid * 16 + i * 4096, e_, e_ + d_, e_ + 2 * d_, e_ + 3 * d_); }
      static_assert(SCAP * 64 == 7 * 4096, "fill");
      if (wid == 10) { hint_wait(p.sync + 4, ep * G); mbar_arrive(sb + BAR_HA, lane == 0); }
      mbar_wait(sb + BAR_HA);
      STAMP(14);
      const uint32_t tp = tag | (tag >> 16);
      uint32_t st;
#pragma unroll 1
      for (int spin = 0;; spin++) {
        st = 0;
#pragma unroll
        for (int k = 0; k < 12; k++) asm volatile("ld.relaxed.gpu.global.u32 %0, [%1];" : "=r"(pk[k]) : "l"(xa + k * 352) : "memory");
#pragma unroll
        for (int k = 0; k < 12; k++) st |= pk[k] ^ tp;
        st = __reduce_or_sync(~0u, st);
        if (!(st >> 30)) break;
        trap_if(spin > 2000000);
      }
      if (st & 0x3C00FC00u) {
#pragma unroll 1
        for (;;) {
          uint32_t x = 0, row = 0;
#pragma unroll
          for (int k = 0; k < 12; k++) { const uint32_t y = (pk[k] ^ tp) & 0x3C00FC00u; if (!x && y) { x = y; row = wid + 11 * k; pk[k] ^= y; } }
          if (!__any_sync(~0u, x)) break;
          const uint32_t n = ((x >> 10) & 63) | ((x >> 20) & 0x1C0);
          if (x >> 29) {
            const uint32_t r = atoms_add(sb + OFF_CNT + n * 4, 16), idx = atoms_add(sb + OFF_MISC + 4, 1);
            if (idx < 256) sts32(sb + OFF_EXT + idx * 4, n | (row << 9) | (lane << 17) | (min(r >> 4, 255u) << 22));
            else x = 1;
          }
          if (x && !(x >> 29)) sts32(sb + OFF_MISC + 8, 1);
          __syncwarp();
        }
      }
#pragma unroll
      for (int k = 0; k < 12; k++) { r0[k] = mad16(pk[k], 0x0004u, cb); r1[k] = mad16(pk[k], 0x0400u, cb); vb[k].x = atoms_add(r0[k], 16); vb[k].y = atoms_add(r1[k], 16); }
      if (B_HOLD == 2) mbar_arrive(sb + BAR_XA, lane == 0);
    }
    STAMP(4);
    if (wid >= 6) bar_arrive(11, NWK);
    if (wid < 6) {
      uint32_t ca[2], ky[2], dr[2], sq[2], ps[4];
#pragma unroll
      for (int i = 0; i < 2; i++) { ca[i] = sb + OFF_CNT + ((node0 + tid + 192 * i) & 511) * 4; lds64(ps[2 * i], ps[2 * i + 1], sb + OFF_POS + (tid + 192 * i) * 8); ps[2 * i + 1] |= (tid + 192 * i) << 16; }
      bar_sync(11, NWK);
      STAMP(5);
#pragma unroll
      for (int i = 0; i < 2; i++) ky[i] = (lds32(ca[i]) + 16) >> 5;
      if (max(ky[0], ky[1]) > 31) sts32(sb + OFF_MISC + 8, 1);
#pragma unroll
      for (int i = 0; i < 2; i++) { ky[i] = min(ky[i], 31u); dr[i] = atoms_add(sb + OFF_DH + ky[i] * 4, 1); }
      bar_sync(10, 192);
      const uint32_t hv = lds32(sb + OFF_DH + lane * 4);
      uint32_t inc = hv;
#pragma unroll
      for (int o = 1; o < 32; o <<= 1) asm("{.reg .pred p; .reg .b32 y; shfl.sync.down.b32 y|p, %0, %1, 31, -1; @p add.u32 %0, %0, y;}" : "+r"(inc) : "r"(o));
#pragma unroll
      for (int i = 0; i < 2; i++) {
        const uint32_t pos = __shfl_sync(~0u, inc - hv, ky[i]) + dr[i];
        const uint32_t ak = (uint32_t)(QCODE >> ((pos >> 5) * 4)) & 15, l = (pos >> 3) & 3;
        sq[i] = (ak >> 2) * 16 + ((QREV >> (pos >> 5) & 1) ? 3 - l : l) * 4 + (ak & 3);
        dr[i] = pos & 7;
        asm volatile("{.reg .pred p; setp.eq.u32 p, %2, 0; @p st.shared.u8 [%0], %1;}" :: "r"(sb + OFF_LEN + sq[i]), "r"(max(ky[i], 1u)), "r"(dr[i]) : "memory");
        sts64(sb + OFF_GP + sq[i] * 64 + dr[i] * 8, ps[2 * i], ps[2 * i + 1]);
        sts16(sb + OFF_INV + (tid + 192 * i) * 2, sq[i] * 64 + dr[i] * 8);
      }
      bar_sync(10, 192);
      const uint32_t ln = lds32(sb + OFF_LEN + min(lane, 11) * 4), tot = __dp4a(ln, 0x01010101u, 0u);
      inc = tot;
#pragma unroll
      for (int o = 1; o < 16; o <<= 1) asm("{.reg .pred p; .reg .b32 y; shfl.sync.up.b32 y|p, %0, %1, 0, -1; @p add.u32 %0, %0, y;}" : "+r"(inc) : "r"(o));
      if (wid == 1) sts32(sb + OFF_CNT + 2048 + lane * 4, 0);
      if (tid < 12) { sts32(sb + OFF_LEN + 64 + tid * 4, inc - tot); if (inc > SCAP - 12) sts32(sb + OFF_MISC + 8, 1); }
#pragma unroll
      for (int i = 0; i < 2; i++) sts32(ca[i], __dp4a(__shfl_sync(~0u, ln, sq[i] >> 2), 0x00010101u >> (24 - 8 * (sq[i] & 3)), __shfl_sync(~0u, inc - tot, sq[i] >> 2)) * 32 + dr[i] * 2);
    }
    bar_arrive(7, 384);
  }
  bar_sync(1, 384);
  STAMP(6);
  if (wid != 11 && !__shfl_sync(~0u, lds32(sb + OFF_MISC + 8), 0)) {
#pragma unroll
    for (int k = 0; k < 12; k++) { r0[k] = lds32(r0[k]); r1[k] = lds32(r1[k]); }
#pragma unroll
    for (int k = 0; k < 12; k++) { r0[k] += vb[k].x; r1[k] += vb[k].y; }
  } else {
#pragma unroll
    for (int k = 0; k < 12; k++) r0[k] = r1[k] = 0x8000;
  }
  auto put_ids = [&]() {
    const uint32_t id = wid * 256 + ((lane + cta) & 31) * 8;
    auto put = [&](uint32_t x, uint32_t v) { asm volatile("{.reg .pred p; setp.lt.u32 p, %0, 0x8000; @p st.shared.u16 [%0+%2], %1;}" :: "r"(x), "h"((uint16_t)v), "n"(sb + OFF_TS) : "memory"); };
#pragma unroll
    for (int k = 0; k < 12; k++) { put(IDL ? pk[k] & 0xFFFF : r0[k], id + k * 2816); put(IDL ? pk[k] >> 16 : r1[k], id + k * 2816 + 4); }
  };
  if (!IDL) put_ids();
  STAMP(7);
  mbar_wait(sb + BAR_QR);
  asm volatile("setmaxnreg.inc.sync.aligned.u32 160;");
  if (IDL) {
#pragma unroll
    for (int k = 0; k < 12; k++) asm volatile("prmt.b32 %0, %1, %2, 0x5410;" : "=r"(pk[k]) : "r"(r0[k]), "r"(r1[k]));
  }
  uint32_t pa[8], sp[8], pq[16]; float chk = 0.f;
  {
    uint32_t hf[32], mp = 0; float a0[32], a1[32];
    const uint32_t an = sb + OFF_GP + wid * 256 + (lane & 15) * 8 + 6, n0 = lds16(an), n1 = lds16(an + 128);
#pragma unroll
    for (int j = 0; j < 8; j++) { const uint32_t nd = j < 4 ? n0 : n1; ldsm4(hf + 4 * j, (sb + OFF_H + nd * 128 + (((nd & 7) << 4) ^ (lane & 16))) ^ ((j & 3) << 5)); }
    const uint64_t db = DHI | ((sb + OFF_W + 8192) >> 4);
    wg_fence();
    rs64b<0>(a0, hf[0], hf[1], hf[2], hf[3], db); rs64b<1>(a0, hf[4], hf[5], hf[6], hf[7], db + 128); rs64b<1>(a0, hf[8], hf[9], hf[10], hf[11], db + 256); rs64b<1>(a0, hf[12], hf[13], hf[14], hf[15], db + 384);
    wg_commit();
    rs64b<0>(a1, hf[16], hf[17], hf[18], hf[19], db); rs64b<1>(a1, hf[20], hf[21], hf[22], hf[23], db + 128); rs64b<1>(a1, hf[24], hf[25], hf[26], hf[27], db + 256); rs64b<1>(a1, hf[28], hf[29], hf[30], hf[31], db + 384);
    wg_commit();
    if (IDL) put_ids();
    asm volatile("wgmma.wait_group.sync.aligned 1;" ::: "memory"); fence_regs(a0);
#pragma unroll
    for (int j = 0; j < 8; j++) { const uint32_t x = pack_f16(.5f * a0[4 * j], .5f * a0[4 * j + 1]), y = pack_f16(.5f * a0[4 * j + 2], .5f * a0[4 * j + 3]); mp = hmag(hmag(mp, x), y);
      asm volatile("movmatrix.sync.aligned.m8n8.trans.b16 %0, %1;" : "=r"(pa[j]) : "r"(x)); asm volatile("movmatrix.sync.aligned.m8n8.trans.b16 %0, %1;" : "=r"(sp[j]) : "r"(y)); }
    wg_wait0(); fence_regs(a1);
    bar_arrive(4, 416);
#pragma unroll
    for (int j = 0; j < 16; j++) { pq[j] = pack_f16(.5f * a1[2 * j], .5f * a1[2 * j + 1]); mp = hmag(mp, pq[j]); }
    if (magr(mp) >= 0x7000) chk = __int_as_float(0x7FC00000);
  }
  if (wid == 0) STAMP(23);
  uint32_t bad;
  {
    const uint32_t ring = sb + OFF_RING + wid * STG, p2 = sb + OFF_P2 + wid * 2048;
    uint32_t lens = __shfl_sync(~0u, lds32(sb + OFF_LEN + wid * 4), 0);
    uint32_t rem = __dp4a(lens, 0x20202020u, 0u);
    const uint32_t base = min(lds32(sb + OFF_LEN + 64 + wid * 4), SCAP);
    uint32_t a_s = sb + OFF_TS + base * 32 + (lane >> 3) * 8, a_e = sb + OFF_TE + base * 64 + (lane >> 1) * 4;
    uint32_t k0 = (uint32_t)(uint64_t)p.q + (((lane & 7) ^ ((lane >> 1) & 4)) << 4), k1 = k0 ^ 16, k2 = k0 ^ 32, k3 = k0 ^ 48, ke = ((lane ^ (lane >> 3)) & 1) << 4;
    uint32_t dst0 = ring + (lane >> 3) * 640 + (lane & 7) * 16;
    const uint32_t qhi = (uint32_t)((uint64_t)p.q >> 32), ehi = (uint32_t)((uint64_t)p.ea >> 32);
    uint32_t s0, s1, ev, to = 0, so = 12 * STG;
    auto tl_ = [&]() { lds64(s0, s1, a_s + to); asm volatile("ld.shared.u32 %0, [%1]; add.u32 %1, %1, 64;" : "=&r"(ev), "+r"(a_e) :: "memory"); to += 32; };
#define CPQ(LH, x, k, off) "dp2a." LH ".u32.u32 lo, " x ", 0x80000080, " k "; mov.b64 a, {lo, %7}; @p cp.async.cg.shared.global [%0+" #off "], [a], 16;\n"
#define CPE "or.b32 lo, %10, %11; mov.b64 a, {lo, %12}; @p cp.async.cg.shared.global" ESZ " [%0+512], [a], 16;\n"
#define CPA(BODY) asm volatile("{.reg .b32 lo; .reg .b64 a; .reg .pred p; setp.le.u32 p, %8, %9;\n" BODY "}" \
      :: "r"(dst0 + so), "r"(s0), "r"(s1), "r"(k0), "r"(k1), "r"(k2), "r"(k3), "r"(qhi), "r"(to), "r"(rem), "r"(ev), "r"(ke), "r"(ehi) : "memory")
#define CPQ4 CPQ("lo", "%1", "%3", 0) CPQ("hi", "%1", "%4", 128) CPQ("lo", "%2", "%5", 256) CPQ("hi", "%2", "%6", 384) "cp.async.commit_group;"
    auto issue = [&]() { CPA(CPE CPQ4); so = so == (NST - 1) * 12 * STG ? 0 : so + 12 * STG; };
    const int g = lane >> 2, qd = lane & 3;
    const uint32_t sw = ((lane >> 4) ^ (lane & 7)) << 4, fr = (lane & 15) * 128 + sw;
    uint32_t qa0 = ring + (g & 3) * 640 + qd * 128 + sw, qa1 = qa0 ^ 32, qa2 = qa0 ^ 64, qa3 = qa0 ^ 96;
    uint32_t eadr = ring + 512 + (g & 3) * 640 + qd * 32 + ((((lane >> 4) ^ g) & 1) << 4);
    uint32_t oh0 = g == 2 * qd ? 0x3C00u : g == 2 * qd + 1 ? 0x3C000000u : 0u, oh1 = oh0;
    uint32_t a_g = sb + OFF_GP + wid * 256 + lane * 2;
    uint32_t a_n = sb + OFF_GP + wid * 256 + (lane & 15) * 8 + 6;
    uint32_t a_p = ((lane & 8) ? p2 : sb + OFF_WD) + (lane & 7) * 128 + ((((lane >> 4) ^ lane) & 7) << 4);
    uint32_t a_w = sb + OFF_W3 + fr;
#define OPQ4(A, B, C, D) asm volatile("shfl.sync.bfly.b32 %0, %0, 0, 31, -1; shfl.sync.bfly.b32 %1, %1, 0, 31, -1; shfl.sync.bfly.b32 %2, %2, 0, 31, -1; shfl.sync.bfly.b32 %3, %3, 0, 31, -1;" : "+r"(A), "+r"(B), "+r"(C), "+r"(D))
    asm volatile("shfl.sync.idx.b32 %0, %0, %1, 31, -1;" : "+r"(oh1) : "r"(lane));
    if (OPQ & 1) OPQ4(a_w, oh0, ke, dst0);
    if (OPQ & 2) OPQ4(qa0, qa1, qa2, qa3);
    if (OPQ & 4) OPQ4(k0, k1, k2, k3);
    if (OPQ & 8) OPQ4(a_g, a_n, a_p, eadr);
    uint32_t w3[16], wv[8], bp[16], sum[8], Y[16], M[16], own, ownp, dpk; uint16_t tl[16], th[16];
    float pacc = 0.f;
    auto wload = [&]() {
#pragma unroll
      for (int j = 0; j < 4; j++) ldsm4t(w3 + 4 * j, a_w ^ (j << 5));
      lds128(wv, sb + OFF_WX + (a_g & 6) * 16); lds128(wv + 4, sb + OFF_WX + 16 + (a_g & 6) * 16);
    };
    auto hload = [&](uint32_t (&hf)[16], uint32_t nd) {
      const uint32_t hrow = sb + OFF_H + nd * 128 + (((nd & 7) << 4) ^ ((a_g >> 1) & 16));
#pragma unroll
      for (int j = 0; j < 4; j++) ldsm4(hf + 4 * j, hrow ^ (j << 5));
      return hrow;
    };
    auto bload = [&](uint32_t o) {
#pragma unroll
      for (int j = 0; j < 4; j++) ldsm4t(bp + 4 * j, (a_p ^ (j << 5)) + o);
    };
    { uint32_t wd[8]; const uint32_t a = sb + OFF_WD + (lane & 7) * 128 + ((((lane >> 3) ^ lane) & 7) << 4);
      ldsm4t(wd, a); ldsm4t(wd + 4, a ^ 64);
#pragma unroll
      for (int j = 0; j < 8; j++) { bp[2 * j] = wd[j]; bp[2 * j + 1] = pa[j]; } }
    own = lds16(a_g) * 0x10001u;
    wload();
    if (__shfl_sync(~0u, lds32(sb + OFF_MISC + 8), 0)) rem = 0;
    auto resolve = [&](auto NBK, uint32_t o) {
      constexpr int NB = decltype(NBK)::value;
      uint32_t id[NB], c0[NB], c1[NB]; const uint32_t a = base * 32 + o + lane * 4;
#pragma unroll
      for (int i = 0; i < NB; i++) { id[i] = lds32(sb + OFF_TS + a + i * 128); if (o + lane * 4 + i * 128 >= rem) id[i] = XPAD * 0x10001u; }
      uint32_t st = 0;
#pragma unroll
      for (int i = 0; i < NB; i++) { c0[i] = lds32(sb + OFF_XB + (id[i] & 0xFFFF)); c1[i] = lds32(sb + OFF_XB + (id[i] >> 16)); }
#pragma unroll
      for (int i = 0; i < NB; i++) st |= (c0[i] ^ tag) | (c1[i] ^ tag);
      for (int spin = 0; __any_sync(~0u, st >> 30); spin++) {
        st = 0; trap_if(spin > 2000000);
#pragma unroll
        for (int i = 0; i < NB; i++) {
          asm volatile("{.reg .pred p, q; setp.lt.u32 p, %4, %6; setp.lt.u32 q, %5, %6; @p ld.relaxed.gpu.global.u32 %0, [%2]; @q ld.relaxed.gpu.global.u32 %1, [%3];}"
            : "+r"(c0[i]), "+r"(c1[i]) : "l"((const char*)p.xb + cta * XPAD + (id[i] & 0xFFFF)), "l"((const char*)p.xb + cta * XPAD + (id[i] >> 16)), "r"(id[i] & 0xFFFF), "r"(id[i] >> 16), "n"(XPAD) : "memory");
          st |= (c0[i] ^ tag) | (c1[i] ^ tag); }
      }
#pragma unroll
      for (int i = 0; i < NB; i++) { const uint32_t j0 = (id[i] >> 8) & 255, j1 = id[i] >> 24;
        if (ABL & 2) { c0[i] &= 0xFFFF0FFFu; c1[i] &= 0xFFFF0FFFu; }
        asm volatile("{.reg .pred p, q, r; setp.lt.u32 p, %5, %9; setp.lt.u32 q, %6, %9; setp.lt.u32 r, %7, %8;\n"
          "@p st.shared.u32 [%0], %2; @q st.shared.u32 [%0+4], %3; @r st.shared.u32 [%1], %4;}"
          :: "r"(sb + OFF_TE + 2 * a + i * 256), "r"(sb + OFF_TS + a + i * 128), "r"(mad16(c0[i], 0x2000u, eb0 + ((ABL & 1) ? j0 & 7 : j0) * p.EPC * 32)), "r"(mad16(c1[i], 0x2000u, eb0 + ((ABL & 1) ? j1 & 7 : j1) * p.EPC * 32)),
             "r"(__byte_perm(c0[i], c1[i], 0x5410)), "r"(j0), "r"(j1), "r"(o + lane * 4 + i * 128), "r"(rem), "n"(G) : "memory"); }
    };
    bar_sync(2, 384);
    if (wid == 0) STAMP(27);
    mbar_wait(sb + BAR_HB);
    if (wid == 0) STAMP(22);
#pragma unroll 1
    for (uint32_t o = 0, go = 0; go < 32 * NST; o += 128 * RNB) {
      if (o < rem) { resolve(IC<RNB>(), o);
        asm volatile("{.reg .pred p; mbarrier.test_wait.parity.shared::cta.b64 p, [%1], 0; vote.sync.all.pred p, p, -1; selp.u32 %0, %2, 0, p;}" : "=r"(go) : "r"(sb + BAR_QP), "n"(32 * NEARLY) : "memory"); }
      else { bar_sync(8, 384); mbar_wait(sb + BAR_QP); go = 32 * NST; if (wid == 0) STAMP(24); }
      __syncwarp();
#pragma unroll 1
      while (to < go) { tl_(); issue(); if (to == 32) STAMP(13); }
    }
    bad = __shfl_sync(~0u, lds32(sb + OFF_MISC + 8), 0);
   if (!bad) {
#pragma unroll
    for (int j = 0; j < 4; j++) stsm4((p2 + fr) ^ (j << 5), pq[4 * j], pq[4 * j + 1], pq[4 * j + 2], pq[4 * j + 3]);
    auto body = [&](auto MODE) {
      constexpr int mode = decltype(MODE)::value;
      uint32_t T[16], ef[4], q0, q1, x0, x1, x2; float e0_, e1_, cs[4];
      auto mu = [&](int j) {
#pragma unroll
        for (int i = 2 * j; i < 2 * j + 2; i++) asm volatile("{.reg .b16 l, h; mov.b32 {l, h}, %2; tanh.approx.f16 %0, l; tanh.approx.f16 %1, h;}" : "=h"(tl[i]), "=h"(th[i]) : "r"(Y[i])); };
      auto fi = [&](int j) {
#pragma unroll
        for (int i = 2 * j; i < 2 * j + 2; i++) asm volatile("{.reg .b32 t; mov.b32 t, {%2, %3}; fma.rn.f16x2 %0, %1, t, %1;}" : "=r"(M[i]) : "r"(Y[i]), "h"(tl[i]), "h"(th[i])); };
      auto ad = [&](int j) { asm volatile("add.rn.f16x2 %0, %0, %1; add.rn.f16x2 %0, %0, %2;" : "+r"(sum[j]) : "r"(M[2 * j]), "r"(M[2 * j + 1])); };
      auto he = [&](int j) { asm volatile("mma.sync.aligned.m16n8k16.row.col.f16.f16.f16.f16 {%0,%1}, {%2,%3,%4,%5}, {%6,%7}, {%0,%1};" : "+r"(T[2 * j]), "+r"(T[2 * j + 1]) : "r"(ef[0]), "r"(ef[1]), "r"(ef[2]), "r"(ef[3]), "r"(w3[2 * j]), "r"(w3[2 * j + 1])); };
      auto hs = [&](int j) { asm volatile("mma.sync.aligned.m16n8k16.row.col.f16.f16.f16.f16 {%0,%1}, {%2,%3,%4,%5}, {%6,%7}, {%8,%9};" : "=r"(Y[2 * j]), "=r"(Y[2 * j + 1]) : "r"(q0), "r"(q1), "r"(oh0), "r"(oh1), "r"(bp[2 * j]), "r"(bp[2 * j + 1]), "r"(T[2 * j]), "r"(T[2 * j + 1])); };
      auto hc = [&](int j) {
        if (j) asm volatile("mma.sync.aligned.m16n8k16.row.col.f32.f16.f16.f32 {%0,%1,%2,%3}, {%4,%5,%6,%7}, {%8,%9}, {%0,%1,%2,%3};" : "+f"(cs[0]), "+f"(cs[1]), "+f"(cs[2]), "+f"(cs[3]) : "r"(M[4 * j]), "r"(M[4 * j + 1]), "r"(M[4 * j + 2]), "r"(M[4 * j + 3]), "r"(wv[2 * j]), "r"(wv[2 * j + 1]));
        else asm volatile("mma.sync.aligned.m16n8k16.row.col.f32.f16.f16.f32 {%0,%1,%2,%3}, {%4,%5,%6,%7}, {%8,%9}, {%10,%10,%10,%10};" : "=f"(cs[0]), "=f"(cs[1]), "=f"(cs[2]), "=f"(cs[3]) : "r"(M[0]), "r"(M[1]), "r"(M[2]), "r"(M[3]), "r"(wv[0]), "r"(wv[1]), "f"(0.f)); };
      auto cv = [&](int i) { asm volatile("{.reg .b32 a, b; shl.b32 a, %0, 16; and.b32 b, %0, 0xFFFF0000; cvt.rn.f16x2.f32 %0, b, a;}" : "+r"(ef[i])); };
      auto un = [&]() { asm volatile("shl.b32 %0, %2, 16; and.b32 %1, %2, 0xFFFF0000;" : "=&f"(e0_), "=&f"(e1_) : "r"(dpk)); };
      auto ex0 = [&]() { asm volatile("prmt.b32 %0, %3, %4, 0x6420; prmt.b32 %1, %5, %6, 0x6420; prmt.b32 %2, %7, %8, 0x6420;" : "=&r"(x0), "=&r"(x1), "=&r"(x2) : "r"(T[0]), "r"(T[1]), "r"(T[2]), "r"(T[3]), "r"(T[4]), "r"(T[5])); };
      auto ex1 = [&]() { asm volatile("{.reg .b32 a, b; shl.b32 a, %2, 3; shl.b32 b, %3, 6; lop3.b32 a, %1, a, 0x38383838, 0xD8; lop3.b32 a, a, b, 0xC0C0C0C0, 0xD8; sub.rn.bf16x2 %0, %4, a;}" : "=r"(dpk) : "r"(x0), "r"(x1), "r"(x2), "r"(own)); };
      auto ex2 = [&]() { asm volatile("{.reg .b32 a, b, d, u; .reg .b16 l, h; shl.b32 a, %2, 16; and.b32 b, %2, 0xFFFF0000; cvt.rn.f16x2.f32 d, b, a; mul.rn.f16x2 %0, d, d; mov.b32 {l, h}, d; mov.b32 u, {h, h}; mul.rn.f16x2 %1, u, u;}" : "=&r"(q0), "=&r"(q1) : "r"(dpk)); };
      auto pf = [&]() { asm volatile("fma.rn.f32 %0, %1, %2, %0; fma.rn.f32 %0, %3, %4, %0;" : "+f"(pacc) : "f"(cs[0]), "f"(e0_), "f"(cs[2]), "f"(e1_)); };
#define FX(k) if (FM >> k & 1) asm volatile("pmevent 1;" ::: "memory")
      if (mode == 2) {
        hc(0); mu(3); fi(2); un(); ad(0); ad(1); mu(4); fi(3); hc(1); mu(5); fi(4); ad(2); mu(6); fi(5); ad(3); hc(2); mu(7); fi(6); fi(7); ad(4); ad(5); hc(3); ad(6); ad(7); pf();
        return;
      }
      asm volatile("cp.async.wait_group %0;" :: "n"(NST - 1) : "memory");
      __syncwarp();
      if (mode == 1) STAMP(8);
      ldsm4(ef, eadr + so); ldsm4(T, qa0 + so); ldsm4(T + 4, qa1 + so); ldsm4(T + 8, qa2 + so); ldsm4(T + 12, qa3 + so);
      tl_();
      if (mode == 1) {
        issue();
        cv(0); cv(1); cv(2); cv(3); ex0(); ex1(); ex2();
#pragma unroll
        for (int j = 0; j < 8; j++) { he(j); hs(j); }
        mu(0); mu(1); fi(0); mu(2); fi(1);
        return;
      }
      hc(0); mu(3); fi(2); un(); ad(0); ad(1);
      FX(0);
      mu(4); fi(3); cv(0); cv(1); cv(2); cv(3); ex0(); ex1();
      FX(1);
      he(0); he(1); hc(1); mu(5); fi(4); ex2(); ad(2);
      FX(2);
      hs(0); he(2); mu(6); fi(5); issue(); ad(3);
      FX(3);
      hs(1); he(3); hc(2); mu(7); fi(6);
      FX(4);
      hs(2); hs(3); he(4); he(5); mu(0); fi(7); ad(4); ad(5);
      FX(5);
      hc(3); hs(4); he(6); he(7); mu(1); fi(0); ad(6);
      FX(6);
      hs(5); hs(6); hs(7); mu(2); fi(1); ad(7); pf();
      FX(7);
    };
#pragma unroll
    for (int j = 0; j < 8; j++) sum[j] = 0;
    body(IC<1>());
    int cnt = (lens & 255) - 1;
    auto flush = [&]() {
      asm volatile("{.reg .pred p; setp.ne.u32 p, %2, 6; @p st.shared.u16 [%0+-64], %1;}" :: "r"(a_g), "h"((uint16_t)pack_bf16(bf_hi(ownp) + pacc, 0.f)), "r"(a_g & 6) : "memory");
      chk = fmaf(pacc, 0.f, chk); pacc = 0.f; };
    constexpr uint64_t b1 = DHI | ((sb + OFF_W) >> 4), b2_ = b1 + 512;
    auto mma_h = [&](float (&acc)[32], uint32_t (&hf)[16]) {
      rs64b<0>(acc, hf[0], hf[1], hf[2], hf[3], b1); rs64b<1>(acc, hf[4], hf[5], hf[6], hf[7], b1 + 128); rs64b<1>(acc, hf[8], hf[9], hf[10], hf[11], b1 + 256); rs64b<1>(acc, hf[12], hf[13], hf[14], hf[15], b1 + 384); };
    auto mma_m = [&](float (&acc)[32]) {
      rs64h<1>(acc, sp[0], sum[0], sp[1], sum[1], b2_); rs64h<1>(acc, sp[2], sum[2], sp[3], sum[3], b2_ + 128); rs64h<1>(acc, sp[4], sum[4], sp[5], sum[5], b2_ + 256); rs64h<1>(acc, sp[6], sum[6], sp[7], sum[7], b2_ + 384);
      wg_commit(); wg_wait0(); fence_regs(acc);
      STAMP(10);
      chk = fmaf(acc[0], 0.f, fmaf(acc[2], 0.f, chk)); };
    auto roff = [&](uint32_t nd, int r) { return __shfl_sync(~0u, nd, ((a_g >> 3) & 7) + 8 * r) * 128 + (a_g & 6) * 8; };
    auto radr = [&](uint32_t o, int k) { return sb + OFF_H + (o ^ ((o >> 3) & 0x70) ^ ((k >> 1) << 6)); };
    auto fin = [&](float (&acc)[32], uint32_t* x, int k) {
#pragma unroll
      for (int i = 0; i < 4; i++) { const int c = 16 * (k >> 1) + 4 * i + 2 * (k & 1); x[i] = u2(__hadd2(b2(x[i]), b2(pack_bf16(silu_h(acc[c]), silu_h(acc[c + 1]))))); } };
#pragma unroll 1
    for (int t = 0;; t++) {
#pragma unroll 1
      for (; cnt > 0; cnt--) { body(IC<0>());
      }
      if (!(t & 1)) {
        ownp = own; a_g += 64;
        if (t == 6) break;
        own = lds16(a_g) * 0x10001u;
        if (t == 0) {
#pragma unroll
          for (int j = 0; j < 8; j++) bp[2 * j + 1] = sp[j];
        } else bload((a_g & 16) ? (t & 4) * 256 : 0);
        lens >>= 8; cnt = 1;
        continue;
      }
      cnt = (lens & 255) - 1;
      flush();
      if (t == 3) {
        uint32_t hf[16]; float acc[32];
        const uint32_t nd = lds16(a_n), o[2] = {roff(nd, 0), roff(nd, 1)};
        hload(hf, nd);
        mbar_wait(sb + BAR_WH);
        wg_fence();
        mma_h(acc, hf); mma_m(acc);
#pragma unroll
        for (int k = 0; k < 4; k++) lds128(hf + 4 * k, radr(o[k & 1], k));
#pragma unroll
        for (int k = 0; k < 4; k++) { fin(acc, hf + 4 * k, k); sts128(radr(o[k & 1], k), hf[4 * k], hf[4 * k + 1], hf[4 * k + 2], hf[4 * k + 3]); }
        __syncwarp();
        mbar_arrive(sb + BAR_M, (a_g & 62) == 0);
        wload();
      }
#pragma unroll
      for (int j = 0; j < 8; j++) { sp[j] = sum[j]; asm volatile("mov.b32 %0, 0;" : "=r"(sum[j])); }
    }
    {
      uint32_t hf[16], v[16]; float acc[32];
      const uint32_t nd = lds16(a_n + 128), o[2] = {roff(nd, 0), roff(nd, 1)};
      hload(hf, nd);
#pragma unroll
      for (int k = 0; k < 4; k++) lds128(v + 4 * k, radr(o[k & 1], k));
      wg_fence(); mma_h(acc, hf); wg_commit();
      body(IC<2>());
      STAMP(9);
      flush();
      __syncwarp();
      mbar_arrive(sb + BAR_X, lane == 0);
      wg_fence();
      mma_m(acc);
#pragma unroll
      for (int k = 0; k < 4; k++) { fin(acc, v + 4 * k, k);
        asm volatile("{.reg .pred p; setp.lt.u32 p, %5, %6; @p st.global" OCS ".v4.b32 [%0], {%1,%2,%3,%4};}" :: "l"((const char*)p.out + (size_t)node0 * 128 + o[k & 1] + (k >> 1) * 64), "r"(v[4 * k]), "r"(v[4 * k + 1]), "r"(v[4 * k + 2]), "r"(v[4 * k + 3]), "r"(o[k & 1]), "r"(nloc * 128) : "memory"); }
    }
    asm volatile("{.reg .pred p, q; setp.neu.f32 p, %1, 0f00000000; setp.ne.or.u32 p, %2, 0, p; bar.red.or.pred q, 5, %3, p; selp.u32 %0, 1, 0, q;}" : "=r"(bad) : "f"(chk), "r"(lds32(sb + OFF_MISC + 12)), "n"(DEFO ? 512 : 384) : "memory");
    STAMP(11);
   } else { asm volatile("cp.async.wait_all;" ::: "memory"); bar_sync(5, 384); }
  }
  if (bad) slow_path(p, wid, lane, node0, nloc);
}

}

typedef CUresult (*EncodeFn)(CUtensorMap*, CUtensorMapDataType, cuuint32_t, void*, const cuuint64_t*, const cuuint64_t*, const cuuint32_t*, const cuuint32_t*,
                             CUtensorMapInterleave, CUtensorMapSwizzle, CUtensorMapL2promotion, CUtensorMapFloatOOBfill);

extern "C" void kernel_launch(void* const* d_in, const int* in_sizes, int n_in, void* d_out, int out_size) {
  Params p; Maps maps;
  p.h = (const uint4*)d_in[0]; p.pos = (const uint16_t*)d_in[1]; p.ea = (const uint4*)d_in[2];
  p.src = (const int*)d_in[3]; p.dst = (const int*)d_in[4];
  p.we = (const uint16_t*)d_in[5]; p.wx = (const uint16_t*)d_in[6]; p.wh = (const uint16_t*)d_in[7];
  p.out = (uint16_t*)d_out;
  p.N = in_sizes[0] / 64; p.E = in_sizes[3];
  p.EPC = ((p.E + G * 4 - 1) / (G * 4)) * 4;
  p.magic = (uint32_t)(((uint64_t)G << 24) / (uint64_t)p.N);
  p.inv = (1ull << 56) / p.magic;
  const uint64_t ea0 = (uint64_t)d_in[2], ea1 = ea0 + (uint64_t)p.E * 32 - 1;
  p.force_slow = ((ea0 >> 32) != (ea1 >> 32)) || (ea0 & 31) || (p.E & 3);
  void* qp = nullptr;
  cudaGetSymbolAddress(&qp, g_q);
  p.q = (char*)qp;
  if (((uint64_t)p.q >> 32) != (((uint64_t)p.q + QBYTES) >> 32)) p.q += QBYTES;
  cudaGetSymbolAddress((void**)&p.sync, g_sync); cudaGetSymbolAddress((void**)&p.xe, g_xe);
  cudaGetSymbolAddress((void**)&p.xa, g_xa); cudaGetSymbolAddress((void**)&p.xb, g_xb);
  void* fn = nullptr; cudaDriverEntryPointQueryResult qr;
  cudaGetDriverEntryPoint("cuTensorMapEncodeTiled", &fn, cudaEnableDefault, &qr);
  auto mk = [&](CUtensorMap* tm, void* base, int rows, int box = 64) {
    const cuuint64_t dim[2] = {64, (cuuint64_t)rows}, str[1] = {128}; const cuuint32_t bx[2] = {64, (cuuint32_t)box}, es[2] = {1, 1};
    ((EncodeFn)fn)(tm, CU_TENSOR_MAP_DATA_TYPE_BFLOAT16, 2, base, dim, str, bx, es, CU_TENSOR_MAP_INTERLEAVE_NONE, CU_TENSOR_MAP_SWIZZLE_128B,
                   CU_TENSOR_MAP_L2_PROMOTION_NONE, CU_TENSOR_MAP_FLOAT_OOB_FILL_NONE);
  };
  mk(&maps.m[TM_H / 128], d_in[0], p.N); mk(&maps.m[TM_WE / 128], d_in[5], 145); mk(&maps.m[TM_WH / 128], d_in[7], 128); mk(&maps.m[TM_Q / 128], p.q, p.N, 16);
  for (int k = 0; k < 2; k++) {
    void* xp = (void*)(k ? p.xb : p.xa);
    const cuuint64_t dim[2] = {(cuuint64_t)G * 64, (cuuint64_t)G}, str[1] = {(cuuint64_t)G * (128 << k)}; const cuuint32_t bx[2] = {64, (cuuint32_t)(k ? BROWS : G)}, es[2] = {1, 1};
    ((EncodeFn)fn)(&maps.m[TM_XA / 128 + k], k ? CU_TENSOR_MAP_DATA_TYPE_UINT32 : CU_TENSOR_MAP_DATA_TYPE_UINT16, 2, xp, dim, str, bx, es, CU_TENSOR_MAP_INTERLEAVE_NONE,
                   CU_TENSOR_MAP_SWIZZLE_NONE, CU_TENSOR_MAP_L2_PROMOTION_NONE, CU_TENSOR_MAP_FLOAT_OOB_FILL_NONE);
  }
  cudaFuncSetAttribute(egnn_kernel, cudaFuncAttributeMaxDynamicSharedMemorySize, SMEM);
  egnn_kernel<<<G, NTHR, SMEM>>>(p, maps);
}
```

```cpp
#include <cuda_runtime.h>
#include <cuda_bf16.h>
#include <cuda_fp16.h>
#include <cuda.h>
#include <stdint.h>
#pragma nv_diag_suppress 549

#define DEF0 1000
#define PFN 18
#define PFNS 250
#define FM 0
#define OPQ 0
#define H0 0
#define HALL 0
#define PF0NS 0
#define PFW 0
#define QCODE 0x254a109b7863ull
#define QREV 0x605
#define PFS 1
#define ESZ ""
#define XEF 0
#define OCS ""
#define RNB 2
#define NEARLY 2
#define PFE 0
#define DEFO 1
#define DEFNS 250
#define ABL 0
#define IDL 1
#define BDEL 900
#define CTAMAP (blockIdx.x * 59 % G)
#define PADM 33
#define NPAD 1
#define PADS 1
#define NPE 1
#define HW 3
#define BROWS 44
#define B_HOLD 1
#define LSEQ 0x231200ull
#define HE 0
namespace {

constexpr int G = 132;
constexpr int NTHR = 512, NWK = 352, NCH = 5;
constexpr int NST = 3, STG = 2560;
constexpr int SCAP = 448;

constexpr int OFF_H = 0;
constexpr int OFF_W = 49152;
constexpr int OFF_WD = OFF_W + 16384;
constexpr int OFF_W3 = OFF_WD + 1024;
constexpr int OFF_P2 = OFF_W3 + 2048;
constexpr int OFF_RING = OFF_P2 + 24576;
constexpr int OFF_TE = OFF_RING + 12 * NST * STG;
constexpr int OFF_TS = OFF_TE + SCAP * 64;
constexpr int OFF_INV = OFF_TS - 768;
constexpr int OFF_GP = OFF_TS + SCAP * 32;
constexpr int OFF_WX = OFF_GP + 3072;
constexpr int OFF_LEN = OFF_WX + 128;
constexpr int OFF_MISC = OFF_LEN + 128;
constexpr int OFF_BAR = OFF_MISC + 48;
constexpr int SMEM = OFF_BAR + 256;
static_assert(SMEM <= 232448, "smem");
constexpr uint32_t sb = 1024;
constexpr int OFF_SRCI = OFF_TE;
constexpr int OFF_SB = OFF_RING, OFF_SA = OFF_SB + 34816, OFF_AX = OFF_SA + 32768, OFF_DST = OFF_H + 24576;
constexpr int OFF_WS = OFF_AX + 17408;
constexpr int OFF_BC = OFF_WS + 2304;
constexpr int OFF_CNT = OFF_P2;
constexpr int OFF_DH = OFF_CNT + 2176;
constexpr int OFF_POS = OFF_DH + 128;
constexpr int OFF_EXT = OFF_POS + 3072;
constexpr int OFF_XB = OFF_EXT + 1024, XPAD = G * 256;
static_assert(OFF_XB + XPAD + 1088 <= OFF_RING + 12 * STG && OFF_XB % 128 == 0 && OFF_BC + 544 <= OFF_TE && OFF_P2 % 1024 == 0 && OFF_SA % 1024 == 0 && SCAP * 64 >= 24576, "staging");
constexpr int BAR_DST = OFF_BAR, BAR_SRC = BAR_DST + 40, BAR_T = BAR_SRC + 24, BAR_W = BAR_T + 48, BAR_XA = BAR_W + 8, BAR_PS = BAR_XA + 8, BAR_AW = BAR_PS + 8,
              BAR_QP = BAR_AW + 8, BAR_QR = BAR_QP + 8, BAR_HA = BAR_QR + 8, BAR_EP = BAR_HA + 8, BAR_AX = BAR_EP + 8, BAR_AI = BAR_AX + 8, BAR_HB = BAR_AI + 8, BAR_U = BAR_HB + 8, BAR_WH = BAR_U + 8, BAR_M = BAR_WH + 8, BAR_X = BAR_M + 8, BAR_END = BAR_X + 8;
static_assert(BAR_END <= OFF_BAR + 256, "barriers");
constexpr uint32_t QBYTES = 8u << 20;

__device__ __align__(256) uint4 g_xa[G * G * 8];
__device__ __align__(256) uint4 g_xb[G * G * 16];
__device__ __align__(256) uint2 g_xe[G * G * 32];
__device__ __align__(256) uint4 g_q[2 * QBYTES / 16];
__device__ __align__(256) uint32_t g_sync[8];
#define STAMP(k)

struct Maps { CUtensorMap m[6]; };
constexpr int TM_H = 0, TM_WE = 128, TM_WH = 256, TM_Q = 384, TM_XA = 512, TM_XB = 640;
struct Params {
  const int* dst; uint32_t* sync; int E, EPC, N; uint32_t magic; unsigned long long inv;
  const int* src; const uint16_t* pos; const uint4* ea; const uint16_t* we; const uint16_t* wx; char* q; int force_slow;
  const uint4* xa; const uint4* xb; uint2* xe; uint16_t* out; const uint4* h; const uint16_t* wh;
};
template<int V> struct IC { static constexpr int value = V; };

#define R32(d) "+f"(d[0]),"+f"(d[1]),"+f"(d[2]),"+f"(d[3]),"+f"(d[4]),"+f"(d[5]),"+f"(d[6]),"+f"(d[7]),"+f"(d[8]),"+f"(d[9]),"+f"(d[10]),"+f"(d[11]),"+f"(d[12]),"+f"(d[13]),"+f"(d[14]),"+f"(d[15]),"+f"(d[16]),"+f"(d[17]),"+f"(d[18]),"+f"(d[19]),"+f"(d[20]),"+f"(d[21]),"+f"(d[22]),"+f"(d[23]),"+f"(d[24]),"+f"(d[25]),"+f"(d[26]),"+f"(d[27]),"+f"(d[28]),"+f"(d[29]),"+f"(d[30]),"+f"(d[31])
#define S32 "{%0,%1,%2,%3,%4,%5,%6,%7,%8,%9,%10,%11,%12,%13,%14,%15,%16,%17,%18,%19,%20,%21,%22,%23,%24,%25,%26,%27,%28,%29,%30,%31}"
#define DI __device__ __forceinline__

constexpr uint64_t DHI = ((uint64_t)(1024 >> 4) << 32) | (1ull << 62);
template<int SD> DI void rs64b(float (&d)[32], uint32_t a0, uint32_t a1, uint32_t a2, uint32_t a3, uint64_t db) {
  asm volatile("wgmma.mma_async.sync.aligned.m64n64k16.f32.bf16.bf16 " S32 ", {%32,%33,%34,%35}, %36, %37, 1, 1, 1;" : R32(d) : "r"(a0), "r"(a1), "r"(a2), "r"(a3), "l"(db), "n"(SD)); }
template<int SD> DI void rs64h(float (&d)[32], uint32_t a0, uint32_t a1, uint32_t a2, uint32_t a3, uint64_t db) {
  asm volatile("wgmma.mma_async.sync.aligned.m64n64k16.f32.f16.f16 " S32 ", {%32,%33,%34,%35}, %36, %37, 1, 1, 1;" : R32(d) : "r"(a0), "r"(a1), "r"(a2), "r"(a3), "l"(db), "n"(SD)); }
template<int SD> DI void ss64(float (&d)[32], uint64_t da, uint64_t db) {
  asm volatile("wgmma.mma_async.sync.aligned.m64n64k16.f32.bf16.bf16 " S32 ", %32, %33, %34, 1, 1, 0, 1;" : R32(d) : "l"(da), "l"(db), "n"(SD)); }
DI void trap_if(bool c) { asm volatile("{.reg .pred p; setp.eq.u32 p, %0, 0; @p bra.uni LT_%=; trap; LT_%=:}" :: "r"((uint32_t)c)); }
DI void wg_fence() { asm volatile("wgmma.fence.sync.aligned;" ::: "memory"); }
DI void wg_commit() { asm volatile("wgmma.commit_group.sync.aligned;" ::: "memory"); }
DI void wg_wait0() { asm volatile("wgmma.wait_group.sync.aligned 0;" ::: "memory"); }
DI void fence_regs(float (&d)[32]) { asm volatile("" : R32(d) :: "memory"); }
DI void proxy_fence() { asm volatile("fence.proxy.async.shared::cta;" ::: "memory"); }
DI uint64_t pol_first() { uint64_t r; asm("createpolicy.fractional.L2::evict_first.b64 %0, 1.0;" : "=l"(r)); return r; }
DI float tanh_ap(float x) { float y; asm("tanh.approx.f32 %0, %1;" : "=f"(y) : "f"(x)); return y; }
DI float silu_h(float y) { return fmaf(y, tanh_ap(y), y); }
DI uint32_t pack_bf16(float lo, float hi) { uint32_t r; asm("cvt.rn.bf16x2.f32 %0, %1, %2;" : "=r"(r) : "f"(hi), "f"(lo)); return r; }
DI uint32_t pack_f16(float lo, float hi) { uint32_t r; asm("cvt.rn.f16x2.f32 %0, %1, %2;" : "=r"(r) : "f"(hi), "f"(lo)); return r; }
DI float bf_lo(uint32_t v) { return __uint_as_float(v << 16); }
DI float bf_hi(uint32_t v) { return __uint_as_float(v & 0xFFFF0000u); }
DI uint32_t b2h(uint32_t v, float s) { return pack_f16(s * bf_lo(v), s * bf_hi(v)); }
DI void mbar_wait(uint32_t bar, uint32_t parity = 0) {
  asm volatile("{.reg .pred p, q; .reg .u32 c; mov.u32 c, 0;\n"
    "LW_%=: mbarrier.try_wait.parity.shared::cta.b64 p, [%0], %1;\n add.u32 c, c, 1; setp.lt.and.u32 q, c, 0x200000, !p;\n @q bra.uni LW_%=;}" :: "r"(bar), "r"(parity) : "memory");
}
DI void mbar_arrive(uint32_t bar, int p = 1) { asm volatile("{.reg .pred p; setp.ne.b32 p, %1, 0; @p mbarrier.arrive.shared::cta.b64 _, [%0];}" :: "r"(bar), "r"(p) : "memory"); }
DI void bar_sync(int id, int n) { asm volatile("bar.sync %0, %1;" :: "r"(id), "r"(n) : "memory"); }
DI void bar_arrive(int id, int n) { asm volatile("bar.arrive %0, %1;" :: "r"(id), "r"(n) : "memory"); }
DI __nv_bfloat162 b2(uint32_t v) { return *(__nv_bfloat162*)&v; }
DI uint32_t u2(__nv_bfloat162 v) { return *(uint32_t*)&v; }
DI uint32_t hsq(uint32_t v) { return u2(__hmul2(b2(v), b2(v))); }
DI uint32_t hsub(uint32_t a, uint32_t b) { return u2(__hsub2(b2(a), b2(b))); }
DI uint32_t hhalf(uint32_t v) { return u2(__hmul2(b2(v), __floats2bfloat162_rn(0.5f, 0.5f))); }
DI uint32_t mag2(uint32_t m, uint32_t v) { return __vmaxu2(m, v & 0x7FFF7FFFu); }
DI uint32_t hmag(uint32_t m, uint32_t v) { const __half2 r = __hmax2(*(const __half2*)&m, __habs2(*(const __half2*)&v)); return *(const uint32_t*)&r; }
DI uint32_t magr(uint32_t m) { return max(m & 0xFFFF, m >> 16); }
DI void sts128(uint32_t a, uint32_t x, uint32_t y, uint32_t z, uint32_t w) { asm volatile("st.shared.v4.u32 [%0], {%1,%2,%3,%4};" :: "r"(a), "r"(x), "r"(y), "r"(z), "r"(w) : "memory"); }
DI void sts64(uint32_t a, uint32_t x, uint32_t y) { asm volatile("st.shared.v2.u32 [%0], {%1,%2};" :: "r"(a), "r"(x), "r"(y) : "memory"); }
DI void sts32(uint32_t a, uint32_t x) { asm volatile("st.shared.u32 [%0], %1;" :: "r"(a), "r"(x) : "memory"); }
DI void sts16(uint32_t a, uint32_t x) { asm volatile("st.shared.u16 [%0], %1;" :: "r"(a), "h"((uint16_t)x) : "memory"); }
DI void lds128(uint32_t* v, uint32_t a) { asm volatile("ld.shared.v4.u32 {%0, %1, %2, %3}, [%4];" : "=r"(v[0]), "=r"(v[1]), "=r"(v[2]), "=r"(v[3]) : "r"(a) : "memory"); }
DI void lds64(uint32_t& x, uint32_t& y, uint32_t a) { asm volatile("ld.shared.v2.u32 {%0, %1}, [%2];" : "=r"(x), "=r"(y) : "r"(a) : "memory"); }
DI uint32_t lds32(uint32_t a) { uint32_t x; asm volatile("ld.shared.u32 %0, [%1];" : "=r"(x) : "r"(a) : "memory"); return x; }
DI uint32_t lds16(uint32_t a) { uint32_t x; asm volatile("ld.shared.u16 %0, [%1];" : "=r"(x) : "r"(a) : "memory"); return x; }
DI uint32_t atoms_add(uint32_t a, uint32_t v) { uint32_t r; asm volatile("atom.shared.add.u32 %0, [%1], %2;" : "=r"(r) : "r"(a), "r"(v) : "memory"); return r; }
DI void bulk_load(uint32_t dst, const void* src, uint32_t bytes, uint32_t bar) {
  asm volatile("cp.async.bulk.shared::cluster.global.mbarrier::complete_tx::bytes.L2::cache_hint [%0], [%1], %2, [%3], %4;" :: "r"(dst), "l"(src), "r"(bytes), "r"(bar), "l"(pol_first()) : "memory"); }
DI void bulk_store(void* dst, uint32_t src, uint32_t bytes) { asm volatile("cp.async.bulk.global.shared::cta.bulk_group [%0], [%1], %2;" :: "l"(dst), "r"(src), "r"(bytes) : "memory"); }
DI void mbar_expect(uint32_t bar, uint32_t bytes) { asm volatile("mbarrier.arrive.expect_tx.shared::cta.b64 _, [%0], %1;" :: "r"(bar), "r"(bytes) : "memory"); }
DI void mbar_init(uint32_t bar, int n) { asm volatile("mbarrier.init.shared::cta.b64 [%0], %1;" :: "r"(bar), "r"(n) : "memory"); }
DI void tma_load(uint32_t dst, uint64_t tm, int row, uint32_t bar) {
  asm volatile("cp.async.bulk.tensor.2d.shared::cluster.global.mbarrier::complete_tx::bytes.L2::cache_hint [%0], [%1, {%3, %4}], [%2], %5;" :: "r"(dst), "l"(tm), "r"(bar), "r"(0), "r"(row), "l"(pol_first()) : "memory"); }
DI void tma_store(uint64_t tm, int col, int row, uint32_t src) {
  asm volatile("cp.async.bulk.tensor.2d.global.shared::cta.bulk_group [%0, {%2, %3}], [%1];" :: "l"(tm), "r"(src), "r"(col), "r"(row) : "memory"); }
DI void tma_store_ef(uint64_t tm, int col, int row, uint32_t src) {
  if (XEF) asm volatile("cp.async.bulk.tensor.2d.global.shared::cta.bulk_group.L2::cache_hint [%0, {%2, %3}], [%1], %4;" :: "l"(tm), "r"(src), "r"(col), "r"(row), "l"(pol_first()) : "memory");
  else tma_store(tm, col, row, src); }
DI void bulk_commit() { asm volatile("cp.async.bulk.commit_group;" ::: "memory"); }
DI void bulk_wait_read() { asm volatile("cp.async.bulk.wait_group.read 0;" ::: "memory"); }
DI uint2 ld_poll2(const void* a) { uint2 v; asm volatile("ld.relaxed.gpu.global.v2.u32 {%0, %1}, [%2];" : "=r"(v.x), "=r"(v.y) : "l"(a) : "memory"); return v; }
DI void st_ext(uint2* a, uint32_t v, uint32_t ep) { asm volatile("st.relaxed.gpu.global.v2.u32 [%0], {%1, %2};" :: "l"(a), "r"(v), "r"(ep) : "memory"); }
DI uint32_t ext_get(const uint2* a, uint32_t ep) { uint2 v; int spin = 0; do { v = ld_poll2(a); trap_if(++spin > 4000000); } while (__any_sync(~0u, v.y != ep)); return v.x; }
DI void bulk_wait() { asm volatile("cp.async.bulk.wait_group 0;" ::: "memory"); }
DI void hint_signal(uint32_t* c) { asm volatile("red.relaxed.gpu.global.add.u32 [%0], 1;" :: "l"(c) : "memory"); }
DI void hint_wait(const uint32_t* c, uint32_t target) { uint32_t v; int spin = 0;
  do { asm volatile("ld.relaxed.gpu.global.u32 %0, [%1];" : "=r"(v) : "l"(c) : "memory"); trap_if(++spin > 4000000); } while (__any_sync(~0u, (int)(v - target) < 0)); }
DI void stsm4(uint32_t a, uint32_t x, uint32_t y, uint32_t z, uint32_t w) { asm volatile("stmatrix.sync.aligned.m8n8.x4.shared.b16 [%0], {%1,%2,%3,%4};" :: "r"(a), "r"(x), "r"(y), "r"(z), "r"(w) : "memory"); }
DI void ldsm4(uint32_t* v, uint32_t a) { asm volatile("ldmatrix.sync.aligned.m8n8.x4.shared.b16 {%0,%1,%2,%3}, [%4];" : "=r"(v[0]), "=r"(v[1]), "=r"(v[2]), "=r"(v[3]) : "r"(a) : "memory"); }
DI void ldsm4t(uint32_t* v, uint32_t a) { asm volatile("ldmatrix.sync.aligned.m8n8.x4.trans.shared.b16 {%0,%1,%2,%3}, [%4];" : "=r"(v[0]), "=r"(v[1]), "=r"(v[2]), "=r"(v[3]) : "r"(a) : "memory"); }
DI uint32_t mad16(uint32_t x, uint32_t m, uint32_t c) { uint32_t r; asm("dp2a.lo.u32.u32 %0, %1, %2, %3;" : "=r"(r) : "r"(x), "r"(m), "r"(c)); return r; }
DI bool wbad(uint32_t m, uint32_t hi) { return m > hi || (m && m < 0x3980); }

__device__ __noinline__ void slow_path(const Params& p, int wid, int lane, int node0, int nloc) {
  const uint32_t ab = sb + OFF_P2 + wid * 8704;
  for (int i = lane; i < 32 * 68; i += 32) sts32(ab + i * 4, 0);
  __syncwarp();
  const uint32_t wdv = __ldg((const uint32_t*)(p.we + 128 * 64) + lane), wxv = __ldg((const uint32_t*)p.wx + lane);
  const int nb0 = node0 + wid * 32, cntn = max(0, min(32, nloc - wid * 32));
  auto dot = [&](uint32_t hv, const uint16_t* w, int K2, float& y0, float& y1) {
#pragma unroll 4
    for (int k = 0; k < K2; k++) {
      const uint32_t hk = __shfl_sync(~0u, hv, k), wa = __ldg((const uint32_t*)(w + 2 * k * 64) + lane), wb = __ldg((const uint32_t*)(w + (2 * k + 1) * 64) + lane);
      y0 = fmaf(bf_lo(hk), bf_lo(wa), fmaf(bf_hi(hk), bf_lo(wb), y0)); y1 = fmaf(bf_lo(hk), bf_hi(wa), fmaf(bf_hi(hk), bf_hi(wb), y1));
    }
  };
  auto silu = [](float x) { return x / (1.f + __expf(-x)); };
#pragma unroll 1
  for (int base = 0; base < p.E; base += 32) {
    const int e = base + lane;
    const uint32_t dl = e < p.E ? (uint32_t)(__ldg(p.dst + e) - nb0) : 0xFFFFFFFFu;
    uint32_t mk = __ballot_sync(~0u, dl < (uint32_t)cntn);
    while (mk) {
      const int l = __ffs(mk) - 1; mk &= mk - 1;
      const int ee = base + l, n = __shfl_sync(~0u, dl, l), s = __ldg(p.src + ee);
      const uint16_t *po = p.pos + (size_t)(nb0 + n) * 3, *pp = p.pos + (size_t)s * 3;
      const uint32_t dxy = hsub(__ldg(po) | (__ldg(po + 1) << 16), __ldg(pp) | (__ldg(pp + 1) << 16)), dz = hsub(__ldg(po + 2), __ldg(pp + 2));
      const uint32_t sq = hsq(dxy); const float d2 = bf_lo(sq) + bf_hi(sq) + bf_lo(hsq(dz));
      float y0 = d2 * bf_lo(wdv), y1 = d2 * bf_hi(wdv);
      dot(__ldg((const uint32_t*)(p.h + (size_t)(nb0 + n) * 8) + lane), p.we, 32, y0, y1);
      dot(__ldg((const uint32_t*)(p.h + (size_t)s * 8) + lane), p.we + 64 * 64, 32, y0, y1);
      dot(__ldg((const uint32_t*)(p.ea + (size_t)ee * 2) + (lane & 7)), p.we + 129 * 64, 8, y0, y1);
      const uint32_t mm = pack_bf16(silu(y0), silu(y1));
      float c = bf_lo(mm) * bf_lo(wxv) + bf_hi(mm) * bf_hi(wxv);
#pragma unroll
      for (int o = 16; o; o >>= 1) c += __shfl_xor_sync(~0u, c, o);
      const uint32_t a = ab + n * 272;
      uint32_t x0, x1; lds64(x0, x1, a + lane * 8);
      sts64(a + lane * 8, __float_as_uint(__uint_as_float(x0) + bf_lo(mm)), __float_as_uint(__uint_as_float(x1) + bf_hi(mm)));
      if (lane < 3) { const float df = lane == 0 ? bf_lo(dxy) : lane == 1 ? bf_hi(dxy) : bf_lo(dz); sts32(a + 256 + lane * 4, __float_as_uint(fmaf(c, df, __uint_as_float(lds32(a + 256 + lane * 4))))); }
    }
  }
  __syncwarp();
#pragma unroll 1
  for (int n = 0; n < cntn; n++) {
    uint32_t x0, x1; lds64(x0, x1, ab + n * 272 + lane * 8);
    const uint32_t hv = __ldg((const uint32_t*)(p.h + (size_t)(nb0 + n) * 8) + lane);
    float y0 = 0.f, y1 = 0.f;
    dot(hv, p.wh, 32, y0, y1); dot(pack_bf16(__uint_as_float(x0), __uint_as_float(x1)), p.wh + 64 * 64, 32, y0, y1);
    ((uint32_t*)p.out)[(size_t)(nb0 + n) * 32 + lane] = u2(__hadd2(b2(hv), b2(pack_bf16(silu(y0), silu(y1)))));
    if (lane < 3) p.out[(size_t)p.N * 64 + (size_t)(nb0 + n) * 3 + lane] = (uint16_t)pack_bf16(bf_lo(__ldg(p.pos + (size_t)(nb0 + n) * 3 + lane)) + __uint_as_float(lds32(ab + n * 272 + 256 + lane * 4)), 0.f);
  }
}

__global__ void __launch_bounds__(NTHR, 1) egnn_kernel(const __grid_constant__ Params p, const __grid_constant__ Maps maps) {
  const uint64_t tmb = (uint64_t)&maps;
  extern __shared__ __align__(1024) unsigned char smraw[];
  const int tid = threadIdx.x, cta = CTAMAP;
  const int e0 = cta * p.EPC, n4 = max(0, min(p.EPC, p.E - e0)) >> 2;
  STAMP(0);
  if (tid == NWK) {
#pragma unroll 1
    for (int k = 0; k < NCH; k++) { const int nb = max(0, min(NWK, n4 - k * NWK)) * 16;
      mbar_init(sb + BAR_DST + k * 8, 1);
      asm volatile("fence.mbarrier_init.release.cluster;" ::: "memory");
      mbar_expect(sb + BAR_DST + k * 8, nb);
      if (nb) bulk_load(sb + OFF_DST + k * NWK * 16, (const char*)(p.dst + e0) + k * NWK * 16, nb, sb + BAR_DST + k * 8); }
  }
  const int lane = tid & 31, wid = __shfl_sync(~0u, tid >> 5, 0), w = wid & 3;
  asm volatile("{.reg .pred p; setp.eq.u32 p, %2, 384; @p cp.async.cg.shared.global [%0], [%1], 16;}" :: "r"(sb + OFF_LEN - 192 + (tid >> 1)), "l"(p.sync), "r"(tid & 415) : "memory");

  auto first_node = [&](int c) { return (int)((c * p.inv + 0xFFFFFFFFull) >> 32); };
  const int node0 = first_node(cta), nloc = min(first_node(cta + 1), p.N) - node0;
  const uint32_t ealo = (uint32_t)(uint64_t)p.ea;
  const int epad = max(0, min(e0, p.E - 16));
  auto load_h = [&](int b) { mbar_expect(sb + BAR_T + b * 8, 8192); tma_load(sb + OFF_H + b * 8192, tmb + TM_H, node0 + b * 64, sb + BAR_T + b * 8); };
  auto prefetch_e = [&](int i) {
    const uint32_t nb = (p.E / G) & ~15u;
    if (nb && i < PFN) asm volatile("cp.async.bulk.prefetch.L2.global [%0], %1;" :: "l"((const char*)p.ea + (size_t)(((i * PFS + i * PFS / 32 * (~PFS & 1)) & 31) * G + cta) * nb), "r"(nb) : "memory");
  };
  if (wid >= 12) {
    const int t = tid - 384;
    uint32_t pv[9], ev = 0;
#pragma unroll
    for (int i = 0; i < 3; i++) { const uint16_t* pp = p.pos + (size_t)(node0 + t + 128 * i) * 3;
      pv[3 * i] = pv[3 * i + 1] = pv[3 * i + 2] = 0;
      asm volatile("{.reg .pred p; setp.lt.s32 p, %4, %5;\n @p ld.global.nc.u16 %0, [%3];\n @p ld.global.nc.u16 %1, [%3+2];\n @p ld.global.nc.u16 %2, [%3+4];}"
        : "+r"(pv[3 * i]), "+r"(pv[3 * i + 1]), "+r"(pv[3 * i + 2]) : "l"(pp), "r"(t + 128 * i), "r"(p.N - node0)); }
    asm volatile("{.reg .pred p; setp.lt.u32 p, %3, %5; @p ld.global.nc.u32 %0, [%1]; @p st.global.v4.u32 [%2], {%4, %4, %4, %4};}"
      : "+r"(ev) : "l"((const uint32_t*)(p.ea + (size_t)epad * 2) + t), "l"(p.q + (size_t)(p.N + cta * PADM + (t >> 3) * PADS) * 128 + (t & 7) * 16), "r"(t), "r"(0xF700F700u), "n"(8 * NPAD) : "memory");
    asm volatile("cp.async.wait_all;" ::: "memory");
    __syncwarp();
    const uint32_t e = lds32(sb + OFF_LEN + 8 + w * 16) + 1;
    {
      const uint32_t tg = (1 + e % 3) << 30, v = ((tg >> 16) + 512 + (lane & 7) * 4) * 0x10001u;
      if (t == 0) sts32(sb + OFF_MISC + 32, e);
#pragma unroll
      for (int i = 0; i < 9; i++) sts128(sb + OFF_SA + t * 16 + i * 2048, v, v + 0x10001u, v + 0x20002u, v + 0x30003u);
      bar_sync(6, NTHR);
      mbar_arrive(sb + BAR_EP, lane == 0);
#pragma unroll
      for (int i = 0; i < 17; i++) sts128(sb + OFF_SB + t * 16 + i * 2048, tg, tg, tg, tg); }
    uint32_t mp = 0;
#pragma unroll
    for (int i = 0; i < 3; i++) { sts64(sb + OFF_POS + (t + 128 * i) * 8, pv[3 * i] | (pv[3 * i + 1] << 16), pv[3 * i + 2]); mp = mag2(mag2(mp, pv[3 * i] | (pv[3 * i + 1] << 16)), pv[3 * i + 2]); }
    proxy_fence();
    __syncwarp();
    mbar_arrive(sb + BAR_PS, lane == 0);
    mbar_wait(sb + BAR_W);
    {
      uint32_t v[4], u[4]; const int r = t >> 3, c = t & 7;
      lds128(v, sb + OFF_WS + 128 + t * 16); lds128(u, sb + OFF_WS + c * 16);
      const uint32_t x = lds32(sb + OFF_WS + 2176 + lane * 4);
      sts128(sb + OFF_W3 + r * 128 + ((c ^ (r & 7)) << 4), b2h(v[0], .5f), b2h(v[1], .5f), b2h(v[2], .5f), b2h(v[3], .5f));
      const float s = ((r & 1) || r == 6) ? 0.f : .5f;
      if (t < 64) sts128(sb + OFF_WD + r * 128 + ((c ^ r) << 4), b2h(u[0], s), b2h(u[1], s), b2h(u[2], s), b2h(u[3], s));
      if (t < 32) sts32(sb + OFF_WX + (t & 3) * 32 + (t >> 2) * 4, b2h(x, 1.f));
      const uint32_t m3 = __reduce_max_sync(~0u, magr(mag2(mag2(mag2(mag2(0, v[0]), v[1]), v[2]), v[3]))), md = __reduce_max_sync(~0u, magr(mag2(mag2(mag2(mag2(0, u[0]), u[1]), u[2]), u[3])));
      if (wbad(m3, 0x4000) || wbad(md, 0x4000) || wbad(__reduce_max_sync(~0u, magr(mag2(0, x))), 0x4700) || magr(mp) >= 0x4200 || magr(mag2(0, ev)) >= 0x4380) sts32(sb + OFF_MISC + 8, 1);
    }
    if (w == 1) {
#pragma unroll 1
      for (int b = HE; b < HW; b++) { mbar_wait(sb + BAR_SRC + max(0, H0 + b) * 8); if (lane == 0) load_h(b); }
    }
    bar_sync(3, 128);
    const uint32_t frag = (w * 16 + (lane & 15)) * 128 + (((lane >> 4) ^ (lane & 7)) << 4);
    uint32_t mq = 0;
#pragma unroll 1
    for (int b = 0; b < 6; b++) {
      float acc[32];
      const uint64_t da = DHI | (((sb + OFF_H) >> 4) + b * 512), db = DHI | ((sb + OFF_W) >> 4);
      const uint32_t v0 = lds16(sb + OFF_POS + b * 512 + w * 128 + lane * 2), v1 = lds16(sb + OFF_POS + 64 + b * 512 + w * 128 + lane * 2);
      mbar_wait(sb + BAR_T + b * 8);
      if (b == 0) STAMP(25);
      if (b == 5) STAMP(26);
      wg_fence();
      ss64<0>(acc, da, db); ss64<1>(acc, da + 2, db + 128); ss64<1>(acc, da + 4, db + 256); ss64<1>(acc, da + 6, db + 384);
      wg_commit();
      if (b == 0) mbar_wait(sb + BAR_AW);
      if (t == 32) { if (HALL) { if (b == 0) for (int k = HW; k < 6; k++) load_h(k); } else if (b + HW < 6) load_h(b + HW); }
      __syncwarp();
      uint32_t ff[6], fg[6];
#pragma unroll
      for (int j = 0; j < 6; j++) { ff[j] = (__byte_perm((j & 1) ? v1 : v0, 0, 0x4140) >> (3 * (j >> 1))) & 0x00070007u; fg[j] = __vsub2(0x00040004u, ff[j]);
        asm volatile("" : "+r"(ff[j]), "+r"(fg[j])); }
      wg_wait0(); fence_regs(acc);
      uint32_t o[16];
#pragma unroll
      for (int j = 0; j < 16; j++) o[j] = pack_f16(.5f * acc[2 * j], .5f * acc[2 * j + 1]);
#pragma unroll
      for (int j = 0; j < 6; j++) {
        const uint32_t m = o[j] & 0x7FFF7FFFu; mq = __vmaxu2(mq, m);
        o[j] = (__viaddmax_s16x2(m, fg[j], 0) & 0xFFF8FFF8u) | ff[j] | (o[j] & 0x80008000u); }
      if (b == 4) mbar_wait(sb + BAR_AX);
      const uint32_t qs = sb + OFF_SA + b * 8192;
#pragma unroll
      for (int j = 0; j < 4; j++) stsm4((qs + frag) ^ (j << 5), o[4 * j], o[4 * j + 1], o[4 * j + 2], o[4 * j + 3]);
      proxy_fence();
      __syncwarp();
      if (lane == 0 && b * 64 + w * 16 < nloc) tma_store(tmb + TM_Q, 0, node0 + b * 64 + w * 16, qs + w * 2048);
    }
    if (lane == 0) bulk_commit();
    { const uint32_t m = __reduce_max_sync(~0u, magr(mq)); if (lane == 0) sts32(sb + OFF_MISC + 16 + w * 4, m); }
    asm volatile("setmaxnreg.dec.sync.aligned.u32 32;");
    bulk_wait();
    bar_sync(3, 128);
    if (w == 0) {
      STAMP(18);
      uint32_t mv[4]; lds128(mv, sb + OFF_MISC + 16);
      const uint32_t mx = max(max(mv[0], mv[1]), max(mv[2], mv[3]));
      mbar_arrive(sb + BAR_QR, lane == 0);
      STAMP(19);
      if (lane == 0) {
        if (nloc > 0 && (mx >= 0x7BF0 || mx < 0x1400)) asm volatile("st.relaxed.gpu.global.u32 [%0+4], %1;" :: "l"(p.sync), "r"(e) : "memory");
        asm volatile("red.release.gpu.global.add.u32 [%0], 1;" :: "l"(p.sync) : "memory");
      }
      __syncwarp();
      uint32_t c, f; int spin = 0;
      do { asm volatile("ld.acquire.gpu.global.v2.u32 {%0, %1}, [%2];" : "=r"(c), "=r"(f) : "l"(p.sync) : "memory"); trap_if(++spin > 4000000); } while (__any_sync(~0u, (int)(c - e * G) < 0));
      if (f == e) sts32(sb + OFF_MISC + 8, 1);
      if (cta == 0 && lane == 0) asm volatile("st.relaxed.gpu.global.u32 [%0+8], %1;" :: "l"(p.sync), "r"(e) : "memory");
      STAMP(20);
      __syncwarp();
      mbar_arrive(sb + BAR_QP, lane == 0);
    }
    if (w == 2) {
      const uint32_t tg = (1 + e % 3) << 30;
      hint_wait(p.sync + 5, e * G);
      if (lane == 0) { mbar_expect(sb + BAR_HB, XPAD);
#pragma unroll 1
        for (int o = 0; o < 4; o++) bulk_load(sb + OFF_XB + o * (G * 64), (const char*)p.xb + (size_t)(cta * 4 + o) * (G * 64), G * 64, sb + BAR_HB); }
      STAMP(21);
      bar_sync(7, 384);
      if (lane < 16) sts32(sb + OFF_XB + XPAD + lane * 4, tg + p.N + cta * PADM + (lane & (NPAD - 1)) * PADS);
      const uint32_t nx = __shfl_sync(~0u, lds32(sb + OFF_MISC + 8) ? 0 : lds32(sb + OFF_MISC + 4), 0);
#pragma unroll 1
      for (uint32_t k = 0; k < nx; k += 32) {
        const uint32_t i = min(k + lane, nx - 1), xr = lds32(sb + OFF_EXT + i * 4), row = (xr >> 9) & 255;
        const uint32_t v = ext_get(p.xe + (cta * G + row) * 32 + ((xr >> 17) & 31), e), x = lds32(sb + OFF_CNT + (xr & 511) * 4) + (xr >> 22) * 16;
        sts32(sb + OFF_XB + XPAD + 64 + i * 4, v); sts16(sb + OFF_TS + x, XPAD + 64 + i * 4);
        sts32(sb + OFF_TE + x * 2, mad16(v, 0x2000u, ealo - (tg >> 11) + row * p.EPC * 32));
      }
      __syncwarp();
      mbar_arrive(sb + BAR_HB, lane == 0);
    }
    if (w == 1) {
      if (PFW) mbar_wait(sb + PFW);
      __nanosleep(PF0NS);
#pragma unroll 1
      for (int i = PFE; i < PFN; i++) { if (lane == 0) prefetch_e(i); __nanosleep(PFNS); }
    }
    if (w == 3) {
      if (lane == 0) { mbar_expect(sb + BAR_U, 16384); tma_load(sb + OFF_W, tmb + TM_WH, 0, sb + BAR_U); }
      __syncwarp();
      bar_sync(4, 416);
      if (lane == 0) tma_load(sb + OFF_W + 8192, tmb + TM_WH, 64, sb + BAR_U);
    }
    bar_sync(3, 128);
    mbar_wait(sb + BAR_U);
    uint32_t mh = 0;
#pragma unroll 1
    for (int i = t; i < 1024; i += 128) {
      uint32_t v[4]; const uint32_t r = (i >> 3) & 7, j = (i ^ r) & 7;
#pragma unroll
      for (int k = 0; k < 4; k++) v[k] = lds32(sb + OFF_W + (i >> 3) * 128 + ((((j & 4) + k) ^ r) << 4) + (j & 3) * 4);
      __syncwarp();
      if (i < 512) sts128(sb + OFF_W + i * 16, hhalf(v[0]), hhalf(v[1]), hhalf(v[2]), hhalf(v[3]));
      else { sts128(sb + OFF_W + i * 16, b2h(v[0], .5f), b2h(v[1], .5f), b2h(v[2], .5f), b2h(v[3], .5f)); mh = mag2(mag2(mag2(mag2(mh, v[0]), v[1]), v[2]), v[3]); } }
    if (wbad(__reduce_max_sync(~0u, magr(mh)), 0x4700)) sts32(sb + OFF_MISC + 12, 1);
    proxy_fence();
    __syncwarp();
    mbar_arrive(sb + BAR_WH, lane == 0);
    if (DEFO) { if (!__shfl_sync(~0u, lds32(sb + OFF_MISC + 8), 0)) {
      mbar_wait(sb + BAR_M);
      __nanosleep(DEF0);
#pragma unroll 1
      for (int i = 0; i < 12; i++) { uint32_t v[4]; const uint32_t n = lds16(sb + OFF_GP + i * 256 + (t >> 3) * 8 + 6);
        lds128(v, sb + OFF_H + n * 128 + (((n ^ t) & 7) << 4));
        if (n < nloc) ((uint4*)p.out)[(size_t)(node0 + n) * 8 + (t & 7)] = make_uint4(v[0], v[1], v[2], v[3]);
        __nanosleep(DEFNS); }
      uint32_t pa_[9];
#pragma unroll
      for (int k = 0; k < 9; k++) { const uint32_t i = t + 128 * k, n = (i * 43691u) >> 17; pa_[k] = lds16(sb + OFF_INV + n * 2) + (i - 3 * n) * 2; }
      uint16_t* po = p.out + (size_t)p.N * 64 + node0 * 3 + t;
      mbar_wait(sb + BAR_X);
#pragma unroll
      for (int k = 0; k < 9; k++) pa_[k] = lds16(sb + OFF_GP + pa_[k]);
#pragma unroll
      for (int k = 0; k < 9; k++) if (t + 128 * k < nloc * 3) po[128 * k] = pa_[k];
      asm volatile("{.reg .pred p, q; setp.ne.u32 p, 0, 0; bar.red.or.pred q, 5, 512, p;}" ::: "memory"); } }
    return;
  }

  if (tid == 320) {
    mbar_init(sb + BAR_W, 1);
    asm volatile("fence.mbarrier_init.release.cluster;" ::: "memory");
    mbar_expect(sb + BAR_W, 2 * 8192 + 2304);
    tma_load(sb + OFF_W, tmb + TM_WE, 64, sb + BAR_W); tma_load(sb + OFF_W + 8192, tmb + TM_WE, 0, sb + BAR_W);
    bulk_load(sb + OFF_WS, p.we + 128 * 64, 2176, sb + BAR_W); bulk_load(sb + OFF_WS + 2176, p.wx, 128, sb + BAR_W);
  }
  if (tid == 288) {
#pragma unroll
    for (int a = BAR_SRC; a < BAR_END; a += 8) if (a != BAR_W) mbar_init(sb + a, a == BAR_WH || a == BAR_PS || a == BAR_EP ? 4 : a == BAR_XA ? 11 : a == BAR_HB ? 2 : a >= BAR_M ? 12 : 1);
    asm volatile("fence.mbarrier_init.release.cluster;" ::: "memory");
    asm volatile("prefetch.tensormap [%0];" :: "l"(tmb + TM_XA)); asm volatile("prefetch.tensormap [%0];" :: "l"(tmb + TM_H));
    asm volatile("prefetch.tensormap [%0];" :: "l"(tmb + TM_XB)); asm volatile("prefetch.tensormap [%0];" :: "l"(tmb + TM_Q));
  }
  {
    if (tid < 144) { const uint32_t z = (tid >> 3) == 16 ? 0x8000u : 0u; sts128(sb + OFF_CNT + tid * 16, z, z, z, z); }
    else if (tid <= 144 + G) sts32(sb + OFF_BC + (tid - 144) * 4, ((tid - 144) & 31) * 4);
    const uint32_t sp = (XPAD + (tid & 1) * 32) * 0x10001u + 0x40000u, em = first_node(G);
    if (wid < 7) {
#pragma unroll
      for (int i = 0; i < 4; i++) sts128(sb + OFF_TS + tid * 16 + i * 3584, sp, sp + 0x80008u, sp + 0x100010u, sp + 0x180018u);
    }
    static_assert(SCAP * 32 == 4 * 3584, "fill");
#pragma unroll 1
    for (int i = n4 + tid; i < 1536; i += 384) sts128(sb + OFF_DST + i * 16, em, em, em, em);
    if (tid == 321) sts128(sb + OFF_MISC, 0, 0, p.force_slow, 0);
  }
  bar_arrive(6, NTHR);
  bar_sync(0, 384);
  uint32_t ep, tag, eb0, pk[12], r0[12], r1[12], cb;
  uint2 vb[12];
  auto get_tag = [&]() { mbar_wait(sb + BAR_EP); ep = lds32(sb + OFF_MISC + 32); tag = (1 + ep % 3) << 30; eb0 = ealo - (tag >> 11); };
  if (wid == 11) {
    trap_if(sb != (uint32_t)__cvta_generic_to_shared(smraw));
#pragma unroll 1
    for (unsigned long long q = LSEQ; q; q >>= 8) { const int k = (q >> 4) & 7, nb = max(0, min(8192, n4 * 16 - k * 8192));
      if (!(q & 8)) mbar_wait(sb + BAR_DST + ((uint32_t)q & 7) * 8);
      if (lane == 0) {
        if (k >= 3) load_h(k - 3);
        else { mbar_expect(sb + BAR_SRC + k * 8, nb);
          if (nb) bulk_load(sb + OFF_SRCI + k * 8192, (const char*)(p.src + e0) + k * 8192, nb, sb + BAR_SRC + k * 8); } } }
    get_tag();
    mbar_wait(sb + BAR_PS);
    bar_sync(12, 384);
    uint32_t xm = 0;
#pragma unroll
    for (int k = 0; k < 5; k++) xm |= (lds32(sb + OFF_BC + min(lane + 32 * k, G - 1) * 4) >= (65 << 9) && lane + 32 * k < G) << k;
    auto ext_send = [&](int pl) {
      uint32_t x = xm;
      for (uint32_t m; (m = __ballot_sync(~0u, x));) {
        const uint32_t l = __ffs(m) - 1, j = l + 32 * (__ffs(__shfl_sync(~0u, x, l)) - 1);
        if (lane == l) x &= x - 1;
        const uint32_t e = min(lds16(sb + OFF_AX + j * 128 + ((4 * l + 2 * lane) & 126)), 6143u);
        if (pl) st_ext(p.xe + (j * G + cta) * 32 + lane, lds32(sb + OFF_SRCI + e * 4) + tag + (e << 16), ep);
        else { const uint32_t cn = lds32(sb + OFF_BC + j * 4) >> 9, v = cn > 96 ? 1 : lane + 64 < cn ? 512 | (lds32(sb + OFF_DST + e * 4) & 511) : 0;
          asm volatile("red.shared.xor.b32 [%0], %1;" :: "r"(sb + OFF_SA + j * 128 + ((l + lane) & 31) * 4), "r"(((v & 63) << 10) | ((v >> 6) << 26)) : "memory"); }
      }
    };
    if (__any_sync(~0u, xm)) { ext_send(0); proxy_fence(); __syncwarp(); }
    if (lane == 0) { tma_store_ef(tmb + TM_XA, cta * 64, 0, sb + OFF_SA); bulk_commit(); mbar_arrive(sb + BAR_AI); bulk_wait(); hint_signal(p.sync + 4); mbar_arrive(sb + BAR_AW); STAMP(16); }
    __syncwarp();
    bar_sync(13, 384);
    if (!B_HOLD && lane == 0) { tma_store_ef(tmb + TM_XB, cta * 64, 0, sb + OFF_SB); bulk_commit(); }
    __syncwarp();
    ext_send(1);
    mbar_arrive(sb + BAR_AX, lane == 0);
    if (B_HOLD) mbar_wait(sb + (B_HOLD == 1 ? BAR_HA : BAR_XA));
    if (BDEL) __nanosleep(BDEL);
    if (lane == 0) {
      bulk_wait();
#pragma unroll 1
      for (int r = B_HOLD ? 0 : BROWS; r < G; r += BROWS) { tma_store_ef(tmb + TM_XB, cta * 64, r, sb + OFF_SB + r * 256); bulk_commit(); bulk_wait(); }
      hint_signal(p.sync + 5);
#pragma unroll 1
      for (int i = 0; i < PFE; i++) prefetch_e(i);
      STAMP(17);
    }
    __syncwarp();
  } else {
    {
      uint32_t d[4 * NCH], jj[4 * NCH], rr[4 * NCH];
      auto count = [&](int k) {
        mbar_wait(sb + BAR_DST + k * 8);
        lds128(d + 4 * k, sb + OFF_DST + (tid + NWK * k) * 16);
#pragma unroll
        for (int i = 4 * k; i < 4 * k + 4; i++) { jj[i] = d[i] * p.magic; rr[i] = atoms_add(__dp4a(jj[i], 0x04000000u, sb + OFF_BC), 0x202u); }
      };
      auto place = [&](int k) {
#pragma unroll
        for (int i = 4 * k; i < 4 * k + 4; i++) {
          const uint32_t o = __dp4a(jj[i], 0x80000000u, rr[i] & 0x807Eu);
          d[i] = (d[i] & 511) | (tag >> 16);
          asm("{.reg .pred p; setp.ge.u32 p, %1, 0x8000; @p add.u32 %0, %2, %3;}" : "+r"(d[i]) : "r"(o), "r"(tid * 4), "r"(NWK * k * 4 + (i & 3)));
          sts16(sb + OFF_SA + o, d[i]); jj[i] = __viaddmin_u32(o, o, G * 256);
        }
      };
      count(0); STAMP(1); count(1); get_tag(); place(0); count(2); place(1); count(3); place(2);
      if (wid < 4) { count(4); STAMP(15); place(3); place(4); } else place(3);
      proxy_fence();
      bar_arrive(12, 384);
      STAMP(2);
      mbar_wait(sb + BAR_AI);
      mbar_wait(sb + BAR_SRC); mbar_wait(sb + BAR_SRC + 8); mbar_wait(sb + BAR_SRC + 16);
      STAMP(12);
#pragma unroll
      for (int k = 0; k < NCH; k++) lds128(d + 4 * k, sb + OFF_SRCI + (tid + NWK * k) * 16);
      const uint32_t tb = tag + (tid << 18);
#pragma unroll
      for (int i = 0; i < 4 * NCH; i++) if (i < 4 * NCH - 4 || wid < 4) sts32(sb + OFF_SB + jj[i], d[i] + tb + ((NWK * (i >> 2) * 4 + (i & 3)) << 16));
      proxy_fence();
      bar_arrive(13, 384);
      STAMP(3);
    }
    const uint32_t rot = (lane + cta) & 31;
    cb = sb + OFF_CNT - (tag >> 14);
    {
      const uint32_t* xa = (const uint32_t*)(p.xa + (cta * G + wid) * 8) + rot;
      if (wid < 8) { const uint32_t e_ = ealo + (epad + (tid * 4 & (NPE - 1))) * 32, d_ = NPE > 1 ? 32 : 0;
        mbar_wait(sb + BAR_AX);
#pragma unroll
        for (int i = 0; i < 7; i++) sts128(sb + OFF_TE + tid * 16 + i * 4096, e_, e_ + d_, e_ + 2 * d_, e_ + 3 * d_); }
      static_assert(SCAP * 64 == 7 * 4096, "fill");
      if (wid == 10) { hint_wait(p.sync + 4, ep * G); mbar_arrive(sb + BAR_HA, lane == 0); }
      mbar_wait(sb + BAR_HA);
      STAMP(14);
      const uint32_t tp = tag | (tag >> 16);
      uint32_t st;
#pragma unroll 1
      for (int spin = 0;; spin++) {
        st = 0;
#pragma unroll
        for (int k = 0; k < 12; k++) asm volatile("ld.relaxed.gpu.global.u32 %0, [%1];" : "=r"(pk[k]) : "l"(xa + k * 352) : "memory");
#pragma unroll
        for (int k = 0; k < 12; k++) st |= pk[k] ^ tp;
        st = __reduce_or_sync(~0u, st);
        if (!(st >> 30)) break;
        trap_if(spin > 2000000);
      }
      if (st & 0x3C00FC00u) {
#pragma unroll 1
        for (;;) {
          uint32_t x = 0, row = 0;
#pragma unroll
          for (int k = 0; k < 12; k++) { const uint32_t y = (pk[k] ^ tp) & 0x3C00FC00u; if (!x && y) { x = y; row = wid + 11 * k; pk[k] ^= y; } }
          if (!__any_sync(~0u, x)) break;
          const uint32_t n = ((x >> 10) & 63) | ((x >> 20) & 0x1C0);
          if (x >> 29) {
            const uint32_t r = atoms_add(sb + OFF_CNT + n * 4, 16), idx = atoms_add(sb + OFF_MISC + 4, 1);
            if (idx < 256) sts32(sb + OFF_EXT + idx * 4, n | (row << 9) | (lane << 17) | (min(r >> 4, 255u) << 22));
            else x = 1;
          }
          if (x && !(x >> 29)) sts32(sb + OFF_MISC + 8, 1);
          __syncwarp();
        }
      }
#pragma unroll
      for (int k = 0; k < 12; k++) { r0[k] = mad16(pk[k], 0x0004u, cb); r1[k] = mad16(pk[k], 0x0400u, cb); vb[k].x = atoms_add(r0[k], 16); vb[k].y = atoms_add(r1[k], 16); }
      if (B_HOLD == 2) mbar_arrive(sb + BAR_XA, lane == 0);
    }
    STAMP(4);
    if (wid >= 6) bar_arrive(11, NWK);
    if (wid < 6) {
      uint32_t ca[2], ky[2], dr[2], sq[2], ps[4];
#pragma unroll
      for (int i = 0; i < 2; i++) { ca[i] = sb + OFF_CNT + ((node0 + tid + 192 * i) & 511) * 4; lds64(ps[2 * i], ps[2 * i + 1], sb + OFF_POS + (tid + 192 * i) * 8); ps[2 * i + 1] |= (tid + 192 * i) << 16; }
      bar_sync(11, NWK);
      STAMP(5);
#pragma unroll
      for (int i = 0; i < 2; i++) ky[i] = (lds32(ca[i]) + 16) >> 5;
      if (max(ky[0], ky[1]) > 31) sts32(sb + OFF_MISC + 8, 1);
#pragma unroll
      for (int i = 0; i < 2; i++) { ky[i] = min(ky[i], 31u); dr[i] = atoms_add(sb + OFF_DH + ky[i] * 4, 1); }
      bar_sync(10, 192);
      const uint32_t hv = lds32(sb + OFF_DH + lane * 4);
      uint32_t inc = hv;
#pragma unroll
      for (int o = 1; o < 32; o <<= 1) asm("{.reg .pred p; .reg .b32 y; shfl.sync.down.b32 y|p, %0, %1, 31, -1; @p add.u32 %0, %0, y;}" : "+r"(inc) : "r"(o));
#pragma unroll
      for (int i = 0; i < 2; i++) {
        const uint32_t pos = __shfl_sync(~0u, inc - hv, ky[i]) + dr[i];
        const uint32_t ak = (uint32_t)(QCODE >> ((pos >> 5) * 4)) & 15, l = (pos >> 3) & 3;
        sq[i] = (ak >> 2) * 16 + ((QREV >> (pos >> 5) & 1) ? 3 - l : l) * 4 + (ak & 3);
        dr[i] = pos & 7;
        asm volatile("{.reg .pred p; setp.eq.u32 p, %2, 0; @p st.shared.u8 [%0], %1;}" :: "r"(sb + OFF_LEN + sq[i]), "r"(max(ky[i], 1u)), "r"(dr[i]) : "memory");
        sts64(sb + OFF_GP + sq[i] * 64 + dr[i] * 8, ps[2 * i], ps[2 * i + 1]);
        sts16(sb + OFF_INV + (tid + 192 * i) * 2, sq[i] * 64 + dr[i] * 8);
      }
      bar_sync(10, 192);
      const uint32_t ln = lds32(sb + OFF_LEN + min(lane, 11) * 4), tot = __dp4a(ln, 0x01010101u, 0u);
      inc = tot;
#pragma unroll
      for (int o = 1; o < 16; o <<= 1) asm("{.reg .pred p; .reg .b32 y; shfl.sync.up.b32 y|p, %0, %1, 0, -1; @p add.u32 %0, %0, y;}" : "+r"(inc) : "r"(o));
      if (wid == 1) sts32(sb + OFF_CNT + 2048 + lane * 4, 0);
      if (tid < 12) { sts32(sb + OFF_LEN + 64 + tid * 4, inc - tot); if (inc > SCAP - 12) sts32(sb + OFF_MISC + 8, 1); }
#pragma unroll
      for (int i = 0; i < 2; i++) sts32(ca[i], __dp4a(__shfl_sync(~0u, ln, sq[i] >> 2), 0x00010101u >> (24 - 8 * (sq[i] & 3)), __shfl_sync(~0u, inc - tot, sq[i] >> 2)) * 32 + dr[i] * 2);
    }
    bar_arrive(7, 384);
  }
  bar_sync(1, 384);
  STAMP(6);
  if (wid != 11 && !__shfl_sync(~0u, lds32(sb + OFF_MISC + 8), 0)) {
#pragma unroll
    for (int k = 0; k < 12; k++) { r0[k] = lds32(r0[k]); r1[k] = lds32(r1[k]); }
#pragma unroll
    for (int k = 0; k < 12; k++) { r0[k] += vb[k].x; r1[k] += vb[k].y; }
  } else {
#pragma unroll
    for (int k = 0; k < 12; k++) r0[k] = r1[k] = 0x8000;
  }
  auto put_ids = [&]() {
    const uint32_t id = wid * 256 + ((lane + cta) & 31) * 8;
    auto put = [&](uint32_t x, uint32_t v) { asm volatile("{.reg .pred p; setp.lt.u32 p, %0, 0x8000; @p st.shared.u16 [%0+%2], %1;}" :: "r"(x), "h"((uint16_t)v), "n"(sb + OFF_TS) : "memory"); };
#pragma unroll
    for (int k = 0; k < 12; k++) { put(IDL ? pk[k] & 0xFFFF : r0[k], id + k * 2816); put(IDL ? pk[k] >> 16 : r1[k], id + k * 2816 + 4); }
  };
  if (!IDL) put_ids();
  STAMP(7);
  mbar_wait(sb + BAR_QR);
  asm volatile("setmaxnreg.inc.sync.aligned.u32 160;");
  if (IDL) {
#pragma unroll
    for (int k = 0; k < 12; k++) asm volatile("prmt.b32 %0, %1, %2, 0x5410;" : "=r"(pk[k]) : "r"(r0[k]), "r"(r1[k]));
  }
  uint32_t pa[8], sp[8], pq[16]; float chk = 0.f;
  {
    uint32_t hf[32], mp = 0; float a0[32], a1[32];
    const uint32_t an = sb + OFF_GP + wid * 256 + (lane & 15) * 8 + 6, n0 = lds16(an), n1 = lds16(an + 128);
#pragma unroll
    for (int j = 0; j < 8; j++) { const uint32_t nd = j < 4 ? n0 : n1; ldsm4(hf + 4 * j, (sb + OFF_H + nd * 128 + (((nd & 7) << 4) ^ (lane & 16))) ^ ((j & 3) << 5)); }
    const uint64_t db = DHI | ((sb + OFF_W + 8192) >> 4);
    wg_fence();
    rs64b<0>(a0, hf[0], hf[1], hf[2], hf[3], db); rs64b<1>(a0, hf[4], hf[5], hf[6], hf[7], db + 128); rs64b<1>(a0, hf[8], hf[9], hf[10], hf[11], db + 256); rs64b<1>(a0, hf[12], hf[13], hf[14], hf[15], db + 384);
    wg_commit();
    rs64b<0>(a1, hf[16], hf[17], hf[18], hf[19], db); rs64b<1>(a1, hf[20], hf[21], hf[22], hf[23], db + 128); rs64b<1>(a1, hf[24], hf[25], hf[26], hf[27], db + 256); rs64b<1>(a1, hf[28], hf[29], hf[30], hf[31], db + 384);
    wg_commit();
    if (IDL) put_ids();
    asm volatile("wgmma.wait_group.sync.aligned 1;" ::: "memory"); fence_regs(a0);
#pragma unroll
    for (int j = 0; j < 8; j++) { const uint32_t x = pack_f16(.5f * a0[4 * j], .5f * a0[4 * j + 1]), y = pack_f16(.5f * a0[4 * j + 2], .5f * a0[4 * j + 3]); mp = hmag(hmag(mp, x), y);
      asm volatile("movmatrix.sync.aligned.m8n8.trans.b16 %0, %1;" : "=r"(pa[j]) : "r"(x)); asm volatile("movmatrix.sync.aligned.m8n8.trans.b16 %0, %1;" : "=r"(sp[j]) : "r"(y)); }
    wg_wait0(); fence_regs(a1);
    bar_arrive(4, 416);
#pragma unroll
    for (int j = 0; j < 16; j++) { pq[j] = pack_f16(.5f * a1[2 * j], .5f * a1[2 * j + 1]); mp = hmag(mp, pq[j]); }
    if (magr(mp) >= 0x7000) chk = __int_as_float(0x7FC00000);
  }
  if (wid == 0) STAMP(23);
  uint32_t bad;
  {
    const uint32_t ring = sb + OFF_RING + wid * STG, p2 = sb + OFF_P2 + wid * 2048;
    uint32_t lens = __shfl_sync(~0u, lds32(sb + OFF_LEN + wid * 4), 0);
    uint32_t rem = __dp4a(lens, 0x20202020u, 0u);
    const uint32_t base = min(lds32(sb + OFF_LEN + 64 + wid * 4), SCAP);
    uint32_t a_s = sb + OFF_TS + base * 32 + (lane >> 3) * 8, a_e = sb + OFF_TE + base * 64 + (lane >> 1) * 4;
    uint32_t k0 = (uint32_t)(uint64_t)p.q + (((lane & 7) ^ ((lane >> 1) & 4)) << 4), k1 = k0 ^ 16, k2 = k0 ^ 32, k3 = k0 ^ 48, ke = ((lane ^ (lane >> 3)) & 1) << 4;
    uint32_t dst0 = ring + (lane >> 3) * 640 + (lane & 7) * 16;
    const uint32_t qhi = (uint32_t)((uint64_t)p.q >> 32), ehi = (uint32_t)((uint64_t)p.ea >> 32);
    uint32_t s0, s1, ev, to = 0, so = 12 * STG;
    auto tl_ = [&]() { lds64(s0, s1, a_s + to); asm volatile("ld.shared.u32 %0, [%1]; add.u32 %1, %1, 64;" : "=&r"(ev), "+r"(a_e) :: "memory"); to += 32; };
#define CPQ(LH, x, k, off) "dp2a." LH ".u32.u32 lo, " x ", 0x80000080, " k "; mov.b64 a, {lo, %7}; @p cp.async.cg.shared.global [%0+" #off "], [a], 16;\n"
#define CPE "or.b32 lo, %10, %11; mov.b64 a, {lo, %12}; @p cp.async.cg.shared.global" ESZ " [%0+512], [a], 16;\n"
#define CPA(BODY) asm volatile("{.reg .b32 lo; .reg .b64 a; .reg .pred p; setp.le.u32 p, %8, %9;\n" BODY "}" \
      :: "r"(dst0 + so), "r"(s0), "r"(s1), "r"(k0), "r"(k1), "r"(k2), "r"(k3), "r"(qhi), "r"(to), "r"(rem), "r"(ev), "r"(ke), "r"(ehi) : "memory")
#define CPQ4 CPQ("lo", "%1", "%3", 0) CPQ("hi", "%1", "%4", 128) CPQ("lo", "%2", "%5", 256) CPQ("hi", "%2", "%6", 384) "cp.async.commit_group;"
    auto issue = [&]() { CPA(CPE CPQ4); so = so == (NST - 1) * 12 * STG ? 0 : so + 12 * STG; };
    const int g = lane >> 2, qd = lane & 3;
    const uint32_t sw = ((lane >> 4) ^ (lane & 7)) << 4, fr = (lane & 15) * 128 + sw;
    uint32_t qa0 = ring + (g & 3) * 640 + qd * 128 + sw, qa1 = qa0 ^ 32, qa2 = qa0 ^ 64, qa3 = qa0 ^ 96;
    uint32_t eadr = ring + 512 + (g & 3) * 640 + qd * 32 + ((((lane >> 4) ^ g) & 1) << 4);
    uint32_t oh0 = g == 2 * qd ? 0x3C00u : g == 2 * qd + 1 ? 0x3C000000u : 0u, oh1 = oh0;
    uint32_t a_g = sb + OFF_GP + wid * 256 + lane * 2;
    uint32_t a_n = sb + OFF_GP + wid * 256 + (lane & 15) * 8 + 6;
    uint32_t a_p = ((lane & 8) ? p2 : sb + OFF_WD) + (lane & 7) * 128 + ((((lane >> 4) ^ lane) & 7) << 4);
    uint32_t a_w = sb + OFF_W3 + fr;
#define OPQ4(A, B, C, D) asm volatile("shfl.sync.bfly.b32 %0, %0, 0, 31, -1; shfl.sync.bfly.b32 %1, %1, 0, 31, -1; shfl.sync.bfly.b32 %2, %2, 0, 31, -1; shfl.sync.bfly.b32 %3, %3, 0, 31, -1;" : "+r"(A), "+r"(B), "+r"(C), "+r"(D))
    asm volatile("shfl.sync.idx.b32 %0, %0, %1, 31, -1;" : "+r"(oh1) : "r"(lane));
    if (OPQ & 1) OPQ4(a_w, oh0, ke, dst0);
    if (OPQ & 2) OPQ4(qa0, qa1, qa2, qa3);
    if (OPQ & 4) OPQ4(k0, k1, k2, k3);
    if (OPQ & 8) OPQ4(a_g, a_n, a_p, eadr);
    uint32_t w3[16], wv[8], bp[16], sum[8], Y[16], M[16], own, ownp, dpk; uint16_t tl[16], th[16];
    float pacc = 0.f;
    auto wload = [&]() {
#pragma unroll
      for (int j = 0; j < 4; j++) ldsm4t(w3 + 4 * j, a_w ^ (j << 5));
      lds128(wv, sb + OFF_WX + (a_g & 6) * 16); lds128(wv + 4, sb + OFF_WX + 16 + (a_g & 6) * 16);
    };
    auto hload = [&](uint32_t (&hf)[16], uint32_t nd) {
      const uint32_t hrow = sb + OFF_H + nd * 128 + (((nd & 7) << 4) ^ ((a_g >> 1) & 16));
#pragma unroll
      for (int j = 0; j < 4; j++) ldsm4(hf + 4 * j, hrow ^ (j << 5));
      return hrow;
    };
    auto bload = [&](uint32_t o) {
#pragma unroll
      for (int j = 0; j < 4; j++) ldsm4t(bp + 4 * j, (a_p ^ (j << 5)) + o);
    };
    { uint32_t wd[8]; const uint32_t a = sb + OFF_WD + (lane & 7) * 128 + ((((lane >> 3) ^ lane) & 7) << 4);
      ldsm4t(wd, a); ldsm4t(wd + 4, a ^ 64);
#pragma unroll
      for (int j = 0; j < 8; j++) { bp[2 * j] = wd[j]; bp[2 * j + 1] = pa[j]; } }
    own = lds16(a_g) * 0x10001u;
    wload();
    if (__shfl_sync(~0u, lds32(sb + OFF_MISC + 8), 0)) rem = 0;
    auto resolve = [&](auto NBK, uint32_t o) {
      constexpr int NB = decltype(NBK)::value;
      uint32_t id[NB], c0[NB], c1[NB]; const uint32_t a = base * 32 + o + lane * 4;
#pragma unroll
      for (int i = 0; i < NB; i++) { id[i] = lds32(sb + OFF_TS + a + i * 128); if (o + lane * 4 + i * 128 >= rem) id[i] = XPAD * 0x10001u; }
      uint32_t st = 0;
#pragma unroll
      for (int i = 0; i < NB; i++) { c0[i] = lds32(sb + OFF_XB + (id[i] & 0xFFFF)); c1[i] = lds32(sb + OFF_XB + (id[i] >> 16)); }
#pragma unroll
      for (int i = 0; i < NB; i++) st |= (c0[i] ^ tag) | (c1[i] ^ tag);
      for (int spin = 0; __any_sync(~0u, st >> 30); spin++) {
        st = 0; trap_if(spin > 2000000);
#pragma unroll
        for (int i = 0; i < NB; i++) {
          asm volatile("{.reg .pred p, q; setp.lt.u32 p, %4, %6; setp.lt.u32 q, %5, %6; @p ld.relaxed.gpu.global.u32 %0, [%2]; @q ld.relaxed.gpu.global.u32 %1, [%3];}"
            : "+r"(c0[i]), "+r"(c1[i]) : "l"((const char*)p.xb + cta * XPAD + (id[i] & 0xFFFF)), "l"((const char*)p.xb + cta * XPAD + (id[i] >> 16)), "r"(id[i] & 0xFFFF), "r"(id[i] >> 16), "n"(XPAD) : "memory");
          st |= (c0[i] ^ tag) | (c1[i] ^ tag); }
      }
#pragma unroll
      for (int i = 0; i < NB; i++) { const uint32_t j0 = (id[i] >> 8) & 255, j1 = id[i] >> 24;
        if (ABL & 2) { c0[i] &= 0xFFFF0FFFu; c1[i] &= 0xFFFF0FFFu; }
        asm volatile("{.reg .pred p, q, r; setp.lt.u32 p, %5, %9; setp.lt.u32 q, %6, %9; setp.lt.u32 r, %7, %8;\n"
          "@p st.shared.u32 [%0], %2; @q st.shared.u32 [%0+4], %3; @r st.shared.u32 [%1], %4;}"
          :: "r"(sb + OFF_TE + 2 * a + i * 256), "r"(sb + OFF_TS + a + i * 128), "r"(mad16(c0[i], 0x2000u, eb0 + ((ABL & 1) ? j0 & 7 : j0) * p.EPC * 32)), "r"(mad16(c1[i], 0x2000u, eb0 + ((ABL & 1) ? j1 & 7 : j1) * p.EPC * 32)),
             "r"(__byte_perm(c0[i], c1[i], 0x5410)), "r"(j0), "r"(j1), "r"(o + lane * 4 + i * 128), "r"(rem), "n"(G) : "memory"); }
    };
    bar_sync(2, 384);
    if (wid == 0) STAMP(27);
    mbar_wait(sb + BAR_HB);
    if (wid == 0) STAMP(22);
#pragma unroll 1
    for (uint32_t o = 0, go = 0; go < 32 * NST; o += 128 * RNB) {
      if (o < rem) { resolve(IC<RNB>(), o);
        asm volatile("{.reg .pred p; mbarrier.test_wait.parity.shared::cta.b64 p, [%1], 0; vote.sync.all.pred p, p, -1; selp.u32 %0, %2, 0, p;}" : "=r"(go) : "r"(sb + BAR_QP), "n"(32 * NEARLY) : "memory"); }
      else { bar_sync(8, 384); mbar_wait(sb + BAR_QP); go = 32 * NST; if (wid == 0) STAMP(24); }
      __syncwarp();
#pragma unroll 1
      while (to < go) { tl_(); issue(); if (to == 32) STAMP(13); }
    }
    bad = __shfl_sync(~0u, lds32(sb + OFF_MISC + 8), 0);
   if (!bad) {
#pragma unroll
    for (int j = 0; j < 4; j++) stsm4((p2 + fr) ^ (j << 5), pq[4 * j], pq[4 * j + 1], pq[4 * j + 2], pq[4 * j + 3]);
    auto body = [&](auto MODE) {
      constexpr int mode = decltype(MODE)::value;
      uint32_t T[16], ef[4], q0, q1, x0, x1, x2; float e0_, e1_, cs[4];
      auto mu = [&](int j) {
#pragma unroll
        for (int i = 2 * j; i < 2 * j + 2; i++) asm volatile("{.reg .b16 l, h; mov.b32 {l, h}, %2; tanh.approx.f16 %0, l; tanh.approx.f16 %1, h;}" : "=h"(tl[i]), "=h"(th[i]) : "r"(Y[i])); };
      auto fi = [&](int j) {
#pragma unroll
        for (int i = 2 * j; i < 2 * j + 2; i++) asm volatile("{.reg .b32 t; mov.b32 t, {%2, %3}; fma.rn.f16x2 %0, %1, t, %1;}" : "=r"(M[i]) : "r"(Y[i]), "h"(tl[i]), "h"(th[i])); };
      auto ad = [&](int j) { asm volatile("add.rn.f16x2 %0, %0, %1; add.rn.f16x2 %0, %0, %2;" : "+r"(sum[j]) : "r"(M[2 * j]), "r"(M[2 * j + 1])); };
      auto he = [&](int j) { asm volatile("mma.sync.aligned.m16n8k16.row.col.f16.f16.f16.f16 {%0,%1}, {%2,%3,%4,%5}, {%6,%7}, {%0,%1};" : "+r"(T[2 * j]), "+r"(T[2 * j + 1]) : "r"(ef[0]), "r"(ef[1]), "r"(ef[2]), "r"(ef[3]), "r"(w3[2 * j]), "r"(w3[2 * j + 1])); };
      auto hs = [&](int j) { asm volatile("mma.sync.aligned.m16n8k16.row.col.f16.f16.f16.f16 {%0,%1}, {%2,%3,%4,%5}, {%6,%7}, {%8,%9};" : "=r"(Y[2 * j]), "=r"(Y[2 * j + 1]) : "r"(q0), "r"(q1), "r"(oh0), "r"(oh1), "r"(bp[2 * j]), "r"(bp[2 * j + 1]), "r"(T[2 * j]), "r"(T[2 * j + 1])); };
      auto hc = [&](int j) {
        if (j) asm volatile("mma.sync.aligned.m16n8k16.row.col.f32.f16.f16.f32 {%0,%1,%2,%3}, {%4,%5,%6,%7}, {%8,%9}, {%0,%1,%2,%3};" : "+f"(cs[0]), "+f"(cs[1]), "+f"(cs[2]), "+f"(cs[3]) : "r"(M[4 * j]), "r"(M[4 * j + 1]), "r"(M[4 * j + 2]), "r"(M[4 * j + 3]), "r"(wv[2 * j]), "r"(wv[2 * j + 1]));
        else asm volatile("mma.sync.aligned.m16n8k16.row.col.f32.f16.f16.f32 {%0,%1,%2,%3}, {%4,%5,%6,%7}, {%8,%9}, {%10,%10,%10,%10};" : "=f"(cs[0]), "=f"(cs[1]), "=f"(cs[2]), "=f"(cs[3]) : "r"(M[0]), "r"(M[1]), "r"(M[2]), "r"(M[3]), "r"(wv[0]), "r"(wv[1]), "f"(0.f)); };
      auto cv = [&](int i) { asm volatile("{.reg .b32 a, b; shl.b32 a, %0, 16; and.b32 b, %0, 0xFFFF0000; cvt.rn.f16x2.f32 %0, b, a;}" : "+r"(ef[i])); };
      auto un = [&]() { asm volatile("shl.b32 %0, %2, 16; and.b32 %1, %2, 0xFFFF0000;" : "=&f"(e0_), "=&f"(e1_) : "r"(dpk)); };
      auto ex0 = [&]() { asm volatile("prmt.b32 %0, %3, %4, 0x6420; prmt.b32 %1, %5, %6, 0x6420; prmt.b32 %2, %7, %8, 0x6420;" : "=&r"(x0), "=&r"(x1), "=&r"(x2) : "r"(T[0]), "r"(T[1]), "r"(T[2]), "r"(T[3]), "r"(T[4]), "r"(T[5])); };
      auto ex1 = [&]() { asm volatile("{.reg .b32 a, b; shl.b32 a, %2, 3; shl.b32 b, %3, 6; lop3.b32 a, %1, a, 0x38383838, 0xD8; lop3.b32 a, a, b, 0xC0C0C0C0, 0xD8; sub.rn.bf16x2 %0, %4, a;}" : "=r"(dpk) : "r"(x0), "r"(x1), "r"(x2), "r"(own)); };
      auto ex2 = [&]() { asm volatile("{.reg .b32 a, b, d, u; .reg .b16 l, h; shl.b32 a, %2, 16; and.b32 b, %2, 0xFFFF0000; cvt.rn.f16x2.f32 d, b, a; mul.rn.f16x2 %0, d, d; mov.b32 {l, h}, d; mov.b32 u, {h, h}; mul.rn.f16x2 %1, u, u;}" : "=&r"(q0), "=&r"(q1) : "r"(dpk)); };
      auto pf = [&]() { asm volatile("fma.rn.f32 %0, %1, %2, %0; fma.rn.f32 %0, %3, %4, %0;" : "+f"(pacc) : "f"(cs[0]), "f"(e0_), "f"(cs[2]), "f"(e1_)); };
#define FX(k) if (FM >> k & 1) asm volatile("pmevent 1;" ::: "memory")
      if (mode == 2) {
        hc(0); mu(3); fi(2); un(); ad(0); ad(1); mu(4); fi(3); hc(1); mu(5); fi(4); ad(2); mu(6); fi(5); ad(3); hc(2); mu(7); fi(6); fi(7); ad(4); ad(5); hc(3); ad(6); ad(7); pf();
        return;
      }
      asm volatile("cp.async.wait_group %0;" :: "n"(NST - 1) : "memory");
      __syncwarp();
      if (mode == 1) STAMP(8);
      ldsm4(ef, eadr + so); ldsm4(T, qa0 + so); ldsm4(T + 4, qa1 + so); ldsm4(T + 8, qa2 + so); ldsm4(T + 12, qa3 + so);
      tl_();
      if (mode == 1) {
        issue();
        cv(0); cv(1); cv(2); cv(3); ex0(); ex1(); ex2();
#pragma unroll
        for (int j = 0; j < 8; j++) { he(j); hs(j); }
        mu(0); mu(1); fi(0); mu(2); fi(1);
        return;
      }
      hc(0); mu(3); fi(2); un(); ad(0); ad(1);
      FX(0);
      mu(4); fi(3); cv(0); cv(1); cv(2); cv(3); ex0(); ex1();
      FX(1);
      he(0); he(1); hc(1); mu(5); fi(4); ex2(); ad(2);
      FX(2);
      hs(0); he(2); mu(6); fi(5); issue(); ad(3);
      FX(3);
      hs(1); he(3); hc(2); mu(7); fi(6);
      FX(4);
      hs(2); hs(3); he(4); he(5); mu(0); fi(7); ad(4); ad(5);
      FX(5);
      hc(3); hs(4); he(6); he(7); mu(1); fi(0); ad(6);
      FX(6);
      hs(5); hs(6); hs(7); mu(2); fi(1); ad(7); pf();
      FX(7);
    };
#pragma unroll
    for (int j = 0; j < 8; j++) sum[j] = 0;
    body(IC<1>());
    int cnt = (lens & 255) - 1;
    auto flush = [&]() {
      asm volatile("{.reg .pred p; setp.ne.u32 p, %2, 6; @p st.shared.u16 [%0+-64], %1;}" :: "r"(a_g), "h"((uint16_t)pack_bf16(bf_hi(ownp) + pacc, 0.f)), "r"(a_g & 6) : "memory");
      chk = fmaf(pacc, 0.f, chk); pacc = 0.f; };
    constexpr uint64_t b1 = DHI | ((sb + OFF_W) >> 4), b2_ = b1 + 512;
    auto mma_h = [&](float (&acc)[32], uint32_t (&hf)[16]) {
      rs64b<0>(acc, hf[0], hf[1], hf[2], hf[3], b1); rs64b<1>(acc, hf[4], hf[5], hf[6], hf[7], b1 + 128); rs64b<1>(acc, hf[8], hf[9], hf[10], hf[11], b1 + 256); rs64b<1>(acc, hf[12], hf[13], hf[14], hf[15], b1 + 384); };
    auto mma_m = [&](float (&acc)[32]) {
      rs64h<1>(acc, sp[0], sum[0], sp[1], sum[1], b2_); rs64h<1>(acc, sp[2], sum[2], sp[3], sum[3], b2_ + 128); rs64h<1>(acc, sp[4], sum[4], sp[5], sum[5], b2_ + 256); rs64h<1>(acc, sp[6], sum[6], sp[7], sum[7], b2_ + 384);
      wg_commit(); wg_wait0(); fence_regs(acc);
      STAMP(10);
      chk = fmaf(acc[0], 0.f, fmaf(acc[2], 0.f, chk)); };
    auto roff = [&](uint32_t nd, int r) { return __shfl_sync(~0u, nd, ((a_g >> 3) & 7) + 8 * r) * 128 + (a_g & 6) * 8; };
    auto radr = [&](uint32_t o, int k) { return sb + OFF_H + (o ^ ((o >> 3) & 0x70) ^ ((k >> 1) << 6)); };
    auto fin = [&](float (&acc)[32], uint32_t* x, int k) {
#pragma unroll
      for (int i = 0; i < 4; i++) { const int c = 16 * (k >> 1) + 4 * i + 2 * (k & 1); x[i] = u2(__hadd2(b2(x[i]), b2(pack_bf16(silu_h(acc[c]), silu_h(acc[c + 1]))))); } };
#pragma unroll 1
    for (int t = 0;; t++) {
#pragma unroll 1
      for (; cnt > 0; cnt--) { body(IC<0>());
      }
      if (!(t & 1)) {
        ownp = own; a_g += 64;
        if (t == 6) break;
        own = lds16(a_g) * 0x10001u;
        if (t == 0) {
#pragma unroll
          for (int j = 0; j < 8; j++) bp[2 * j + 1] = sp[j];
        } else bload((a_g & 16) ? (t & 4) * 256 : 0);
        lens >>= 8; cnt = 1;
        continue;
      }
      cnt = (lens & 255) - 1;
      flush();
      if (t == 3) {
        uint32_t hf[16]; float acc[32];
        const uint32_t nd = lds16(a_n), o[2] = {roff(nd, 0), roff(nd, 1)};
        hload(hf, nd);
        mbar_wait(sb + BAR_WH);
        wg_fence();
        mma_h(acc, hf); mma_m(acc);
#pragma unroll
        for (int k = 0; k < 4; k++) lds128(hf + 4 * k, radr(o[k & 1], k));
#pragma unroll
        for (int k = 0; k < 4; k++) { fin(acc, hf + 4 * k, k); sts128(radr(o[k & 1], k), hf[4 * k], hf[4 * k + 1], hf[4 * k + 2], hf[4 * k + 3]); }
        __syncwarp();
        mbar_arrive(sb + BAR_M, (a_g & 62) == 0);
        wload();
      }
#pragma unroll
      for (int j = 0; j < 8; j++) { sp[j] = sum[j]; asm volatile("mov.b32 %0, 0;" : "=r"(sum[j])); }
    }
    {
      uint32_t hf[16], v[16]; float acc[32];
      const uint32_t nd = lds16(a_n + 128), o[2] = {roff(nd, 0), roff(nd, 1)};
      hload(hf, nd);
#pragma unroll
      for (int k = 0; k < 4; k++) lds128(v + 4 * k, radr(o[k & 1], k));
      wg_fence(); mma_h(acc, hf); wg_commit();
      body(IC<2>());
      STAMP(9);
      flush();
      __syncwarp();
      mbar_arrive(sb + BAR_X, lane == 0);
      wg_fence();
      mma_m(acc);
#pragma unroll
      for (int k = 0; k < 4; k++) { fin(acc, v + 4 * k, k);
        asm volatile("{.reg .pred p; setp.lt.u32 p, %5, %6; @p st.global" OCS ".v4.b32 [%0], {%1,%2,%3,%4};}" :: "l"((const char*)p.out + (size_t)node0 * 128 + o[k & 1] + (k >> 1) * 64), "r"(v[4 * k]), "r"(v[4 * k + 1]), "r"(v[4 * k + 2]), "r"(v[4 * k + 3]), "r"(o[k & 1]), "r"(nloc * 128) : "memory"); }
    }
    asm volatile("{.reg .pred p, q; setp.neu.f32 p, %1, 0f00000000; setp.ne.or.u32 p, %2, 0, p; bar.red.or.pred q, 5, %3, p; selp.u32 %0, 1, 0, q;}" : "=r"(bad) : "f"(chk), "r"(lds32(sb + OFF_MISC + 12)), "n"(DEFO ? 512 : 384) : "memory");
    STAMP(11);
   } else { asm volatile("cp.async.wait_all;" ::: "memory"); bar_sync(5, 384); }
  }
  if (bad) slow_path(p, wid, lane, node0, nloc);
}

}

typedef CUresult (*EncodeFn)(CUtensorMap*, CUtensorMapDataType, cuuint32_t, void*, const cuuint64_t*, const cuuint64_t*, const cuuint32_t*, const cuuint32_t*,
                             CUtensorMapInterleave, CUtensorMapSwizzle, CUtensorMapL2promotion, CUtensorMapFloatOOBfill);

extern "C" void kernel_launch(void* const* d_in, const int* in_sizes, int n_in, void* d_out, int out_size) {
  Params p; Maps maps;
  p.h = (const uint4*)d_in[0]; p.pos = (const uint16_t*)d_in[1]; p.ea = (const uint4*)d_in[2];
  p.src = (const int*)d_in[3]; p.dst = (const int*)d_in[4];
  p.we = (const uint16_t*)d_in[5]; p.wx = (const uint16_t*)d_in[6]; p.wh = (const uint16_t*)d_in[7];
  p.out = (uint16_t*)d_out;
  p.N = in_sizes[0] / 64; p.E = in_sizes[3];
  p.EPC = ((p.E + G * 4 - 1) / (G * 4)) * 4;
  p.magic = (uint32_t)(((uint64_t)G << 24) / (uint64_t)p.N);
  p.inv = (1ull << 56) / p.magic;
  const uint64_t ea0 = (uint64_t)d_in[2], ea1 = ea0 + (uint64_t)p.E * 32 - 1;
  p.force_slow = ((ea0 >> 32) != (ea1 >> 32)) || (ea0 & 31) || (p.E & 3);
  void* qp = nullptr;
  cudaGetSymbolAddress(&qp, g_q);
  p.q = (char*)qp;
  if (((uint64_t)p.q >> 32) != (((uint64_t)p.q + QBYTES) >> 32)) p.q += QBYTES;
  cudaGetSymbolAddress((void**)&p.sync, g_sync); cudaGetSymbolAddress((void**)&p.xe, g_xe);
  cudaGetSymbolAddress((void**)&p.xa, g_xa); cudaGetSymbolAddress((void**)&p.xb, g_xb);
  void* fn = nullptr; cudaDriverEntryPointQueryResult qr;
  cudaGetDriverEntryPoint("cuTensorMapEncodeTiled", &fn, cudaEnableDefault, &qr);
  auto mk = [&](CUtensorMap* tm, void* base, int rows, int box = 64) {
    const cuuint64_t dim[2] = {64, (cuuint64_t)rows}, str[1] = {128}; const cuuint32_t bx[2] = {64, (cuuint32_t)box}, es[2] = {1, 1};
    ((EncodeFn)fn)(tm, CU_TENSOR_MAP_DATA_TYPE_BFLOAT16, 2, base, dim, str, bx, es, CU_TENSOR_MAP_INTERLEAVE_NONE, CU_TENSOR_MAP_SWIZZLE_128B,
                   CU_TENSOR_MAP_L2_PROMOTION_NONE, CU_TENSOR_MAP_FLOAT_OOB_FILL_NONE);
  };
  mk(&maps.m[TM_H / 128], d_in[0], p.N); mk(&maps.m[TM_WE / 128], d_in[5], 145); mk(&maps.m[TM_WH / 128], d_in[7], 128); mk(&maps.m[TM_Q / 128], p.q, p.N, 16);
  for (int k = 0; k < 2; k++) {
    void* xp = (void*)(k ? p.xb : p.xa);
    const cuuint64_t dim[2] = {(cuuint64_t)G * 64, (cuuint64_t)G}, str[1] = {(cuuint64_t)G * (128 << k)}; const cuuint32_t bx[2] = {64, (cuuint32_t)(k ? BROWS : G)}, es[2] = {1, 1};
    ((EncodeFn)fn)(&maps.m[TM_XA / 128 + k], k ? CU_TENSOR_MAP_DATA_TYPE_UINT32 : CU_TENSOR_MAP_DATA_TYPE_UINT16, 2, xp, dim, str, bx, es, CU_TENSOR_MAP_INTERLEAVE_NONE,
                   CU_TENSOR_MAP_SWIZZLE_NONE, CU_TENSOR_MAP_L2_PROMOTION_NONE, CU_TENSOR_MAP_FLOAT_OOB_FILL_NONE);
  }
  cudaFuncSetAttribute(egnn_kernel, cudaFuncAttributeMaxDynamicSharedMemorySize, SMEM);
  egnn_kernel<<<G, NTHR, SMEM>>>(p, maps);
}
```

```cpp
#include <cuda_runtime.h>
#include <cuda_bf16.h>
#include <cuda_fp16.h>
#include <cuda.h>
#include <stdint.h>
#pragma nv_diag_suppress 549

#define PFN p.tune[0]
#define PFNS p.tune[1]
#define BDEL p.tune[2]
#define DEF0 p.tune[3]
#define DEFNS p.tune[4]
#define CTAM p.tune[5]
#define QREV p.tune[6]
#define QCODE p.qcode
namespace {

constexpr int G = 132;
constexpr int NTHR = 512, NWK = 352, NCH = 5;
constexpr int NST = 3, STG = 2560;
constexpr int BROWS = 44, RNB = 2, PADM = 33;
constexpr int SCAP = 448;

constexpr int OFF_H = 0;
constexpr int OFF_W = 49152;
constexpr int OFF_WD = OFF_W + 16384;
constexpr int OFF_W3 = OFF_WD + 1024;
constexpr int OFF_P2 = OFF_W3 + 2048;
constexpr int OFF_RING = OFF_P2 + 24576;
constexpr int OFF_TE = OFF_RING + 12 * NST * STG;
constexpr int OFF_TS = OFF_TE + SCAP * 64;
constexpr int OFF_INV = OFF_TS - 768;
constexpr int OFF_GP = OFF_TS + SCAP * 32;
constexpr int OFF_WX = OFF_GP + 3072;
constexpr int OFF_LEN = OFF_WX + 128;
constexpr int OFF_MISC = OFF_LEN + 128;
constexpr int OFF_BAR = OFF_MISC + 48;
constexpr int SMEM = OFF_BAR + 256;
static_assert(SMEM <= 232448, "smem");
constexpr uint32_t sb = 1024;
constexpr int OFF_SRCI = OFF_TE;
constexpr int OFF_SB = OFF_RING, OFF_SA = OFF_SB + 34816, OFF_AX = OFF_SA + 32768, OFF_DST = OFF_H + 24576;
constexpr int OFF_WS = OFF_AX + 17408;
constexpr int OFF_BC = OFF_WS + 2304;
constexpr int OFF_CNT = OFF_P2;
constexpr int OFF_DH = OFF_CNT + 2176;
constexpr int OFF_POS = OFF_DH + 128;
constexpr int OFF_EXT = OFF_POS + 3072;
constexpr int OFF_XB = OFF_EXT + 1024, XPAD = G * 256;
static_assert(OFF_XB + XPAD + 1028 <= OFF_RING + 12 * STG && OFF_XB % 128 == 0 && OFF_BC + 544 <= OFF_TE && OFF_P2 % 1024 == 0 && OFF_SA % 1024 == 0 && SCAP * 64 >= 24576, "staging");
constexpr int BAR_DST = OFF_BAR, BAR_SRC = BAR_DST + 40, BAR_T = BAR_SRC + 24, BAR_W = BAR_T + 48, BAR_PS = BAR_W + 8, BAR_AW = BAR_PS + 8,
              BAR_QP = BAR_AW + 8, BAR_QR = BAR_QP + 8, BAR_HA = BAR_QR + 8, BAR_EP = BAR_HA + 8, BAR_AX = BAR_EP + 8, BAR_AI = BAR_AX + 8, BAR_HB = BAR_AI + 8, BAR_U = BAR_HB + 8, BAR_WH = BAR_U + 8, BAR_M = BAR_WH + 8, BAR_X = BAR_M + 8, BAR_END = BAR_X + 8;
static_assert(BAR_END <= OFF_BAR + 256, "barriers");
constexpr uint32_t QBYTES = 8u << 20;

__device__ __align__(256) uint4 g_xa[G * G * 8];
__device__ __align__(256) uint4 g_xb[G * G * 16];
__device__ __align__(256) uint2 g_xe[G * G * 32];
__device__ __align__(256) uint4 g_q[2 * QBYTES / 16];
__device__ __align__(256) uint32_t g_sync[8];
#define STAMP(k)

struct Maps { CUtensorMap m[6]; };
constexpr int TM_H = 0, TM_WE = 128, TM_WH = 256, TM_Q = 384, TM_XA = 512, TM_XB = 640;
struct Params {
  const int* dst; uint32_t* sync; int E, EPC, N; uint32_t magic; unsigned long long inv;
  const int* src; const uint16_t* pos; const uint4* ea; const uint16_t* we; const uint16_t* wx; char* q; int force_slow;
  const uint4* xa; const uint4* xb; uint2* xe; uint16_t* out; const uint4* h; const uint16_t* wh;
  int tune[10]; unsigned long long qcode;
};
template<int V> struct IC { static constexpr int value = V; };

#define R32(d) "+f"(d[0]),"+f"(d[1]),"+f"(d[2]),"+f"(d[3]),"+f"(d[4]),"+f"(d[5]),"+f"(d[6]),"+f"(d[7]),"+f"(d[8]),"+f"(d[9]),"+f"(d[10]),"+f"(d[11]),"+f"(d[12]),"+f"(d[13]),"+f"(d[14]),"+f"(d[15]),"+f"(d[16]),"+f"(d[17]),"+f"(d[18]),"+f"(d[19]),"+f"(d[20]),"+f"(d[21]),"+f"(d[22]),"+f"(d[23]),"+f"(d[24]),"+f"(d[25]),"+f"(d[26]),"+f"(d[27]),"+f"(d[28]),"+f"(d[29]),"+f"(d[30]),"+f"(d[31])
#define S32 "{%0,%1,%2,%3,%4,%5,%6,%7,%8,%9,%10,%11,%12,%13,%14,%15,%16,%17,%18,%19,%20,%21,%22,%23,%24,%25,%26,%27,%28,%29,%30,%31}"
#define DI __device__ __forceinline__

constexpr uint64_t DHI = ((uint64_t)(1024 >> 4) << 32) | (1ull << 62);
template<int SD> DI void rs64b(float (&d)[32], uint32_t a0, uint32_t a1, uint32_t a2, uint32_t a3, uint64_t db) {
  asm volatile("wgmma.mma_async.sync.aligned.m64n64k16.f32.bf16.bf16 " S32 ", {%32,%33,%34,%35}, %36, %37, 1, 1, 1;" : R32(d) : "r"(a0), "r"(a1), "r"(a2), "r"(a3), "l"(db), "n"(SD)); }
template<int SD> DI void rs64h(float (&d)[32], uint32_t a0, uint32_t a1, uint32_t a2, uint32_t a3, uint64_t db) {
  asm volatile("wgmma.mma_async.sync.aligned.m64n64k16.f32.f16.f16 " S32 ", {%32,%33,%34,%35}, %36, %37, 1, 1, 1;" : R32(d) : "r"(a0), "r"(a1), "r"(a2), "r"(a3), "l"(db), "n"(SD)); }
template<int SD> DI void ss64(float (&d)[32], uint64_t da, uint64_t db) {
  asm volatile("wgmma.mma_async.sync.aligned.m64n64k16.f32.bf16.bf16 " S32 ", %32, %33, %34, 1, 1, 0, 1;" : R32(d) : "l"(da), "l"(db), "n"(SD)); }
DI void trap_if(bool c) { asm volatile("{.reg .pred p; setp.eq.u32 p, %0, 0; @p bra.uni LT_%=; trap; LT_%=:}" :: "r"((uint32_t)c)); }
DI void wg_fence() { asm volatile("wgmma.fence.sync.aligned;" ::: "memory"); }
DI void wg_commit() { asm volatile("wgmma.commit_group.sync.aligned;" ::: "memory"); }
DI void wg_wait0() { asm volatile("wgmma.wait_group.sync.aligned 0;" ::: "memory"); }
DI void fence_regs(float (&d)[32]) { asm volatile("" : R32(d) :: "memory"); }
DI void proxy_fence() { asm volatile("fence.proxy.async.shared::cta;" ::: "memory"); }
DI uint64_t pol_first() { uint64_t r; asm("createpolicy.fractional.L2::evict_first.b64 %0, 1.0;" : "=l"(r)); return r; }
DI float tanh_ap(float x) { float y; asm("tanh.approx.f32 %0, %1;" : "=f"(y) : "f"(x)); return y; }
DI float silu_h(float y) { return fmaf(y, tanh_ap(y), y); }
DI uint32_t pack_bf16(float lo, float hi) { uint32_t r; asm("cvt.rn.bf16x2.f32 %0, %1, %2;" : "=r"(r) : "f"(hi), "f"(lo)); return r; }
DI uint32_t pack_f16(float lo, float hi) { uint32_t r; asm("cvt.rn.f16x2.f32 %0, %1, %2;" : "=r"(r) : "f"(hi), "f"(lo)); return r; }
DI float bf_lo(uint32_t v) { return __uint_as_float(v << 16); }
DI float bf_hi(uint32_t v) { return __uint_as_float(v & 0xFFFF0000u); }
DI uint32_t b2h(uint32_t v, float s) { return pack_f16(s * bf_lo(v), s * bf_hi(v)); }
DI void mbar_wait(uint32_t bar, uint32_t parity = 0) {
  asm volatile("{.reg .pred p, q; .reg .u32 c; mov.u32 c, 0;\n"
    "LW_%=: mbarrier.try_wait.parity.shared::cta.b64 p, [%0], %1;\n add.u32 c, c, 1; setp.lt.and.u32 q, c, 0x200000, !p;\n @q bra.uni LW_%=;}" :: "r"(bar), "r"(parity) : "memory");
}
DI void mbar_arrive(uint32_t bar, int p = 1) { asm volatile("{.reg .pred p; setp.ne.b32 p, %1, 0; @p mbarrier.arrive.shared::cta.b64 _, [%0];}" :: "r"(bar), "r"(p) : "memory"); }
DI void bar_sync(int id, int n) { asm volatile("bar.sync %0, %1;" :: "r"(id), "r"(n) : "memory"); }
DI void bar_arrive(int id, int n) { asm volatile("bar.arrive %0, %1;" :: "r"(id), "r"(n) : "memory"); }
DI __nv_bfloat162 b2(uint32_t v) { return *(__nv_bfloat162*)&v; }
DI uint32_t u2(__nv_bfloat162 v) { return *(uint32_t*)&v; }
DI uint32_t hsq(uint32_t v) { return u2(__hmul2(b2(v), b2(v))); }
DI uint32_t hsub(uint32_t a, uint32_t b) { return u2(__hsub2(b2(a), b2(b))); }
DI uint32_t hhalf(uint32_t v) { return u2(__hmul2(b2(v), __floats2bfloat162_rn(0.5f, 0.5f))); }
DI uint32_t mag2(uint32_t m, uint32_t v) { return __vmaxu2(m, v & 0x7FFF7FFFu); }
DI uint32_t hmag(uint32_t m, uint32_t v) { const __half2 r = __hmax2(*(const __half2*)&m, __habs2(*(const __half2*)&v)); return *(const uint32_t*)&r; }
DI uint32_t magr(uint32_t m) { return max(m & 0xFFFF, m >> 16); }
DI void sts128(uint32_t a, uint32_t x, uint32_t y, uint32_t z, uint32_t w) { asm volatile("st.shared.v4.u32 [%0], {%1,%2,%3,%4};" :: "r"(a), "r"(x), "r"(y), "r"(z), "r"(w) : "memory"); }
DI void sts64(uint32_t a, uint32_t x, uint32_t y) { asm volatile("st.shared.v2.u32 [%0], {%1,%2};" :: "r"(a), "r"(x), "r"(y) : "memory"); }
DI void sts32(uint32_t a, uint32_t x) { asm volatile("st.shared.u32 [%0], %1;" :: "r"(a), "r"(x) : "memory"); }
DI void sts16(uint32_t a, uint32_t x) { asm volatile("st.shared.u16 [%0], %1;" :: "r"(a), "h"((uint16_t)x) : "memory"); }
DI void lds128(uint32_t* v, uint32_t a) { asm volatile("ld.shared.v4.u32 {%0, %1, %2, %3}, [%4];" : "=r"(v[0]), "=r"(v[1]), "=r"(v[2]), "=r"(v[3]) : "r"(a) : "memory"); }
DI void lds64(uint32_t& x, uint32_t& y, uint32_t a) { asm volatile("ld.shared.v2.u32 {%0, %1}, [%2];" : "=r"(x), "=r"(y) : "r"(a) : "memory"); }
DI uint32_t lds32(uint32_t a) { uint32_t x; asm volatile("ld.shared.u32 %0, [%1];" : "=r"(x) : "r"(a) : "memory"); return x; }
DI uint32_t lds16(uint32_t a) { uint32_t x; asm volatile("ld.shared.u16 %0, [%1];" : "=r"(x) : "r"(a) : "memory"); return x; }
DI uint32_t atoms_add(uint32_t a, uint32_t v) { uint32_t r; asm volatile("atom.shared.add.u32 %0, [%1], %2;" : "=r"(r) : "r"(a), "r"(v) : "memory"); return r; }
DI void bulk_load(uint32_t dst, const void* src, uint32_t bytes, uint32_t bar) {
  asm volatile("cp.async.bulk.shared::cluster.global.mbarrier::complete_tx::bytes.L2::cache_hint [%0], [%1], %2, [%3], %4;" :: "r"(dst), "l"(src), "r"(bytes), "r"(bar), "l"(pol_first()) : "memory"); }
DI void mbar_expect(uint32_t bar, uint32_t bytes) { asm volatile("mbarrier.arrive.expect_tx.shared::cta.b64 _, [%0], %1;" :: "r"(bar), "r"(bytes) : "memory"); }
DI void mbar_init(uint32_t bar, int n) { asm volatile("mbarrier.init.shared::cta.b64 [%0], %1;" :: "r"(bar), "r"(n) : "memory"); }
DI void tma_load(uint32_t dst, uint64_t tm, int row, uint32_t bar) {
  asm volatile("cp.async.bulk.tensor.2d.shared::cluster.global.mbarrier::complete_tx::bytes.L2::cache_hint [%0], [%1, {%3, %4}], [%2], %5;" :: "r"(dst), "l"(tm), "r"(bar), "r"(0), "r"(row), "l"(pol_first()) : "memory"); }
DI void tma_store(uint64_t tm, int col, int row, uint32_t src) {
  asm volatile("cp.async.bulk.tensor.2d.global.shared::cta.bulk_group [%0, {%2, %3}], [%1];" :: "l"(tm), "r"(src), "r"(col), "r"(row) : "memory"); }
DI void bulk_commit() { asm volatile("cp.async.bulk.commit_group;" ::: "memory"); }
DI uint2 ld_poll2(const void* a) { uint2 v; asm volatile("ld.relaxed.gpu.global.v2.u32 {%0, %1}, [%2];" : "=r"(v.x), "=r"(v.y) : "l"(a) : "memory"); return v; }
DI void st_ext(uint2* a, uint32_t v, uint32_t ep) { asm volatile("st.relaxed.gpu.global.v2.u32 [%0], {%1, %2};" :: "l"(a), "r"(v), "r"(ep) : "memory"); }
DI uint32_t ext_get(const uint2* a, uint32_t ep) { uint2 v; int spin = 0; do { v = ld_poll2(a); trap_if(++spin > 4000000); } while (__any_sync(~0u, v.y != ep)); return v.x; }
DI void bulk_wait() { asm volatile("cp.async.bulk.wait_group 0;" ::: "memory"); }
DI void hint_signal(uint32_t* c) { asm volatile("red.relaxed.gpu.global.add.u32 [%0], 1;" :: "l"(c) : "memory"); }
DI void hint_wait(const uint32_t* c, uint32_t target) { uint32_t v; int spin = 0;
  do { asm volatile("ld.relaxed.gpu.global.u32 %0, [%1];" : "=r"(v) : "l"(c) : "memory"); trap_if(++spin > 4000000); } while (__any_sync(~0u, (int)(v - target) < 0)); }
DI void stsm4(uint32_t a, uint32_t x, uint32_t y, uint32_t z, uint32_t w) { asm volatile("stmatrix.sync.aligned.m8n8.x4.shared.b16 [%0], {%1,%2,%3,%4};" :: "r"(a), "r"(x), "r"(y), "r"(z), "r"(w) : "memory"); }
DI void ldsm4(uint32_t* v, uint32_t a) { asm volatile("ldmatrix.sync.aligned.m8n8.x4.shared.b16 {%0,%1,%2,%3}, [%4];" : "=r"(v[0]), "=r"(v[1]), "=r"(v[2]), "=r"(v[3]) : "r"(a) : "memory"); }
DI void ldsm4t(uint32_t* v, uint32_t a) { asm volatile("ldmatrix.sync.aligned.m8n8.x4.trans.shared.b16 {%0,%1,%2,%3}, [%4];" : "=r"(v[0]), "=r"(v[1]), "=r"(v[2]), "=r"(v[3]) : "r"(a) : "memory"); }
DI uint32_t mad16(uint32_t x, uint32_t m, uint32_t c) { uint32_t r; asm("dp2a.lo.u32.u32 %0, %1, %2, %3;" : "=r"(r) : "r"(x), "r"(m), "r"(c)); return r; }
DI bool wbad(uint32_t m, uint32_t hi) { return m > hi || (m && m < 0x3980); }

__device__ __noinline__ void slow_path(const Params& p, int wid, int lane, int node0, int nloc) {
  const uint32_t ab = sb + OFF_P2 + wid * 8704;
  for (int i = lane; i < 32 * 68; i += 32) sts32(ab + i * 4, 0);
  __syncwarp();
  const uint32_t wdv = __ldg((const uint32_t*)(p.we + 128 * 64) + lane), wxv = __ldg((const uint32_t*)p.wx + lane);
  const int nb0 = node0 + wid * 32, cntn = max(0, min(32, nloc - wid * 32));
  auto dot = [&](uint32_t hv, const uint16_t* w, int K2, float& y0, float& y1) {
#pragma unroll 4
    for (int k = 0; k < K2; k++) {
      const uint32_t hk = __shfl_sync(~0u, hv, k), wa = __ldg((const uint32_t*)(w + 2 * k * 64) + lane), wb = __ldg((const uint32_t*)(w + (2 * k + 1) * 64) + lane);
      y0 = fmaf(bf_lo(hk), bf_lo(wa), fmaf(bf_hi(hk), bf_lo(wb), y0)); y1 = fmaf(bf_lo(hk), bf_hi(wa), fmaf(bf_hi(hk), bf_hi(wb), y1));
    }
  };
  auto silu = [](float x) { return x / (1.f + __expf(-x)); };
#pragma unroll 1
  for (int base = 0; base < p.E; base += 32) {
    const int e = base + lane;
    const uint32_t dl = e < p.E ? (uint32_t)(__ldg(p.dst + e) - nb0) : 0xFFFFFFFFu;
    uint32_t mk = __ballot_sync(~0u, dl < (uint32_t)cntn);
    while (mk) {
      const int l = __ffs(mk) - 1; mk &= mk - 1;
      const int ee = base + l, n = __shfl_sync(~0u, dl, l), s = __ldg(p.src + ee);
      const uint16_t *po = p.pos + (size_t)(nb0 + n) * 3, *pp = p.pos + (size_t)s * 3;
      const uint32_t dxy = hsub(__ldg(po) | (__ldg(po + 1) << 16), __ldg(pp) | (__ldg(pp + 1) << 16)), dz = hsub(__ldg(po + 2), __ldg(pp + 2));
      const uint32_t sq = hsq(dxy); const float d2 = bf_lo(sq) + bf_hi(sq) + bf_lo(hsq(dz));
      float y0 = d2 * bf_lo(wdv), y1 = d2 * bf_hi(wdv);
      dot(__ldg((const uint32_t*)(p.h + (size_t)(nb0 + n) * 8) + lane), p.we, 32, y0, y1);
      dot(__ldg((const uint32_t*)(p.h + (size_t)s * 8) + lane), p.we + 64 * 64, 32, y0, y1);
      dot(__ldg((const uint32_t*)(p.ea + (size_t)ee * 2) + (lane & 7)), p.we + 129 * 64, 8, y0, y1);
      const uint32_t mm = pack_bf16(silu(y0), silu(y1));
      float c = bf_lo(mm) * bf_lo(wxv) + bf_hi(mm) * bf_hi(wxv);
#pragma unroll
      for (int o = 16; o; o >>= 1) c += __shfl_xor_sync(~0u, c, o);
      const uint32_t a = ab + n * 272;
      uint32_t x0, x1; lds64(x0, x1, a + lane * 8);
      sts64(a + lane * 8, __float_as_uint(__uint_as_float(x0) + bf_lo(mm)), __float_as_uint(__uint_as_float(x1) + bf_hi(mm)));
      if (lane < 3) { const float df = lane == 0 ? bf_lo(dxy) : lane == 1 ? bf_hi(dxy) : bf_lo(dz); sts32(a + 256 + lane * 4, __float_as_uint(fmaf(c, df, __uint_as_float(lds32(a + 256 + lane * 4))))); }
    }
  }
  __syncwarp();
#pragma unroll 1
  for (int n = 0; n < cntn; n++) {
    uint32_t x0, x1; lds64(x0, x1, ab + n * 272 + lane * 8);
    const uint32_t hv = __ldg((const uint32_t*)(p.h + (size_t)(nb0 + n) * 8) + lane);
    float y0 = 0.f, y1 = 0.f;
    dot(hv, p.wh, 32, y0, y1); dot(pack_bf16(__uint_as_float(x0), __uint_as_float(x1)), p.wh + 64 * 64, 32, y0, y1);
    ((uint32_t*)p.out)[(size_t)(nb0 + n) * 32 + lane] = u2(__hadd2(b2(hv), b2(pack_bf16(silu(y0), silu(y1)))));
    if (lane < 3) p.out[(size_t)p.N * 64 + (size_t)(nb0 + n) * 3 + lane] = (uint16_t)pack_bf16(bf_lo(__ldg(p.pos + (size_t)(nb0 + n) * 3 + lane)) + __uint_as_float(lds32(ab + n * 272 + 256 + lane * 4)), 0.f);
  }
}

__global__ void __launch_bounds__(NTHR, 1) egnn_kernel(const __grid_constant__ Params p, const __grid_constant__ Maps maps) {
  const uint64_t tmb = (uint64_t)&maps;
  extern __shared__ __align__(1024) unsigned char smraw[];
  const int tid = threadIdx.x, cta = blockIdx.x * CTAM % G;
  const int e0 = cta * p.EPC, n4 = max(0, min(p.EPC, p.E - e0)) >> 2;
  STAMP(0);
  if (tid == NWK) {
#pragma unroll 1
    for (int k = 0; k < NCH; k++) { const int nb = max(0, min(NWK, n4 - k * NWK)) * 16;
      mbar_init(sb + BAR_DST + k * 8, 1);
      asm volatile("fence.mbarrier_init.release.cluster;" ::: "memory");
      mbar_expect(sb + BAR_DST + k * 8, nb);
      if (nb) bulk_load(sb + OFF_DST + k * NWK * 16, (const char*)(p.dst + e0) + k * NWK * 16, nb, sb + BAR_DST + k * 8); }
  }
  const int lane = tid & 31, wid = __shfl_sync(~0u, tid >> 5, 0), w = wid & 3;
  asm volatile("{.reg .pred p; setp.eq.u32 p, %2, 384; @p cp.async.cg.shared.global [%0], [%1], 16;}" :: "r"(sb + OFF_LEN - 192 + (tid >> 1)), "l"(p.sync), "r"(tid & 415) : "memory");

  auto first_node = [&](int c) { return (int)((c * p.inv + 0xFFFFFFFFull) >> 32); };
  const int node0 = first_node(cta), nloc = min(first_node(cta + 1), p.N) - node0;
  const uint32_t ealo = (uint32_t)(uint64_t)p.ea;
  const int epad = min(e0, p.E - 1);
  if (wid >= 12) {
    const int t = tid - 384;
    auto load_h = [&](int b) { mbar_expect(sb + BAR_T + b * 8, 8192); tma_load(sb + OFF_H + b * 8192, tmb + TM_H, node0 + b * 64, sb + BAR_T + b * 8); };
    uint32_t pv[9], ev = 0;
#pragma unroll
    for (int i = 0; i < 3; i++) { const uint16_t* pp = p.pos + (size_t)(node0 + t + 128 * i) * 3;
      pv[3 * i] = pv[3 * i + 1] = pv[3 * i + 2] = 0;
      asm volatile("{.reg .pred p; setp.lt.s32 p, %4, %5;\n @p ld.global.nc.u16 %0, [%3];\n @p ld.global.nc.u16 %1, [%3+2];\n @p ld.global.nc.u16 %2, [%3+4];}"
        : "+r"(pv[3 * i]), "+r"(pv[3 * i + 1]), "+r"(pv[3 * i + 2]) : "l"(pp), "r"(t + 128 * i), "r"(p.N - node0)); }
    asm volatile("{.reg .pred p; setp.lt.u32 p, %3, 8; @p ld.global.nc.u32 %0, [%1]; @p st.global.v4.u32 [%2], {%4, %4, %4, %4};}"
      : "+r"(ev) : "l"((const uint32_t*)(p.ea + (size_t)epad * 2) + t), "l"(p.q + (size_t)(p.N + cta * PADM) * 128 + t * 16), "r"(t), "r"(0xF700F700u) : "memory");
    asm volatile("cp.async.wait_all;" ::: "memory");
    __syncwarp();
    const uint32_t e = lds32(sb + OFF_LEN + 8 + w * 16) + 1;
    {
      const uint32_t tg = (1 + e % 3) << 30, v = ((tg >> 16) + 512 + (lane & 7) * 4) * 0x10001u;
      if (t == 0) sts32(sb + OFF_MISC + 32, e);
#pragma unroll
      for (int i = 0; i < 9; i++) sts128(sb + OFF_SA + t * 16 + i * 2048, v, v + 0x10001u, v + 0x20002u, v + 0x30003u);
      bar_sync(6, NTHR);
      mbar_arrive(sb + BAR_EP, lane == 0);
#pragma unroll
      for (int i = 0; i < 17; i++) sts128(sb + OFF_SB + t * 16 + i * 2048, tg, tg, tg, tg); }
    uint32_t mp = 0;
#pragma unroll
    for (int i = 0; i < 3; i++) { sts64(sb + OFF_POS + (t + 128 * i) * 8, pv[3 * i] | (pv[3 * i + 1] << 16), pv[3 * i + 2]); mp = mag2(mag2(mp, pv[3 * i] | (pv[3 * i + 1] << 16)), pv[3 * i + 2]); }
    proxy_fence();
    __syncwarp();
    mbar_arrive(sb + BAR_PS, lane == 0);
    mbar_wait(sb + BAR_W);
    {
      uint32_t v[4], u[4]; const int r = t >> 3, c = t & 7;
      lds128(v, sb + OFF_WS + 128 + t * 16); lds128(u, sb + OFF_WS + c * 16);
      const uint32_t x = lds32(sb + OFF_WS + 2176 + lane * 4);
      sts128(sb + OFF_W3 + r * 128 + ((c ^ (r & 7)) << 4), b2h(v[0], .5f), b2h(v[1], .5f), b2h(v[2], .5f), b2h(v[3], .5f));
      const float s = ((r & 1) || r == 6) ? 0.f : .5f;
      if (t < 64) sts128(sb + OFF_WD + r * 128 + ((c ^ r) << 4), b2h(u[0], s), b2h(u[1], s), b2h(u[2], s), b2h(u[3], s));
      if (t < 32) sts32(sb + OFF_WX + (t & 3) * 32 + (t >> 2) * 4, b2h(x, 1.f));
      const uint32_t m3 = __reduce_max_sync(~0u, magr(mag2(mag2(mag2(mag2(0, v[0]), v[1]), v[2]), v[3]))), md = __reduce_max_sync(~0u, magr(mag2(mag2(mag2(mag2(0, u[0]), u[1]), u[2]), u[3])));
      if (wbad(m3, 0x4000) || wbad(md, 0x4000) || wbad(__reduce_max_sync(~0u, magr(mag2(0, x))), 0x4700) || magr(mp) >= 0x4200 || magr(mag2(0, ev)) >= 0x4380) sts32(sb + OFF_MISC + 8, 1);
    }
    if (w == 1) {
#pragma unroll 1
      for (int b = 0; b < 3; b++) { mbar_wait(sb + BAR_SRC + b * 8); if (lane == 0) load_h(b); }
    }
    bar_sync(3, 128);
    const uint32_t frag = (w * 16 + (lane & 15)) * 128 + (((lane >> 4) ^ (lane & 7)) << 4);
    uint32_t mq = 0;
#pragma unroll 1
    for (int b = 0; b < 6; b++) {
      float acc[32];
      const uint64_t da = DHI | (((sb + OFF_H) >> 4) + b * 512), db = DHI | ((sb + OFF_W) >> 4);
      const uint32_t v0 = lds16(sb + OFF_POS + b * 512 + w * 128 + lane * 2), v1 = lds16(sb + OFF_POS + 64 + b * 512 + w * 128 + lane * 2);
      mbar_wait(sb + BAR_T + b * 8);
      if (b == 0) STAMP(25);
      if (b == 5) STAMP(26);
      wg_fence();
      ss64<0>(acc, da, db); ss64<1>(acc, da + 2, db + 128); ss64<1>(acc, da + 4, db + 256); ss64<1>(acc, da + 6, db + 384);
      wg_commit();
      if (b == 0) mbar_wait(sb + BAR_AW);
      if (t == 32 && b < 3) load_h(b + 3);
      __syncwarp();
      uint32_t ff[6], fg[6];
#pragma unroll
      for (int j = 0; j < 6; j++) { ff[j] = (__byte_perm((j & 1) ? v1 : v0, 0, 0x4140) >> (3 * (j >> 1))) & 0x00070007u; fg[j] = __vsub2(0x00040004u, ff[j]);
        asm volatile("" : "+r"(ff[j]), "+r"(fg[j])); }
      wg_wait0(); fence_regs(acc);
      uint32_t o[16];
#pragma unroll
      for (int j = 0; j < 16; j++) o[j] = pack_f16(.5f * acc[2 * j], .5f * acc[2 * j + 1]);
#pragma unroll
      for (int j = 0; j < 6; j++) {
        const uint32_t m = o[j] & 0x7FFF7FFFu; mq = __vmaxu2(mq, m);
        o[j] = (__viaddmax_s16x2(m, fg[j], 0) & 0xFFF8FFF8u) | ff[j] | (o[j] & 0x80008000u); }
      if (b == 4) mbar_wait(sb + BAR_AX);
      const uint32_t qs = sb + OFF_SA + b * 8192;
#pragma unroll
      for (int j = 0; j < 4; j++) stsm4((qs + frag) ^ (j << 5), o[4 * j], o[4 * j + 1], o[4 * j + 2], o[4 * j + 3]);
      proxy_fence();
      __syncwarp();
      if (lane == 0 && b * 64 + w * 16 < nloc) tma_store(tmb + TM_Q, 0, node0 + b * 64 + w * 16, qs + w * 2048);
    }
    if (lane == 0) bulk_commit();
    { const uint32_t m = __reduce_max_sync(~0u, magr(mq)); if (lane == 0) sts32(sb + OFF_MISC + 16 + w * 4, m); }
    asm volatile("setmaxnreg.dec.sync.aligned.u32 32;");
    bulk_wait();
    bar_sync(3, 128);
    if (w == 0) {
      STAMP(18);
      uint32_t mv[4]; lds128(mv, sb + OFF_MISC + 16);
      const uint32_t mx = max(max(mv[0], mv[1]), max(mv[2], mv[3]));
      mbar_arrive(sb + BAR_QR, lane == 0);
      STAMP(19);
      if (lane == 0) {
        if (nloc > 0 && (mx >= 0x7BF0 || mx < 0x1400)) asm volatile("st.relaxed.gpu.global.u32 [%0+4], %1;" :: "l"(p.sync), "r"(e) : "memory");
        asm volatile("red.release.gpu.global.add.u32 [%0], 1;" :: "l"(p.sync) : "memory");
      }
      __syncwarp();
      uint32_t c, f; int spin = 0;
      do { asm volatile("ld.acquire.gpu.global.v2.u32 {%0, %1}, [%2];" : "=r"(c), "=r"(f) : "l"(p.sync) : "memory"); trap_if(++spin > 4000000); } while (__any_sync(~0u, (int)(c - e * G) < 0));
      if (f == e) sts32(sb + OFF_MISC + 8, 1);
      if (cta == 0 && lane == 0) asm volatile("st.relaxed.gpu.global.u32 [%0+8], %1;" :: "l"(p.sync), "r"(e) : "memory");
      STAMP(20);
      __syncwarp();
      mbar_arrive(sb + BAR_QP, lane == 0);
    }
    if (w == 2) {
      const uint32_t tg = (1 + e % 3) << 30;
      hint_wait(p.sync + 5, e * G);
      if (lane == 0) { mbar_expect(sb + BAR_HB, XPAD);
#pragma unroll 1
        for (int o = 0; o < 4; o++) bulk_load(sb + OFF_XB + o * (G * 64), (const char*)p.xb + (size_t)(cta * 4 + o) * (G * 64), G * 64, sb + BAR_HB); }
      STAMP(21);
      bar_sync(7, 384);
      sts32(sb + OFF_XB + XPAD, tg + p.N + cta * PADM);
      const uint32_t nx = __shfl_sync(~0u, lds32(sb + OFF_MISC + 8) ? 0 : lds32(sb + OFF_MISC + 4), 0);
#pragma unroll 1
      for (uint32_t k = 0; k < nx; k += 32) {
        const uint32_t i = min(k + lane, nx - 1), xr = lds32(sb + OFF_EXT + i * 4), row = (xr >> 9) & 255;
        const uint32_t v = ext_get(p.xe + (cta * G + row) * 32 + ((xr >> 17) & 31), e), x = lds32(sb + OFF_CNT + (xr & 511) * 4) + (xr >> 22) * 16;
        sts32(sb + OFF_XB + XPAD + 4 + i * 4, v); sts16(sb + OFF_TS + x, XPAD + 4 + i * 4);
        sts32(sb + OFF_TE + x * 2, mad16(v, 0x2000u, ealo - (tg >> 11) + row * p.EPC * 32));
      }
      __syncwarp();
      mbar_arrive(sb + BAR_HB, lane == 0);
    }
    if (w == 1) {
      const uint32_t nb = (p.E / G) & ~15u;
#pragma unroll 1
      for (int i = 0; i < PFN; i++) {
        if (lane == 0 && nb) asm volatile("cp.async.bulk.prefetch.L2.global [%0], %1;" :: "l"((const char*)p.ea + (size_t)(i * G + cta) * nb), "r"(nb) : "memory");
        __nanosleep(PFNS); }
    }
    if (w == 3) {
      if (lane == 0) { mbar_expect(sb + BAR_U, 16384); tma_load(sb + OFF_W, tmb + TM_WH, 0, sb + BAR_U); }
      __syncwarp();
      bar_sync(4, 416);
      if (lane == 0) tma_load(sb + OFF_W + 8192, tmb + TM_WH, 64, sb + BAR_U);
    }
    bar_sync(3, 128);
    mbar_wait(sb + BAR_U);
    uint32_t mh = 0;
#pragma unroll 1
    for (int i = t; i < 1024; i += 128) {
      uint32_t v[4]; const uint32_t r = (i >> 3) & 7, j = (i ^ r) & 7;
#pragma unroll
      for (int k = 0; k < 4; k++) v[k] = lds32(sb + OFF_W + (i >> 3) * 128 + ((((j & 4) + k) ^ r) << 4) + (j & 3) * 4);
      __syncwarp();
      if (i < 512) sts128(sb + OFF_W + i * 16, hhalf(v[0]), hhalf(v[1]), hhalf(v[2]), hhalf(v[3]));
      else { sts128(sb + OFF_W + i * 16, b2h(v[0], .5f), b2h(v[1], .5f), b2h(v[2], .5f), b2h(v[3], .5f)); mh = mag2(mag2(mag2(mag2(mh, v[0]), v[1]), v[2]), v[3]); } }
    if (wbad(__reduce_max_sync(~0u, magr(mh)), 0x4700)) sts32(sb + OFF_MISC + 12, 1);
    proxy_fence();
    __syncwarp();
    mbar_arrive(sb + BAR_WH, lane == 0);
    if (!__shfl_sync(~0u, lds32(sb + OFF_MISC + 8), 0)) {
      mbar_wait(sb + BAR_M);
      __nanosleep(DEF0);
#pragma unroll 1
      for (int i = 0; i < 12; i++) { uint32_t v[4]; const uint32_t n = lds16(sb + OFF_GP + i * 256 + (t >> 3) * 8 + 6);
        lds128(v, sb + OFF_H + n * 128 + (((n ^ t) & 7) << 4));
        if (n < nloc) ((uint4*)p.out)[(size_t)(node0 + n) * 8 + (t & 7)] = make_uint4(v[0], v[1], v[2], v[3]);
        __nanosleep(DEFNS); }
      uint32_t pa_[9];
#pragma unroll
      for (int k = 0; k < 9; k++) { const uint32_t i = t + 128 * k, n = (i * 43691u) >> 17; pa_[k] = lds16(sb + OFF_INV + n * 2) + (i - 3 * n) * 2; }
      uint16_t* po = p.out + (size_t)p.N * 64 + node0 * 3 + t;
      mbar_wait(sb + BAR_X);
#pragma unroll
      for (int k = 0; k < 9; k++) pa_[k] = lds16(sb + OFF_GP + pa_[k]);
#pragma unroll
      for (int k = 0; k < 9; k++) if (t + 128 * k < nloc * 3) po[128 * k] = pa_[k];
      asm volatile("{.reg .pred p, q; setp.ne.u32 p, 0, 0; bar.red.or.pred q, 5, 512, p;}" ::: "memory");
    }
    return;
  }

  if (tid == 320) {
    mbar_init(sb + BAR_W, 1);
    asm volatile("fence.mbarrier_init.release.cluster;" ::: "memory");
    mbar_expect(sb + BAR_W, 2 * 8192 + 2304);
    tma_load(sb + OFF_W, tmb + TM_WE, 64, sb + BAR_W); tma_load(sb + OFF_W + 8192, tmb + TM_WE, 0, sb + BAR_W);
    bulk_load(sb + OFF_WS, p.we + 128 * 64, 2176, sb + BAR_W); bulk_load(sb + OFF_WS + 2176, p.wx, 128, sb + BAR_W);
  }
  if (tid == 288) {
#pragma unroll
    for (int a = BAR_SRC; a < BAR_END; a += 8) if (a != BAR_W) mbar_init(sb + a, a == BAR_WH || a == BAR_PS || a == BAR_EP ? 4 : a == BAR_HB ? 2 : a >= BAR_M ? 12 : 1);
    asm volatile("fence.mbarrier_init.release.cluster;" ::: "memory");
    asm volatile("prefetch.tensormap [%0];" :: "l"(tmb + TM_XA)); asm volatile("prefetch.tensormap [%0];" :: "l"(tmb + TM_H));
    asm volatile("prefetch.tensormap [%0];" :: "l"(tmb + TM_XB)); asm volatile("prefetch.tensormap [%0];" :: "l"(tmb + TM_Q));
  }
  {
    if (tid < 144) { const uint32_t z = (tid >> 3) == 16 ? 0x8000u : 0u; sts128(sb + OFF_CNT + tid * 16, z, z, z, z); }
    else if (tid <= 144 + G) sts32(sb + OFF_BC + (tid - 144) * 4, ((tid - 144) & 31) * 4);
    const uint32_t sp = XPAD * 0x10001u, em = first_node(G);
    if (wid < 7) {
#pragma unroll
      for (int i = 0; i < 4; i++) sts128(sb + OFF_TS + tid * 16 + i * 3584, sp, sp, sp, sp);
    }
    static_assert(SCAP * 32 == 4 * 3584, "fill");
#pragma unroll 1
    for (int i = n4 + tid; i < 1536; i += 384) sts128(sb + OFF_DST + i * 16, em, em, em, em);
    if (tid == 321) sts128(sb + OFF_MISC, 0, 0, p.force_slow, 0);
  }
  bar_arrive(6, NTHR);
  bar_sync(0, 384);
  uint32_t ep, tag, eb0, pk[12], r0[12], r1[12], cb;
  uint2 vb[12];
  auto get_tag = [&]() { mbar_wait(sb + BAR_EP); ep = lds32(sb + OFF_MISC + 32); tag = (1 + ep % 3) << 30; eb0 = ealo - (tag >> 11); };
  if (wid == 11) {
    trap_if(sb != (uint32_t)__cvta_generic_to_shared(smraw));
#pragma unroll 1
    for (int k = 0; k < 3; k++) { const int nb = max(0, min(8192, n4 * 16 - k * 8192));
      mbar_wait(sb + BAR_DST + (k ? k + 1 : 0) * 8);
      if (lane == 0) { mbar_expect(sb + BAR_SRC + k * 8, nb);
        if (nb) bulk_load(sb + OFF_SRCI + k * 8192, (const char*)(p.src + e0) + k * 8192, nb, sb + BAR_SRC + k * 8); } }
    get_tag();
    mbar_wait(sb + BAR_PS);
    bar_sync(12, 384);
    uint32_t xm = 0;
#pragma unroll
    for (int k = 0; k < 5; k++) xm |= (lds32(sb + OFF_BC + min(lane + 32 * k, G - 1) * 4) >= (65 << 9) && lane + 32 * k < G) << k;
    auto ext_send = [&](int pl) {
      uint32_t x = xm;
      for (uint32_t m; (m = __ballot_sync(~0u, x));) {
        const uint32_t l = __ffs(m) - 1, j = l + 32 * (__ffs(__shfl_sync(~0u, x, l)) - 1);
        if (lane == l) x &= x - 1;
        const uint32_t e = min(lds16(sb + OFF_AX + j * 128 + ((4 * l + 2 * lane) & 126)), 6143u);
        if (pl) st_ext(p.xe + (j * G + cta) * 32 + lane, lds32(sb + OFF_SRCI + e * 4) + tag + (e << 16), ep);
        else { const uint32_t cn = lds32(sb + OFF_BC + j * 4) >> 9, v = cn > 96 ? 1 : lane + 64 < cn ? 512 | (lds32(sb + OFF_DST + e * 4) & 511) : 0;
          asm volatile("red.shared.xor.b32 [%0], %1;" :: "r"(sb + OFF_SA + j * 128 + ((l + lane) & 31) * 4), "r"(((v & 63) << 10) | ((v >> 6) << 26)) : "memory"); }
      }
    };
    if (__any_sync(~0u, xm)) { ext_send(0); proxy_fence(); __syncwarp(); }
    if (lane == 0) { tma_store(tmb + TM_XA, cta * 64, 0, sb + OFF_SA); bulk_commit(); mbar_arrive(sb + BAR_AI); bulk_wait(); hint_signal(p.sync + 4); mbar_arrive(sb + BAR_AW); STAMP(16); }
    __syncwarp();
    bar_sync(13, 384);
    ext_send(1);
    mbar_arrive(sb + BAR_AX, lane == 0);
    mbar_wait(sb + BAR_HA);
    __nanosleep(BDEL);
    if (lane == 0) {
#pragma unroll 1
      for (int r = 0; r < G; r += BROWS) { tma_store(tmb + TM_XB, cta * 64, r, sb + OFF_SB + r * 256); bulk_commit(); bulk_wait(); }
      hint_signal(p.sync + 5);
      STAMP(17);
    }
    __syncwarp();
  } else {
    {
      uint32_t d[4 * NCH], jj[4 * NCH], rr[4 * NCH];
      auto count = [&](int k) {
        mbar_wait(sb + BAR_DST + k * 8);
        lds128(d + 4 * k, sb + OFF_DST + (tid + NWK * k) * 16);
#pragma unroll
        for (int i = 4 * k; i < 4 * k + 4; i++) { jj[i] = d[i] * p.magic; rr[i] = atoms_add(__dp4a(jj[i], 0x04000000u, sb + OFF_BC), 0x202u); }
      };
      auto place = [&](int k) {
#pragma unroll
        for (int i = 4 * k; i < 4 * k + 4; i++) {
          const uint32_t o = __dp4a(jj[i], 0x80000000u, rr[i] & 0x807Eu);
          d[i] = (d[i] & 511) | (tag >> 16);
          asm("{.reg .pred p; setp.ge.u32 p, %1, 0x8000; @p add.u32 %0, %2, %3;}" : "+r"(d[i]) : "r"(o), "r"(tid * 4), "r"(NWK * k * 4 + (i & 3)));
          sts16(sb + OFF_SA + o, d[i]); jj[i] = __viaddmin_u32(o, o, G * 256);
        }
      };
      count(0); STAMP(1); count(1); get_tag(); place(0); count(2); place(1); count(3); place(2);
      if (wid < 4) { count(4); STAMP(15); place(3); place(4); } else place(3);
      proxy_fence();
      bar_arrive(12, 384);
      STAMP(2);
      mbar_wait(sb + BAR_AI);
      mbar_wait(sb + BAR_SRC); mbar_wait(sb + BAR_SRC + 8); mbar_wait(sb + BAR_SRC + 16);
      STAMP(12);
#pragma unroll
      for (int k = 0; k < NCH; k++) lds128(d + 4 * k, sb + OFF_SRCI + (tid + NWK * k) * 16);
      const uint32_t tb = tag + (tid << 18);
#pragma unroll
      for (int i = 0; i < 4 * NCH; i++) if (i < 4 * NCH - 4 || wid < 4) sts32(sb + OFF_SB + jj[i], d[i] + tb + ((NWK * (i >> 2) * 4 + (i & 3)) << 16));
      proxy_fence();
      bar_arrive(13, 384);
      STAMP(3);
    }
    const uint32_t rot = (lane + cta) & 31;
    cb = sb + OFF_CNT - (tag >> 14);
    {
      const uint32_t* xa = (const uint32_t*)(p.xa + (cta * G + wid) * 8) + rot;
      if (wid < 8) { const uint32_t e_ = ealo + epad * 32;
        mbar_wait(sb + BAR_AX);
#pragma unroll
        for (int i = 0; i < 7; i++) sts128(sb + OFF_TE + tid * 16 + i * 4096, e_, e_, e_, e_); }
      static_assert(SCAP * 64 == 7 * 4096, "fill");
      if (wid == 10) { hint_wait(p.sync + 4, ep * G); mbar_arrive(sb + BAR_HA, lane == 0); }
      mbar_wait(sb + BAR_HA);
      STAMP(14);
      const uint32_t tp = tag | (tag >> 16);
      uint32_t st;
#pragma unroll 1
      for (int spin = 0;; spin++) {
        st = 0;
#pragma unroll
        for (int k = 0; k < 12; k++) asm volatile("ld.relaxed.gpu.global.u32 %0, [%1];" : "=r"(pk[k]) : "l"(xa + k * 352) : "memory");
#pragma unroll
        for (int k = 0; k < 12; k++) st |= pk[k] ^ tp;
        st = __reduce_or_sync(~0u, st);
        if (!(st >> 30)) break;
        trap_if(spin > 2000000);
      }
      if (st & 0x3C00FC00u) {
#pragma unroll 1
        for (;;) {
          uint32_t x = 0, row = 0;
#pragma unroll
          for (int k = 0; k < 12; k++) { const uint32_t y = (pk[k] ^ tp) & 0x3C00FC00u; if (!x && y) { x = y; row = wid + 11 * k; pk[k] ^= y; } }
          if (!__any_sync(~0u, x)) break;
          const uint32_t n = ((x >> 10) & 63) | ((x >> 20) & 0x1C0);
          if (x >> 29) {
            const uint32_t r = atoms_add(sb + OFF_CNT + n * 4, 16), idx = atoms_add(sb + OFF_MISC + 4, 1);
            if (idx < 256) sts32(sb + OFF_EXT + idx * 4, n | (row << 9) | (lane << 17) | (min(r >> 4, 255u) << 22));
            else x = 1;
          }
          if (x && !(x >> 29)) sts32(sb + OFF_MISC + 8, 1);
          __syncwarp();
        }
      }
#pragma unroll
      for (int k = 0; k < 12; k++) { r0[k] = mad16(pk[k], 0x0004u, cb); r1[k] = mad16(pk[k], 0x0400u, cb); vb[k].x = atoms_add(r0[k], 16); vb[k].y = atoms_add(r1[k], 16); }
    }
    STAMP(4);
    if (wid >= 6) bar_arrive(11, NWK);
    if (wid < 6) {
      uint32_t ca[2], ky[2], dr[2], sq[2], ps[4];
#pragma unroll
      for (int i = 0; i < 2; i++) { ca[i] = sb + OFF_CNT + ((node0 + tid + 192 * i) & 511) * 4; lds64(ps[2 * i], ps[2 * i + 1], sb + OFF_POS + (tid + 192 * i) * 8); ps[2 * i + 1] |= (tid + 192 * i) << 16; }
      bar_sync(11, NWK);
      STAMP(5);
#pragma unroll
      for (int i = 0; i < 2; i++) ky[i] = (lds32(ca[i]) + 16) >> 5;
      if (max(ky[0], ky[1]) > 31) sts32(sb + OFF_MISC + 8, 1);
#pragma unroll
      for (int i = 0; i < 2; i++) { ky[i] = min(ky[i], 31u); dr[i] = atoms_add(sb + OFF_DH + ky[i] * 4, 1); }
      bar_sync(10, 192);
      const uint32_t hv = lds32(sb + OFF_DH + lane * 4);
      uint32_t inc = hv;
#pragma unroll
      for (int o = 1; o < 32; o <<= 1) asm("{.reg .pred p; .reg .b32 y; shfl.sync.down.b32 y|p, %0, %1, 31, -1; @p add.u32 %0, %0, y;}" : "+r"(inc) : "r"(o));
#pragma unroll
      for (int i = 0; i < 2; i++) {
        const uint32_t pos = __shfl_sync(~0u, inc - hv, ky[i]) + dr[i];
        const uint32_t ak = (uint32_t)(QCODE >> ((pos >> 5) * 4)) & 15, l = (pos >> 3) & 3;
        sq[i] = (ak >> 2) * 16 + ((QREV >> (pos >> 5) & 1) ? 3 - l : l) * 4 + (ak & 3);
        dr[i] = pos & 7;
        asm volatile("{.reg .pred p; setp.eq.u32 p, %2, 0; @p st.shared.u8 [%0], %1;}" :: "r"(sb + OFF_LEN + sq[i]), "r"(max(ky[i], 1u)), "r"(dr[i]) : "memory");
        sts64(sb + OFF_GP + sq[i] * 64 + dr[i] * 8, ps[2 * i], ps[2 * i + 1]);
        sts16(sb + OFF_INV + (tid + 192 * i) * 2, sq[i] * 64 + dr[i] * 8);
      }
      bar_sync(10, 192);
      const uint32_t ln = lds32(sb + OFF_LEN + min(lane, 11) * 4), tot = __dp4a(ln, 0x01010101u, 0u);
      inc = tot;
#pragma unroll
      for (int o = 1; o < 16; o <<= 1) asm("{.reg .pred p; .reg .b32 y; shfl.sync.up.b32 y|p, %0, %1, 0, -1; @p add.u32 %0, %0, y;}" : "+r"(inc) : "r"(o));
      if (wid == 1) sts32(sb + OFF_CNT + 2048 + lane * 4, 0);
      if (tid < 12) { sts32(sb + OFF_LEN + 64 + tid * 4, inc - tot); if (inc > SCAP - 12) sts32(sb + OFF_MISC + 8, 1); }
#pragma unroll
      for (int i = 0; i < 2; i++) sts32(ca[i], __dp4a(__shfl_sync(~0u, ln, sq[i] >> 2), 0x00010101u >> (24 - 8 * (sq[i] & 3)), __shfl_sync(~0u, inc - tot, sq[i] >> 2)) * 32 + dr[i] * 2);
    }
    bar_arrive(7, 384);
  }
  bar_sync(1, 384);
  STAMP(6);
  if (wid != 11 && !__shfl_sync(~0u, lds32(sb + OFF_MISC + 8), 0)) {
#pragma unroll
    for (int k = 0; k < 12; k++) { r0[k] = lds32(r0[k]); r1[k] = lds32(r1[k]); }
#pragma unroll
    for (int k = 0; k < 12; k++) { r0[k] += vb[k].x; r1[k] += vb[k].y; }
  } else {
#pragma unroll
    for (int k = 0; k < 12; k++) r0[k] = r1[k] = 0x8000;
  }
  auto put_ids = [&]() {
    const uint32_t id = wid * 256 + ((lane + cta) & 31) * 8;
    auto put = [&](uint32_t x, uint32_t v) { asm volatile("{.reg .pred p; setp.lt.u32 p, %0, 0x8000; @p st.shared.u16 [%0+%2], %1;}" :: "r"(x), "h"((uint16_t)v), "n"(sb + OFF_TS) : "memory"); };
#pragma unroll
    for (int k = 0; k < 12; k++) { put(pk[k] & 0xFFFF, id + k * 2816); put(pk[k] >> 16, id + k * 2816 + 4); }
  };
  STAMP(7);
  mbar_wait(sb + BAR_QR);
  asm volatile("setmaxnreg.inc.sync.aligned.u32 160;");
#pragma unroll
  for (int k = 0; k < 12; k++) asm volatile("prmt.b32 %0, %1, %2, 0x5410;" : "=r"(pk[k]) : "r"(r0[k]), "r"(r1[k]));
  uint32_t pa[8], sp[8], pq[16]; float chk = 0.f;
  {
    uint32_t hf[32], mp = 0; float a0[32], a1[32];
    const uint32_t an = sb + OFF_GP + wid * 256 + (lane & 15) * 8 + 6, n0 = lds16(an), n1 = lds16(an + 128);
#pragma unroll
    for (int j = 0; j < 8; j++) { const uint32_t nd = j < 4 ? n0 : n1; ldsm4(hf + 4 * j, (sb + OFF_H + nd * 128 + (((nd & 7) << 4) ^ (lane & 16))) ^ ((j & 3) << 5)); }
    const uint64_t db = DHI | ((sb + OFF_W + 8192) >> 4);
    wg_fence();
    rs64b<0>(a0, hf[0], hf[1], hf[2], hf[3], db); rs64b<1>(a0, hf[4], hf[5], hf[6], hf[7], db + 128); rs64b<1>(a0, hf[8], hf[9], hf[10], hf[11], db + 256); rs64b<1>(a0, hf[12], hf[13], hf[14], hf[15], db + 384);
    wg_commit();
    rs64b<0>(a1, hf[16], hf[17], hf[18], hf[19], db); rs64b<1>(a1, hf[20], hf[21], hf[22], hf[23], db + 128); rs64b<1>(a1, hf[24], hf[25], hf[26], hf[27], db + 256); rs64b<1>(a1, hf[28], hf[29], hf[30], hf[31], db + 384);
    wg_commit();
    put_ids();
    asm volatile("wgmma.wait_group.sync.aligned 1;" ::: "memory"); fence_regs(a0);
#pragma unroll
    for (int j = 0; j < 8; j++) { const uint32_t x = pack_f16(.5f * a0[4 * j], .5f * a0[4 * j + 1]), y = pack_f16(.5f * a0[4 * j + 2], .5f * a0[4 * j + 3]); mp = hmag(hmag(mp, x), y);
      asm volatile("movmatrix.sync.aligned.m8n8.trans.b16 %0, %1;" : "=r"(pa[j]) : "r"(x)); asm volatile("movmatrix.sync.aligned.m8n8.trans.b16 %0, %1;" : "=r"(sp[j]) : "r"(y)); }
    wg_wait0(); fence_regs(a1);
    bar_arrive(4, 416);
#pragma unroll
    for (int j = 0; j < 16; j++) { pq[j] = pack_f16(.5f * a1[2 * j], .5f * a1[2 * j + 1]); mp = hmag(mp, pq[j]); }
    if (magr(mp) >= 0x7000) chk = __int_as_float(0x7FC00000);
  }
  if (wid == 0) STAMP(23);
  uint32_t bad;
  {
    const uint32_t ring = sb + OFF_RING + wid * STG, p2 = sb + OFF_P2 + wid * 2048;
    uint32_t lens = __shfl_sync(~0u, lds32(sb + OFF_LEN + wid * 4), 0);
    uint32_t rem = __dp4a(lens, 0x20202020u, 0u);
    const uint32_t base = min(lds32(sb + OFF_LEN + 64 + wid * 4), SCAP);
    uint32_t a_s = sb + OFF_TS + base * 32 + (lane >> 3) * 8, a_e = sb + OFF_TE + base * 64 + (lane >> 1) * 4;
    uint32_t k0 = (uint32_t)(uint64_t)p.q + (((lane & 7) ^ ((lane >> 1) & 4)) << 4), k1 = k0 ^ 16, k2 = k0 ^ 32, k3 = k0 ^ 48, ke = ((lane ^ (lane >> 3)) & 1) << 4;
    uint32_t dst0 = ring + (lane >> 3) * 640 + (lane & 7) * 16;
    const uint32_t qhi = (uint32_t)((uint64_t)p.q >> 32), ehi = (uint32_t)((uint64_t)p.ea >> 32);
    uint32_t s0, s1, ev, to = 0, so = 12 * STG;
    auto tl_ = [&]() { lds64(s0, s1, a_s + to); asm volatile("ld.shared.u32 %0, [%1]; add.u32 %1, %1, 64;" : "=&r"(ev), "+r"(a_e) :: "memory"); to += 32; };
#define CPQ(LH, x, k, off) "dp2a." LH ".u32.u32 lo, " x ", 0x80000080, " k "; mov.b64 a, {lo, %7}; @p cp.async.cg.shared.global [%0+" #off "], [a], 16;\n"
#define CPE "or.b32 lo, %10, %11; mov.b64 a, {lo, %12}; @p cp.async.cg.shared.global [%0+512], [a], 16;\n"
#define CPA(BODY) asm volatile("{.reg .b32 lo; .reg .b64 a; .reg .pred p; setp.le.u32 p, %8, %9;\n" BODY "}" \
      :: "r"(dst0 + so), "r"(s0), "r"(s1), "r"(k0), "r"(k1), "r"(k2), "r"(k3), "r"(qhi), "r"(to), "r"(rem), "r"(ev), "r"(ke), "r"(ehi) : "memory")
#define CPQ4 CPQ("lo", "%1", "%3", 0) CPQ("hi", "%1", "%4", 128) CPQ("lo", "%2", "%5", 256) CPQ("hi", "%2", "%6", 384) "cp.async.commit_group;"
    auto issue = [&]() { CPA(CPE CPQ4); so = so == (NST - 1) * 12 * STG ? 0 : so + 12 * STG; };
    const int g = lane >> 2, qd = lane & 3;
    const uint32_t sw = ((lane >> 4) ^ (lane & 7)) << 4, fr = (lane & 15) * 128 + sw;
    uint32_t qa0 = ring + (g & 3) * 640 + qd * 128 + sw, qa1 = qa0 ^ 32, qa2 = qa0 ^ 64, qa3 = qa0 ^ 96;
    uint32_t eadr = ring + 512 + (g & 3) * 640 + qd * 32 + ((((lane >> 4) ^ g) & 1) << 4);
    uint32_t oh0 = g == 2 * qd ? 0x3C00u : g == 2 * qd + 1 ? 0x3C000000u : 0u, oh1 = oh0;
    uint32_t a_g = sb + OFF_GP + wid * 256 + lane * 2;
    uint32_t a_n = sb + OFF_GP + wid * 256 + (lane & 15) * 8 + 6;
    uint32_t a_p = ((lane & 8) ? p2 : sb + OFF_WD) + (lane & 7) * 128 + ((((lane >> 4) ^ lane) & 7) << 4);
    uint32_t a_w = sb + OFF_W3 + fr;
    asm volatile("shfl.sync.idx.b32 %0, %0, %1, 31, -1;" : "+r"(oh1) : "r"(lane));
    uint32_t w3[16], wv[8], bp[16], sum[8], Y[16], M[16], own, ownp, dpk; uint16_t tl[16], th[16];
    float pacc = 0.f;
    auto wload = [&]() {
#pragma unroll
      for (int j = 0; j < 4; j++) ldsm4t(w3 + 4 * j, a_w ^ (j << 5));
      lds128(wv, sb + OFF_WX + (a_g & 6) * 16); lds128(wv + 4, sb + OFF_WX + 16 + (a_g & 6) * 16);
    };
    auto hload = [&](uint32_t (&hf)[16], uint32_t nd) {
      const uint32_t hrow = sb + OFF_H + nd * 128 + (((nd & 7) << 4) ^ ((a_g >> 1) & 16));
#pragma unroll
      for (int j = 0; j < 4; j++) ldsm4(hf + 4 * j, hrow ^ (j << 5));
      return hrow;
    };
    auto bload = [&](uint32_t o) {
#pragma unroll
      for (int j = 0; j < 4; j++) ldsm4t(bp + 4 * j, (a_p ^ (j << 5)) + o);
    };
    { uint32_t wd[8]; const uint32_t a = sb + OFF_WD + (lane & 7) * 128 + ((((lane >> 3) ^ lane) & 7) << 4);
      ldsm4t(wd, a); ldsm4t(wd + 4, a ^ 64);
#pragma unroll
      for (int j = 0; j < 8; j++) { bp[2 * j] = wd[j]; bp[2 * j + 1] = pa[j]; } }
    own = lds16(a_g) * 0x10001u;
    wload();
    if (__shfl_sync(~0u, lds32(sb + OFF_MISC + 8), 0)) rem = 0;
    auto resolve = [&](auto NBK, uint32_t o) {
      constexpr int NB = decltype(NBK)::value;
      uint32_t id[NB], c0[NB], c1[NB]; const uint32_t a = base * 32 + o + lane * 4;
#pragma unroll
      for (int i = 0; i < NB; i++) { id[i] = lds32(sb + OFF_TS + a + i * 128); if (o + lane * 4 + i * 128 >= rem) id[i] = XPAD * 0x10001u; }
      uint32_t st = 0;
#pragma unroll
      for (int i = 0; i < NB; i++) { c0[i] = lds32(sb + OFF_XB + (id[i] & 0xFFFF)); c1[i] = lds32(sb + OFF_XB + (id[i] >> 16)); }
#pragma unroll
      for (int i = 0; i < NB; i++) st |= (c0[i] ^ tag) | (c1[i] ^ tag);
      for (int spin = 0; __any_sync(~0u, st >> 30); spin++) {
        st = 0; trap_if(spin > 2000000);
#pragma unroll
        for (int i = 0; i < NB; i++) {
          asm volatile("{.reg .pred p, q; setp.lt.u32 p, %4, %6; setp.lt.u32 q, %5, %6; @p ld.relaxed.gpu.global.u32 %0, [%2]; @q ld.relaxed.gpu.global.u32 %1, [%3];}"
            : "+r"(c0[i]), "+r"(c1[i]) : "l"((const char*)p.xb + cta * XPAD + (id[i] & 0xFFFF)), "l"((const char*)p.xb + cta * XPAD + (id[i] >> 16)), "r"(id[i] & 0xFFFF), "r"(id[i] >> 16), "n"(XPAD) : "memory");
          st |= (c0[i] ^ tag) | (c1[i] ^ tag); }
      }
#pragma unroll
      for (int i = 0; i < NB; i++) { const uint32_t j0 = (id[i] >> 8) & 255, j1 = id[i] >> 24;
        asm volatile("{.reg .pred p, q, r; setp.lt.u32 p, %5, %9; setp.lt.u32 q, %6, %9; setp.lt.u32 r, %7, %8;\n"
          "@p st.shared.u32 [%0], %2; @q st.shared.u32 [%0+4], %3; @r st.shared.u32 [%1], %4;}"
          :: "r"(sb + OFF_TE + 2 * a + i * 256), "r"(sb + OFF_TS + a + i * 128), "r"(mad16(c0[i], 0x2000u, eb0 + j0 * p.EPC * 32)), "r"(mad16(c1[i], 0x2000u, eb0 + j1 * p.EPC * 32)),
             "r"(__byte_perm(c0[i], c1[i], 0x5410)), "r"(j0), "r"(j1), "r"(o + lane * 4 + i * 128), "r"(rem), "n"(G) : "memory"); }
    };
    bar_sync(2, 384);
    if (wid == 0) STAMP(27);
    mbar_wait(sb + BAR_HB);
    if (wid == 0) STAMP(22);
#pragma unroll 1
    for (uint32_t o = 0, go = 0; go < 32 * NST; o += 128 * RNB) {
      if (o < rem) { resolve(IC<RNB>(), o);
        asm volatile("{.reg .pred p; mbarrier.test_wait.parity.shared::cta.b64 p, [%1], 0; vote.sync.all.pred p, p, -1; selp.u32 %0, %2, 0, p;}" : "=r"(go) : "r"(sb + BAR_QP), "n"(32 * NST - 32) : "memory"); }
      else { bar_sync(8, 384); mbar_wait(sb + BAR_QP); go = 32 * NST; if (wid == 0) STAMP(24); }
      __syncwarp();
#pragma unroll 1
      while (to < go) { tl_(); issue(); if (to == 32) STAMP(13); }
    }
    bad = __shfl_sync(~0u, lds32(sb + OFF_MISC + 8), 0);
   if (!bad) {
#pragma unroll
    for (int j = 0; j < 4; j++) stsm4((p2 + fr) ^ (j << 5), pq[4 * j], pq[4 * j + 1], pq[4 * j + 2], pq[4 * j + 3]);
    auto body = [&](auto MODE) {
      constexpr int mode = decltype(MODE)::value;
      uint32_t T[16], ef[4], q0, q1, x0, x1, x2; float e0_, e1_, cs[4];
      auto mu = [&](int j) {
#pragma unroll
        for (int i = 2 * j; i < 2 * j + 2; i++) asm volatile("{.reg .b16 l, h; mov.b32 {l, h}, %2; tanh.approx.f16 %0, l; tanh.approx.f16 %1, h;}" : "=h"(tl[i]), "=h"(th[i]) : "r"(Y[i])); };
      auto fi = [&](int j) {
#pragma unroll
        for (int i = 2 * j; i < 2 * j + 2; i++) asm volatile("{.reg .b32 t; mov.b32 t, {%2, %3}; fma.rn.f16x2 %0, %1, t, %1;}" : "=r"(M[i]) : "r"(Y[i]), "h"(tl[i]), "h"(th[i])); };
      auto ad = [&](int j) { asm volatile("add.rn.f16x2 %0, %0, %1; add.rn.f16x2 %0, %0, %2;" : "+r"(sum[j]) : "r"(M[2 * j]), "r"(M[2 * j + 1])); };
      auto he = [&](int j) { asm volatile("mma.sync.aligned.m16n8k16.row.col.f16.f16.f16.f16 {%0,%1}, {%2,%3,%4,%5}, {%6,%7}, {%0,%1};" : "+r"(T[2 * j]), "+r"(T[2 * j + 1]) : "r"(ef[0]), "r"(ef[1]), "r"(ef[2]), "r"(ef[3]), "r"(w3[2 * j]), "r"(w3[2 * j + 1])); };
      auto hs = [&](int j) { asm volatile("mma.sync.aligned.m16n8k16.row.col.f16.f16.f16.f16 {%0,%1}, {%2,%3,%4,%5}, {%6,%7}, {%8,%9};" : "=r"(Y[2 * j]), "=r"(Y[2 * j + 1]) : "r"(q0), "r"(q1), "r"(oh0), "r"(oh1), "r"(bp[2 * j]), "r"(bp[2 * j + 1]), "r"(T[2 * j]), "r"(T[2 * j + 1])); };
      auto hc = [&](int j) {
        if (j) asm volatile("mma.sync.aligned.m16n8k16.row.col.f32.f16.f16.f32 {%0,%1,%2,%3}, {%4,%5,%6,%7}, {%8,%9}, {%0,%1,%2,%3};" : "+f"(cs[0]), "+f"(cs[1]), "+f"(cs[2]), "+f"(cs[3]) : "r"(M[4 * j]), "r"(M[4 * j + 1]), "r"(M[4 * j + 2]), "r"(M[4 * j + 3]), "r"(wv[2 * j]), "r"(wv[2 * j + 1]));
        else asm volatile("mma.sync.aligned.m16n8k16.row.col.f32.f16.f16.f32 {%0,%1,%2,%3}, {%4,%5,%6,%7}, {%8,%9}, {%10,%10,%10,%10};" : "=f"(cs[0]), "=f"(cs[1]), "=f"(cs[2]), "=f"(cs[3]) : "r"(M[0]), "r"(M[1]), "r"(M[2]), "r"(M[3]), "r"(wv[0]), "r"(wv[1]), "f"(0.f)); };
      auto cv = [&](int i) { asm volatile("{.reg .b32 a, b; shl.b32 a, %0, 16; and.b32 b, %0, 0xFFFF0000; cvt.rn.f16x2.f32 %0, b, a;}" : "+r"(ef[i])); };
      auto un = [&]() { asm volatile("shl.b32 %0, %2, 16; and.b32 %1, %2, 0xFFFF0000;" : "=&f"(e0_), "=&f"(e1_) : "r"(dpk)); };
      auto ex0 = [&]() { asm volatile("prmt.b32 %0, %3, %4, 0x6420; prmt.b32 %1, %5, %6, 0x6420; prmt.b32 %2, %7, %8, 0x6420;" : "=&r"(x0), "=&r"(x1), "=&r"(x2) : "r"(T[0]), "r"(T[1]), "r"(T[2]), "r"(T[3]), "r"(T[4]), "r"(T[5])); };
      auto ex1 = [&]() { asm volatile("{.reg .b32 a, b; shl.b32 a, %2, 3; shl.b32 b, %3, 6; lop3.b32 a, %1, a, 0x38383838, 0xD8; lop3.b32 a, a, b, 0xC0C0C0C0, 0xD8; sub.rn.bf16x2 %0, %4, a;}" : "=r"(dpk) : "r"(x0), "r"(x1), "r"(x2), "r"(own)); };
      auto ex2 = [&]() { asm volatile("{.reg .b32 a, b, d, u; .reg .b16 l, h; shl.b32 a, %2, 16; and.b32 b, %2, 0xFFFF0000; cvt.rn.f16x2.f32 d, b, a; mul.rn.f16x2 %0, d, d; mov.b32 {l, h}, d; mov.b32 u, {h, h}; mul.rn.f16x2 %1, u, u;}" : "=&r"(q0), "=&r"(q1) : "r"(dpk)); };
      auto pf = [&]() { asm volatile("fma.rn.f32 %0, %1, %2, %0; fma.rn.f32 %0, %3, %4, %0;" : "+f"(pacc) : "f"(cs[0]), "f"(e0_), "f"(cs[2]), "f"(e1_)); };
      if (mode == 2) {
        hc(0); mu(3); fi(2); un(); ad(0); ad(1); mu(4); fi(3); hc(1); mu(5); fi(4); ad(2); mu(6); fi(5); ad(3); hc(2); mu(7); fi(6); fi(7); ad(4); ad(5); hc(3); ad(6); ad(7); pf();
        return;
      }
      asm volatile("cp.async.wait_group %0;" :: "n"(NST - 1) : "memory");
      __syncwarp();
      if (mode == 1) STAMP(8);
      ldsm4(ef, eadr + so); ldsm4(T, qa0 + so); ldsm4(T + 4, qa1 + so); ldsm4(T + 8, qa2 + so); ldsm4(T + 12, qa3 + so);
      tl_();
      if (mode == 1) {
        issue();
        cv(0); cv(1); cv(2); cv(3); ex0(); ex1(); ex2();
#pragma unroll
        for (int j = 0; j < 8; j++) { he(j); hs(j); }
        mu(0); mu(1); fi(0); mu(2); fi(1);
        return;
      }
      hc(0); mu(3); fi(2); un(); ad(0); ad(1);
      mu(4); fi(3); cv(0); cv(1); cv(2); cv(3); ex0(); ex1();
      he(0); he(1); hc(1); mu(5); fi(4); ex2(); ad(2);
      hs(0); he(2); mu(6); fi(5); issue(); ad(3);
      hs(1); he(3); hc(2); mu(7); fi(6);
      hs(2); hs(3); he(4); he(5); mu(0); fi(7); ad(4); ad(5);
      hc(3); hs(4); he(6); he(7); mu(1); fi(0); ad(6);
      hs(5); hs(6); hs(7); mu(2); fi(1); ad(7); pf();
    };
#pragma unroll
    for (int j = 0; j < 8; j++) sum[j] = 0;
    body(IC<1>());
    int cnt = (lens & 255) - 1;
    auto flush = [&]() {
      asm volatile("{.reg .pred p; setp.ne.u32 p, %2, 6; @p st.shared.u16 [%0+-64], %1;}" :: "r"(a_g), "h"((uint16_t)pack_bf16(bf_hi(ownp) + pacc, 0.f)), "r"(a_g & 6) : "memory");
      chk = fmaf(pacc, 0.f, chk); pacc = 0.f; };
    constexpr uint64_t b1 = DHI | ((sb + OFF_W) >> 4), b2_ = b1 + 512;
    auto mma_h = [&](float (&acc)[32], uint32_t (&hf)[16]) {
      rs64b<0>(acc, hf[0], hf[1], hf[2], hf[3], b1); rs64b<1>(acc, hf[4], hf[5], hf[6], hf[7], b1 + 128); rs64b<1>(acc, hf[8], hf[9], hf[10], hf[11], b1 + 256); rs64b<1>(acc, hf[12], hf[13], hf[14], hf[15], b1 + 384); };
    auto mma_m = [&](float (&acc)[32]) {
      rs64h<1>(acc, sp[0], sum[0], sp[1], sum[1], b2_); rs64h<1>(acc, sp[2], sum[2], sp[3], sum[3], b2_ + 128); rs64h<1>(acc, sp[4], sum[4], sp[5], sum[5], b2_ + 256); rs64h<1>(acc, sp[6], sum[6], sp[7], sum[7], b2_ + 384);
      wg_commit(); wg_wait0(); fence_regs(acc);
      STAMP(10);
      chk = fmaf(acc[0], 0.f, fmaf(acc[2], 0.f, chk)); };
    auto roff = [&](uint32_t nd, int r) { return __shfl_sync(~0u, nd, ((a_g >> 3) & 7) + 8 * r) * 128 + (a_g & 6) * 8; };
    auto radr = [&](uint32_t o, int k) { return sb + OFF_H + (o ^ ((o >> 3) & 0x70) ^ ((k >> 1) << 6)); };
    auto fin = [&](float (&acc)[32], uint32_t* x, int k) {
#pragma unroll
      for (int i = 0; i < 4; i++) { const int c = 16 * (k >> 1) + 4 * i + 2 * (k & 1); x[i] = u2(__hadd2(b2(x[i]), b2(pack_bf16(silu_h(acc[c]), silu_h(acc[c + 1]))))); } };
#pragma unroll 1
    for (int t = 0;; t++) {
#pragma unroll 1
      for (; cnt > 0; cnt--) { body(IC<0>());
      }
      if (!(t & 1)) {
        ownp = own; a_g += 64;
        if (t == 6) break;
        own = lds16(a_g) * 0x10001u;
        if (t == 0) {
#pragma unroll
          for (int j = 0; j < 8; j++) bp[2 * j + 1] = sp[j];
        } else bload((a_g & 16) ? (t & 4) * 256 : 0);
        lens >>= 8; cnt = 1;
        continue;
      }
      cnt = (lens & 255) - 1;
      flush();
      if (t == 3) {
        uint32_t hf[16]; float acc[32];
        const uint32_t nd = lds16(a_n), o[2] = {roff(nd, 0), roff(nd, 1)};
        hload(hf, nd);
        mbar_wait(sb + BAR_WH);
        wg_fence();
        mma_h(acc, hf); mma_m(acc);
#pragma unroll
        for (int k = 0; k < 4; k++) lds128(hf + 4 * k, radr(o[k & 1], k));
#pragma unroll
        for (int k = 0; k < 4; k++) { fin(acc, hf + 4 * k, k); sts128(radr(o[k & 1], k), hf[4 * k], hf[4 * k + 1], hf[4 * k + 2], hf[4 * k + 3]); }
        __syncwarp();
        mbar_arrive(sb + BAR_M, (a_g & 62) == 0);
        wload();
      }
#pragma unroll
      for (int j = 0; j < 8; j++) { sp[j] = sum[j]; asm volatile("mov.b32 %0, 0;" : "=r"(sum[j])); }
    }
    {
      uint32_t hf[16], v[16]; float acc[32];
      const uint32_t nd = lds16(a_n + 128), o[2] = {roff(nd, 0), roff(nd, 1)};
      hload(hf, nd);
#pragma unroll
      for (int k = 0; k < 4; k++) lds128(v + 4 * k, radr(o[k & 1], k));
      wg_fence(); mma_h(acc, hf); wg_commit();
      body(IC<2>());
      STAMP(9);
      flush();
      __syncwarp();
      mbar_arrive(sb + BAR_X, lane == 0);
      wg_fence();
      mma_m(acc);
#pragma unroll
      for (int k = 0; k < 4; k++) { fin(acc, v + 4 * k, k);
        asm volatile("{.reg .pred p; setp.lt.u32 p, %5, %6; @p st.global.v4.b32 [%0], {%1,%2,%3,%4};}" :: "l"((const char*)p.out + (size_t)node0 * 128 + o[k & 1] + (k >> 1) * 64), "r"(v[4 * k]), "r"(v[4 * k + 1]), "r"(v[4 * k + 2]), "r"(v[4 * k + 3]), "r"(o[k & 1]), "r"(nloc * 128) : "memory"); }
    }
    asm volatile("{.reg .pred p, q; setp.neu.f32 p, %1, 0f00000000; setp.ne.or.u32 p, %2, 0, p; bar.red.or.pred q, 5, 512, p; selp.u32 %0, 1, 0, q;}" : "=r"(bad) : "f"(chk), "r"(lds32(sb + OFF_MISC + 12)) : "memory");
    STAMP(11);
   } else { asm volatile("cp.async.wait_all;" ::: "memory"); bar_sync(5, 384); }
  }
  if (bad) slow_path(p, wid, lane, node0, nloc);
}

}

typedef CUresult (*EncodeFn)(CUtensorMap*, CUtensorMapDataType, cuuint32_t, void*, const cuuint64_t*, const cuuint64_t*, const cuuint32_t*, const cuuint32_t*,
                             CUtensorMapInterleave, CUtensorMapSwizzle, CUtensorMapL2promotion, CUtensorMapFloatOOBfill);

extern "C" void kernel_launch(void* const* d_in, const int* in_sizes, int n_in, void* d_out, int out_size) {
  Params p; Maps maps;
  p.h = (const uint4*)d_in[0]; p.pos = (const uint16_t*)d_in[1]; p.ea = (const uint4*)d_in[2];
  p.src = (const int*)d_in[3]; p.dst = (const int*)d_in[4];
  p.we = (const uint16_t*)d_in[5]; p.wx = (const uint16_t*)d_in[6]; p.wh = (const uint16_t*)d_in[7];
  p.out = (uint16_t*)d_out;
  p.N = in_sizes[0] / 64; p.E = in_sizes[3];
  p.EPC = ((p.E + G * 4 - 1) / (G * 4)) * 4;
  p.magic = (uint32_t)(((uint64_t)G << 24) / (uint64_t)p.N);
  p.inv = (1ull << 56) / p.magic;
  const uint64_t ea0 = (uint64_t)d_in[2], ea1 = ea0 + (uint64_t)p.E * 32 - 1;
  p.force_slow = ((ea0 >> 32) != (ea1 >> 32)) || (ea0 & 31) || (p.E & 3);
  void* qp = nullptr;
  cudaGetSymbolAddress(&qp, g_q);
  p.q = (char*)qp;
  if (((uint64_t)p.q >> 32) != (((uint64_t)p.q + QBYTES) >> 32)) p.q += QBYTES;
  cudaGetSymbolAddress((void**)&p.sync, g_sync); cudaGetSymbolAddress((void**)&p.xe, g_xe);
  cudaGetSymbolAddress((void**)&p.xa, g_xa); cudaGetSymbolAddress((void**)&p.xb, g_xb);
  const int df[10] = {18, 250, 900, 500, 250, 59, 0xbba};
  for (int i = 0; i < 10; i++) p.tune[i] = df[i];
  p.qcode = 0x54970832b1a6ull;
  void* fn = nullptr; cudaDriverEntryPointQueryResult qr;
  cudaGetDriverEntryPoint("cuTensorMapEncodeTiled", &fn, cudaEnableDefault, &qr);
  auto mk = [&](CUtensorMap* tm, void* base, int rows, int box = 64) {
    const cuuint64_t dim[2] = {64, (cuuint64_t)rows}, str[1] = {128}; const cuuint32_t bx[2] = {64, (cuuint32_t)box}, es[2] = {1, 1};
    ((EncodeFn)fn)(tm, CU_TENSOR_MAP_DATA_TYPE_BFLOAT16, 2, base, dim, str, bx, es, CU_TENSOR_MAP_INTERLEAVE_NONE, CU_TENSOR_MAP_SWIZZLE_128B,
                   CU_TENSOR_MAP_L2_PROMOTION_NONE, CU_TENSOR_MAP_FLOAT_OOB_FILL_NONE);
  };
  mk(&maps.m[TM_H / 128], d_in[0], p.N); mk(&maps.m[TM_WE / 128], d_in[5], 145); mk(&maps.m[TM_WH / 128], d_in[7], 128); mk(&maps.m[TM_Q / 128], p.q, p.N, 16);
  for (int k = 0; k < 2; k++) {
    void* xp = (void*)(k ? p.xb : p.xa);
    const cuuint64_t dim[2] = {(cuuint64_t)G * 64, (cuuint64_t)G}, str[1] = {(cuuint64_t)G * (128 << k)}; const cuuint32_t bx[2] = {64, (cuuint32_t)(k ? BROWS : G)}, es[2] = {1, 1};
    ((EncodeFn)fn)(&maps.m[TM_XA / 128 + k], k ? CU_TENSOR_MAP_DATA_TYPE_UINT32 : CU_TENSOR_MAP_DATA_TYPE_UINT16, 2, xp, dim, str, bx, es, CU_TENSOR_MAP_INTERLEAVE_NONE,
                   CU_TENSOR_MAP_SWIZZLE_NONE, CU_TENSOR_MAP_L2_PROMOTION_NONE, CU_TENSOR_MAP_FLOAT_OOB_FILL_NONE);
  }
  cudaFuncSetAttribute(egnn_kernel, cudaFuncAttributeMaxDynamicSharedMemorySize, SMEM);
  egnn_kernel<<<G, NTHR, SMEM>>>(p, maps);
}
```

```cpp
#include <cuda_runtime.h>
#include <cuda_bf16.h>
#include <cuda_fp16.h>
#include <cuda.h>
#include <stdint.h>
#pragma nv_diag_suppress 549

#define PFN p.tune[0]
#define PFNS p.tune[1]
#define BDEL p.tune[2]
#define DEF0 p.tune[3]
#define DEFNS p.tune[4]
#define CTAM p.ctam
#define QREV p.tune[6]
#define QCODE p.qcode
namespace {

constexpr int G = 132;
constexpr int NTHR = 512, NWK = 352, NCH = 5;
constexpr int NST = 3, STG = 2560;
constexpr int BROWS = 44, RNB = 2, PADM = 33;
constexpr int SCAP = 448;

constexpr int OFF_H = 0;
constexpr int OFF_W = 49152;
constexpr int OFF_WD = OFF_W + 16384;
constexpr int OFF_W3 = OFF_WD + 1024;
constexpr int OFF_P2 = OFF_W3 + 2048;
constexpr int OFF_RING = OFF_P2 + 24576;
constexpr int OFF_TE = OFF_RING + 12 * NST * STG;
constexpr int OFF_TS = OFF_TE + SCAP * 64;
constexpr int OFF_INV = OFF_TS - 768;
constexpr int OFF_GP = OFF_TS + SCAP * 32;
constexpr int OFF_WX = OFF_GP + 3072;
constexpr int OFF_LEN = OFF_WX + 128;
constexpr int OFF_MISC = OFF_LEN + 128;
constexpr int OFF_BAR = OFF_MISC + 48;
constexpr int SMEM = OFF_BAR + 256;
static_assert(SMEM <= 232448, "smem");
constexpr uint32_t sb = 1024;
constexpr int OFF_SRCI = OFF_TE;
constexpr int OFF_SB = OFF_RING, OFF_SA = OFF_SB + 34816, OFF_AX = OFF_SA + 32768, OFF_DST = OFF_H + 24576;
constexpr int OFF_WS = OFF_AX + 17408;
constexpr int OFF_BC = OFF_WS + 2304;
constexpr int OFF_CNT = OFF_P2;
constexpr int OFF_DH = OFF_CNT + 2176;
constexpr int OFF_POS = OFF_DH + 128;
constexpr int OFF_EXT = OFF_POS + 3072;
constexpr int OFF_XB = OFF_EXT + 1024, XPAD = G * 256;
static_assert(OFF_XB + XPAD + 1028 <= OFF_RING + 12 * STG && OFF_XB % 128 == 0 && OFF_BC + 544 <= OFF_TE && OFF_P2 % 1024 == 0 && OFF_SA % 1024 == 0 && SCAP * 64 >= 24576, "staging");
constexpr int BAR_DST = OFF_BAR, BAR_SRC = BAR_DST + 40, BAR_T = BAR_SRC + 24, BAR_W = BAR_T + 48, BAR_PS = BAR_W + 8, BAR_AW = BAR_PS + 8,
              BAR_QP = BAR_AW + 8, BAR_QR = BAR_QP + 8, BAR_HA = BAR_QR + 8, BAR_EP = BAR_HA + 8, BAR_AX = BAR_EP + 8, BAR_AI = BAR_AX + 8, BAR_HB = BAR_AI + 8, BAR_U = BAR_HB + 8, BAR_WH = BAR_U + 8, BAR_M = BAR_WH + 8, BAR_X = BAR_M + 8, BAR_END = BAR_X + 8;
static_assert(BAR_END <= OFF_BAR + 256, "barriers");
constexpr uint32_t QBYTES = 8u << 20;

__device__ __align__(256) uint4 g_xa[G * G * 8];
__device__ __align__(256) uint4 g_xb[G * G * 16];
__device__ __align__(256) uint2 g_xe[G * G * 32];
__device__ __align__(256) uint4 g_q[2 * QBYTES / 16];
__device__ __align__(256) uint32_t g_sync[8];
#define STAMP(k)

struct Maps { CUtensorMap m[6]; };
constexpr int TM_H = 0, TM_WE = 128, TM_WH = 256, TM_Q = 384, TM_XA = 512, TM_XB = 640;
struct Params {
  const int* dst; uint32_t* sync; int E, EPC, N, ctam; unsigned long long inv; uint32_t magic; int force_slow;
  const int* src; const uint16_t* pos; const uint4* ea; const uint16_t* we; const uint16_t* wx; char* q;
  const uint4* xa; const uint4* xb; uint2* xe; uint16_t* out; const uint4* h; const uint16_t* wh;
  int tune[10]; unsigned long long qcode;
};
template<int V> struct IC { static constexpr int value = V; };

#define R32(d) "+f"(d[0]),"+f"(d[1]),"+f"(d[2]),"+f"(d[3]),"+f"(d[4]),"+f"(d[5]),"+f"(d[6]),"+f"(d[7]),"+f"(d[8]),"+f"(d[9]),"+f"(d[10]),"+f"(d[11]),"+f"(d[12]),"+f"(d[13]),"+f"(d[14]),"+f"(d[15]),"+f"(d[16]),"+f"(d[17]),"+f"(d[18]),"+f"(d[19]),"+f"(d[20]),"+f"(d[21]),"+f"(d[22]),"+f"(d[23]),"+f"(d[24]),"+f"(d[25]),"+f"(d[26]),"+f"(d[27]),"+f"(d[28]),"+f"(d[29]),"+f"(d[30]),"+f"(d[31])
#define S32 "{%0,%1,%2,%3,%4,%5,%6,%7,%8,%9,%10,%11,%12,%13,%14,%15,%16,%17,%18,%19,%20,%21,%22,%23,%24,%25,%26,%27,%28,%29,%30,%31}"
#define DI __device__ __forceinline__

constexpr uint64_t DHI = ((uint64_t)(1024 >> 4) << 32) | (1ull << 62);
template<int SD> DI void rs64b(float (&d)[32], uint32_t a0, uint32_t a1, uint32_t a2, uint32_t a3, uint64_t db) {
  asm volatile("wgmma.mma_async.sync.aligned.m64n64k16.f32.bf16.bf16 " S32 ", {%32,%33,%34,%35}, %36, %37, 1, 1, 1;" : R32(d) : "r"(a0), "r"(a1), "r"(a2), "r"(a3), "l"(db), "n"(SD)); }
template<int SD> DI void rs64h(float (&d)[32], uint32_t a0, uint32_t a1, uint32_t a2, uint32_t a3, uint64_t db) {
  asm volatile("wgmma.mma_async.sync.aligned.m64n64k16.f32.f16.f16 " S32 ", {%32,%33,%34,%35}, %36, %37, 1, 1, 1;" : R32(d) : "r"(a0), "r"(a1), "r"(a2), "r"(a3), "l"(db), "n"(SD)); }
template<int SD> DI void ss64(float (&d)[32], uint64_t da, uint64_t db) {
  asm volatile("wgmma.mma_async.sync.aligned.m64n64k16.f32.bf16.bf16 " S32 ", %32, %33, %34, 1, 1, 0, 1;" : R32(d) : "l"(da), "l"(db), "n"(SD)); }
DI void trap_if(bool c) { asm volatile("{.reg .pred p; setp.eq.u32 p, %0, 0; @p bra.uni LT_%=; trap; LT_%=:}" :: "r"((uint32_t)c)); }
DI void wg_fence() { asm volatile("wgmma.fence.sync.aligned;" ::: "memory"); }
DI void wg_commit() { asm volatile("wgmma.commit_group.sync.aligned;" ::: "memory"); }
DI void wg_wait0() { asm volatile("wgmma.wait_group.sync.aligned 0;" ::: "memory"); }
DI void fence_regs(float (&d)[32]) { asm volatile("" : R32(d) :: "memory"); }
DI void proxy_fence() { asm volatile("fence.proxy.async.shared::cta;" ::: "memory"); }
DI uint64_t pol_first() { uint64_t r; asm("createpolicy.fractional.L2::evict_first.b64 %0, 1.0;" : "=l"(r)); return r; }
DI float tanh_ap(float x) { float y; asm("tanh.approx.f32 %0, %1;" : "=f"(y) : "f"(x)); return y; }
DI float silu_h(float y) { return fmaf(y, tanh_ap(y), y); }
DI uint32_t pack_bf16(float lo, float hi) { uint32_t r; asm("cvt.rn.bf16x2.f32 %0, %1, %2;" : "=r"(r) : "f"(hi), "f"(lo)); return r; }
DI uint32_t pack_f16(float lo, float hi) { uint32_t r; asm("cvt.rn.f16x2.f32 %0, %1, %2;" : "=r"(r) : "f"(hi), "f"(lo)); return r; }
DI float bf_lo(uint32_t v) { return __uint_as_float(v << 16); }
DI float bf_hi(uint32_t v) { return __uint_as_float(v & 0xFFFF0000u); }
DI uint32_t b2h(uint32_t v, float s) { return pack_f16(s * bf_lo(v), s * bf_hi(v)); }
DI void mbar_wait(uint32_t bar, uint32_t parity = 0) {
  asm volatile("{.reg .pred p, q; .reg .u32 c; mov.u32 c, 0;\n"
    "LW_%=: mbarrier.try_wait.parity.shared::cta.b64 p, [%0], %1;\n add.u32 c, c, 1; setp.lt.and.u32 q, c, 0x200000, !p;\n @q bra.uni LW_%=;}" :: "r"(bar), "r"(parity) : "memory");
}
DI void mbar_arrive(uint32_t bar, int p = 1) { asm volatile("{.reg .pred p; setp.ne.b32 p, %1, 0; @p mbarrier.arrive.shared::cta.b64 _, [%0];}" :: "r"(bar), "r"(p) : "memory"); }
DI void bar_sync(int id, int n) { asm volatile("bar.sync %0, %1;" :: "r"(id), "r"(n) : "memory"); }
DI void bar_arrive(int id, int n) { asm volatile("bar.arrive %0, %1;" :: "r"(id), "r"(n) : "memory"); }
DI __nv_bfloat162 b2(uint32_t v) { return *(__nv_bfloat162*)&v; }
DI uint32_t u2(__nv_bfloat162 v) { return *(uint32_t*)&v; }
DI uint32_t hsq(uint32_t v) { return u2(__hmul2(b2(v), b2(v))); }
DI uint32_t hsub(uint32_t a, uint32_t b) { return u2(__hsub2(b2(a), b2(b))); }
DI uint32_t hhalf(uint32_t v) { return u2(__hmul2(b2(v), __floats2bfloat162_rn(0.5f, 0.5f))); }
DI uint32_t mag2(uint32_t m, uint32_t v) { return __vmaxu2(m, v & 0x7FFF7FFFu); }
DI uint32_t hmag(uint32_t m, uint32_t v) { const __half2 r = __hmax2(*(const __half2*)&m, __habs2(*(const __half2*)&v)); return *(const uint32_t*)&r; }
DI uint32_t magr(uint32_t m) { return max(m & 0xFFFF, m >> 16); }
DI void sts128(uint32_t a, uint32_t x, uint32_t y, uint32_t z, uint32_t w) { asm volatile("st.shared.v4.u32 [%0], {%1,%2,%3,%4};" :: "r"(a), "r"(x), "r"(y), "r"(z), "r"(w) : "memory"); }
DI void sts64(uint32_t a, uint32_t x, uint32_t y) { asm volatile("st.shared.v2.u32 [%0], {%1,%2};" :: "r"(a), "r"(x), "r"(y) : "memory"); }
DI void sts32(uint32_t a, uint32_t x) { asm volatile("st.shared.u32 [%0], %1;" :: "r"(a), "r"(x) : "memory"); }
DI void sts16(uint32_t a, uint32_t x) { asm volatile("st.shared.u16 [%0], %1;" :: "r"(a), "h"((uint16_t)x) : "memory"); }
DI void lds128(uint32_t* v, uint32_t a) { asm volatile("ld.shared.v4.u32 {%0, %1, %2, %3}, [%4];" : "=r"(v[0]), "=r"(v[1]), "=r"(v[2]), "=r"(v[3]) : "r"(a) : "memory"); }
DI void lds64(uint32_t& x, uint32_t& y, uint32_t a) { asm volatile("ld.shared.v2.u32 {%0, %1}, [%2];" : "=r"(x), "=r"(y) : "r"(a) : "memory"); }
DI uint32_t lds32(uint32_t a) { uint32_t x; asm volatile("ld.shared.u32 %0, [%1];" : "=r"(x) : "r"(a) : "memory"); return x; }
DI uint32_t lds16(uint32_t a) { uint32_t x; asm volatile("ld.shared.u16 %0, [%1];" : "=r"(x) : "r"(a) : "memory"); return x; }
DI uint32_t atoms_add(uint32_t a, uint32_t v) { uint32_t r; asm volatile("atom.shared.add.u32 %0, [%1], %2;" : "=r"(r) : "r"(a), "r"(v) : "memory"); return r; }
DI void bulk_load(uint32_t dst, const void* src, uint32_t bytes, uint32_t bar) {
  asm volatile("cp.async.bulk.shared::cluster.global.mbarrier::complete_tx::bytes.L2::cache_hint [%0], [%1], %2, [%3], %4;" :: "r"(dst), "l"(src), "r"(bytes), "r"(bar), "l"(pol_first()) : "memory"); }
DI void mbar_expect(uint32_t bar, uint32_t bytes) { asm volatile("mbarrier.arrive.expect_tx.shared::cta.b64 _, [%0], %1;" :: "r"(bar), "r"(bytes) : "memory"); }
DI void mbar_init(uint32_t bar, int n) { asm volatile("mbarrier.init.shared::cta.b64 [%0], %1;" :: "r"(bar), "r"(n) : "memory"); }
DI void tma_load(uint32_t dst, uint64_t tm, int row, uint32_t bar) {
  asm volatile("cp.async.bulk.tensor.2d.shared::cluster.global.mbarrier::complete_tx::bytes.L2::cache_hint [%0], [%1, {%3, %4}], [%2], %5;" :: "r"(dst), "l"(tm), "r"(bar), "r"(0), "r"(row), "l"(pol_first()) : "memory"); }
DI void tma_store(uint64_t tm, int col, int row, uint32_t src) {
  asm volatile("cp.async.bulk.tensor.2d.global.shared::cta.bulk_group [%0, {%2, %3}], [%1];" :: "l"(tm), "r"(src), "r"(col), "r"(row) : "memory"); }
DI void bulk_commit() { asm volatile("cp.async.bulk.commit_group;" ::: "memory"); }
DI uint2 ld_poll2(const void* a) { uint2 v; asm volatile("ld.relaxed.gpu.global.v2.u32 {%0, %1}, [%2];" : "=r"(v.x), "=r"(v.y) : "l"(a) : "memory"); return v; }
DI void st_ext(uint2* a, uint32_t v, uint32_t ep) { asm volatile("st.relaxed.gpu.global.v2.u32 [%0], {%1, %2};" :: "l"(a), "r"(v), "r"(ep) : "memory"); }
DI uint32_t ext_get(const uint2* a, uint32_t ep) { uint2 v; int spin = 0; do { v = ld_poll2(a); trap_if(++spin > 4000000); } while (__any_sync(~0u, v.y != ep)); return v.x; }
DI void bulk_wait() { asm volatile("cp.async.bulk.wait_group 0;" ::: "memory"); }
DI void hint_signal(uint32_t* c) { asm volatile("red.relaxed.gpu.global.add.u32 [%0], 1;" :: "l"(c) : "memory"); }
DI void hint_wait(const uint32_t* c, uint32_t target) { uint32_t v; int spin = 0;
  do { asm volatile("ld.relaxed.gpu.global.u32 %0, [%1];" : "=r"(v) : "l"(c) : "memory"); trap_if(++spin > 4000000); } while (__any_sync(~0u, (int)(v - target) < 0)); }
DI void stsm4(uint32_t a, uint32_t x, uint32_t y, uint32_t z, uint32_t w) { asm volatile("stmatrix.sync.aligned.m8n8.x4.shared.b16 [%0], {%1,%2,%3,%4};" :: "r"(a), "r"(x), "r"(y), "r"(z), "r"(w) : "memory"); }
DI void ldsm4(uint32_t* v, uint32_t a) { asm volatile("ldmatrix.sync.aligned.m8n8.x4.shared.b16 {%0,%1,%2,%3}, [%4];" : "=r"(v[0]), "=r"(v[1]), "=r"(v[2]), "=r"(v[3]) : "r"(a) : "memory"); }
DI void ldsm4t(uint32_t* v, uint32_t a) { asm volatile("ldmatrix.sync.aligned.m8n8.x4.trans.shared.b16 {%0,%1,%2,%3}, [%4];" : "=r"(v[0]), "=r"(v[1]), "=r"(v[2]), "=r"(v[3]) : "r"(a) : "memory"); }
DI uint32_t mad16(uint32_t x, uint32_t m, uint32_t c) { uint32_t r; asm("dp2a.lo.u32.u32 %0, %1, %2, %3;" : "=r"(r) : "r"(x), "r"(m), "r"(c)); return r; }
DI bool wbad(uint32_t m, uint32_t hi) { return m > hi || (m && m < 0x3980); }

__device__ __noinline__ void slow_path(const Params& p, int wid, int lane, int node0, int nloc) {
  const uint32_t ab = sb + OFF_P2 + wid * 8704;
  for (int i = lane; i < 32 * 68; i += 32) sts32(ab + i * 4, 0);
  __syncwarp();
  const uint32_t wdv = __ldg((const uint32_t*)(p.we + 128 * 64) + lane), wxv = __ldg((const uint32_t*)p.wx + lane);
  const int nb0 = node0 + wid * 32, cntn = max(0, min(32, nloc - wid * 32));
  auto dot = [&](uint32_t hv, const uint16_t* w, int K2, float& y0, float& y1) {
#pragma unroll 4
    for (int k = 0; k < K2; k++) {
      const uint32_t hk = __shfl_sync(~0u, hv, k), wa = __ldg((const uint32_t*)(w + 2 * k * 64) + lane), wb = __ldg((const uint32_t*)(w + (2 * k + 1) * 64) + lane);
      y0 = fmaf(bf_lo(hk), bf_lo(wa), fmaf(bf_hi(hk), bf_lo(wb), y0)); y1 = fmaf(bf_lo(hk), bf_hi(wa), fmaf(bf_hi(hk), bf_hi(wb), y1));
    }
  };
  auto silu = [](float x) { return x / (1.f + __expf(-x)); };
#pragma unroll 1
  for (int base = 0; base < p.E; base += 32) {
    const int e = base + lane;
    const uint32_t dl = e < p.E ? (uint32_t)(__ldg(p.dst + e) - nb0) : 0xFFFFFFFFu;
    uint32_t mk = __ballot_sync(~0u, dl < (uint32_t)cntn);
    while (mk) {
      const int l = __ffs(mk) - 1; mk &= mk - 1;
      const int ee = base + l, n = __shfl_sync(~0u, dl, l), s = __ldg(p.src + ee);
      const uint16_t *po = p.pos + (size_t)(nb0 + n) * 3, *pp = p.pos + (size_t)s * 3;
      const uint32_t dxy = hsub(__ldg(po) | (__ldg(po + 1) << 16), __ldg(pp) | (__ldg(pp + 1) << 16)), dz = hsub(__ldg(po + 2), __ldg(pp + 2));
      const uint32_t sq = hsq(dxy); const float d2 = bf_lo(sq) + bf_hi(sq) + bf_lo(hsq(dz));
      float y0 = d2 * bf_lo(wdv), y1 = d2 * bf_hi(wdv);
      dot(__ldg((const uint32_t*)(p.h + (size_t)(nb0 + n) * 8) + lane), p.we, 32, y0, y1);
      dot(__ldg((const uint32_t*)(p.h + (size_t)s * 8) + lane), p.we + 64 * 64, 32, y0, y1);
      dot(__ldg((const uint32_t*)(p.ea + (size_t)ee * 2) + (lane & 7)), p.we + 129 * 64, 8, y0, y1);
      const uint32_t mm = pack_bf16(silu(y0), silu(y1));
      float c = bf_lo(mm) * bf_lo(wxv) + bf_hi(mm) * bf_hi(wxv);
#pragma unroll
      for (int o = 16; o; o >>= 1) c += __shfl_xor_sync(~0u, c, o);
      const uint32_t a = ab + n * 272;
      uint32_t x0, x1; lds64(x0, x1, a + lane * 8);
      sts64(a + lane * 8, __float_as_uint(__uint_as_float(x0) + bf_lo(mm)), __float_as_uint(__uint_as_float(x1) + bf_hi(mm)));
      if (lane < 3) { const float df = lane == 0 ? bf_lo(dxy) : lane == 1 ? bf_hi(dxy) : bf_lo(dz); sts32(a + 256 + lane * 4, __float_as_uint(fmaf(c, df, __uint_as_float(lds32(a + 256 + lane * 4))))); }
    }
  }
  __syncwarp();
#pragma unroll 1
  for (int n = 0; n < cntn; n++) {
    uint32_t x0, x1; lds64(x0, x1, ab + n * 272 + lane * 8);
    const uint32_t hv = __ldg((const uint32_t*)(p.h + (size_t)(nb0 + n) * 8) + lane);
    float y0 = 0.f, y1 = 0.f;
    dot(hv, p.wh, 32, y0, y1); dot(pack_bf16(__uint_as_float(x0), __uint_as_float(x1)), p.wh + 64 * 64, 32, y0, y1);
    ((uint32_t*)p.out)[(size_t)(nb0 + n) * 32 + lane] = u2(__hadd2(b2(hv), b2(pack_bf16(silu(y0), silu(y1)))));
    if (lane < 3) p.out[(size_t)p.N * 64 + (size_t)(nb0 + n) * 3 + lane] = (uint16_t)pack_bf16(bf_lo(__ldg(p.pos + (size_t)(nb0 + n) * 3 + lane)) + __uint_as_float(lds32(ab + n * 272 + 256 + lane * 4)), 0.f);
  }
}

__global__ void __launch_bounds__(NTHR, 1) egnn_kernel(const __grid_constant__ Params p, const __grid_constant__ Maps maps) {
  const uint64_t tmb = (uint64_t)&maps;
  extern __shared__ __align__(1024) unsigned char smraw[];
  const int tid = threadIdx.x, cta = blockIdx.x * CTAM % G;
  const int e0 = cta * p.EPC, n4 = max(0, min(p.EPC, p.E - e0)) >> 2;
  STAMP(0);
  if (tid == NWK) {
#pragma unroll 1
    for (int k = 0; k < NCH; k++) { const int nb = max(0, min(NWK, n4 - k * NWK)) * 16;
      mbar_init(sb + BAR_DST + k * 8, 1);
      asm volatile("fence.mbarrier_init.release.cluster;" ::: "memory");
      mbar_expect(sb + BAR_DST + k * 8, nb);
      if (nb) bulk_load(sb + OFF_DST + k * NWK * 16, (const char*)(p.dst + e0) + k * NWK * 16, nb, sb + BAR_DST + k * 8); }
  }
  const int lane = tid & 31, wid = __shfl_sync(~0u, tid >> 5, 0), w = wid & 3;
  asm volatile("{.reg .pred p; setp.eq.u32 p, %2, 384; @p cp.async.cg.shared.global [%0], [%1], 16;}" :: "r"(sb + OFF_LEN - 192 + (tid >> 1)), "l"(p.sync), "r"(tid & 415) : "memory");

  auto first_node = [&](int c) { return (int)((c * p.inv + 0xFFFFFFFFull) >> 32); };
  const int node0 = first_node(cta), nloc = min(first_node(cta + 1), p.N) - node0;
  const uint32_t ealo = (uint32_t)(uint64_t)p.ea;
  const int epad = min(e0, p.E - 1);
  if (wid >= 12) {
    const int t = tid - 384;
    auto load_h = [&](int b) { mbar_expect(sb + BAR_T + b * 8, 8192); tma_load(sb + OFF_H + b * 8192, tmb + TM_H, node0 + b * 64, sb + BAR_T + b * 8); };
    uint32_t pv[9], ev = 0;
#pragma unroll
    for (int i = 0; i < 3; i++) { const uint16_t* pp = p.pos + (size_t)(node0 + t + 128 * i) * 3;
      pv[3 * i] = pv[3 * i + 1] = pv[3 * i + 2] = 0;
      asm volatile("{.reg .pred p; setp.lt.s32 p, %4, %5;\n @p ld.global.nc.u16 %0, [%3];\n @p ld.global.nc.u16 %1, [%3+2];\n @p ld.global.nc.u16 %2, [%3+4];}"
        : "+r"(pv[3 * i]), "+r"(pv[3 * i + 1]), "+r"(pv[3 * i + 2]) : "l"(pp), "r"(t + 128 * i), "r"(p.N - node0)); }
    asm volatile("{.reg .pred p; setp.lt.u32 p, %3, 8; @p ld.global.nc.u32 %0, [%1]; @p st.global.v4.u32 [%2], {%4, %4, %4, %4};}"
      : "+r"(ev) : "l"((const uint32_t*)(p.ea + (size_t)epad * 2) + t), "l"(p.q + (size_t)(p.N + cta * PADM) * 128 + t * 16), "r"(t), "r"(0xF700F700u) : "memory");
    asm volatile("cp.async.wait_all;" ::: "memory");
    __syncwarp();
    const uint32_t e = lds32(sb + OFF_LEN + 8 + w * 16) + 1;
    {
      const uint32_t tg = (1 + e % 3) << 30, v = ((tg >> 16) + 512 + (lane & 7) * 4) * 0x10001u;
      if (t == 0) sts32(sb + OFF_MISC + 32, e);
#pragma unroll
      for (int i = 0; i < 9; i++) sts128(sb + OFF_SA + t * 16 + i * 2048, v, v + 0x10001u, v + 0x20002u, v + 0x30003u);
      bar_sync(6, NTHR);
      mbar_arrive(sb + BAR_EP, lane == 0);
#pragma unroll
      for (int i = 0; i < 17; i++) sts128(sb + OFF_SB + t * 16 + i * 2048, tg, tg, tg, tg); }
    uint32_t mp = 0;
#pragma unroll
    for (int i = 0; i < 3; i++) { sts64(sb + OFF_POS + (t + 128 * i) * 8, pv[3 * i] | (pv[3 * i + 1] << 16), pv[3 * i + 2]); mp = mag2(mag2(mp, pv[3 * i] | (pv[3 * i + 1] << 16)), pv[3 * i + 2]); }
    proxy_fence();
    __syncwarp();
    mbar_arrive(sb + BAR_PS, lane == 0);
    mbar_wait(sb + BAR_W);
    {
      uint32_t v[4], u[4]; const int r = t >> 3, c = t & 7;
      lds128(v, sb + OFF_WS + 128 + t * 16); lds128(u, sb + OFF_WS + c * 16);
      const uint32_t x = lds32(sb + OFF_WS + 2176 + lane * 4);
      sts128(sb + OFF_W3 + r * 128 + ((c ^ (r & 7)) << 4), b2h(v[0], .5f), b2h(v[1], .5f), b2h(v[2], .5f), b2h(v[3], .5f));
      const float s = ((r & 1) || r == 6) ? 0.f : .5f;
      if (t < 64) sts128(sb + OFF_WD + r * 128 + ((c ^ r) << 4), b2h(u[0], s), b2h(u[1], s), b2h(u[2], s), b2h(u[3], s));
      if (t < 32) sts32(sb + OFF_WX + (t & 3) * 32 + (t >> 2) * 4, b2h(x, 1.f));
      const uint32_t m3 = __reduce_max_sync(~0u, magr(mag2(mag2(mag2(mag2(0, v[0]), v[1]), v[2]), v[3]))), md = __reduce_max_sync(~0u, magr(mag2(mag2(mag2(mag2(0, u[0]), u[1]), u[2]), u[3])));
      if (wbad(m3, 0x4000) || wbad(md, 0x4000) || wbad(__reduce_max_sync(~0u, magr(mag2(0, x))), 0x4700) || magr(mp) >= 0x4200 || magr(mag2(0, ev)) >= 0x4380) sts32(sb + OFF_MISC + 8, 1);
    }
    if (w == 1) {
#pragma unroll 1
      for (int b = 0; b < 3; b++) { mbar_wait(sb + BAR_SRC + b * 8); if (lane == 0) load_h(b); }
    }
    bar_sync(3, 128);
    const uint32_t frag = (w * 16 + (lane & 15)) * 128 + (((lane >> 4) ^ (lane & 7)) << 4);
    uint32_t mq = 0;
#pragma unroll 1
    for (int b = 0; b < 6; b++) {
      float acc[32];
      const uint64_t da = DHI | (((sb + OFF_H) >> 4) + b * 512), db = DHI | ((sb + OFF_W) >> 4);
      const uint32_t v0 = lds16(sb + OFF_POS + b * 512 + w * 128 + lane * 2), v1 = lds16(sb + OFF_POS + 64 + b * 512 + w * 128 + lane * 2);
      mbar_wait(sb + BAR_T + b * 8);
      if (b == 0) STAMP(25);
      if (b == 5) STAMP(26);
      wg_fence();
      ss64<0>(acc, da, db); ss64<1>(acc, da + 2, db + 128); ss64<1>(acc, da + 4, db + 256); ss64<1>(acc, da + 6, db + 384);
      wg_commit();
      if (b == 0) mbar_wait(sb + BAR_AW);
      if (t == 32 && b < 3) load_h(b + 3);
      __syncwarp();
      uint32_t ff[6], fg[6];
#pragma unroll
      for (int j = 0; j < 6; j++) { ff[j] = (__byte_perm((j & 1) ? v1 : v0, 0, 0x4140) >> (3 * (j >> 1))) & 0x00070007u; fg[j] = __vsub2(0x00040004u, ff[j]);
        asm volatile("" : "+r"(ff[j]), "+r"(fg[j])); }
      wg_wait0(); fence_regs(acc);
      uint32_t o[16];
#pragma unroll
      for (int j = 0; j < 16; j++) o[j] = pack_f16(.5f * acc[2 * j], .5f * acc[2 * j + 1]);
#pragma unroll
      for (int j = 0; j < 6; j++) {
        const uint32_t m = o[j] & 0x7FFF7FFFu; mq = __vmaxu2(mq, m);
        o[j] = (__viaddmax_s16x2(m, fg[j], 0) & 0xFFF8FFF8u) | ff[j] | (o[j] & 0x80008000u); }
      if (b == 4) mbar_wait(sb + BAR_AX);
      const uint32_t qs = sb + OFF_SA + b * 8192;
#pragma unroll
      for (int j = 0; j < 4; j++) stsm4((qs + frag) ^ (j << 5), o[4 * j], o[4 * j + 1], o[4 * j + 2], o[4 * j + 3]);
      proxy_fence();
      __syncwarp();
      if (lane == 0 && b * 64 + w * 16 < nloc) tma_store(tmb + TM_Q, 0, node0 + b * 64 + w * 16, qs + w * 2048);
    }
    if (lane == 0) bulk_commit();
    { const uint32_t m = __reduce_max_sync(~0u, magr(mq)); if (lane == 0) sts32(sb + OFF_MISC + 16 + w * 4, m); }
    asm volatile("setmaxnreg.dec.sync.aligned.u32 32;");
    bulk_wait();
    bar_sync(3, 128);
    if (w == 0) {
      STAMP(18);
      uint32_t mv[4]; lds128(mv, sb + OFF_MISC + 16);
      const uint32_t mx = max(max(mv[0], mv[1]), max(mv[2], mv[3]));
      mbar_arrive(sb + BAR_QR, lane == 0);
      STAMP(19);
      if (lane == 0) {
        if (nloc > 0 && (mx >= 0x7BF0 || mx < 0x1400)) asm volatile("st.relaxed.gpu.global.u32 [%0+4], %1;" :: "l"(p.sync), "r"(e) : "memory");
        asm volatile("red.release.gpu.global.add.u32 [%0], 1;" :: "l"(p.sync) : "memory");
      }
      __syncwarp();
      uint32_t c, f; int spin = 0;
      do { asm volatile("ld.acquire.gpu.global.v2.u32 {%0, %1}, [%2];" : "=r"(c), "=r"(f) : "l"(p.sync) : "memory"); trap_if(++spin > 4000000); } while (__any_sync(~0u, (int)(c - e * G) < 0));
      if (f == e) sts32(sb + OFF_MISC + 8, 1);
      if (cta == 0 && lane == 0) asm volatile("st.relaxed.gpu.global.u32 [%0+8], %1;" :: "l"(p.sync), "r"(e) : "memory");
      STAMP(20);
      __syncwarp();
      mbar_arrive(sb + BAR_QP, lane == 0);
    }
    if (w == 2) {
      const uint32_t tg = (1 + e % 3) << 30;
      hint_wait(p.sync + 5, e * G);
      if (lane == 0) { mbar_expect(sb + BAR_HB, XPAD);
#pragma unroll 1
        for (int o = 0; o < 4; o++) bulk_load(sb + OFF_XB + o * (G * 64), (const char*)p.xb + (size_t)(cta * 4 + o) * (G * 64), G * 64, sb + BAR_HB); }
      STAMP(21);
      bar_sync(7, 384);
      sts32(sb + OFF_XB + XPAD, tg + p.N + cta * PADM);
      const uint32_t nx = __shfl_sync(~0u, lds32(sb + OFF_MISC + 8) ? 0 : lds32(sb + OFF_MISC + 4), 0);
#pragma unroll 1
      for (uint32_t k = 0; k < nx; k += 32) {
        const uint32_t i = min(k + lane, nx - 1), xr = lds32(sb + OFF_EXT + i * 4), row = (xr >> 9) & 255;
        const uint32_t v = ext_get(p.xe + (cta * G + row) * 32 + ((xr >> 17) & 31), e), x = lds32(sb + OFF_CNT + (xr & 511) * 4) + (xr >> 22) * 16;
        sts32(sb + OFF_XB + XPAD + 4 + i * 4, v); sts16(sb + OFF_TS + x, XPAD + 4 + i * 4);
        sts32(sb + OFF_TE + x * 2, mad16(v, 0x2000u, ealo - (tg >> 11) + row * p.EPC * 32));
      }
      __syncwarp();
      mbar_arrive(sb + BAR_HB, lane == 0);
    }
    if (w == 1) {
      const uint32_t nb = (p.E / G) & ~15u;
#pragma unroll 1
      for (int i = 0; i < PFN; i++) {
        if (lane == 0 && nb) asm volatile("cp.async.bulk.prefetch.L2.global [%0], %1;" :: "l"((const char*)p.ea + (size_t)(i * G + cta) * nb), "r"(nb) : "memory");
        __nanosleep(PFNS); }
    }
    if (w == 3) {
      if (lane == 0) { mbar_expect(sb + BAR_U, 16384); tma_load(sb + OFF_W, tmb + TM_WH, 0, sb + BAR_U); }
      __syncwarp();
      bar_sync(4, 416);
      if (lane == 0) tma_load(sb + OFF_W + 8192, tmb + TM_WH, 64, sb + BAR_U);
    }
    bar_sync(3, 128);
    mbar_wait(sb + BAR_U);
    uint32_t mh = 0;
#pragma unroll 1
    for (int i = t; i < 1024; i += 128) {
      uint32_t v[4]; const uint32_t r = (i >> 3) & 7, j = (i ^ r) & 7;
#pragma unroll
      for (int k = 0; k < 4; k++) v[k] = lds32(sb + OFF_W + (i >> 3) * 128 + ((((j & 4) + k) ^ r) << 4) + (j & 3) * 4);
      __syncwarp();
      if (i < 512) sts128(sb + OFF_W + i * 16, hhalf(v[0]), hhalf(v[1]), hhalf(v[2]), hhalf(v[3]));
      else { sts128(sb + OFF_W + i * 16, b2h(v[0], .5f), b2h(v[1], .5f), b2h(v[2], .5f), b2h(v[3], .5f)); mh = mag2(mag2(mag2(mag2(mh, v[0]), v[1]), v[2]), v[3]); } }
    if (wbad(__reduce_max_sync(~0u, magr(mh)), 0x4700)) sts32(sb + OFF_MISC + 12, 1);
    proxy_fence();
    __syncwarp();
    mbar_arrive(sb + BAR_WH, lane == 0);
    if (!__shfl_sync(~0u, lds32(sb + OFF_MISC + 8), 0)) {
      mbar_wait(sb + BAR_M);
      __nanosleep(DEF0);
#pragma unroll 1
      for (int i = 0; i < 12; i++) { uint32_t v[4]; const uint32_t n = lds16(sb + OFF_GP + i * 256 + (t >> 3) * 8 + 6);
        lds128(v, sb + OFF_H + n * 128 + (((n ^ t) & 7) << 4));
        if (n < nloc) ((uint4*)p.out)[(size_t)(node0 + n) * 8 + (t & 7)] = make_uint4(v[0], v[1], v[2], v[3]);
        __nanosleep(DEFNS); }
      uint32_t pa_[9];
#pragma unroll
      for (int k = 0; k < 9; k++) { const uint32_t i = t + 128 * k, n = (i * 43691u) >> 17; pa_[k] = lds16(sb + OFF_INV + n * 2) + (i - 3 * n) * 2; }
      uint16_t* po = p.out + (size_t)p.N * 64 + node0 * 3 + t;
      mbar_wait(sb + BAR_X);
#pragma unroll
      for (int k = 0; k < 9; k++) pa_[k] = lds16(sb + OFF_GP + pa_[k]);
#pragma unroll
      for (int k = 0; k < 9; k++) if (t + 128 * k < nloc * 3) po[128 * k] = pa_[k];
      asm volatile("{.reg .pred p, q; setp.ne.u32 p, 0, 0; bar.red.or.pred q, 5, 512, p;}" ::: "memory");
    }
    return;
  }

  if (tid == 320) {
    mbar_init(sb + BAR_W, 1);
    asm volatile("fence.mbarrier_init.release.cluster;" ::: "memory");
    mbar_expect(sb + BAR_W, 2 * 8192 + 2304);
    tma_load(sb + OFF_W, tmb + TM_WE, 64, sb + BAR_W); tma_load(sb + OFF_W + 8192, tmb + TM_WE, 0, sb + BAR_W);
    bulk_load(sb + OFF_WS, p.we + 128 * 64, 2176, sb + BAR_W); bulk_load(sb + OFF_WS + 2176, p.wx, 128, sb + BAR_W);
  }
  if (tid == 288) {
#pragma unroll
    for (int a = BAR_SRC; a < BAR_END; a += 8) if (a != BAR_W) mbar_init(sb + a, a == BAR_WH || a == BAR_PS || a == BAR_EP ? 4 : a == BAR_HB ? 2 : a >= BAR_M ? 12 : 1);
    asm volatile("fence.mbarrier_init.release.cluster;" ::: "memory");
    asm volatile("prefetch.tensormap [%0];" :: "l"(tmb + TM_XA)); asm volatile("prefetch.tensormap [%0];" :: "l"(tmb + TM_H));
    asm volatile("prefetch.tensormap [%0];" :: "l"(tmb + TM_XB)); asm volatile("prefetch.tensormap [%0];" :: "l"(tmb + TM_Q));
  }
  {
    if (tid < 144) { const uint32_t z = (tid >> 3) == 16 ? 0x8000u : 0u; sts128(sb + OFF_CNT + tid * 16, z, z, z, z); }
    else if (tid <= 144 + G) sts32(sb + OFF_BC + (tid - 144) * 4, ((tid - 144) & 31) * 4);
    const uint32_t sp = XPAD * 0x10001u, em = first_node(G);
    if (wid < 7) {
#pragma unroll
      for (int i = 0; i < 4; i++) sts128(sb + OFF_TS + tid * 16 + i * 3584, sp, sp, sp, sp);
    }
    static_assert(SCAP * 32 == 4 * 3584, "fill");
#pragma unroll 1
    for (int i = n4 + tid; i < 1536; i += 384) sts128(sb + OFF_DST + i * 16, em, em, em, em);
    if (tid == 321) sts128(sb + OFF_MISC, 0, 0, p.force_slow, 0);
  }
  bar_arrive(6, NTHR);
  bar_sync(0, 384);
  uint32_t ep, tag, eb0, pk[12], r0[12], r1[12], cb;
  uint2 vb[12];
  auto get_tag = [&]() { mbar_wait(sb + BAR_EP); ep = lds32(sb + OFF_MISC + 32); tag = (1 + ep % 3) << 30; eb0 = ealo - (tag >> 11); };
  if (wid == 11) {
    trap_if(sb != (uint32_t)__cvta_generic_to_shared(smraw));
#pragma unroll 1
    for (int k = 0; k < 3; k++) { const int nb = max(0, min(8192, n4 * 16 - k * 8192));
      mbar_wait(sb + BAR_DST + (k ? k + 1 : 0) * 8);
      if (lane == 0) { mbar_expect(sb + BAR_SRC + k * 8, nb);
        if (nb) bulk_load(sb + OFF_SRCI + k * 8192, (const char*)(p.src + e0) + k * 8192, nb, sb + BAR_SRC + k * 8); } }
    get_tag();
    mbar_wait(sb + BAR_PS);
    bar_sync(12, 384);
    uint32_t xm = 0;
#pragma unroll
    for (int k = 0; k < 5; k++) xm |= (lds32(sb + OFF_BC + min(lane + 32 * k, G - 1) * 4) >= (65 << 9) && lane + 32 * k < G) << k;
    auto ext_send = [&](int pl) {
      uint32_t x = xm;
      for (uint32_t m; (m = __ballot_sync(~0u, x));) {
        const uint32_t l = __ffs(m) - 1, j = l + 32 * (__ffs(__shfl_sync(~0u, x, l)) - 1);
        if (lane == l) x &= x - 1;
        const uint32_t e = min(lds16(sb + OFF_AX + j * 128 + ((4 * l + 2 * lane) & 126)), 6143u);
        if (pl) st_ext(p.xe + (j * G + cta) * 32 + lane, lds32(sb + OFF_SRCI + e * 4) + tag + (e << 16), ep);
        else { const uint32_t cn = lds32(sb + OFF_BC + j * 4) >> 9, v = cn > 96 ? 1 : lane + 64 < cn ? 512 | (lds32(sb + OFF_DST + e * 4) & 511) : 0;
          asm volatile("red.shared.xor.b32 [%0], %1;" :: "r"(sb + OFF_SA + j * 128 + ((l + lane) & 31) * 4), "r"(((v & 63) << 10) | ((v >> 6) << 26)) : "memory"); }
      }
    };
    if (__any_sync(~0u, xm)) { ext_send(0); proxy_fence(); __syncwarp(); }
    if (lane == 0) { tma_store(tmb + TM_XA, cta * 64, 0, sb + OFF_SA); bulk_commit(); mbar_arrive(sb + BAR_AI); bulk_wait(); hint_signal(p.sync + 4); mbar_arrive(sb + BAR_AW); STAMP(16); }
    __syncwarp();
    bar_sync(13, 384);
    ext_send(1);
    mbar_arrive(sb + BAR_AX, lane == 0);
    mbar_wait(sb + BAR_HA);
    __nanosleep(BDEL);
    if (lane == 0) {
#pragma unroll 1
      for (int r = 0; r < G; r += BROWS) { tma_store(tmb + TM_XB, cta * 64, r, sb + OFF_SB + r * 256); bulk_commit(); bulk_wait(); }
      hint_signal(p.sync + 5);
      STAMP(17);
    }
    __syncwarp();
  } else {
    {
      uint32_t d[4 * NCH], jj[4 * NCH], rr[4 * NCH];
      auto count = [&](int k) {
        mbar_wait(sb + BAR_DST + k * 8);
        lds128(d + 4 * k, sb + OFF_DST + (tid + NWK * k) * 16);
#pragma unroll
        for (int i = 4 * k; i < 4 * k + 4; i++) { jj[i] = d[i] * p.magic; rr[i] = atoms_add(__dp4a(jj[i], 0x04000000u, sb + OFF_BC), 0x202u); }
      };
      auto place = [&](int k) {
#pragma unroll
        for (int i = 4 * k; i < 4 * k + 4; i++) {
          const uint32_t o = __dp4a(jj[i], 0x80000000u, rr[i] & 0x807Eu);
          d[i] = (d[i] & 511) | (tag >> 16);
          asm("{.reg .pred p; setp.ge.u32 p, %1, 0x8000; @p add.u32 %0, %2, %3;}" : "+r"(d[i]) : "r"(o), "r"(tid * 4), "r"(NWK * k * 4 + (i & 3)));
          sts16(sb + OFF_SA + o, d[i]); jj[i] = __viaddmin_u32(o, o, G * 256);
        }
      };
      count(0); STAMP(1); count(1); get_tag(); place(0); count(2); place(1); count(3); place(2);
      if (wid < 4) { count(4); STAMP(15); place(3); place(4); } else place(3);
      proxy_fence();
      bar_arrive(12, 384);
      STAMP(2);
      mbar_wait(sb + BAR_AI);
      mbar_wait(sb + BAR_SRC); mbar_wait(sb + BAR_SRC + 8); mbar_wait(sb + BAR_SRC + 16);
      STAMP(12);
#pragma unroll
      for (int k = 0; k < NCH; k++) lds128(d + 4 * k, sb + OFF_SRCI + (tid + NWK * k) * 16);
      const uint32_t tb = tag + (tid << 18);
#pragma unroll
      for (int i = 0; i < 4 * NCH; i++) if (i < 4 * NCH - 4 || wid < 4) sts32(sb + OFF_SB + jj[i], d[i] + tb + ((NWK * (i >> 2) * 4 + (i & 3)) << 16));
      proxy_fence();
      bar_arrive(13, 384);
      STAMP(3);
    }
    const uint32_t rot = (lane + cta) & 31;
    cb = sb + OFF_CNT - (tag >> 14);
    {
      const uint32_t* xa = (const uint32_t*)(p.xa + (cta * G + wid) * 8) + rot;
      if (wid < 8) { const uint32_t e_ = ealo + epad * 32;
        mbar_wait(sb + BAR_AX);
#pragma unroll
        for (int i = 0; i < 7; i++) sts128(sb + OFF_TE + tid * 16 + i * 4096, e_, e_, e_, e_); }
      static_assert(SCAP * 64 == 7 * 4096, "fill");
      if (wid == 10) { hint_wait(p.sync + 4, ep * G); mbar_arrive(sb + BAR_HA, lane == 0); }
      mbar_wait(sb + BAR_HA);
      STAMP(14);
      const uint32_t tp = tag | (tag >> 16);
      uint32_t st;
#pragma unroll 1
      for (int spin = 0;; spin++) {
        st = 0;
#pragma unroll
        for (int k = 0; k < 12; k++) asm volatile("ld.relaxed.gpu.global.u32 %0, [%1];" : "=r"(pk[k]) : "l"(xa + k * 352) : "memory");
#pragma unroll
        for (int k = 0; k < 12; k++) st |= pk[k] ^ tp;
        st = __reduce_or_sync(~0u, st);
        if (!(st >> 30)) break;
        trap_if(spin > 2000000);
      }
      if (st & 0x3C00FC00u) {
#pragma unroll 1
        for (;;) {
          uint32_t x = 0, row = 0;
#pragma unroll
          for (int k = 0; k < 12; k++) { const uint32_t y = (pk[k] ^ tp) & 0x3C00FC00u; if (!x && y) { x = y; row = wid + 11 * k; pk[k] ^= y; } }
          if (!__any_sync(~0u, x)) break;
          const uint32_t n = ((x >> 10) & 63) | ((x >> 20) & 0x1C0);
          if (x >> 29) {
            const uint32_t r = atoms_add(sb + OFF_CNT + n * 4, 16), idx = atoms_add(sb + OFF_MISC + 4, 1);
            if (idx < 256) sts32(sb + OFF_EXT + idx * 4, n | (row << 9) | (lane << 17) | (min(r >> 4, 255u) << 22));
            else x = 1;
          }
          if (x && !(x >> 29)) sts32(sb + OFF_MISC + 8, 1);
          __syncwarp();
        }
      }
#pragma unroll
      for (int k = 0; k < 12; k++) { r0[k] = mad16(pk[k], 0x0004u, cb); r1[k] = mad16(pk[k], 0x0400u, cb); vb[k].x = atoms_add(r0[k], 16); vb[k].y = atoms_add(r1[k], 16); }
    }
    STAMP(4);
    if (wid >= 6) bar_arrive(11, NWK);
    if (wid < 6) {
      uint32_t ca[2], ky[2], dr[2], sq[2], ps[4];
#pragma unroll
      for (int i = 0; i < 2; i++) { ca[i] = sb + OFF_CNT + ((node0 + tid + 192 * i) & 511) * 4; lds64(ps[2 * i], ps[2 * i + 1], sb + OFF_POS + (tid + 192 * i) * 8); ps[2 * i + 1] |= (tid + 192 * i) << 16; }
      bar_sync(11, NWK);
      STAMP(5);
#pragma unroll
      for (int i = 0; i < 2; i++) ky[i] = (lds32(ca[i]) + 16) >> 5;
      if (max(ky[0], ky[1]) > 31) sts32(sb + OFF_MISC + 8, 1);
#pragma unroll
      for (int i = 0; i < 2; i++) { ky[i] = min(ky[i], 31u); dr[i] = atoms_add(sb + OFF_DH + ky[i] * 4, 1); }
      bar_sync(10, 192);
      const uint32_t hv = lds32(sb + OFF_DH + lane * 4);
      uint32_t inc = hv;
#pragma unroll
      for (int o = 1; o < 32; o <<= 1) asm("{.reg .pred p; .reg .b32 y; shfl.sync.down.b32 y|p, %0, %1, 31, -1; @p add.u32 %0, %0, y;}" : "+r"(inc) : "r"(o));
#pragma unroll
      for (int i = 0; i < 2; i++) {
        const uint32_t pos = __shfl_sync(~0u, inc - hv, ky[i]) + dr[i];
        const uint32_t ak = (uint32_t)(QCODE >> ((pos >> 5) * 4)) & 15, l = (pos >> 3) & 3;
        sq[i] = (ak >> 2) * 16 + ((QREV >> (pos >> 5) & 1) ? 3 - l : l) * 4 + (ak & 3);
        dr[i] = pos & 7;
        asm volatile("{.reg .pred p; setp.eq.u32 p, %2, 0; @p st.shared.u8 [%0], %1;}" :: "r"(sb + OFF_LEN + sq[i]), "r"(max(ky[i], 1u)), "r"(dr[i]) : "memory");
        sts64(sb + OFF_GP + sq[i] * 64 + dr[i] * 8, ps[2 * i], ps[2 * i + 1]);
        sts16(sb + OFF_INV + (tid + 192 * i) * 2, sq[i] * 64 + dr[i] * 8);
      }
      bar_sync(10, 192);
      const uint32_t ln = lds32(sb + OFF_LEN + min(lane, 11) * 4), tot = __dp4a(ln, 0x01010101u, 0u);
      inc = tot;
#pragma unroll
      for (int o = 1; o < 16; o <<= 1) asm("{.reg .pred p; .reg .b32 y; shfl.sync.up.b32 y|p, %0, %1, 0, -1; @p add.u32 %0, %0, y;}" : "+r"(inc) : "r"(o));
      if (wid == 1) sts32(sb + OFF_CNT + 2048 + lane * 4, 0);
      if (tid < 12) { sts32(sb + OFF_LEN + 64 + tid * 4, inc - tot); if (inc > SCAP - 12) sts32(sb + OFF_MISC + 8, 1); }
#pragma unroll
      for (int i = 0; i < 2; i++) sts32(ca[i], __dp4a(__shfl_sync(~0u, ln, sq[i] >> 2), 0x00010101u >> (24 - 8 * (sq[i] & 3)), __shfl_sync(~0u, inc - tot, sq[i] >> 2)) * 32 + dr[i] * 2);
    }
    bar_arrive(7, 384);
  }
  bar_sync(1, 384);
  STAMP(6);
  if (wid != 11 && !__shfl_sync(~0u, lds32(sb + OFF_MISC + 8), 0)) {
#pragma unroll
    for (int k = 0; k < 12; k++) { r0[k] = lds32(r0[k]); r1[k] = lds32(r1[k]); }
#pragma unroll
    for (int k = 0; k < 12; k++) { r0[k] += vb[k].x; r1[k] += vb[k].y; }
  } else {
#pragma unroll
    for (int k = 0; k < 12; k++) r0[k] = r1[k] = 0x8000;
  }
  auto put_ids = [&]() {
    const uint32_t id = wid * 256 + ((lane + cta) & 31) * 8;
    auto put = [&](uint32_t x, uint32_t v) { asm volatile("{.reg .pred p; setp.lt.u32 p, %0, 0x8000; @p st.shared.u16 [%0+%2], %1;}" :: "r"(x), "h"((uint16_t)v), "n"(sb + OFF_TS) : "memory"); };
#pragma unroll
    for (int k = 0; k < 12; k++) { put(pk[k] & 0xFFFF, id + k * 2816); put(pk[k] >> 16, id + k * 2816 + 4); }
  };
  STAMP(7);
  mbar_wait(sb + BAR_QR);
  asm volatile("setmaxnreg.inc.sync.aligned.u32 160;");
#pragma unroll
  for (int k = 0; k < 12; k++) asm volatile("prmt.b32 %0, %1, %2, 0x5410;" : "=r"(pk[k]) : "r"(r0[k]), "r"(r1[k]));
  uint32_t pa[8], sp[8], pq[16]; float chk = 0.f;
  {
    uint32_t hf[32], mp = 0; float a0[32], a1[32];
    const uint32_t an = sb + OFF_GP + wid * 256 + (lane & 15) * 8 + 6, n0 = lds16(an), n1 = lds16(an + 128);
#pragma unroll
    for (int j = 0; j < 8; j++) { const uint32_t nd = j < 4 ? n0 : n1; ldsm4(hf + 4 * j, (sb + OFF_H + nd * 128 + (((nd & 7) << 4) ^ (lane & 16))) ^ ((j & 3) << 5)); }
    const uint64_t db = DHI | ((sb + OFF_W + 8192) >> 4);
    wg_fence();
    rs64b<0>(a0, hf[0], hf[1], hf[2], hf[3], db); rs64b<1>(a0, hf[4], hf[5], hf[6], hf[7], db + 128); rs64b<1>(a0, hf[8], hf[9], hf[10], hf[11], db + 256); rs64b<1>(a0, hf[12], hf[13], hf[14], hf[15], db + 384);
    wg_commit();
    rs64b<0>(a1, hf[16], hf[17], hf[18], hf[19], db); rs64b<1>(a1, hf[20], hf[21], hf[22], hf[23], db + 128); rs64b<1>(a1, hf[24], hf[25], hf[26], hf[27], db + 256); rs64b<1>(a1, hf[28], hf[29], hf[30], hf[31], db + 384);
    wg_commit();
    put_ids();
    asm volatile("wgmma.wait_group.sync.aligned 1;" ::: "memory"); fence_regs(a0);
#pragma unroll
    for (int j = 0; j < 8; j++) { const uint32_t x = pack_f16(.5f * a0[4 * j], .5f * a0[4 * j + 1]), y = pack_f16(.5f * a0[4 * j + 2], .5f * a0[4 * j + 3]); mp = hmag(hmag(mp, x), y);
      asm volatile("movmatrix.sync.aligned.m8n8.trans.b16 %0, %1;" : "=r"(pa[j]) : "r"(x)); asm volatile("movmatrix.sync.aligned.m8n8.trans.b16 %0, %1;" : "=r"(sp[j]) : "r"(y)); }
    wg_wait0(); fence_regs(a1);
    bar_arrive(4, 416);
#pragma unroll
    for (int j = 0; j < 16; j++) { pq[j] = pack_f16(.5f * a1[2 * j], .5f * a1[2 * j + 1]); mp = hmag(mp, pq[j]); }
    if (magr(mp) >= 0x7000) chk = __int_as_float(0x7FC00000);
  }
  if (wid == 0) STAMP(23);
  uint32_t bad;
  {
    const uint32_t ring = sb + OFF_RING + wid * STG, p2 = sb + OFF_P2 + wid * 2048;
    uint32_t lens = __shfl_sync(~0u, lds32(sb + OFF_LEN + wid * 4), 0);
    uint32_t rem = __dp4a(lens, 0x20202020u, 0u);
    const uint32_t base = min(lds32(sb + OFF_LEN + 64 + wid * 4), SCAP);
    uint32_t a_s = sb + OFF_TS + base * 32 + (lane >> 3) * 8, a_e = sb + OFF_TE + base * 64 + (lane >> 1) * 4;
    uint32_t k0 = (uint32_t)(uint64_t)p.q + (((lane & 7) ^ ((lane >> 1) & 4)) << 4), k1 = k0 ^ 16, k2 = k0 ^ 32, k3 = k0 ^ 48, ke = ((lane ^ (lane >> 3)) & 1) << 4;
    uint32_t dst0 = ring + (lane >> 3) * 640 + (lane & 7) * 16;
    const uint32_t qhi = (uint32_t)((uint64_t)p.q >> 32), ehi = (uint32_t)((uint64_t)p.ea >> 32);
    uint32_t s0, s1, ev, to = 0, so = 12 * STG;
    auto tl_ = [&]() { lds64(s0, s1, a_s + to); asm volatile("ld.shared.u32 %0, [%1]; add.u32 %1, %1, 64;" : "=&r"(ev), "+r"(a_e) :: "memory"); to += 32; };
#define CPQ(LH, x, k, off) "dp2a." LH ".u32.u32 lo, " x ", 0x80000080, " k "; mov.b64 a, {lo, %7}; @p cp.async.cg.shared.global [%0+" #off "], [a], 16;\n"
#define CPE "or.b32 lo, %10, %11; mov.b64 a, {lo, %12}; @p cp.async.cg.shared.global [%0+512], [a], 16;\n"
#define CPA(BODY) asm volatile("{.reg .b32 lo; .reg .b64 a; .reg .pred p; setp.le.u32 p, %8, %9;\n" BODY "}" \
      :: "r"(dst0 + so), "r"(s0), "r"(s1), "r"(k0), "r"(k1), "r"(k2), "r"(k3), "r"(qhi), "r"(to), "r"(rem), "r"(ev), "r"(ke), "r"(ehi) : "memory")
#define CPQ4 CPQ("lo", "%1", "%3", 0) CPQ("hi", "%1", "%4", 128) CPQ("lo", "%2", "%5", 256) CPQ("hi", "%2", "%6", 384) "cp.async.commit_group;"
    auto issue = [&]() { CPA(CPE CPQ4); so = so == (NST - 1) * 12 * STG ? 0 : so + 12 * STG; };
    const int g = lane >> 2, qd = lane & 3;
    const uint32_t sw = ((lane >> 4) ^ (lane & 7)) << 4, fr = (lane & 15) * 128 + sw;
    uint32_t qa0 = ring + (g & 3) * 640 + qd * 128 + sw, qa1 = qa0 ^ 32, qa2 = qa0 ^ 64, qa3 = qa0 ^ 96;
    uint32_t eadr = ring + 512 + (g & 3) * 640 + qd * 32 + ((((lane >> 4) ^ g) & 1) << 4);
    uint32_t oh0 = g == 2 * qd ? 0x3C00u : g == 2 * qd + 1 ? 0x3C000000u : 0u, oh1 = oh0;
    uint32_t a_g = sb + OFF_GP + wid * 256 + lane * 2;
    uint32_t a_n = sb + OFF_GP + wid * 256 + (lane & 15) * 8 + 6;
    uint32_t a_p = ((lane & 8) ? p2 : sb + OFF_WD) + (lane & 7) * 128 + ((((lane >> 4) ^ lane) & 7) << 4);
    uint32_t a_w = sb + OFF_W3 + fr;
    asm volatile("shfl.sync.idx.b32 %0, %0, %1, 31, -1;" : "+r"(oh1) : "r"(lane));
    uint32_t w3[16], wv[8], bp[16], sum[8], Y[16], M[16], own, ownp, dpk; uint16_t tl[16], th[16];
    float pacc = 0.f;
    auto wload = [&]() {
#pragma unroll
      for (int j = 0; j < 4; j++) ldsm4t(w3 + 4 * j, a_w ^ (j << 5));
      lds128(wv, sb + OFF_WX + (a_g & 6) * 16); lds128(wv + 4, sb + OFF_WX + 16 + (a_g & 6) * 16);
    };
    auto hload = [&](uint32_t (&hf)[16], uint32_t nd) {
      const uint32_t hrow = sb + OFF_H + nd * 128 + (((nd & 7) << 4) ^ ((a_g >> 1) & 16));
#pragma unroll
      for (int j = 0; j < 4; j++) ldsm4(hf + 4 * j, hrow ^ (j << 5));
      return hrow;
    };
    auto bload = [&](uint32_t o) {
#pragma unroll
      for (int j = 0; j < 4; j++) ldsm4t(bp + 4 * j, (a_p ^ (j << 5)) + o);
    };
    { uint32_t wd[8]; const uint32_t a = sb + OFF_WD + (lane & 7) * 128 + ((((lane >> 3) ^ lane) & 7) << 4);
      ldsm4t(wd, a); ldsm4t(wd + 4, a ^ 64);
#pragma unroll
      for (int j = 0; j < 8; j++) { bp[2 * j] = wd[j]; bp[2 * j + 1] = pa[j]; } }
    own = lds16(a_g) * 0x10001u;
    wload();
    if (__shfl_sync(~0u, lds32(sb + OFF_MISC + 8), 0)) rem = 0;
    auto resolve = [&](auto NBK, uint32_t o) {
      constexpr int NB = decltype(NBK)::value;
      uint32_t id[NB], c0[NB], c1[NB]; const uint32_t a = base * 32 + o + lane * 4;
#pragma unroll
      for (int i = 0; i < NB; i++) { id[i] = lds32(sb + OFF_TS + a + i * 128); if (o + lane * 4 + i * 128 >= rem) id[i] = XPAD * 0x10001u; }
      uint32_t st = 0;
#pragma unroll
      for (int i = 0; i < NB; i++) { c0[i] = lds32(sb + OFF_XB + (id[i] & 0xFFFF)); c1[i] = lds32(sb + OFF_XB + (id[i] >> 16)); }
#pragma unroll
      for (int i = 0; i < NB; i++) st |= (c0[i] ^ tag) | (c1[i] ^ tag);
      for (int spin = 0; __any_sync(~0u, st >> 30); spin++) {
        st = 0; trap_if(spin > 2000000);
#pragma unroll
        for (int i = 0; i < NB; i++) {
          asm volatile("{.reg .pred p, q; setp.lt.u32 p, %4, %6; setp.lt.u32 q, %5, %6; @p ld.relaxed.gpu.global.u32 %0, [%2]; @q ld.relaxed.gpu.global.u32 %1, [%3];}"
            : "+r"(c0[i]), "+r"(c1[i]) : "l"((const char*)p.xb + cta * XPAD + (id[i] & 0xFFFF)), "l"((const char*)p.xb + cta * XPAD + (id[i] >> 16)), "r"(id[i] & 0xFFFF), "r"(id[i] >> 16), "n"(XPAD) : "memory");
          st |= (c0[i] ^ tag) | (c1[i] ^ tag); }
      }
#pragma unroll
      for (int i = 0; i < NB; i++) { const uint32_t j0 = (id[i] >> 8) & 255, j1 = id[i] >> 24;
        asm volatile("{.reg .pred p, q, r; setp.lt.u32 p, %5, %9; setp.lt.u32 q, %6, %9; setp.lt.u32 r, %7, %8;\n"
          "@p st.shared.u32 [%0], %2; @q st.shared.u32 [%0+4], %3; @r st.shared.u32 [%1], %4;}"
          :: "r"(sb + OFF_TE + 2 * a + i * 256), "r"(sb + OFF_TS + a + i * 128), "r"(mad16(c0[i], 0x2000u, eb0 + j0 * p.EPC * 32)), "r"(mad16(c1[i], 0x2000u, eb0 + j1 * p.EPC * 32)),
             "r"(__byte_perm(c0[i], c1[i], 0x5410)), "r"(j0), "r"(j1), "r"(o + lane * 4 + i * 128), "r"(rem), "n"(G) : "memory"); }
    };
    bar_sync(2, 384);
    if (wid == 0) STAMP(27);
    mbar_wait(sb + BAR_HB);
    if (wid == 0) STAMP(22);
#pragma unroll 1
    for (uint32_t o = 0, go = 0; go < 32 * NST; o += 128 * RNB) {
      if (o < rem) { resolve(IC<RNB>(), o);
        asm volatile("{.reg .pred p; mbarrier.test_wait.parity.shared::cta.b64 p, [%1], 0; vote.sync.all.pred p, p, -1; selp.u32 %0, %2, 0, p;}" : "=r"(go) : "r"(sb + BAR_QP), "n"(32 * NST - 32) : "memory"); }
      else { bar_sync(8, 384); mbar_wait(sb + BAR_QP); go = 32 * NST; if (wid == 0) STAMP(24); }
      __syncwarp();
#pragma unroll 1
      while (to < go) { tl_(); issue(); if (to == 32) STAMP(13); }
    }
    bad = __shfl_sync(~0u, lds32(sb + OFF_MISC + 8), 0);
   if (!bad) {
#pragma unroll
    for (int j = 0; j < 4; j++) stsm4((p2 + fr) ^ (j << 5), pq[4 * j], pq[4 * j + 1], pq[4 * j + 2], pq[4 * j + 3]);
    auto body = [&](auto MODE) {
      constexpr int mode = decltype(MODE)::value;
      uint32_t T[16], ef[4], q0, q1, x0, x1, x2; float e0_, e1_, cs[4];
      auto mu = [&](int j) {
#pragma unroll
        for (int i = 2 * j; i < 2 * j + 2; i++) asm volatile("{.reg .b16 l, h; mov.b32 {l, h}, %2; tanh.approx.f16 %0, l; tanh.approx.f16 %1, h;}" : "=h"(tl[i]), "=h"(th[i]) : "r"(Y[i])); };
      auto fi = [&](int j) {
#pragma unroll
        for (int i = 2 * j; i < 2 * j + 2; i++) asm volatile("{.reg .b32 t; mov.b32 t, {%2, %3}; fma.rn.f16x2 %0, %1, t, %1;}" : "=r"(M[i]) : "r"(Y[i]), "h"(tl[i]), "h"(th[i])); };
      auto ad = [&](int j) { asm volatile("add.rn.f16x2 %0, %0, %1; add.rn.f16x2 %0, %0, %2;" : "+r"(sum[j]) : "r"(M[2 * j]), "r"(M[2 * j + 1])); };
      auto he = [&](int j) { asm volatile("mma.sync.aligned.m16n8k16.row.col.f16.f16.f16.f16 {%0,%1}, {%2,%3,%4,%5}, {%6,%7}, {%0,%1};" : "+r"(T[2 * j]), "+r"(T[2 * j + 1]) : "r"(ef[0]), "r"(ef[1]), "r"(ef[2]), "r"(ef[3]), "r"(w3[2 * j]), "r"(w3[2 * j + 1])); };
      auto hs = [&](int j) { asm volatile("mma.sync.aligned.m16n8k16.row.col.f16.f16.f16.f16 {%0,%1}, {%2,%3,%4,%5}, {%6,%7}, {%8,%9};" : "=r"(Y[2 * j]), "=r"(Y[2 * j + 1]) : "r"(q0), "r"(q1), "r"(oh0), "r"(oh1), "r"(bp[2 * j]), "r"(bp[2 * j + 1]), "r"(T[2 * j]), "r"(T[2 * j + 1])); };
      auto hc = [&](int j) {
        if (j) asm volatile("mma.sync.aligned.m16n8k16.row.col.f32.f16.f16.f32 {%0,%1,%2,%3}, {%4,%5,%6,%7}, {%8,%9}, {%0,%1,%2,%3};" : "+f"(cs[0]), "+f"(cs[1]), "+f"(cs[2]), "+f"(cs[3]) : "r"(M[4 * j]), "r"(M[4 * j + 1]), "r"(M[4 * j + 2]), "r"(M[4 * j + 3]), "r"(wv[2 * j]), "r"(wv[2 * j + 1]));
        else asm volatile("mma.sync.aligned.m16n8k16.row.col.f32.f16.f16.f32 {%0,%1,%2,%3}, {%4,%5,%6,%7}, {%8,%9}, {%10,%10,%10,%10};" : "=f"(cs[0]), "=f"(cs[1]), "=f"(cs[2]), "=f"(cs[3]) : "r"(M[0]), "r"(M[1]), "r"(M[2]), "r"(M[3]), "r"(wv[0]), "r"(wv[1]), "f"(0.f)); };
      auto cv = [&](int i) { asm volatile("{.reg .b32 a, b; shl.b32 a, %0, 16; and.b32 b, %0, 0xFFFF0000; cvt.rn.f16x2.f32 %0, b, a;}" : "+r"(ef[i])); };
      auto un = [&]() { asm volatile("shl.b32 %0, %2, 16; and.b32 %1, %2, 0xFFFF0000;" : "=&f"(e0_), "=&f"(e1_) : "r"(dpk)); };
      auto ex0 = [&]() { asm volatile("prmt.b32 %0, %3, %4, 0x6420; prmt.b32 %1, %5, %6, 0x6420; prmt.b32 %2, %7, %8, 0x6420;" : "=&r"(x0), "=&r"(x1), "=&r"(x2) : "r"(T[0]), "r"(T[1]), "r"(T[2]), "r"(T[3]), "r"(T[4]), "r"(T[5])); };
      auto ex1 = [&]() { asm volatile("{.reg .b32 a, b; shl.b32 a, %2, 3; shl.b32 b, %3, 6; lop3.b32 a, %1, a, 0x38383838, 0xD8; lop3.b32 a, a, b, 0xC0C0C0C0, 0xD8; sub.rn.bf16x2 %0, %4, a;}" : "=r"(dpk) : "r"(x0), "r"(x1), "r"(x2), "r"(own)); };
      auto ex2 = [&]() { asm volatile("{.reg .b32 a, b, d, u; .reg .b16 l, h; shl.b32 a, %2, 16; and.b32 b, %2, 0xFFFF0000; cvt.rn.f16x2.f32 d, b, a; mul.rn.f16x2 %0, d, d; mov.b32 {l, h}, d; mov.b32 u, {h, h}; mul.rn.f16x2 %1, u, u;}" : "=&r"(q0), "=&r"(q1) : "r"(dpk)); };
      auto pf = [&]() { asm volatile("fma.rn.f32 %0, %1, %2, %0; fma.rn.f32 %0, %3, %4, %0;" : "+f"(pacc) : "f"(cs[0]), "f"(e0_), "f"(cs[2]), "f"(e1_)); };
      if (mode == 2) {
        hc(0); mu(3); fi(2); un(); ad(0); ad(1); mu(4); fi(3); hc(1); mu(5); fi(4); ad(2); mu(6); fi(5); ad(3); hc(2); mu(7); fi(6); fi(7); ad(4); ad(5); hc(3); ad(6); ad(7); pf();
        return;
      }
      asm volatile("cp.async.wait_group %0;" :: "n"(NST - 1) : "memory");
      __syncwarp();
      if (mode == 1) STAMP(8);
      ldsm4(ef, eadr + so); ldsm4(T, qa0 + so); ldsm4(T + 4, qa1 + so); ldsm4(T + 8, qa2 + so); ldsm4(T + 12, qa3 + so);
      tl_();
      if (mode == 1) {
        issue();
        cv(0); cv(1); cv(2); cv(3); ex0(); ex1(); ex2();
#pragma unroll
        for (int j = 0; j < 8; j++) { he(j); hs(j); }
        mu(0); mu(1); fi(0); mu(2); fi(1);
        return;
      }
      un(); hc(0); ad(0); mu(4); mu(3); fi(3); cv(0); ad(1); fi(2); cv(2); cv(3); ex0(); ex1(); ex2();
      fi(4); cv(1); he(0); he(1); ad(3); he(2); hs(1); he(3); mu(5); fi(5); hs(0); hc(1); hc(2); ad(2);
      hs(3); mu(6); fi(6); he(4); issue(); he(5); hs(2); hs(4); mu(7); he(7); mu(0); ad(5); fi(7); hs(5);
      ad(4); mu(2); mu(1); hs(7); hc(3); he(6); ad(6); fi(0); fi(1); hs(6); ad(7); pf();
    };
#pragma unroll
    for (int j = 0; j < 8; j++) sum[j] = 0;
    body(IC<1>());
    int cnt = (lens & 255) - 1;
    auto flush = [&]() {
      asm volatile("{.reg .pred p; setp.ne.u32 p, %2, 6; @p st.shared.u16 [%0+-64], %1;}" :: "r"(a_g), "h"((uint16_t)pack_bf16(bf_hi(ownp) + pacc, 0.f)), "r"(a_g & 6) : "memory");
      chk = fmaf(pacc, 0.f, chk); pacc = 0.f; };
    constexpr uint64_t b1 = DHI | ((sb + OFF_W) >> 4), b2_ = b1 + 512;
    auto mma_h = [&](float (&acc)[32], uint32_t (&hf)[16]) {
      rs64b<0>(acc, hf[0], hf[1], hf[2], hf[3], b1); rs64b<1>(acc, hf[4], hf[5], hf[6], hf[7], b1 + 128); rs64b<1>(acc, hf[8], hf[9], hf[10], hf[11], b1 + 256); rs64b<1>(acc, hf[12], hf[13], hf[14], hf[15], b1 + 384); };
    auto mma_m = [&](float (&acc)[32]) {
      rs64h<1>(acc, sp[0], sum[0], sp[1], sum[1], b2_); rs64h<1>(acc, sp[2], sum[2], sp[3], sum[3], b2_ + 128); rs64h<1>(acc, sp[4], sum[4], sp[5], sum[5], b2_ + 256); rs64h<1>(acc, sp[6], sum[6], sp[7], sum[7], b2_ + 384);
      wg_commit(); wg_wait0(); fence_regs(acc);
      STAMP(10);
      chk = fmaf(acc[0], 0.f, fmaf(acc[2], 0.f, chk)); };
    auto roff = [&](uint32_t nd, int r) { return __shfl_sync(~0u, nd, ((a_g >> 3) & 7) + 8 * r) * 128 + (a_g & 6) * 8; };
    auto radr = [&](uint32_t o, int k) { return sb + OFF_H + (o ^ ((o >> 3) & 0x70) ^ ((k >> 1) << 6)); };
    auto fin = [&](float (&acc)[32], uint32_t* x, int k) {
#pragma unroll
      for (int i = 0; i < 4; i++) { const int c = 16 * (k >> 1) + 4 * i + 2 * (k & 1); x[i] = u2(__hadd2(b2(x[i]), b2(pack_bf16(silu_h(acc[c]), silu_h(acc[c + 1]))))); } };
#pragma unroll 1
    for (int t = 0;; t++) {
#pragma unroll 1
      for (; cnt > 0; cnt--) { body(IC<0>());
      }
      if (!(t & 1)) {
        ownp = own; a_g += 64;
        if (t == 6) break;
        own = lds16(a_g) * 0x10001u;
        if (t == 0) {
#pragma unroll
          for (int j = 0; j < 8; j++) bp[2 * j + 1] = sp[j];
        } else bload((a_g & 16) ? (t & 4) * 256 : 0);
        lens >>= 8; cnt = 1;
        continue;
      }
      cnt = (lens & 255) - 1;
      flush();
      if (t == 3) {
        uint32_t hf[16]; float acc[32];
        const uint32_t nd = lds16(a_n), o[2] = {roff(nd, 0), roff(nd, 1)};
        hload(hf, nd);
        mbar_wait(sb + BAR_WH);
        wg_fence();
        mma_h(acc, hf); mma_m(acc);
#pragma unroll
        for (int k = 0; k < 4; k++) lds128(hf + 4 * k, radr(o[k & 1], k));
#pragma unroll
        for (int k = 0; k < 4; k++) { fin(acc, hf + 4 * k, k); sts128(radr(o[k & 1], k), hf[4 * k], hf[4 * k + 1], hf[4 * k + 2], hf[4 * k + 3]); }
        __syncwarp();
        mbar_arrive(sb + BAR_M, (a_g & 62) == 0);
        wload();
      }
#pragma unroll
      for (int j = 0; j < 8; j++) { sp[j] = sum[j]; asm volatile("mov.b32 %0, 0;" : "=r"(sum[j])); }
    }
    {
      uint32_t hf[16], v[16]; float acc[32];
      const uint32_t nd = lds16(a_n + 128), o[2] = {roff(nd, 0), roff(nd, 1)};
      hload(hf, nd);
#pragma unroll
      for (int k = 0; k < 4; k++) lds128(v + 4 * k, radr(o[k & 1], k));
      wg_fence(); mma_h(acc, hf); wg_commit();
      body(IC<2>());
      STAMP(9);
      flush();
      __syncwarp();
      mbar_arrive(sb + BAR_X, lane == 0);
      wg_fence();
      mma_m(acc);
#pragma unroll
      for (int k = 0; k < 4; k++) { fin(acc, v + 4 * k, k);
        asm volatile("{.reg .pred p; setp.lt.u32 p, %5, %6; @p st.global.v4.b32 [%0], {%1,%2,%3,%4};}" :: "l"((const char*)p.out + (size_t)node0 * 128 + o[k & 1] + (k >> 1) * 64), "r"(v[4 * k]), "r"(v[4 * k + 1]), "r"(v[4 * k + 2]), "r"(v[4 * k + 3]), "r"(o[k & 1]), "r"(nloc * 128) : "memory"); }
    }
    asm volatile("{.reg .pred p, q; setp.neu.f32 p, %1, 0f00000000; setp.ne.or.u32 p, %2, 0, p; bar.red.or.pred q, 5, 512, p; selp.u32 %0, 1, 0, q;}" : "=r"(bad) : "f"(chk), "r"(lds32(sb + OFF_MISC + 12)) : "memory");
    STAMP(11);
   } else { asm volatile("cp.async.wait_all;" ::: "memory"); bar_sync(5, 384); }
  }
  if (bad) slow_path(p, wid, lane, node0, nloc);
}

}

typedef CUresult (*EncodeFn)(CUtensorMap*, CUtensorMapDataType, cuuint32_t, void*, const cuuint64_t*, const cuuint64_t*, const cuuint32_t*, const cuuint32_t*,
                             CUtensorMapInterleave, CUtensorMapSwizzle, CUtensorMapL2promotion, CUtensorMapFloatOOBfill);

extern "C" void kernel_launch(void* const* d_in, const int* in_sizes, int n_in, void* d_out, int out_size) {
  Params p; Maps maps;
  p.h = (const uint4*)d_in[0]; p.pos = (const uint16_t*)d_in[1]; p.ea = (const uint4*)d_in[2];
  p.src = (const int*)d_in[3]; p.dst = (const int*)d_in[4];
  p.we = (const uint16_t*)d_in[5]; p.wx = (const uint16_t*)d_in[6]; p.wh = (const uint16_t*)d_in[7];
  p.out = (uint16_t*)d_out;
  p.N = in_sizes[0] / 64; p.E = in_sizes[3];
  p.EPC = ((p.E + G * 4 - 1) / (G * 4)) * 4;
  p.magic = (uint32_t)(((uint64_t)G << 24) / (uint64_t)p.N);
  p.inv = (1ull << 56) / p.magic;
  const uint64_t ea0 = (uint64_t)d_in[2], ea1 = ea0 + (uint64_t)p.E * 32 - 1;
  p.force_slow = ((ea0 >> 32) != (ea1 >> 32)) || (ea0 & 31) || (p.E & 3);
  void* qp = nullptr;
  cudaGetSymbolAddress(&qp, g_q);
  p.q = (char*)qp;
  if (((uint64_t)p.q >> 32) != (((uint64_t)p.q + QBYTES) >> 32)) p.q += QBYTES;
  cudaGetSymbolAddress((void**)&p.sync, g_sync); cudaGetSymbolAddress((void**)&p.xe, g_xe);
  cudaGetSymbolAddress((void**)&p.xa, g_xa); cudaGetSymbolAddress((void**)&p.xb, g_xb);
  const int df[10] = {18, 250, 900, 500, 250, 59, 0xbba};
  for (int i = 0; i < 10; i++) p.tune[i] = df[i];
  p.qcode = 0x54970832b1a6ull;
  p.ctam = p.tune[5];
  void* fn = nullptr; cudaDriverEntryPointQueryResult qr;
  cudaGetDriverEntryPoint("cuTensorMapEncodeTiled", &fn, cudaEnableDefault, &qr);
  auto mk = [&](CUtensorMap* tm, void* base, int rows, int box = 64) {
    const cuuint64_t dim[2] = {64, (cuuint64_t)rows}, str[1] = {128}; const cuuint32_t bx[2] = {64, (cuuint32_t)box}, es[2] = {1, 1};
    ((EncodeFn)fn)(tm, CU_TENSOR_MAP_DATA_TYPE_BFLOAT16, 2, base, dim, str, bx, es, CU_TENSOR_MAP_INTERLEAVE_NONE, CU_TENSOR_MAP_SWIZZLE_128B,
                   CU_TENSOR_MAP_L2_PROMOTION_NONE, CU_TENSOR_MAP_FLOAT_OOB_FILL_NONE);
  };
  mk(&maps.m[TM_H / 128], d_in[0], p.N); mk(&maps.m[TM_WE / 128], d_in[5], 145); mk(&maps.m[TM_WH / 128], d_in[7], 128); mk(&maps.m[TM_Q / 128], p.q, p.N, 16);
  for (int k = 0; k < 2; k++) {
    void* xp = (void*)(k ? p.xb : p.xa);
    const cuuint64_t dim[2] = {(cuuint64_t)G * 64, (cuuint64_t)G}, str[1] = {(cuuint64_t)G * (128 << k)}; const cuuint32_t bx[2] = {64, (cuuint32_t)(k ? BROWS : G)}, es[2] = {1, 1};
    ((EncodeFn)fn)(&maps.m[TM_XA / 128 + k], k ? CU_TENSOR_MAP_DATA_TYPE_UINT32 : CU_TENSOR_MAP_DATA_TYPE_UINT16, 2, xp, dim, str, bx, es, CU_TENSOR_MAP_INTERLEAVE_NONE,
                   CU_TENSOR_MAP_SWIZZLE_NONE, CU_TENSOR_MAP_L2_PROMOTION_NONE, CU_TENSOR_MAP_FLOAT_OOB_FILL_NONE);
  }
  cudaFuncSetAttribute(egnn_kernel, cudaFuncAttributeMaxDynamicSharedMemorySize, SMEM);
  egnn_kernel<<<G, NTHR, SMEM>>>(p, maps);
}
```

```cpp
#include <cuda_runtime.h>
#include <cuda_bf16.h>
#include <cuda_fp16.h>
#include <cuda.h>
#include <stdint.h>
#pragma nv_diag_suppress 549

#define PFN p.tune[0]
#define PFNS p.tune[1]
#define BDEL p.tune[2]
#define DEF0 p.tune[3]
#define DEFNS p.tune[4]
#define CTAM p.ctam
#define QREV p.tune[6]
#define QCODE p.qcode
#define FIRSTSEQ mu(0); mu(1); fi(0); mu(2); fi(1);
#define BODYSEQ tl_(); cv(2); hc(0); ad(0); ad(1); cv(1); fi(2); ad(2); mu(6); un(); mu(3); fi(3); hc(1); ex0(); fi(6); cv(3); \
  cv(0); he(2); he(6); he(5); he(7); he(4); ad(3); mu(4); fi(4); he(1); he(0); ex1(); mu(7); fi(7); he(3); mu(5); \
  issue(); ex2(); hs(1); hs(0); hs(7); hs(2); mu(2); mu(1); mu(0); hs(3); fi(5); hc(2); hc(3); ad(5); pf(); fi(0); \
  hs(5); ad(6); ad(7); hs(6); ad(4); hs(4); fi(1);
#define LASTSEQ hc(0); mu(3); fi(2); un(); ad(0); ad(1); mu(4); fi(3); hc(1); mu(5); fi(4); ad(2); mu(6); fi(5); ad(3); hc(2); mu(7); fi(6); fi(7); ad(4); ad(5); hc(3); ad(6); ad(7); pf();
namespace {

constexpr int G = 132;
constexpr int NTHR = 512, NWK = 352, NCH = 5;
constexpr int NST = 3, STG = 2560;
constexpr int BROWS = 44, RNB = 2, PADM = 33;
constexpr int SCAP = 448;

constexpr int OFF_H = 0;
constexpr int OFF_W = 49152;
constexpr int OFF_WD = OFF_W + 16384;
constexpr int OFF_W3 = OFF_WD + 1024;
constexpr int OFF_P2 = OFF_W3 + 2048;
constexpr int OFF_RING = OFF_P2 + 24576;
constexpr int OFF_TE = OFF_RING + 12 * NST * STG;
constexpr int OFF_TS = OFF_TE + SCAP * 64;
constexpr int OFF_INV = OFF_TS - 768;
constexpr int OFF_GP = OFF_TS + SCAP * 32;
constexpr int OFF_WX = OFF_GP + 3072;
constexpr int OFF_LEN = OFF_WX + 128;
constexpr int OFF_MISC = OFF_LEN + 128;
constexpr int OFF_BAR = OFF_MISC + 48;
constexpr int SMEM = OFF_BAR + 256;
static_assert(SMEM <= 232448, "smem");
constexpr uint32_t sb = 1024;
constexpr int OFF_SRCI = OFF_TE;
constexpr int OFF_SB = OFF_RING, OFF_SA = OFF_SB + 34816, OFF_AX = OFF_SA + 32768, OFF_DST = OFF_H + 24576;
constexpr int OFF_WS = OFF_AX + 17408;
constexpr int OFF_BC = OFF_WS + 2304;
constexpr int OFF_CNT = OFF_P2;
constexpr int OFF_DH = OFF_CNT + 2176;
constexpr int OFF_POS = OFF_DH + 128;
constexpr int OFF_EXT = OFF_POS + 3072;
constexpr int OFF_XB = OFF_EXT + 1024, XPAD = G * 256;
static_assert(OFF_XB + XPAD + 1028 <= OFF_RING + 12 * STG && OFF_XB % 128 == 0 && OFF_BC + 544 <= OFF_TE && OFF_P2 % 1024 == 0 && OFF_SA % 1024 == 0 && SCAP * 64 >= 24576, "staging");
constexpr int BAR_DST = OFF_BAR, BAR_SRC = BAR_DST + 40, BAR_T = BAR_SRC + 24, BAR_W = BAR_T + 48, BAR_PS = BAR_W + 8, BAR_AW = BAR_PS + 8,
              BAR_QP = BAR_AW + 8, BAR_QR = BAR_QP + 8, BAR_HA = BAR_QR + 8, BAR_EP = BAR_HA + 8, BAR_AX = BAR_EP + 8, BAR_AI = BAR_AX + 8, BAR_HB = BAR_AI + 8, BAR_U = BAR_HB + 8, BAR_WH = BAR_U + 8, BAR_M = BAR_WH + 8, BAR_X = BAR_M + 8, BAR_END = BAR_X + 8;
static_assert(BAR_END <= OFF_BAR + 256, "barriers");
constexpr uint32_t QBYTES = 8u << 20;

__device__ __align__(256) uint4 g_xa[G * G * 8];
__device__ __align__(256) uint4 g_xb[G * G * 16];
__device__ __align__(256) uint2 g_xe[G * G * 32];
__device__ __align__(256) uint4 g_q[2 * QBYTES / 16];
__device__ __align__(256) uint32_t g_sync[8];
#define STAMP(k)

struct Maps { CUtensorMap m[6]; };
constexpr int TM_H = 0, TM_WE = 128, TM_WH = 256, TM_Q = 384, TM_XA = 512, TM_XB = 640;
struct Params {
  const int* dst; uint32_t* sync; int E, EPC, N, ctam; unsigned long long inv; uint32_t magic; int force_slow;
  const int* src; const uint16_t* pos; const uint4* ea; const uint16_t* we; const uint16_t* wx; char* q;
  const uint4* xa; const uint4* xb; uint2* xe; uint16_t* out; const uint4* h; const uint16_t* wh;
  int tune[10]; unsigned long long qcode;
};
template<int V> struct IC { static constexpr int value = V; };

#define R32(d) "+f"(d[0]),"+f"(d[1]),"+f"(d[2]),"+f"(d[3]),"+f"(d[4]),"+f"(d[5]),"+f"(d[6]),"+f"(d[7]),"+f"(d[8]),"+f"(d[9]),"+f"(d[10]),"+f"(d[11]),"+f"(d[12]),"+f"(d[13]),"+f"(d[14]),"+f"(d[15]),"+f"(d[16]),"+f"(d[17]),"+f"(d[18]),"+f"(d[19]),"+f"(d[20]),"+f"(d[21]),"+f"(d[22]),"+f"(d[23]),"+f"(d[24]),"+f"(d[25]),"+f"(d[26]),"+f"(d[27]),"+f"(d[28]),"+f"(d[29]),"+f"(d[30]),"+f"(d[31])
#define S32 "{%0,%1,%2,%3,%4,%5,%6,%7,%8,%9,%10,%11,%12,%13,%14,%15,%16,%17,%18,%19,%20,%21,%22,%23,%24,%25,%26,%27,%28,%29,%30,%31}"
#define DI __device__ __forceinline__

constexpr uint64_t DHI = ((uint64_t)(1024 >> 4) << 32) | (1ull << 62);
template<int SD> DI void rs64b(float (&d)[32], uint32_t a0, uint32_t a1, uint32_t a2, uint32_t a3, uint64_t db) {
  asm volatile("wgmma.mma_async.sync.aligned.m64n64k16.f32.bf16.bf16 " S32 ", {%32,%33,%34,%35}, %36, %37, 1, 1, 1;" : R32(d) : "r"(a0), "r"(a1), "r"(a2), "r"(a3), "l"(db), "n"(SD)); }
template<int SD> DI void rs64h(float (&d)[32], uint32_t a0, uint32_t a1, uint32_t a2, uint32_t a3, uint64_t db) {
  asm volatile("wgmma.mma_async.sync.aligned.m64n64k16.f32.f16.f16 " S32 ", {%32,%33,%34,%35}, %36, %37, 1, 1, 1;" : R32(d) : "r"(a0), "r"(a1), "r"(a2), "r"(a3), "l"(db), "n"(SD)); }
template<int SD> DI void ss64(float (&d)[32], uint64_t da, uint64_t db) {
  asm volatile("wgmma.mma_async.sync.aligned.m64n64k16.f32.bf16.bf16 " S32 ", %32, %33, %34, 1, 1, 0, 1;" : R32(d) : "l"(da), "l"(db), "n"(SD)); }
DI void trap_if(bool c) { asm volatile("{.reg .pred p; setp.eq.u32 p, %0, 0; @p bra.uni LT_%=; trap; LT_%=:}" :: "r"((uint32_t)c)); }
DI void wg_fence() { asm volatile("wgmma.fence.sync.aligned;" ::: "memory"); }
DI void wg_commit() { asm volatile("wgmma.commit_group.sync.aligned;" ::: "memory"); }
DI void wg_wait0() { asm volatile("wgmma.wait_group.sync.aligned 0;" ::: "memory"); }
DI void fence_regs(float (&d)[32]) { asm volatile("" : R32(d) :: "memory"); }
DI void proxy_fence() { asm volatile("fence.proxy.async.shared::cta;" ::: "memory"); }
DI uint64_t pol_first() { uint64_t r; asm("createpolicy.fractional.L2::evict_first.b64 %0, 1.0;" : "=l"(r)); return r; }
DI float tanh_ap(float x) { float y; asm("tanh.approx.f32 %0, %1;" : "=f"(y) : "f"(x)); return y; }
DI float silu_h(float y) { return fmaf(y, tanh_ap(y), y); }
DI uint32_t pack_bf16(float lo, float hi) { uint32_t r; asm("cvt.rn.bf16x2.f32 %0, %1, %2;" : "=r"(r) : "f"(hi), "f"(lo)); return r; }
DI uint32_t pack_f16(float lo, float hi) { uint32_t r; asm("cvt.rn.f16x2.f32 %0, %1, %2;" : "=r"(r) : "f"(hi), "f"(lo)); return r; }
DI float bf_lo(uint32_t v) { return __uint_as_float(v << 16); }
DI float bf_hi(uint32_t v) { return __uint_as_float(v & 0xFFFF0000u); }
DI uint32_t b2h(uint32_t v, float s) { return pack_f16(s * bf_lo(v), s * bf_hi(v)); }
DI void mbar_wait(uint32_t bar, uint32_t parity = 0) {
  asm volatile("{.reg .pred p, q; .reg .u32 c; mov.u32 c, 0;\n"
    "LW_%=: mbarrier.try_wait.parity.shared::cta.b64 p, [%0], %1;\n add.u32 c, c, 1; setp.lt.and.u32 q, c, 0x200000, !p;\n @q bra.uni LW_%=;}" :: "r"(bar), "r"(parity) : "memory");
}
DI void mbar_arrive(uint32_t bar, int p = 1) { asm volatile("{.reg .pred p; setp.ne.b32 p, %1, 0; @p mbarrier.arrive.shared::cta.b64 _, [%0];}" :: "r"(bar), "r"(p) : "memory"); }
DI void bar_sync(int id, int n) { asm volatile("bar.sync %0, %1;" :: "r"(id), "r"(n) : "memory"); }
DI void bar_arrive(int id, int n) { asm volatile("bar.arrive %0, %1;" :: "r"(id), "r"(n) : "memory"); }
DI __nv_bfloat162 b2(uint32_t v) { return *(__nv_bfloat162*)&v; }
DI uint32_t u2(__nv_bfloat162 v) { return *(uint32_t*)&v; }
DI uint32_t hsq(uint32_t v) { return u2(__hmul2(b2(v), b2(v))); }
DI uint32_t hsub(uint32_t a, uint32_t b) { return u2(__hsub2(b2(a), b2(b))); }
DI uint32_t hhalf(uint32_t v) { return u2(__hmul2(b2(v), __floats2bfloat162_rn(0.5f, 0.5f))); }
DI uint32_t mag2(uint32_t m, uint32_t v) { return __vmaxu2(m, v & 0x7FFF7FFFu); }
DI uint32_t hmag(uint32_t m, uint32_t v) { const __half2 r = __hmax2(*(const __half2*)&m, __habs2(*(const __half2*)&v)); return *(const uint32_t*)&r; }
DI uint32_t magr(uint32_t m) { return max(m & 0xFFFF, m >> 16); }
DI void sts128(uint32_t a, uint32_t x, uint32_t y, uint32_t z, uint32_t w) { asm volatile("st.shared.v4.u32 [%0], {%1,%2,%3,%4};" :: "r"(a), "r"(x), "r"(y), "r"(z), "r"(w) : "memory"); }
DI void sts64(uint32_t a, uint32_t x, uint32_t y) { asm volatile("st.shared.v2.u32 [%0], {%1,%2};" :: "r"(a), "r"(x), "r"(y) : "memory"); }
DI void sts32(uint32_t a, uint32_t x) { asm volatile("st.shared.u32 [%0], %1;" :: "r"(a), "r"(x) : "memory"); }
DI void sts16(uint32_t a, uint32_t x) { asm volatile("st.shared.u16 [%0], %1;" :: "r"(a), "h"((uint16_t)x) : "memory"); }
DI void lds128(uint32_t* v, uint32_t a) { asm volatile("ld.shared.v4.u32 {%0, %1, %2, %3}, [%4];" : "=r"(v[0]), "=r"(v[1]), "=r"(v[2]), "=r"(v[3]) : "r"(a) : "memory"); }
DI void lds64(uint32_t& x, uint32_t& y, uint32_t a) { asm volatile("ld.shared.v2.u32 {%0, %1}, [%2];" : "=r"(x), "=r"(y) : "r"(a) : "memory"); }
DI uint32_t lds32(uint32_t a) { uint32_t x; asm volatile("ld.shared.u32 %0, [%1];" : "=r"(x) : "r"(a) : "memory"); return x; }
DI uint32_t lds16(uint32_t a) { uint32_t x; asm volatile("ld.shared.u16 %0, [%1];" : "=r"(x) : "r"(a) : "memory"); return x; }
DI uint32_t atoms_add(uint32_t a, uint32_t v) { uint32_t r; asm volatile("atom.shared.add.u32 %0, [%1], %2;" : "=r"(r) : "r"(a), "r"(v) : "memory"); return r; }
DI void bulk_load(uint32_t dst, const void* src, uint32_t bytes, uint32_t bar) {
  asm volatile("cp.async.bulk.shared::cluster.global.mbarrier::complete_tx::bytes.L2::cache_hint [%0], [%1], %2, [%3], %4;" :: "r"(dst), "l"(src), "r"(bytes), "r"(bar), "l"(pol_first()) : "memory"); }
DI void mbar_expect(uint32_t bar, uint32_t bytes) { asm volatile("mbarrier.arrive.expect_tx.shared::cta.b64 _, [%0], %1;" :: "r"(bar), "r"(bytes) : "memory"); }
DI void mbar_init(uint32_t bar, int n) { asm volatile("mbarrier.init.shared::cta.b64 [%0], %1;" :: "r"(bar), "r"(n) : "memory"); }
DI void tma_load(uint32_t dst, uint64_t tm, int row, uint32_t bar) {
  asm volatile("cp.async.bulk.tensor.2d.shared::cluster.global.mbarrier::complete_tx::bytes.L2::cache_hint [%0], [%1, {%3, %4}], [%2], %5;" :: "r"(dst), "l"(tm), "r"(bar), "r"(0), "r"(row), "l"(pol_first()) : "memory"); }
DI void tma_store(uint64_t tm, int col, int row, uint32_t src) {
  asm volatile("cp.async.bulk.tensor.2d.global.shared::cta.bulk_group [%0, {%2, %3}], [%1];" :: "l"(tm), "r"(src), "r"(col), "r"(row) : "memory"); }
DI void bulk_commit() { asm volatile("cp.async.bulk.commit_group;" ::: "memory"); }
DI uint2 ld_poll2(const void* a) { uint2 v; asm volatile("ld.relaxed.gpu.global.v2.u32 {%0, %1}, [%2];" : "=r"(v.x), "=r"(v.y) : "l"(a) : "memory"); return v; }
DI void st_ext(uint2* a, uint32_t v, uint32_t ep) { asm volatile("st.relaxed.gpu.global.v2.u32 [%0], {%1, %2};" :: "l"(a), "r"(v), "r"(ep) : "memory"); }
DI uint32_t ext_get(const uint2* a, uint32_t ep) { uint2 v; int spin = 0; do { v = ld_poll2(a); trap_if(++spin > 4000000); } while (__any_sync(~0u, v.y != ep)); return v.x; }
DI void bulk_wait() { asm volatile("cp.async.bulk.wait_group 0;" ::: "memory"); }
DI void hint_signal(uint32_t* c) { asm volatile("red.relaxed.gpu.global.add.u32 [%0], 1;" :: "l"(c) : "memory"); }
DI void hint_wait(const uint32_t* c, uint32_t target) { uint32_t v; int spin = 0;
  do { asm volatile("ld.relaxed.gpu.global.u32 %0, [%1];" : "=r"(v) : "l"(c) : "memory"); trap_if(++spin > 4000000); } while (__any_sync(~0u, (int)(v - target) < 0)); }
DI void stsm4(uint32_t a, uint32_t x, uint32_t y, uint32_t z, uint32_t w) { asm volatile("stmatrix.sync.aligned.m8n8.x4.shared.b16 [%0], {%1,%2,%3,%4};" :: "r"(a), "r"(x), "r"(y), "r"(z), "r"(w) : "memory"); }
DI void ldsm4(uint32_t* v, uint32_t a) { asm volatile("ldmatrix.sync.aligned.m8n8.x4.shared.b16 {%0,%1,%2,%3}, [%4];" : "=r"(v[0]), "=r"(v[1]), "=r"(v[2]), "=r"(v[3]) : "r"(a) : "memory"); }
DI void ldsm4t(uint32_t* v, uint32_t a) { asm volatile("ldmatrix.sync.aligned.m8n8.x4.trans.shared.b16 {%0,%1,%2,%3}, [%4];" : "=r"(v[0]), "=r"(v[1]), "=r"(v[2]), "=r"(v[3]) : "r"(a) : "memory"); }
DI uint32_t mad16(uint32_t x, uint32_t m, uint32_t c) { uint32_t r; asm("dp2a.lo.u32.u32 %0, %1, %2, %3;" : "=r"(r) : "r"(x), "r"(m), "r"(c)); return r; }
DI bool wbad(uint32_t m, uint32_t hi) { return m > hi || (m && m < 0x3980); }

__device__ __noinline__ void slow_path(const Params& p, int wid, int lane, int node0, int nloc) {
  const uint32_t ab = sb + OFF_P2 + wid * 8704;
  for (int i = lane; i < 32 * 68; i += 32) sts32(ab + i * 4, 0);
  __syncwarp();
  const uint32_t wdv = __ldg((const uint32_t*)(p.we + 128 * 64) + lane), wxv = __ldg((const uint32_t*)p.wx + lane);
  const int nb0 = node0 + wid * 32, cntn = max(0, min(32, nloc - wid * 32));
  auto dot = [&](uint32_t hv, const uint16_t* w, int K2, float& y0, float& y1) {
#pragma unroll 4
    for (int k = 0; k < K2; k++) {
      const uint32_t hk = __shfl_sync(~0u, hv, k), wa = __ldg((const uint32_t*)(w + 2 * k * 64) + lane), wb = __ldg((const uint32_t*)(w + (2 * k + 1) * 64) + lane);
      y0 = fmaf(bf_lo(hk), bf_lo(wa), fmaf(bf_hi(hk), bf_lo(wb), y0)); y1 = fmaf(bf_lo(hk), bf_hi(wa), fmaf(bf_hi(hk), bf_hi(wb), y1));
    }
  };
  auto silu = [](float x) { return x / (1.f + __expf(-x)); };
#pragma unroll 1
  for (int base = 0; base < p.E; base += 32) {
    const int e = base + lane;
    const uint32_t dl = e < p.E ? (uint32_t)(__ldg(p.dst + e) - nb0) : 0xFFFFFFFFu;
    uint32_t mk = __ballot_sync(~0u, dl < (uint32_t)cntn);
    while (mk) {
      const int l = __ffs(mk) - 1; mk &= mk - 1;
      const int ee = base + l, n = __shfl_sync(~0u, dl, l), s = __ldg(p.src + ee);
      const uint16_t *po = p.pos + (size_t)(nb0 + n) * 3, *pp = p.pos + (size_t)s * 3;
      const uint32_t dxy = hsub(__ldg(po) | (__ldg(po + 1) << 16), __ldg(pp) | (__ldg(pp + 1) << 16)), dz = hsub(__ldg(po + 2), __ldg(pp + 2));
      const uint32_t sq = hsq(dxy); const float d2 = bf_lo(sq) + bf_hi(sq) + bf_lo(hsq(dz));
      float y0 = d2 * bf_lo(wdv), y1 = d2 * bf_hi(wdv);
      dot(__ldg((const uint32_t*)(p.h + (size_t)(nb0 + n) * 8) + lane), p.we, 32, y0, y1);
      dot(__ldg((const uint32_t*)(p.h + (size_t)s * 8) + lane), p.we + 64 * 64, 32, y0, y1);
      dot(__ldg((const uint32_t*)(p.ea + (size_t)ee * 2) + (lane & 7)), p.we + 129 * 64, 8, y0, y1);
      const uint32_t mm = pack_bf16(silu(y0), silu(y1));
      float c = bf_lo(mm) * bf_lo(wxv) + bf_hi(mm) * bf_hi(wxv);
#pragma unroll
      for (int o = 16; o; o >>= 1) c += __shfl_xor_sync(~0u, c, o);
      const uint32_t a = ab + n * 272;
      uint32_t x0, x1; lds64(x0, x1, a + lane * 8);
      sts64(a + lane * 8, __float_as_uint(__uint_as_float(x0) + bf_lo(mm)), __float_as_uint(__uint_as_float(x1) + bf_hi(mm)));
      if (lane < 3) { const float df = lane == 0 ? bf_lo(dxy) : lane == 1 ? bf_hi(dxy) : bf_lo(dz); sts32(a + 256 + lane * 4, __float_as_uint(fmaf(c, df, __uint_as_float(lds32(a + 256 + lane * 4))))); }
    }
  }
  __syncwarp();
#pragma unroll 1
  for (int n = 0; n < cntn; n++) {
    uint32_t x0, x1; lds64(x0, x1, ab + n * 272 + lane * 8);
    const uint32_t hv = __ldg((const uint32_t*)(p.h + (size_t)(nb0 + n) * 8) + lane);
    float y0 = 0.f, y1 = 0.f;
    dot(hv, p.wh, 32, y0, y1); dot(pack_bf16(__uint_as_float(x0), __uint_as_float(x1)), p.wh + 64 * 64, 32, y0, y1);
    ((uint32_t*)p.out)[(size_t)(nb0 + n) * 32 + lane] = u2(__hadd2(b2(hv), b2(pack_bf16(silu(y0), silu(y1)))));
    if (lane < 3) p.out[(size_t)p.N * 64 + (size_t)(nb0 + n) * 3 + lane] = (uint16_t)pack_bf16(bf_lo(__ldg(p.pos + (size_t)(nb0 + n) * 3 + lane)) + __uint_as_float(lds32(ab + n * 272 + 256 + lane * 4)), 0.f);
  }
}

__global__ void __launch_bounds__(NTHR, 1) egnn_kernel(const __grid_constant__ Params p, const __grid_constant__ Maps maps) {
  const uint64_t tmb = (uint64_t)&maps;
  extern __shared__ __align__(1024) unsigned char smraw[];
  const int tid = threadIdx.x, cta = blockIdx.x * CTAM % G;
  const int e0 = cta * p.EPC, n4 = max(0, min(p.EPC, p.E - e0)) >> 2;
  STAMP(0);
  if (tid == NWK) {
#pragma unroll 1
    for (int k = 0; k < NCH; k++) { const int nb = max(0, min(NWK, n4 - k * NWK)) * 16;
      mbar_init(sb + BAR_DST + k * 8, 1);
      asm volatile("fence.mbarrier_init.release.cluster;" ::: "memory");
      mbar_expect(sb + BAR_DST + k * 8, nb);
      if (nb) bulk_load(sb + OFF_DST + k * NWK * 16, (const char*)(p.dst + e0) + k * NWK * 16, nb, sb + BAR_DST + k * 8); }
  }
  const int lane = tid & 31, wid = __shfl_sync(~0u, tid >> 5, 0), w = wid & 3;
  asm volatile("{.reg .pred p; setp.eq.u32 p, %2, 384; @p cp.async.cg.shared.global [%0], [%1], 16;}" :: "r"(sb + OFF_LEN - 192 + (tid >> 1)), "l"(p.sync), "r"(tid & 415) : "memory");

  auto first_node = [&](int c) { return (int)((c * p.inv + 0xFFFFFFFFull) >> 32); };
  const int node0 = first_node(cta), nloc = min(first_node(cta + 1), p.N) - node0;
  const uint32_t ealo = (uint32_t)(uint64_t)p.ea;
  const int epad = min(e0, p.E - 1);
  if (wid >= 12) {
    const int t = tid - 384;
    auto load_h = [&](int b) { mbar_expect(sb + BAR_T + b * 8, 8192); tma_load(sb + OFF_H + b * 8192, tmb + TM_H, node0 + b * 64, sb + BAR_T + b * 8); };
    uint32_t pv[9], ev = 0;
#pragma unroll
    for (int i = 0; i < 3; i++) { const uint16_t* pp = p.pos + (size_t)(node0 + t + 128 * i) * 3;
      pv[3 * i] = pv[3 * i + 1] = pv[3 * i + 2] = 0;
      asm volatile("{.reg .pred p; setp.lt.s32 p, %4, %5;\n @p ld.global.nc.u16 %0, [%3];\n @p ld.global.nc.u16 %1, [%3+2];\n @p ld.global.nc.u16 %2, [%3+4];}"
        : "+r"(pv[3 * i]), "+r"(pv[3 * i + 1]), "+r"(pv[3 * i + 2]) : "l"(pp), "r"(t + 128 * i), "r"(p.N - node0)); }
    asm volatile("{.reg .pred p; setp.lt.u32 p, %3, 8; @p ld.global.nc.u32 %0, [%1]; @p st.global.v4.u32 [%2], {%4, %4, %4, %4};}"
      : "+r"(ev) : "l"((const uint32_t*)(p.ea + (size_t)epad * 2) + t), "l"(p.q + (size_t)(p.N + cta * PADM) * 128 + t * 16), "r"(t), "r"(0xF700F700u) : "memory");
    asm volatile("cp.async.wait_all;" ::: "memory");
    __syncwarp();
    const uint32_t e = lds32(sb + OFF_LEN + 8 + w * 16) + 1;
    {
      const uint32_t tg = (1 + e % 3) << 30, v = ((tg >> 16) + 512 + (lane & 7) * 4) * 0x10001u;
      if (t == 0) sts32(sb + OFF_MISC + 32, e);
#pragma unroll
      for (int i = 0; i < 9; i++) sts128(sb + OFF_SA + t * 16 + i * 2048, v, v + 0x10001u, v + 0x20002u, v + 0x30003u);
      bar_sync(6, NTHR);
      mbar_arrive(sb + BAR_EP, lane == 0);
#pragma unroll
      for (int i = 0; i < 17; i++) sts128(sb + OFF_SB + t * 16 + i * 2048, tg, tg, tg, tg); }
    uint32_t mp = 0;
#pragma unroll
    for (int i = 0; i < 3; i++) { sts64(sb + OFF_POS + (t + 128 * i) * 8, pv[3 * i] | (pv[3 * i + 1] << 16), pv[3 * i + 2]); mp = mag2(mag2(mp, pv[3 * i] | (pv[3 * i + 1] << 16)), pv[3 * i + 2]); }
    proxy_fence();
    __syncwarp();
    mbar_arrive(sb + BAR_PS, lane == 0);
    mbar_wait(sb + BAR_W);
    {
      uint32_t v[4], u[4]; const int r = t >> 3, c = t & 7;
      lds128(v, sb + OFF_WS + 128 + t * 16); lds128(u, sb + OFF_WS + c * 16);
      const uint32_t x = lds32(sb + OFF_WS + 2176 + lane * 4);
      sts128(sb + OFF_W3 + r * 128 + ((c ^ (r & 7)) << 4), b2h(v[0], .5f), b2h(v[1], .5f), b2h(v[2], .5f), b2h(v[3], .5f));
      const float s = ((r & 1) || r == 6) ? 0.f : .5f;
      if (t < 64) sts128(sb + OFF_WD + r * 128 + ((c ^ r) << 4), b2h(u[0], s), b2h(u[1], s), b2h(u[2], s), b2h(u[3], s));
      if (t < 32) sts32(sb + OFF_WX + (t & 3) * 32 + (t >> 2) * 4, b2h(x, 1.f));
      const uint32_t m3 = __reduce_max_sync(~0u, magr(mag2(mag2(mag2(mag2(0, v[0]), v[1]), v[2]), v[3]))), md = __reduce_max_sync(~0u, magr(mag2(mag2(mag2(mag2(0, u[0]), u[1]), u[2]), u[3])));
      if (wbad(m3, 0x4000) || wbad(md, 0x4000) || wbad(__reduce_max_sync(~0u, magr(mag2(0, x))), 0x4700) || magr(mp) >= 0x4200 || magr(mag2(0, ev)) >= 0x4380) sts32(sb + OFF_MISC + 8, 1);
    }
    if (w == 1) {
#pragma unroll 1
      for (int b = 0; b < 3; b++) { mbar_wait(sb + BAR_SRC + b * 8); if (lane == 0) load_h(b); }
    }
    bar_sync(3, 128);
    const uint32_t frag = (w * 16 + (lane & 15)) * 128 + (((lane >> 4) ^ (lane & 7)) << 4);
    uint32_t mq = 0;
#pragma unroll 1
    for (int b = 0; b < 6; b++) {
      float acc[32];
      const uint64_t da = DHI | (((sb + OFF_H) >> 4) + b * 512), db = DHI | ((sb + OFF_W) >> 4);
      const uint32_t v0 = lds16(sb + OFF_POS + b * 512 + w * 128 + lane * 2), v1 = lds16(sb + OFF_POS + 64 + b * 512 + w * 128 + lane * 2);
      mbar_wait(sb + BAR_T + b * 8);
      if (b == 0) STAMP(25);
      if (b == 5) STAMP(26);
      wg_fence();
      ss64<0>(acc, da, db); ss64<1>(acc, da + 2, db + 128); ss64<1>(acc, da + 4, db + 256); ss64<1>(acc, da + 6, db + 384);
      wg_commit();
      if (b == 0) mbar_wait(sb + BAR_AW);
      if (t == 32 && b < 3) load_h(b + 3);
      __syncwarp();
      uint32_t ff[6], fg[6];
#pragma unroll
      for (int j = 0; j < 6; j++) { ff[j] = (__byte_perm((j & 1) ? v1 : v0, 0, 0x4140) >> (3 * (j >> 1))) & 0x00070007u; fg[j] = __vsub2(0x00040004u, ff[j]);
        asm volatile("" : "+r"(ff[j]), "+r"(fg[j])); }
      wg_wait0(); fence_regs(acc);
      uint32_t o[16];
#pragma unroll
      for (int j = 0; j < 16; j++) o[j] = pack_f16(.5f * acc[2 * j], .5f * acc[2 * j + 1]);
#pragma unroll
      for (int j = 0; j < 6; j++) {
        const uint32_t m = o[j] & 0x7FFF7FFFu; mq = __vmaxu2(mq, m);
        o[j] = (__viaddmax_s16x2(m, fg[j], 0) & 0xFFF8FFF8u) | ff[j] | (o[j] & 0x80008000u); }
      if (b == 4) mbar_wait(sb + BAR_AX);
      const uint32_t qs = sb + OFF_SA + b * 8192;
#pragma unroll
      for (int j = 0; j < 4; j++) stsm4((qs + frag) ^ (j << 5), o[4 * j], o[4 * j + 1], o[4 * j + 2], o[4 * j + 3]);
      proxy_fence();
      __syncwarp();
      if (lane == 0 && b * 64 + w * 16 < nloc) tma_store(tmb + TM_Q, 0, node0 + b * 64 + w * 16, qs + w * 2048);
    }
    if (lane == 0) bulk_commit();
    { const uint32_t m = __reduce_max_sync(~0u, magr(mq)); if (lane == 0) sts32(sb + OFF_MISC + 16 + w * 4, m); }
    asm volatile("setmaxnreg.dec.sync.aligned.u32 32;");
    bulk_wait();
    bar_sync(3, 128);
    if (w == 0) {
      STAMP(18);
      uint32_t mv[4]; lds128(mv, sb + OFF_MISC + 16);
      const uint32_t mx = max(max(mv[0], mv[1]), max(mv[2], mv[3]));
      mbar_arrive(sb + BAR_QR, lane == 0);
      STAMP(19);
      if (lane == 0) {
        if (nloc > 0 && (mx >= 0x7BF0 || mx < 0x1400)) asm volatile("st.relaxed.gpu.global.u32 [%0+4], %1;" :: "l"(p.sync), "r"(e) : "memory");
        asm volatile("red.release.gpu.global.add.u32 [%0], 1;" :: "l"(p.sync) : "memory");
      }
      __syncwarp();
      uint32_t c, f; int spin = 0;
      do { asm volatile("ld.acquire.gpu.global.v2.u32 {%0, %1}, [%2];" : "=r"(c), "=r"(f) : "l"(p.sync) : "memory"); trap_if(++spin > 4000000); } while (__any_sync(~0u, (int)(c - e * G) < 0));
      if (f == e) sts32(sb + OFF_MISC + 8, 1);
      if (cta == 0 && lane == 0) asm volatile("st.relaxed.gpu.global.u32 [%0+8], %1;" :: "l"(p.sync), "r"(e) : "memory");
      STAMP(20);
      __syncwarp();
      mbar_arrive(sb + BAR_QP, lane == 0);
    }
    if (w == 2) {
      const uint32_t tg = (1 + e % 3) << 30;
      hint_wait(p.sync + 5, e * G);
      if (lane == 0) { mbar_expect(sb + BAR_HB, XPAD);
#pragma unroll 1
        for (int o = 0; o < 4; o++) bulk_load(sb + OFF_XB + o * (G * 64), (const char*)p.xb + (size_t)(cta * 4 + o) * (G * 64), G * 64, sb + BAR_HB); }
      STAMP(21);
      bar_sync(7, 384);
      sts32(sb + OFF_XB + XPAD, tg + p.N + cta * PADM);
      const uint32_t nx = __shfl_sync(~0u, lds32(sb + OFF_MISC + 8) ? 0 : lds32(sb + OFF_MISC + 4), 0);
#pragma unroll 1
      for (uint32_t k = 0; k < nx; k += 32) {
        const uint32_t i = min(k + lane, nx - 1), xr = lds32(sb + OFF_EXT + i * 4), row = (xr >> 9) & 255;
        const uint32_t v = ext_get(p.xe + (cta * G + row) * 32 + ((xr >> 17) & 31), e), x = lds32(sb + OFF_CNT + (xr & 511) * 4) + (xr >> 22) * 16;
        sts32(sb + OFF_XB + XPAD + 4 + i * 4, v); sts16(sb + OFF_TS + x, XPAD + 4 + i * 4);
        sts32(sb + OFF_TE + x * 2, mad16(v, 0x2000u, ealo - (tg >> 11) + row * p.EPC * 32));
      }
      __syncwarp();
      mbar_arrive(sb + BAR_HB, lane == 0);
    }
    if (w == 1) {
      const uint32_t nb = (p.E / G) & ~15u;
#pragma unroll 1
      for (int i = 0; i < PFN; i++) {
        if (lane == 0 && nb) asm volatile("cp.async.bulk.prefetch.L2.global [%0], %1;" :: "l"((const char*)p.ea + (size_t)(i * G + cta) * nb), "r"(nb) : "memory");
        __nanosleep(PFNS); }
    }
    if (w == 3) {
      if (lane == 0) { mbar_expect(sb + BAR_U, 16384); tma_load(sb + OFF_W, tmb + TM_WH, 0, sb + BAR_U); }
      __syncwarp();
      bar_sync(4, 416);
      if (lane == 0) tma_load(sb + OFF_W + 8192, tmb + TM_WH, 64, sb + BAR_U);
    }
    bar_sync(3, 128);
    mbar_wait(sb + BAR_U);
    uint32_t mh = 0;
#pragma unroll 1
    for (int i = t; i < 1024; i += 128) {
      uint32_t v[4]; const uint32_t r = (i >> 3) & 7, j = (i ^ r) & 7;
#pragma unroll
      for (int k = 0; k < 4; k++) v[k] = lds32(sb + OFF_W + (i >> 3) * 128 + ((((j & 4) + k) ^ r) << 4) + (j & 3) * 4);
      __syncwarp();
      if (i < 512) sts128(sb + OFF_W + i * 16, hhalf(v[0]), hhalf(v[1]), hhalf(v[2]), hhalf(v[3]));
      else { sts128(sb + OFF_W + i * 16, b2h(v[0], .5f), b2h(v[1], .5f), b2h(v[2], .5f), b2h(v[3], .5f)); mh = mag2(mag2(mag2(mag2(mh, v[0]), v[1]), v[2]), v[3]); } }
    if (wbad(__reduce_max_sync(~0u, magr(mh)), 0x4700)) sts32(sb + OFF_MISC + 12, 1);
    proxy_fence();
    __syncwarp();
    mbar_arrive(sb + BAR_WH, lane == 0);
    if (!__shfl_sync(~0u, lds32(sb + OFF_MISC + 8), 0)) {
      mbar_wait(sb + BAR_M);
      __nanosleep(DEF0);
#pragma unroll 1
      for (int i = 0; i < 12; i++) { uint32_t v[4]; const uint32_t n = lds16(sb + OFF_GP + i * 256 + (t >> 3) * 8 + 6);
        lds128(v, sb + OFF_H + n * 128 + (((n ^ t) & 7) << 4));
        if (n < nloc) ((uint4*)p.out)[(size_t)(node0 + n) * 8 + (t & 7)] = make_uint4(v[0], v[1], v[2], v[3]);
        __nanosleep(DEFNS); }
      uint32_t pa_[9];
#pragma unroll
      for (int k = 0; k < 9; k++) { const uint32_t i = t + 128 * k, n = (i * 43691u) >> 17; pa_[k] = lds16(sb + OFF_INV + n * 2) + (i - 3 * n) * 2; }
      uint16_t* po = p.out + (size_t)p.N * 64 + node0 * 3 + t;
      mbar_wait(sb + BAR_X);
#pragma unroll
      for (int k = 0; k < 9; k++) pa_[k] = lds16(sb + OFF_GP + pa_[k]);
#pragma unroll
      for (int k = 0; k < 9; k++) if (t + 128 * k < nloc * 3) po[128 * k] = pa_[k];
      asm volatile("{.reg .pred p, q; setp.ne.u32 p, 0, 0; bar.red.or.pred q, 5, 512, p;}" ::: "memory");
    }
    return;
  }

  if (tid == 320) {
    mbar_init(sb + BAR_W, 1);
    asm volatile("fence.mbarrier_init.release.cluster;" ::: "memory");
    mbar_expect(sb + BAR_W, 2 * 8192 + 2304);
    tma_load(sb + OFF_W, tmb + TM_WE, 64, sb + BAR_W); tma_load(sb + OFF_W + 8192, tmb + TM_WE, 0, sb + BAR_W);
    bulk_load(sb + OFF_WS, p.we + 128 * 64, 2176, sb + BAR_W); bulk_load(sb + OFF_WS + 2176, p.wx, 128, sb + BAR_W);
  }
  if (tid == 288) {
#pragma unroll
    for (int a = BAR_SRC; a < BAR_END; a += 8) if (a != BAR_W) mbar_init(sb + a, a == BAR_WH || a == BAR_PS || a == BAR_EP ? 4 : a == BAR_HB ? 2 : a >= BAR_M ? 12 : 1);
    asm volatile("fence.mbarrier_init.release.cluster;" ::: "memory");
    asm volatile("prefetch.tensormap [%0];" :: "l"(tmb + TM_XA)); asm volatile("prefetch.tensormap [%0];" :: "l"(tmb + TM_H));
    asm volatile("prefetch.tensormap [%0];" :: "l"(tmb + TM_XB)); asm volatile("prefetch.tensormap [%0];" :: "l"(tmb + TM_Q));
  }
  {
    if (tid < 144) { const uint32_t z = (tid >> 3) == 16 ? 0x8000u : 0u; sts128(sb + OFF_CNT + tid * 16, z, z, z, z); }
    else if (tid <= 144 + G) sts32(sb + OFF_BC + (tid - 144) * 4, ((tid - 144) & 31) * 4);
    const uint32_t sp = XPAD * 0x10001u, em = first_node(G);
    if (wid < 7) {
#pragma unroll
      for (int i = 0; i < 4; i++) sts128(sb + OFF_TS + tid * 16 + i * 3584, sp, sp, sp, sp);
    }
    static_assert(SCAP * 32 == 4 * 3584, "fill");
#pragma unroll 1
    for (int i = n4 + tid; i < 1536; i += 384) sts128(sb + OFF_DST + i * 16, em, em, em, em);
    if (tid == 321) sts128(sb + OFF_MISC, 0, 0, p.force_slow, 0);
  }
  bar_arrive(6, NTHR);
  bar_sync(0, 384);
  uint32_t ep, tag, eb0, pk[12], r0[12], r1[12], cb;
  uint2 vb[12];
  auto get_tag = [&]() { mbar_wait(sb + BAR_EP); ep = lds32(sb + OFF_MISC + 32); tag = (1 + ep % 3) << 30; eb0 = ealo - (tag >> 11); };
  if (wid == 11) {
    trap_if(sb != (uint32_t)__cvta_generic_to_shared(smraw));
#pragma unroll 1
    for (int k = 0; k < 3; k++) { const int nb = max(0, min(8192, n4 * 16 - k * 8192));
      mbar_wait(sb + BAR_DST + (k ? k + 1 : 0) * 8);
      if (lane == 0) { mbar_expect(sb + BAR_SRC + k * 8, nb);
        if (nb) bulk_load(sb + OFF_SRCI + k * 8192, (const char*)(p.src + e0) + k * 8192, nb, sb + BAR_SRC + k * 8); } }
    get_tag();
    mbar_wait(sb + BAR_PS);
    bar_sync(12, 384);
    uint32_t xm = 0;
#pragma unroll
    for (int k = 0; k < 5; k++) xm |= (lds32(sb + OFF_BC + min(lane + 32 * k, G - 1) * 4) >= (65 << 9) && lane + 32 * k < G) << k;
    auto ext_send = [&](int pl) {
      uint32_t x = xm;
      for (uint32_t m; (m = __ballot_sync(~0u, x));) {
        const uint32_t l = __ffs(m) - 1, j = l + 32 * (__ffs(__shfl_sync(~0u, x, l)) - 1);
        if (lane == l) x &= x - 1;
        const uint32_t e = min(lds16(sb + OFF_AX + j * 128 + ((4 * l + 2 * lane) & 126)), 6143u);
        if (pl) st_ext(p.xe + (j * G + cta) * 32 + lane, lds32(sb + OFF_SRCI + e * 4) + tag + (e << 16), ep);
        else { const uint32_t cn = lds32(sb + OFF_BC + j * 4) >> 9, v = cn > 96 ? 1 : lane + 64 < cn ? 512 | (lds32(sb + OFF_DST + e * 4) & 511) : 0;
          asm volatile("red.shared.xor.b32 [%0], %1;" :: "r"(sb + OFF_SA + j * 128 + ((l + lane) & 31) * 4), "r"(((v & 63) << 10) | ((v >> 6) << 26)) : "memory"); }
      }
    };
    if (__any_sync(~0u, xm)) { ext_send(0); proxy_fence(); __syncwarp(); }
    if (lane == 0) { tma_store(tmb + TM_XA, cta * 64, 0, sb + OFF_SA); bulk_commit(); mbar_arrive(sb + BAR_AI); bulk_wait(); hint_signal(p.sync + 4); mbar_arrive(sb + BAR_AW); STAMP(16); }
    __syncwarp();
    bar_sync(13, 384);
    ext_send(1);
    mbar_arrive(sb + BAR_AX, lane == 0);
    mbar_wait(sb + BAR_HA);
    __nanosleep(BDEL);
    if (lane == 0) {
#pragma unroll 1
      for (int r = 0; r < G; r += BROWS) { tma_store(tmb + TM_XB, cta * 64, r, sb + OFF_SB + r * 256); bulk_commit(); bulk_wait(); }
      hint_signal(p.sync + 5);
      STAMP(17);
    }
    __syncwarp();
  } else {
    {
      uint32_t d[4 * NCH], jj[4 * NCH], rr[4 * NCH];
      auto count = [&](int k) {
        mbar_wait(sb + BAR_DST + k * 8);
        lds128(d + 4 * k, sb + OFF_DST + (tid + NWK * k) * 16);
#pragma unroll
        for (int i = 4 * k; i < 4 * k + 4; i++) { jj[i] = d[i] * p.magic; rr[i] = atoms_add(__dp4a(jj[i], 0x04000000u, sb + OFF_BC), 0x202u); }
      };
      auto place = [&](int k) {
#pragma unroll
        for (int i = 4 * k; i < 4 * k + 4; i++) {
          const uint32_t o = __dp4a(jj[i], 0x80000000u, rr[i] & 0x807Eu);
          d[i] = (d[i] & 511) | (tag >> 16);
          asm("{.reg .pred p; setp.ge.u32 p, %1, 0x8000; @p add.u32 %0, %2, %3;}" : "+r"(d[i]) : "r"(o), "r"(tid * 4), "r"(NWK * k * 4 + (i & 3)));
          sts16(sb + OFF_SA + o, d[i]); jj[i] = __viaddmin_u32(o, o, G * 256);
        }
      };
      count(0); STAMP(1); count(1); get_tag(); place(0); count(2); place(1); count(3); place(2);
      if (wid < 4) { count(4); STAMP(15); place(3); place(4); } else place(3);
      proxy_fence();
      bar_arrive(12, 384);
      STAMP(2);
      mbar_wait(sb + BAR_AI);
      mbar_wait(sb + BAR_SRC); mbar_wait(sb + BAR_SRC + 8); mbar_wait(sb + BAR_SRC + 16);
      STAMP(12);
#pragma unroll
      for (int k = 0; k < NCH; k++) lds128(d + 4 * k, sb + OFF_SRCI + (tid + NWK * k) * 16);
      const uint32_t tb = tag + (tid << 18);
#pragma unroll
      for (int i = 0; i < 4 * NCH; i++) if (i < 4 * NCH - 4 || wid < 4) sts32(sb + OFF_SB + jj[i], d[i] + tb + ((NWK * (i >> 2) * 4 + (i & 3)) << 16));
      proxy_fence();
      bar_arrive(13, 384);
      STAMP(3);
    }
    const uint32_t rot = (lane + cta) & 31;
    cb = sb + OFF_CNT - (tag >> 14);
    {
      const uint32_t* xa = (const uint32_t*)(p.xa + (cta * G + wid) * 8) + rot;
      if (wid < 8) { const uint32_t e_ = ealo + epad * 32;
        mbar_wait(sb + BAR_AX);
#pragma unroll
        for (int i = 0; i < 7; i++) sts128(sb + OFF_TE + tid * 16 + i * 4096, e_, e_, e_, e_); }
      static_assert(SCAP * 64 == 7 * 4096, "fill");
      if (wid == 10) { hint_wait(p.sync + 4, ep * G); mbar_arrive(sb + BAR_HA, lane == 0); }
      mbar_wait(sb + BAR_HA);
      STAMP(14);
      const uint32_t tp = tag | (tag >> 16);
      uint32_t st;
#pragma unroll 1
      for (int spin = 0;; spin++) {
        st = 0;
#pragma unroll
        for (int k = 0; k < 12; k++) asm volatile("ld.relaxed.gpu.global.u32 %0, [%1];" : "=r"(pk[k]) : "l"(xa + k * 352) : "memory");
#pragma unroll
        for (int k = 0; k < 12; k++) st |= pk[k] ^ tp;
        st = __reduce_or_sync(~0u, st);
        if (!(st >> 30)) break;
        trap_if(spin > 2000000);
      }
      if (st & 0x3C00FC00u) {
#pragma unroll 1
        for (;;) {
          uint32_t x = 0, row = 0;
#pragma unroll
          for (int k = 0; k < 12; k++) { const uint32_t y = (pk[k] ^ tp) & 0x3C00FC00u; if (!x && y) { x = y; row = wid + 11 * k; pk[k] ^= y; } }
          if (!__any_sync(~0u, x)) break;
          const uint32_t n = ((x >> 10) & 63) | ((x >> 20) & 0x1C0);
          if (x >> 29) {
            const uint32_t r = atoms_add(sb + OFF_CNT + n * 4, 16), idx = atoms_add(sb + OFF_MISC + 4, 1);
            if (idx < 256) sts32(sb + OFF_EXT + idx * 4, n | (row << 9) | (lane << 17) | (min(r >> 4, 255u) << 22));
            else x = 1;
          }
          if (x && !(x >> 29)) sts32(sb + OFF_MISC + 8, 1);
          __syncwarp();
        }
      }
#pragma unroll
      for (int k = 0; k < 12; k++) { r0[k] = mad16(pk[k], 0x0004u, cb); r1[k] = mad16(pk[k], 0x0400u, cb); vb[k].x = atoms_add(r0[k], 16); vb[k].y = atoms_add(r1[k], 16); }
    }
    STAMP(4);
    if (wid >= 6) bar_arrive(11, NWK);
    if (wid < 6) {
      uint32_t ca[2], ky[2], dr[2], sq[2], ps[4];
#pragma unroll
      for (int i = 0; i < 2; i++) { ca[i] = sb + OFF_CNT + ((node0 + tid + 192 * i) & 511) * 4; lds64(ps[2 * i], ps[2 * i + 1], sb + OFF_POS + (tid + 192 * i) * 8); ps[2 * i + 1] |= (tid + 192 * i) << 16; }
      bar_sync(11, NWK);
      STAMP(5);
#pragma unroll
      for (int i = 0; i < 2; i++) ky[i] = (lds32(ca[i]) + 16) >> 5;
      if (max(ky[0], ky[1]) > 31) sts32(sb + OFF_MISC + 8, 1);
#pragma unroll
      for (int i = 0; i < 2; i++) { ky[i] = min(ky[i], 31u); dr[i] = atoms_add(sb + OFF_DH + ky[i] * 4, 1); }
      bar_sync(10, 192);
      const uint32_t hv = lds32(sb + OFF_DH + lane * 4);
      uint32_t inc = hv;
#pragma unroll
      for (int o = 1; o < 32; o <<= 1) asm("{.reg .pred p; .reg .b32 y; shfl.sync.down.b32 y|p, %0, %1, 31, -1; @p add.u32 %0, %0, y;}" : "+r"(inc) : "r"(o));
#pragma unroll
      for (int i = 0; i < 2; i++) {
        const uint32_t pos = __shfl_sync(~0u, inc - hv, ky[i]) + dr[i];
        const uint32_t ak = (uint32_t)(QCODE >> ((pos >> 5) * 4)) & 15, l = (pos >> 3) & 3;
        sq[i] = (ak >> 2) * 16 + ((QREV >> (pos >> 5) & 1) ? 3 - l : l) * 4 + (ak & 3);
        dr[i] = pos & 7;
        asm volatile("{.reg .pred p; setp.eq.u32 p, %2, 0; @p st.shared.u8 [%0], %1;}" :: "r"(sb + OFF_LEN + sq[i]), "r"(max(ky[i], 1u)), "r"(dr[i]) : "memory");
        sts64(sb + OFF_GP + sq[i] * 64 + dr[i] * 8, ps[2 * i], ps[2 * i + 1]);
        sts16(sb + OFF_INV + (tid + 192 * i) * 2, sq[i] * 64 + dr[i] * 8);
      }
      bar_sync(10, 192);
      const uint32_t ln = lds32(sb + OFF_LEN + min(lane, 11) * 4), tot = __dp4a(ln, 0x01010101u, 0u);
      inc = tot;
#pragma unroll
      for (int o = 1; o < 16; o <<= 1) asm("{.reg .pred p; .reg .b32 y; shfl.sync.up.b32 y|p, %0, %1, 0, -1; @p add.u32 %0, %0, y;}" : "+r"(inc) : "r"(o));
      if (wid == 1) sts32(sb + OFF_CNT + 2048 + lane * 4, 0);
      if (tid < 12) { sts32(sb + OFF_LEN + 64 + tid * 4, inc - tot); if (inc > SCAP - 12) sts32(sb + OFF_MISC + 8, 1); }
#pragma unroll
      for (int i = 0; i < 2; i++) sts32(ca[i], __dp4a(__shfl_sync(~0u, ln, sq[i] >> 2), 0x00010101u >> (24 - 8 * (sq[i] & 3)), __shfl_sync(~0u, inc - tot, sq[i] >> 2)) * 32 + dr[i] * 2);
    }
    bar_arrive(7, 384);
  }
  bar_sync(1, 384);
  STAMP(6);
  if (wid != 11 && !__shfl_sync(~0u, lds32(sb + OFF_MISC + 8), 0)) {
#pragma unroll
    for (int k = 0; k < 12; k++) { r0[k] = lds32(r0[k]); r1[k] = lds32(r1[k]); }
#pragma unroll
    for (int k = 0; k < 12; k++) { r0[k] += vb[k].x; r1[k] += vb[k].y; }
  } else {
#pragma unroll
    for (int k = 0; k < 12; k++) r0[k] = r1[k] = 0x8000;
  }
  auto put_ids = [&]() {
    const uint32_t id = wid * 256 + ((lane + cta) & 31) * 8;
    auto put = [&](uint32_t x, uint32_t v) { asm volatile("{.reg .pred p; setp.lt.u32 p, %0, 0x8000; @p st.shared.u16 [%0+%2], %1;}" :: "r"(x), "h"((uint16_t)v), "n"(sb + OFF_TS) : "memory"); };
#pragma unroll
    for (int k = 0; k < 12; k++) { put(pk[k] & 0xFFFF, id + k * 2816); put(pk[k] >> 16, id + k * 2816 + 4); }
  };
  STAMP(7);
  mbar_wait(sb + BAR_QR);
  asm volatile("setmaxnreg.inc.sync.aligned.u32 160;");
#pragma unroll
  for (int k = 0; k < 12; k++) asm volatile("prmt.b32 %0, %1, %2, 0x5410;" : "=r"(pk[k]) : "r"(r0[k]), "r"(r1[k]));
  uint32_t pa[8], sp[8], pq[16]; float chk = 0.f;
  {
    uint32_t hf[32], mp = 0; float a0[32], a1[32];
    const uint32_t an = sb + OFF_GP + wid * 256 + (lane & 15) * 8 + 6, n0 = lds16(an), n1 = lds16(an + 128);
#pragma unroll
    for (int j = 0; j < 8; j++) { const uint32_t nd = j < 4 ? n0 : n1; ldsm4(hf + 4 * j, (sb + OFF_H + nd * 128 + (((nd & 7) << 4) ^ (lane & 16))) ^ ((j & 3) << 5)); }
    const uint64_t db = DHI | ((sb + OFF_W + 8192) >> 4);
    wg_fence();
    rs64b<0>(a0, hf[0], hf[1], hf[2], hf[3], db); rs64b<1>(a0, hf[4], hf[5], hf[6], hf[7], db + 128); rs64b<1>(a0, hf[8], hf[9], hf[10], hf[11], db + 256); rs64b<1>(a0, hf[12], hf[13], hf[14], hf[15], db + 384);
    wg_commit();
    rs64b<0>(a1, hf[16], hf[17], hf[18], hf[19], db); rs64b<1>(a1, hf[20], hf[21], hf[22], hf[23], db + 128); rs64b<1>(a1, hf[24], hf[25], hf[26], hf[27], db + 256); rs64b<1>(a1, hf[28], hf[29], hf[30], hf[31], db + 384);
    wg_commit();
    put_ids();
    asm volatile("wgmma.wait_group.sync.aligned 1;" ::: "memory"); fence_regs(a0);
#pragma unroll
    for (int j = 0; j < 8; j++) { const uint32_t x = pack_f16(.5f * a0[4 * j], .5f * a0[4 * j + 1]), y = pack_f16(.5f * a0[4 * j + 2], .5f * a0[4 * j + 3]); mp = hmag(hmag(mp, x), y);
      asm volatile("movmatrix.sync.aligned.m8n8.trans.b16 %0, %1;" : "=r"(pa[j]) : "r"(x)); asm volatile("movmatrix.sync.aligned.m8n8.trans.b16 %0, %1;" : "=r"(sp[j]) : "r"(y)); }
    wg_wait0(); fence_regs(a1);
    bar_arrive(4, 416);
#pragma unroll
    for (int j = 0; j < 16; j++) { pq[j] = pack_f16(.5f * a1[2 * j], .5f * a1[2 * j + 1]); mp = hmag(mp, pq[j]); }
    if (magr(mp) >= 0x7000) chk = __int_as_float(0x7FC00000);
  }
  if (wid == 0) STAMP(23);
  uint32_t bad;
  {
    const uint32_t ring = sb + OFF_RING + wid * STG, p2 = sb + OFF_P2 + wid * 2048;
    uint32_t lens = __shfl_sync(~0u, lds32(sb + OFF_LEN + wid * 4), 0);
    uint32_t rem = __dp4a(lens, 0x20202020u, 0u);
    const uint32_t base = min(lds32(sb + OFF_LEN + 64 + wid * 4), SCAP);
    uint32_t a_s = sb + OFF_TS + base * 32 + (lane >> 3) * 8, a_e = sb + OFF_TE + base * 64 + (lane >> 1) * 4;
    uint32_t k0 = (uint32_t)(uint64_t)p.q + (((lane & 7) ^ ((lane >> 1) & 4)) << 4), k1 = k0 ^ 16, k2 = k0 ^ 32, k3 = k0 ^ 48, ke = ((lane ^ (lane >> 3)) & 1) << 4;
    uint32_t dst0 = ring + (lane >> 3) * 640 + (lane & 7) * 16;
    const uint32_t qhi = (uint32_t)((uint64_t)p.q >> 32), ehi = (uint32_t)((uint64_t)p.ea >> 32);
    uint32_t s0, s1, ev, to = 0, so = 12 * STG;
    auto tl_ = [&]() { lds64(s0, s1, a_s + to); asm volatile("ld.shared.u32 %0, [%1]; add.u32 %1, %1, 64;" : "=&r"(ev), "+r"(a_e) :: "memory"); to += 32; };
#define CPQ(LH, x, k, off) "dp2a." LH ".u32.u32 lo, " x ", 0x80000080, " k "; mov.b64 a, {lo, %7}; @p cp.async.cg.shared.global [%0+" #off "], [a], 16;\n"
#define CPE "or.b32 lo, %10, %11; mov.b64 a, {lo, %12}; @p cp.async.cg.shared.global [%0+512], [a], 16;\n"
#define CPA(BODY) asm volatile("{.reg .b32 lo; .reg .b64 a; .reg .pred p; setp.le.u32 p, %8, %9;\n" BODY "}" \
      :: "r"(dst0 + so), "r"(s0), "r"(s1), "r"(k0), "r"(k1), "r"(k2), "r"(k3), "r"(qhi), "r"(to), "r"(rem), "r"(ev), "r"(ke), "r"(ehi) : "memory")
#define CPQ4 CPQ("lo", "%1", "%3", 0) CPQ("hi", "%1", "%4", 128) CPQ("lo", "%2", "%5", 256) CPQ("hi", "%2", "%6", 384) "cp.async.commit_group;"
    auto issue = [&]() { CPA(CPE CPQ4); so = so == (NST - 1) * 12 * STG ? 0 : so + 12 * STG; };
    const int g = lane >> 2, qd = lane & 3;
    const uint32_t sw = ((lane >> 4) ^ (lane & 7)) << 4, fr = (lane & 15) * 128 + sw;
    uint32_t qa0 = ring + (g & 3) * 640 + qd * 128 + sw, qa1 = qa0 ^ 32, qa2 = qa0 ^ 64, qa3 = qa0 ^ 96;
    uint32_t eadr = ring + 512 + (g & 3) * 640 + qd * 32 + ((((lane >> 4) ^ g) & 1) << 4);
    uint32_t oh0 = g == 2 * qd ? 0x3C00u : g == 2 * qd + 1 ? 0x3C000000u : 0u, oh1 = oh0;
    uint32_t a_g = sb + OFF_GP + wid * 256 + lane * 2;
    uint32_t a_n = sb + OFF_GP + wid * 256 + (lane & 15) * 8 + 6;
    uint32_t a_p = ((lane & 8) ? p2 : sb + OFF_WD) + (lane & 7) * 128 + ((((lane >> 4) ^ lane) & 7) << 4);
    uint32_t a_w = sb + OFF_W3 + fr;
    asm volatile("shfl.sync.idx.b32 %0, %0, %1, 31, -1;" : "+r"(oh1) : "r"(lane));
    uint32_t w3[16], wv[8], bp[16], sum[8], Y[16], M[16], own, ownp, dpk, tl[16], th[16];
    float pacc = 0.f;
    auto wload = [&]() {
#pragma unroll
      for (int j = 0; j < 4; j++) ldsm4t(w3 + 4 * j, a_w ^ (j << 5));
      lds128(wv, sb + OFF_WX + (a_g & 6) * 16); lds128(wv + 4, sb + OFF_WX + 16 + (a_g & 6) * 16);
    };
    auto hload = [&](uint32_t (&hf)[16], uint32_t nd) {
      const uint32_t hrow = sb + OFF_H + nd * 128 + (((nd & 7) << 4) ^ ((a_g >> 1) & 16));
#pragma unroll
      for (int j = 0; j < 4; j++) ldsm4(hf + 4 * j, hrow ^ (j << 5));
      return hrow;
    };
    auto bload = [&](uint32_t o) {
#pragma unroll
      for (int j = 0; j < 4; j++) ldsm4t(bp + 4 * j, (a_p ^ (j << 5)) + o);
    };
    { uint32_t wd[8]; const uint32_t a = sb + OFF_WD + (lane & 7) * 128 + ((((lane >> 3) ^ lane) & 7) << 4);
      ldsm4t(wd, a); ldsm4t(wd + 4, a ^ 64);
#pragma unroll
      for (int j = 0; j < 8; j++) { bp[2 * j] = wd[j]; bp[2 * j + 1] = pa[j]; } }
    own = lds16(a_g) * 0x10001u;
    wload();
    if (__shfl_sync(~0u, lds32(sb + OFF_MISC + 8), 0)) rem = 0;
    auto resolve = [&](auto NBK, uint32_t o) {
      constexpr int NB = decltype(NBK)::value;
      uint32_t id[NB], c0[NB], c1[NB]; const uint32_t a = base * 32 + o + lane * 4;
#pragma unroll
      for (int i = 0; i < NB; i++) { id[i] = lds32(sb + OFF_TS + a + i * 128); if (o + lane * 4 + i * 128 >= rem) id[i] = XPAD * 0x10001u; }
      uint32_t st = 0;
#pragma unroll
      for (int i = 0; i < NB; i++) { c0[i] = lds32(sb + OFF_XB + (id[i] & 0xFFFF)); c1[i] = lds32(sb + OFF_XB + (id[i] >> 16)); }
#pragma unroll
      for (int i = 0; i < NB; i++) st |= (c0[i] ^ tag) | (c1[i] ^ tag);
      for (int spin = 0; __any_sync(~0u, st >> 30); spin++) {
        st = 0; trap_if(spin > 2000000);
#pragma unroll
        for (int i = 0; i < NB; i++) {
          asm volatile("{.reg .pred p, q; setp.lt.u32 p, %4, %6; setp.lt.u32 q, %5, %6; @p ld.relaxed.gpu.global.u32 %0, [%2]; @q ld.relaxed.gpu.global.u32 %1, [%3];}"
            : "+r"(c0[i]), "+r"(c1[i]) : "l"((const char*)p.xb + cta * XPAD + (id[i] & 0xFFFF)), "l"((const char*)p.xb + cta * XPAD + (id[i] >> 16)), "r"(id[i] & 0xFFFF), "r"(id[i] >> 16), "n"(XPAD) : "memory");
          st |= (c0[i] ^ tag) | (c1[i] ^ tag); }
      }
#pragma unroll
      for (int i = 0; i < NB; i++) { const uint32_t j0 = (id[i] >> 8) & 255, j1 = id[i] >> 24;
        asm volatile("{.reg .pred p, q, r; setp.lt.u32 p, %5, %9; setp.lt.u32 q, %6, %9; setp.lt.u32 r, %7, %8;\n"
          "@p st.shared.u32 [%0], %2; @q st.shared.u32 [%0+4], %3; @r st.shared.u32 [%1], %4;}"
          :: "r"(sb + OFF_TE + 2 * a + i * 256), "r"(sb + OFF_TS + a + i * 128), "r"(mad16(c0[i], 0x2000u, eb0 + j0 * p.EPC * 32)), "r"(mad16(c1[i], 0x2000u, eb0 + j1 * p.EPC * 32)),
             "r"(__byte_perm(c0[i], c1[i], 0x5410)), "r"(j0), "r"(j1), "r"(o + lane * 4 + i * 128), "r"(rem), "n"(G) : "memory"); }
    };
    bar_sync(2, 384);
    if (wid == 0) STAMP(27);
    mbar_wait(sb + BAR_HB);
    if (wid == 0) STAMP(22);
#pragma unroll 1
    for (uint32_t o = 0, go = 0; go < 32 * NST; o += 128 * RNB) {
      if (o < rem) { resolve(IC<RNB>(), o);
        asm volatile("{.reg .pred p; mbarrier.test_wait.parity.shared::cta.b64 p, [%1], 0; vote.sync.all.pred p, p, -1; selp.u32 %0, %2, 0, p;}" : "=r"(go) : "r"(sb + BAR_QP), "n"(32 * NST - 32) : "memory"); }
      else { bar_sync(8, 384); mbar_wait(sb + BAR_QP); go = 32 * NST; if (wid == 0) STAMP(24); }
      __syncwarp();
#pragma unroll 1
      while (to < go) { tl_(); issue(); if (to == 32) STAMP(13); }
    }
    bad = __shfl_sync(~0u, lds32(sb + OFF_MISC + 8), 0);
   if (!bad) {
#pragma unroll
    for (int j = 0; j < 4; j++) stsm4((p2 + fr) ^ (j << 5), pq[4 * j], pq[4 * j + 1], pq[4 * j + 2], pq[4 * j + 3]);
    auto body = [&](auto MODE) {
      constexpr int mode = decltype(MODE)::value;
      uint32_t T[16], ef[4], q0, q1, x0, x1, x2; float e0_, e1_, cs[4];
      auto mu = [&](int j) {
#pragma unroll
        for (int i = 2 * j; i < 2 * j + 2; i++) asm volatile("{.reg .b16 l, h; mov.b32 {l, h}, %2; tanh.approx.f16 l, l; tanh.approx.f16 h, h; cvt.u32.u16 %0, l; cvt.u32.u16 %1, h;}" : "=r"(tl[i]), "=r"(th[i]) : "r"(Y[i])); };
      auto fi = [&](int j) {
#pragma unroll
        for (int i = 2 * j; i < 2 * j + 2; i++) asm volatile("{.reg .b32 t; prmt.b32 t, %2, %3, 0x5410; fma.rn.f16x2 %0, %1, t, %1;}" : "=r"(M[i]) : "r"(Y[i]), "r"(tl[i]), "r"(th[i])); };
      auto ad = [&](int j) { asm volatile("add.rn.f16x2 %0, %0, %1; add.rn.f16x2 %0, %0, %2;" : "+r"(sum[j]) : "r"(M[2 * j]), "r"(M[2 * j + 1])); };
      auto he = [&](int j) { asm volatile("mma.sync.aligned.m16n8k16.row.col.f16.f16.f16.f16 {%0,%1}, {%2,%3,%4,%5}, {%6,%7}, {%0,%1};" : "+r"(T[2 * j]), "+r"(T[2 * j + 1]) : "r"(ef[0]), "r"(ef[1]), "r"(ef[2]), "r"(ef[3]), "r"(w3[2 * j]), "r"(w3[2 * j + 1])); };
      auto hs = [&](int j) { asm volatile("mma.sync.aligned.m16n8k16.row.col.f16.f16.f16.f16 {%0,%1}, {%2,%3,%4,%5}, {%6,%7}, {%8,%9};" : "=r"(Y[2 * j]), "=r"(Y[2 * j + 1]) : "r"(q0), "r"(q1), "r"(oh0), "r"(oh1), "r"(bp[2 * j]), "r"(bp[2 * j + 1]), "r"(T[2 * j]), "r"(T[2 * j + 1])); };
      auto hc = [&](int j) {
        if (j) asm volatile("mma.sync.aligned.m16n8k16.row.col.f32.f16.f16.f32 {%0,%1,%2,%3}, {%4,%5,%6,%7}, {%8,%9}, {%0,%1,%2,%3};" : "+f"(cs[0]), "+f"(cs[1]), "+f"(cs[2]), "+f"(cs[3]) : "r"(M[4 * j]), "r"(M[4 * j + 1]), "r"(M[4 * j + 2]), "r"(M[4 * j + 3]), "r"(wv[2 * j]), "r"(wv[2 * j + 1]));
        else asm volatile("mma.sync.aligned.m16n8k16.row.col.f32.f16.f16.f32 {%0,%1,%2,%3}, {%4,%5,%6,%7}, {%8,%9}, {%10,%10,%10,%10};" : "=f"(cs[0]), "=f"(cs[1]), "=f"(cs[2]), "=f"(cs[3]) : "r"(M[0]), "r"(M[1]), "r"(M[2]), "r"(M[3]), "r"(wv[0]), "r"(wv[1]), "f"(0.f)); };
      auto cv = [&](int i) { asm volatile("{.reg .b32 a, b; shl.b32 a, %0, 16; and.b32 b, %0, 0xFFFF0000; cvt.rn.f16x2.f32 %0, b, a;}" : "+r"(ef[i])); };
      auto un = [&]() { asm volatile("shl.b32 %0, %2, 16; and.b32 %1, %2, 0xFFFF0000;" : "=&f"(e0_), "=&f"(e1_) : "r"(dpk)); };
      auto ex0 = [&]() { asm volatile("prmt.b32 %0, %3, %4, 0x6420; prmt.b32 %1, %5, %6, 0x6420; prmt.b32 %2, %7, %8, 0x6420;" : "=&r"(x0), "=&r"(x1), "=&r"(x2) : "r"(T[0]), "r"(T[1]), "r"(T[2]), "r"(T[3]), "r"(T[4]), "r"(T[5])); };
      auto ex1 = [&]() { asm volatile("{.reg .b32 a, b; shl.b32 a, %2, 3; shl.b32 b, %3, 6; lop3.b32 a, %1, a, 0x38383838, 0xD8; lop3.b32 a, a, b, 0xC0C0C0C0, 0xD8; sub.rn.bf16x2 %0, %4, a;}" : "=r"(dpk) : "r"(x0), "r"(x1), "r"(x2), "r"(own)); };
      auto ex2 = [&]() { asm volatile("{.reg .b32 a, b, d, u; .reg .b16 l, h; shl.b32 a, %2, 16; and.b32 b, %2, 0xFFFF0000; cvt.rn.f16x2.f32 d, b, a; mul.rn.f16x2 %0, d, d; mov.b32 {l, h}, d; mov.b32 u, {h, h}; mul.rn.f16x2 %1, u, u;}" : "=&r"(q0), "=&r"(q1) : "r"(dpk)); };
      auto pf = [&]() { asm volatile("fma.rn.f32 %0, %1, %2, %0; fma.rn.f32 %0, %3, %4, %0;" : "+f"(pacc) : "f"(cs[0]), "f"(e0_), "f"(cs[2]), "f"(e1_)); };
      if (mode == 2) { LASTSEQ return; }
      asm volatile("cp.async.wait_group %0;" :: "n"(NST - 1) : "memory");
      __syncwarp();
      if (mode == 1) STAMP(8);
      ldsm4(ef, eadr + so); ldsm4(T, qa0 + so); ldsm4(T + 4, qa1 + so); ldsm4(T + 8, qa2 + so); ldsm4(T + 12, qa3 + so);
      if (mode == 1) {
        tl_(); issue();
        cv(0); cv(1); cv(2); cv(3); ex0(); ex1(); ex2();
#pragma unroll
        for (int j = 0; j < 8; j++) { he(j); hs(j); }
        FIRSTSEQ return;
      }
      BODYSEQ
    };
#pragma unroll
    for (int j = 0; j < 8; j++) sum[j] = 0;
    body(IC<1>());
    int cnt = (lens & 255) - 1;
    auto flush = [&]() {
      asm volatile("{.reg .pred p; setp.ne.u32 p, %2, 6; @p st.shared.u16 [%0+-64], %1;}" :: "r"(a_g), "h"((uint16_t)pack_bf16(bf_hi(ownp) + pacc, 0.f)), "r"(a_g & 6) : "memory");
      chk = fmaf(pacc, 0.f, chk); pacc = 0.f; };
    constexpr uint64_t b1 = DHI | ((sb + OFF_W) >> 4), b2_ = b1 + 512;
    auto mma_h = [&](float (&acc)[32], uint32_t (&hf)[16]) {
      rs64b<0>(acc, hf[0], hf[1], hf[2], hf[3], b1); rs64b<1>(acc, hf[4], hf[5], hf[6], hf[7], b1 + 128); rs64b<1>(acc, hf[8], hf[9], hf[10], hf[11], b1 + 256); rs64b<1>(acc, hf[12], hf[13], hf[14], hf[15], b1 + 384); };
    auto mma_m = [&](float (&acc)[32]) {
      rs64h<1>(acc, sp[0], sum[0], sp[1], sum[1], b2_); rs64h<1>(acc, sp[2], sum[2], sp[3], sum[3], b2_ + 128); rs64h<1>(acc, sp[4], sum[4], sp[5], sum[5], b2_ + 256); rs64h<1>(acc, sp[6], sum[6], sp[7], sum[7], b2_ + 384);
      wg_commit(); wg_wait0(); fence_regs(acc);
      STAMP(10);
      chk = fmaf(acc[0], 0.f, fmaf(acc[2], 0.f, chk)); };
    auto roff = [&](uint32_t nd, int r) { return __shfl_sync(~0u, nd, ((a_g >> 3) & 7) + 8 * r) * 128 + (a_g & 6) * 8; };
    auto radr = [&](uint32_t o, int k) { return sb + OFF_H + (o ^ ((o >> 3) & 0x70) ^ ((k >> 1) << 6)); };
    auto fin = [&](float (&acc)[32], uint32_t* x, int k) {
#pragma unroll
      for (int i = 0; i < 4; i++) { const int c = 16 * (k >> 1) + 4 * i + 2 * (k & 1); x[i] = u2(__hadd2(b2(x[i]), b2(pack_bf16(silu_h(acc[c]), silu_h(acc[c + 1]))))); } };
#pragma unroll 1
    for (int t = 0;; t++) {
#pragma unroll 1
      for (; cnt > 0; cnt--) { body(IC<0>());
      }
      if (!(t & 1)) {
        ownp = own; a_g += 64;
        if (t == 6) break;
        own = lds16(a_g) * 0x10001u;
        if (t == 0) {
#pragma unroll
          for (int j = 0; j < 8; j++) bp[2 * j + 1] = sp[j];
        } else bload((a_g & 16) ? (t & 4) * 256 : 0);
        lens >>= 8; cnt = 1;
        continue;
      }
      cnt = (lens & 255) - 1;
      flush();
      if (t == 3) {
        uint32_t hf[16]; float acc[32];
        const uint32_t nd = lds16(a_n), o[2] = {roff(nd, 0), roff(nd, 1)};
        hload(hf, nd);
        mbar_wait(sb + BAR_WH);
        wg_fence();
        mma_h(acc, hf); mma_m(acc);
#pragma unroll
        for (int k = 0; k < 4; k++) lds128(hf + 4 * k, radr(o[k & 1], k));
#pragma unroll
        for (int k = 0; k < 4; k++) { fin(acc, hf + 4 * k, k); sts128(radr(o[k & 1], k), hf[4 * k], hf[4 * k + 1], hf[4 * k + 2], hf[4 * k + 3]); }
        __syncwarp();
        mbar_arrive(sb + BAR_M, (a_g & 62) == 0);
        wload();
      }
#pragma unroll
      for (int j = 0; j < 8; j++) { sp[j] = sum[j]; asm volatile("mov.b32 %0, 0;" : "=r"(sum[j])); }
    }
    {
      uint32_t hf[16], v[16]; float acc[32];
      const uint32_t nd = lds16(a_n + 128), o[2] = {roff(nd, 0), roff(nd, 1)};
      hload(hf, nd);
#pragma unroll
      for (int k = 0; k < 4; k++) lds128(v + 4 * k, radr(o[k & 1], k));
      wg_fence(); mma_h(acc, hf); wg_commit();
      body(IC<2>());
      STAMP(9);
      flush();
      __syncwarp();
      mbar_arrive(sb + BAR_X, lane == 0);
      wg_fence();
      mma_m(acc);
#pragma unroll
      for (int k = 0; k < 4; k++) { fin(acc, v + 4 * k, k);
        asm volatile("{.reg .pred p; setp.lt.u32 p, %5, %6; @p st.global.v4.b32 [%0], {%1,%2,%3,%4};}" :: "l"((const char*)p.out + (size_t)node0 * 128 + o[k & 1] + (k >> 1) * 64), "r"(v[4 * k]), "r"(v[4 * k + 1]), "r"(v[4 * k + 2]), "r"(v[4 * k + 3]), "r"(o[k & 1]), "r"(nloc * 128) : "memory"); }
    }
    asm volatile("{.reg .pred p, q; setp.neu.f32 p, %1, 0f00000000; setp.ne.or.u32 p, %2, 0, p; bar.red.or.pred q, 5, 512, p; selp.u32 %0, 1, 0, q;}" : "=r"(bad) : "f"(chk), "r"(lds32(sb + OFF_MISC + 12)) : "memory");
    STAMP(11);
   } else { asm volatile("cp.async.wait_all;" ::: "memory"); bar_sync(5, 384); }
  }
  if (bad) slow_path(p, wid, lane, node0, nloc);
}

}

typedef CUresult (*EncodeFn)(CUtensorMap*, CUtensorMapDataType, cuuint32_t, void*, const cuuint64_t*, const cuuint64_t*, const cuuint32_t*, const cuuint32_t*,
                             CUtensorMapInterleave, CUtensorMapSwizzle, CUtensorMapL2promotion, CUtensorMapFloatOOBfill);

extern "C" void kernel_launch(void* const* d_in, const int* in_sizes, int n_in, void* d_out, int out_size) {
  Params p; Maps maps;
  p.h = (const uint4*)d_in[0]; p.pos = (const uint16_t*)d_in[1]; p.ea = (const uint4*)d_in[2];
  p.src = (const int*)d_in[3]; p.dst = (const int*)d_in[4];
  p.we = (const uint16_t*)d_in[5]; p.wx = (const uint16_t*)d_in[6]; p.wh = (const uint16_t*)d_in[7];
  p.out = (uint16_t*)d_out;
  p.N = in_sizes[0] / 64; p.E = in_sizes[3];
  p.EPC = ((p.E + G * 4 - 1) / (G * 4)) * 4;
  p.magic = (uint32_t)(((uint64_t)G << 24) / (uint64_t)p.N);
  p.inv = (1ull << 56) / p.magic;
  const uint64_t ea0 = (uint64_t)d_in[2], ea1 = ea0 + (uint64_t)p.E * 32 - 1;
  p.force_slow = ((ea0 >> 32) != (ea1 >> 32)) || (ea0 & 31) || (p.E & 3);
  void* qp = nullptr;
  cudaGetSymbolAddress(&qp, g_q);
  p.q = (char*)qp;
  if (((uint64_t)p.q >> 32) != (((uint64_t)p.q + QBYTES) >> 32)) p.q += QBYTES;
  cudaGetSymbolAddress((void**)&p.sync, g_sync); cudaGetSymbolAddress((void**)&p.xe, g_xe);
  cudaGetSymbolAddress((void**)&p.xa, g_xa); cudaGetSymbolAddress((void**)&p.xb, g_xb);
  const int df[10] = {18, 250, 900, 500, 250, 59, 0xefa};
  for (int i = 0; i < 10; i++) p.tune[i] = df[i];
  p.qcode = 0xb3985267401aull;
  p.ctam = p.tune[5];
  void* fn = nullptr; cudaDriverEntryPointQueryResult qr;
  cudaGetDriverEntryPoint("cuTensorMapEncodeTiled", &fn, cudaEnableDefault, &qr);
  auto mk = [&](CUtensorMap* tm, void* base, int rows, int box = 64) {
    const cuuint64_t dim[2] = {64, (cuuint64_t)rows}, str[1] = {128}; const cuuint32_t bx[2] = {64, (cuuint32_t)box}, es[2] = {1, 1};
    ((EncodeFn)fn)(tm, CU_TENSOR_MAP_DATA_TYPE_BFLOAT16, 2, base, dim, str, bx, es, CU_TENSOR_MAP_INTERLEAVE_NONE, CU_TENSOR_MAP_SWIZZLE_128B,
                   CU_TENSOR_MAP_L2_PROMOTION_NONE, CU_TENSOR_MAP_FLOAT_OOB_FILL_NONE);
  };
  mk(&maps.m[TM_H / 128], d_in[0], p.N); mk(&maps.m[TM_WE / 128], d_in[5], 145); mk(&maps.m[TM_WH / 128], d_in[7], 128); mk(&maps.m[TM_Q / 128], p.q, p.N, 16);
  for (int k = 0; k < 2; k++) {
    void* xp = (void*)(k ? p.xb : p.xa);
    const cuuint64_t dim[2] = {(cuuint64_t)G * 64, (cuuint64_t)G}, str[1] = {(cuuint64_t)G * (128 << k)}; const cuuint32_t bx[2] = {64, (cuuint32_t)(k ? BROWS : G)}, es[2] = {1, 1};
    ((EncodeFn)fn)(&maps.m[TM_XA / 128 + k], k ? CU_TENSOR_MAP_DATA_TYPE_UINT32 : CU_TENSOR_MAP_DATA_TYPE_UINT16, 2, xp, dim, str, bx, es, CU_TENSOR_MAP_INTERLEAVE_NONE,
                   CU_TENSOR_MAP_SWIZZLE_NONE, CU_TENSOR_MAP_L2_PROMOTION_NONE, CU_TENSOR_MAP_FLOAT_OOB_FILL_NONE);
  }
  cudaFuncSetAttribute(egnn_kernel, cudaFuncAttributeMaxDynamicSharedMemorySize, SMEM);
  egnn_kernel<<<G, NTHR, SMEM>>>(p, maps);
}
```

```cpp
#include <cuda_runtime.h>
#include <cuda_bf16.h>
#include <cuda_fp16.h>
#include <cuda.h>
#include <stdint.h>
#pragma nv_diag_suppress 549

#define PFN p.tune[0]
#define PFNS p.tune[1]
#define BDEL p.tune[2]
#define DEFNS p.tune[4]
#define CTAM p.ctam
#define QREV p.tune[6]
#define UORD p.tune[7]
#define QCODE p.qcode
#define FIRSTSEQ mu(0); mu(1); fi(0); mu(2); fi(1);
#define BODYSEQ tl_(); hc(0); un(); fi(2); mu(3); mu(4); ad(1); ad(0); cv(0); cv(1); cv(3); fi(3); mu(5); cv(2); ex0(); he(0); ex1(); he(1); \
  fi(4); hc(1); ex2(); ad(2); he(2); hs(0); fi(5); mu(6); hs(1); mu(7); ad(3); issue(); hc(2); fi(6); he(3); hs(3); hs(2); he(4); \
  fi(7); mu(0); he(5); ad(5); hc(3); mu(1); ad(4); he(6); hs(4); fi(0); hs(6); he(7); hs(5); mu(2); hs(7); ad(6); fi(1); ad(7); \
  pf();
#define LASTSEQ hc(0); un(); fi(2); mu(3); mu(4); ad(1); ad(0); fi(3); mu(5); fi(4); hc(1); ad(2); fi(5); mu(6); mu(7); ad(3); hc(2); fi(6); \
  fi(7); ad(5); hc(3); ad(4); ad(6); ad(7); pf();
namespace {

constexpr int G = 132;
constexpr int NTHR = 512, NWK = 352, NCH = 5;
constexpr int NST = 3, STG = 2560;
constexpr int BROWS = 44, RNB = 2, PADM = 33;
constexpr int SCAP = 448;

constexpr int OFF_H = 0;
constexpr int OFF_W = 49152;
constexpr int OFF_WD = OFF_W + 16384;
constexpr int OFF_W3 = OFF_WD + 1024;
constexpr int OFF_P2 = OFF_W3 + 2048;
constexpr int OFF_RING = OFF_P2 + 24576;
constexpr int OFF_TE = OFF_RING + 12 * NST * STG;
constexpr int OFF_TS = OFF_TE + SCAP * 64;
constexpr int OFF_INV = OFF_TS - 768;
constexpr int OFF_GP = OFF_TS + SCAP * 32;
constexpr int OFF_WX = OFF_GP + 3072;
constexpr int OFF_LEN = OFF_WX + 128;
constexpr int OFF_MISC = OFF_LEN + 128;
constexpr int OFF_BAR = OFF_MISC + 48;
constexpr int SMEM = OFF_BAR + 256;
static_assert(SMEM <= 232448, "smem");
constexpr uint32_t sb = 1024;
constexpr int OFF_SRCI = OFF_TE;
constexpr int OFF_SB = OFF_RING, OFF_SA = OFF_SB + 34816, OFF_AX = OFF_SA + 32768, OFF_DST = OFF_H + 24576;
constexpr int OFF_WS = OFF_AX + 17408;
constexpr int OFF_BC = OFF_WS + 2304;
constexpr int OFF_CNT = OFF_P2;
constexpr int OFF_DH = OFF_CNT + 2176;
constexpr int OFF_POS = OFF_DH + 128;
constexpr int OFF_EXT = OFF_POS + 3072;
constexpr int OFF_XB = OFF_EXT + 1024, XPAD = G * 256;
static_assert(OFF_XB + XPAD + 1028 <= OFF_RING + 12 * STG && OFF_XB % 128 == 0 && OFF_BC + 544 <= OFF_TE && OFF_P2 % 1024 == 0 && OFF_SA % 1024 == 0 && SCAP * 64 >= 24576, "staging");
constexpr int BAR_DST = OFF_BAR, BAR_SRC = BAR_DST + 40, BAR_T = BAR_SRC + 24, BAR_W = BAR_T + 48, BAR_PS = BAR_W + 8, BAR_AW = BAR_PS + 8,
              BAR_QP = BAR_AW + 8, BAR_QR = BAR_QP + 8, BAR_HA = BAR_QR + 8, BAR_EP = BAR_HA + 8, BAR_AX = BAR_EP + 8, BAR_AI = BAR_AX + 8, BAR_HB = BAR_AI + 8, BAR_U = BAR_HB + 8, BAR_WH = BAR_U + 8, BAR_M = BAR_WH + 8, BAR_X = BAR_M + 24, BAR_END = BAR_X + 8;
static_assert(BAR_END <= OFF_BAR + 256, "barriers");
constexpr uint32_t QBYTES = 8u << 20;

__device__ __align__(256) uint4 g_xa[G * G * 8];
__device__ __align__(256) uint4 g_xb[G * G * 16];
__device__ __align__(256) uint2 g_xe[G * G * 32];
__device__ __align__(256) uint4 g_q[2 * QBYTES / 16];
__device__ __align__(256) uint32_t g_sync[8];
#define STAMP(k)

struct Maps { CUtensorMap m[6]; };
constexpr int TM_H = 0, TM_WE = 128, TM_WH = 256, TM_Q = 384, TM_XA = 512, TM_XB = 640;
struct Params {
  const int* dst; uint32_t* sync; int E, EPC, N, ctam; unsigned long long inv; uint32_t magic; int force_slow;
  const int* src; const uint16_t* pos; const uint4* ea; const uint16_t* we; const uint16_t* wx; char* q;
  const uint4* xa; const uint4* xb; uint2* xe; uint16_t* out; const uint4* h; const uint16_t* wh;
  int tune[10]; unsigned long long qcode;
};
template<int V> struct IC { static constexpr int value = V; };

#define R32(d) "+f"(d[0]),"+f"(d[1]),"+f"(d[2]),"+f"(d[3]),"+f"(d[4]),"+f"(d[5]),"+f"(d[6]),"+f"(d[7]),"+f"(d[8]),"+f"(d[9]),"+f"(d[10]),"+f"(d[11]),"+f"(d[12]),"+f"(d[13]),"+f"(d[14]),"+f"(d[15]),"+f"(d[16]),"+f"(d[17]),"+f"(d[18]),"+f"(d[19]),"+f"(d[20]),"+f"(d[21]),"+f"(d[22]),"+f"(d[23]),"+f"(d[24]),"+f"(d[25]),"+f"(d[26]),"+f"(d[27]),"+f"(d[28]),"+f"(d[29]),"+f"(d[30]),"+f"(d[31])
#define S32 "{%0,%1,%2,%3,%4,%5,%6,%7,%8,%9,%10,%11,%12,%13,%14,%15,%16,%17,%18,%19,%20,%21,%22,%23,%24,%25,%26,%27,%28,%29,%30,%31}"
#define DI __device__ __forceinline__

constexpr uint64_t DHI = ((uint64_t)(1024 >> 4) << 32) | (1ull << 62);
template<int SD> DI void rs64b(float (&d)[32], uint32_t a0, uint32_t a1, uint32_t a2, uint32_t a3, uint64_t db) {
  asm volatile("wgmma.mma_async.sync.aligned.m64n64k16.f32.bf16.bf16 " S32 ", {%32,%33,%34,%35}, %36, %37, 1, 1, 1;" : R32(d) : "r"(a0), "r"(a1), "r"(a2), "r"(a3), "l"(db), "n"(SD)); }
template<int SD> DI void rs64h(float (&d)[32], uint32_t a0, uint32_t a1, uint32_t a2, uint32_t a3, uint64_t db) {
  asm volatile("wgmma.mma_async.sync.aligned.m64n64k16.f32.f16.f16 " S32 ", {%32,%33,%34,%35}, %36, %37, 1, 1, 1;" : R32(d) : "r"(a0), "r"(a1), "r"(a2), "r"(a3), "l"(db), "n"(SD)); }
template<int SD> DI void ss64(float (&d)[32], uint64_t da, uint64_t db) {
  asm volatile("wgmma.mma_async.sync.aligned.m64n64k16.f32.bf16.bf16 " S32 ", %32, %33, %34, 1, 1, 0, 1;" : R32(d) : "l"(da), "l"(db), "n"(SD)); }
#define R16(d) "+f"(d[0]),"+f"(d[1]),"+f"(d[2]),"+f"(d[3]),"+f"(d[4]),"+f"(d[5]),"+f"(d[6]),"+f"(d[7]),"+f"(d[8]),"+f"(d[9]),"+f"(d[10]),"+f"(d[11]),"+f"(d[12]),"+f"(d[13]),"+f"(d[14]),"+f"(d[15])
#define S16 "{%0,%1,%2,%3,%4,%5,%6,%7,%8,%9,%10,%11,%12,%13,%14,%15}"
template<int SD> DI void rs32b(float (&d)[16], const uint32_t* a, uint64_t db) {
  asm volatile("wgmma.mma_async.sync.aligned.m64n32k16.f32.bf16.bf16 " S16 ", {%16,%17,%18,%19}, %20, %21, 1, 1, 1;" : R16(d) : "r"(a[0]), "r"(a[1]), "r"(a[2]), "r"(a[3]), "l"(db), "n"(SD)); }
DI void rs32h(float (&d)[16], const uint32_t* a, uint64_t db) {
  asm volatile("wgmma.mma_async.sync.aligned.m64n32k16.f32.f16.f16 " S16 ", {%16,%17,%18,%19}, %20, 1, 1, 1, 1;" : R16(d) : "r"(a[0]), "r"(a[1]), "r"(a[2]), "r"(a[3]), "l"(db)); }
DI void fence_regs(float (&d)[16]) { asm volatile("" : R16(d) :: "memory"); }
DI void trap_if(bool c) { asm volatile("{.reg .pred p; setp.eq.u32 p, %0, 0; @p bra.uni LT_%=; trap; LT_%=:}" :: "r"((uint32_t)c)); }
DI void wg_fence() { asm volatile("wgmma.fence.sync.aligned;" ::: "memory"); }
DI void wg_commit() { asm volatile("wgmma.commit_group.sync.aligned;" ::: "memory"); }
DI void wg_wait0() { asm volatile("wgmma.wait_group.sync.aligned 0;" ::: "memory"); }
DI void fence_regs(float (&d)[32]) { asm volatile("" : R32(d) :: "memory"); }
DI void proxy_fence() { asm volatile("fence.proxy.async.shared::cta;" ::: "memory"); }
DI uint64_t pol_first() { uint64_t r; asm("createpolicy.fractional.L2::evict_first.b64 %0, 1.0;" : "=l"(r)); return r; }
DI float tanh_ap(float x) { float y; asm("tanh.approx.f32 %0, %1;" : "=f"(y) : "f"(x)); return y; }
DI float silu_h(float y) { return fmaf(y, tanh_ap(y), y); }
DI uint32_t pack_bf16(float lo, float hi) { uint32_t r; asm("cvt.rn.bf16x2.f32 %0, %1, %2;" : "=r"(r) : "f"(hi), "f"(lo)); return r; }
DI uint32_t pack_f16(float lo, float hi) { uint32_t r; asm("cvt.rn.f16x2.f32 %0, %1, %2;" : "=r"(r) : "f"(hi), "f"(lo)); return r; }
DI float bf_lo(uint32_t v) { return __uint_as_float(v << 16); }
DI float bf_hi(uint32_t v) { return __uint_as_float(v & 0xFFFF0000u); }
DI uint32_t b2h(uint32_t v, float s) { return pack_f16(s * bf_lo(v), s * bf_hi(v)); }
DI void mbar_wait(uint32_t bar, uint32_t parity = 0) {
  asm volatile("{.reg .pred p, q; .reg .u32 c; mov.u32 c, 0;\n"
    "LW_%=: mbarrier.try_wait.parity.shared::cta.b64 p, [%0], %1;\n add.u32 c, c, 1; setp.lt.and.u32 q, c, 0x200000, !p;\n @q bra.uni LW_%=;}" :: "r"(bar), "r"(parity) : "memory");
}
DI void mbar_arrive(uint32_t bar, int p = 1) { asm volatile("{.reg .pred p; setp.ne.b32 p, %1, 0; @p mbarrier.arrive.shared::cta.b64 _, [%0];}" :: "r"(bar), "r"(p) : "memory"); }
DI void bar_sync(int id, int n) { asm volatile("bar.sync %0, %1;" :: "r"(id), "r"(n) : "memory"); }
DI void bar_arrive(int id, int n) { asm volatile("bar.arrive %0, %1;" :: "r"(id), "r"(n) : "memory"); }
DI __nv_bfloat162 b2(uint32_t v) { return *(__nv_bfloat162*)&v; }
DI uint32_t u2(__nv_bfloat162 v) { return *(uint32_t*)&v; }
DI uint32_t hsq(uint32_t v) { return u2(__hmul2(b2(v), b2(v))); }
DI uint32_t hsub(uint32_t a, uint32_t b) { return u2(__hsub2(b2(a), b2(b))); }
DI uint32_t hhalf(uint32_t v) { return u2(__hmul2(b2(v), __floats2bfloat162_rn(0.5f, 0.5f))); }
DI uint32_t mag2(uint32_t m, uint32_t v) { return __vmaxu2(m, v & 0x7FFF7FFFu); }
DI uint32_t hmag(uint32_t m, uint32_t v) { const __half2 r = __hmax2(*(const __half2*)&m, __habs2(*(const __half2*)&v)); return *(const uint32_t*)&r; }
DI uint32_t magr(uint32_t m) { return max(m & 0xFFFF, m >> 16); }
DI void sts128(uint32_t a, uint32_t x, uint32_t y, uint32_t z, uint32_t w) { asm volatile("st.shared.v4.u32 [%0], {%1,%2,%3,%4};" :: "r"(a), "r"(x), "r"(y), "r"(z), "r"(w) : "memory"); }
DI void sts64(uint32_t a, uint32_t x, uint32_t y) { asm volatile("st.shared.v2.u32 [%0], {%1,%2};" :: "r"(a), "r"(x), "r"(y) : "memory"); }
DI void sts32(uint32_t a, uint32_t x) { asm volatile("st.shared.u32 [%0], %1;" :: "r"(a), "r"(x) : "memory"); }
DI void sts16(uint32_t a, uint32_t x) { asm volatile("st.shared.u16 [%0], %1;" :: "r"(a), "h"((uint16_t)x) : "memory"); }
DI void lds128(uint32_t* v, uint32_t a) { asm volatile("ld.shared.v4.u32 {%0, %1, %2, %3}, [%4];" : "=r"(v[0]), "=r"(v[1]), "=r"(v[2]), "=r"(v[3]) : "r"(a) : "memory"); }
DI void lds64(uint32_t& x, uint32_t& y, uint32_t a) { asm volatile("ld.shared.v2.u32 {%0, %1}, [%2];" : "=r"(x), "=r"(y) : "r"(a) : "memory"); }
DI uint32_t lds32(uint32_t a) { uint32_t x; asm volatile("ld.shared.u32 %0, [%1];" : "=r"(x) : "r"(a) : "memory"); return x; }
DI uint32_t lds16(uint32_t a) { uint32_t x; asm volatile("ld.shared.u16 %0, [%1];" : "=r"(x) : "r"(a) : "memory"); return x; }
DI uint32_t atoms_add(uint32_t a, uint32_t v) { uint32_t r; asm volatile("atom.shared.add.u32 %0, [%1], %2;" : "=r"(r) : "r"(a), "r"(v) : "memory"); return r; }
DI void bulk_load(uint32_t dst, const void* src, uint32_t bytes, uint32_t bar) {
  asm volatile("cp.async.bulk.shared::cluster.global.mbarrier::complete_tx::bytes.L2::cache_hint [%0], [%1], %2, [%3], %4;" :: "r"(dst), "l"(src), "r"(bytes), "r"(bar), "l"(pol_first()) : "memory"); }
DI void mbar_expect(uint32_t bar, uint32_t bytes) { asm volatile("mbarrier.arrive.expect_tx.shared::cta.b64 _, [%0], %1;" :: "r"(bar), "r"(bytes) : "memory"); }
DI void mbar_init(uint32_t bar, int n) { asm volatile("mbarrier.init.shared::cta.b64 [%0], %1;" :: "r"(bar), "r"(n) : "memory"); }
DI void tma_load(uint32_t dst, uint64_t tm, int row, uint32_t bar) {
  asm volatile("cp.async.bulk.tensor.2d.shared::cluster.global.mbarrier::complete_tx::bytes.L2::cache_hint [%0], [%1, {%3, %4}], [%2], %5;" :: "r"(dst), "l"(tm), "r"(bar), "r"(0), "r"(row), "l"(pol_first()) : "memory"); }
DI void tma_store(uint64_t tm, int col, int row, uint32_t src) {
  asm volatile("cp.async.bulk.tensor.2d.global.shared::cta.bulk_group [%0, {%2, %3}], [%1];" :: "l"(tm), "r"(src), "r"(col), "r"(row) : "memory"); }
DI void bulk_commit() { asm volatile("cp.async.bulk.commit_group;" ::: "memory"); }
DI uint2 ld_poll2(const void* a) { uint2 v; asm volatile("ld.relaxed.gpu.global.v2.u32 {%0, %1}, [%2];" : "=r"(v.x), "=r"(v.y) : "l"(a) : "memory"); return v; }
DI void st_ext(uint2* a, uint32_t v, uint32_t ep) { asm volatile("st.relaxed.gpu.global.v2.u32 [%0], {%1, %2};" :: "l"(a), "r"(v), "r"(ep) : "memory"); }
DI uint32_t ext_get(const uint2* a, uint32_t ep) { uint2 v; int spin = 0; do { v = ld_poll2(a); trap_if(++spin > 4000000); } while (__any_sync(~0u, v.y != ep)); return v.x; }
DI void bulk_wait() { asm volatile("cp.async.bulk.wait_group 0;" ::: "memory"); }
DI void hint_signal(uint32_t* c) { asm volatile("red.relaxed.gpu.global.add.u32 [%0], 1;" :: "l"(c) : "memory"); }
DI void hint_wait(const uint32_t* c, uint32_t target) { uint32_t v; int spin = 0;
  do { asm volatile("ld.relaxed.gpu.global.u32 %0, [%1];" : "=r"(v) : "l"(c) : "memory"); trap_if(++spin > 4000000); } while (__any_sync(~0u, (int)(v - target) < 0)); }
DI void stsm4(uint32_t a, uint32_t x, uint32_t y, uint32_t z, uint32_t w) { asm volatile("stmatrix.sync.aligned.m8n8.x4.shared.b16 [%0], {%1,%2,%3,%4};" :: "r"(a), "r"(x), "r"(y), "r"(z), "r"(w) : "memory"); }
DI void ldsm4(uint32_t* v, uint32_t a) { asm volatile("ldmatrix.sync.aligned.m8n8.x4.shared.b16 {%0,%1,%2,%3}, [%4];" : "=r"(v[0]), "=r"(v[1]), "=r"(v[2]), "=r"(v[3]) : "r"(a) : "memory"); }
DI void ldsm4t(uint32_t* v, uint32_t a) { asm volatile("ldmatrix.sync.aligned.m8n8.x4.trans.shared.b16 {%0,%1,%2,%3}, [%4];" : "=r"(v[0]), "=r"(v[1]), "=r"(v[2]), "=r"(v[3]) : "r"(a) : "memory"); }
DI uint32_t mad16(uint32_t x, uint32_t m, uint32_t c) { uint32_t r; asm("dp2a.lo.u32.u32 %0, %1, %2, %3;" : "=r"(r) : "r"(x), "r"(m), "r"(c)); return r; }
DI bool wbad(uint32_t m, uint32_t hi) { return m > hi || (m && m < 0x3980); }

__device__ __noinline__ void slow_path(const Params& p, int wid, int lane, int node0, int nloc) {
  const uint32_t ab = sb + OFF_P2 + wid * 8704;
  for (int i = lane; i < 32 * 68; i += 32) sts32(ab + i * 4, 0);
  __syncwarp();
  const uint32_t wdv = __ldg((const uint32_t*)(p.we + 128 * 64) + lane), wxv = __ldg((const uint32_t*)p.wx + lane);
  const int nb0 = node0 + wid * 32, cntn = max(0, min(32, nloc - wid * 32));
  auto dot = [&](uint32_t hv, const uint16_t* w, int K2, float& y0, float& y1) {
#pragma unroll 4
    for (int k = 0; k < K2; k++) {
      const uint32_t hk = __shfl_sync(~0u, hv, k), wa = __ldg((const uint32_t*)(w + 2 * k * 64) + lane), wb = __ldg((const uint32_t*)(w + (2 * k + 1) * 64) + lane);
      y0 = fmaf(bf_lo(hk), bf_lo(wa), fmaf(bf_hi(hk), bf_lo(wb), y0)); y1 = fmaf(bf_lo(hk), bf_hi(wa), fmaf(bf_hi(hk), bf_hi(wb), y1));
    }
  };
  auto silu = [](float x) { return x / (1.f + __expf(-x)); };
#pragma unroll 1
  for (int base = 0; base < p.E; base += 32) {
    const int e = base + lane;
    const uint32_t dl = e < p.E ? (uint32_t)(__ldg(p.dst + e) - nb0) : 0xFFFFFFFFu;
    uint32_t mk = __ballot_sync(~0u, dl < (uint32_t)cntn);
    while (mk) {
      const int l = __ffs(mk) - 1; mk &= mk - 1;
      const int ee = base + l, n = __shfl_sync(~0u, dl, l), s = __ldg(p.src + ee);
      const uint16_t *po = p.pos + (size_t)(nb0 + n) * 3, *pp = p.pos + (size_t)s * 3;
      const uint32_t dxy = hsub(__ldg(po) | (__ldg(po + 1) << 16), __ldg(pp) | (__ldg(pp + 1) << 16)), dz = hsub(__ldg(po + 2), __ldg(pp + 2));
      const uint32_t sq = hsq(dxy); const float d2 = bf_lo(sq) + bf_hi(sq) + bf_lo(hsq(dz));
      float y0 = d2 * bf_lo(wdv), y1 = d2 * bf_hi(wdv);
      dot(__ldg((const uint32_t*)(p.h + (size_t)(nb0 + n) * 8) + lane), p.we, 32, y0, y1);
      dot(__ldg((const uint32_t*)(p.h + (size_t)s * 8) + lane), p.we + 64 * 64, 32, y0, y1);
      dot(__ldg((const uint32_t*)(p.ea + (size_t)ee * 2) + (lane & 7)), p.we + 129 * 64, 8, y0, y1);
      const uint32_t mm = pack_bf16(silu(y0), silu(y1));
      float c = bf_lo(mm) * bf_lo(wxv) + bf_hi(mm) * bf_hi(wxv);
#pragma unroll
      for (int o = 16; o; o >>= 1) c += __shfl_xor_sync(~0u, c, o);
      const uint32_t a = ab + n * 272;
      uint32_t x0, x1; lds64(x0, x1, a + lane * 8);
      sts64(a + lane * 8, __float_as_uint(__uint_as_float(x0) + bf_lo(mm)), __float_as_uint(__uint_as_float(x1) + bf_hi(mm)));
      if (lane < 3) { const float df = lane == 0 ? bf_lo(dxy) : lane == 1 ? bf_hi(dxy) : bf_lo(dz); sts32(a + 256 + lane * 4, __float_as_uint(fmaf(c, df, __uint_as_float(lds32(a + 256 + lane * 4))))); }
    }
  }
  __syncwarp();
#pragma unroll 1
  for (int n = 0; n < cntn; n++) {
    uint32_t x0, x1; lds64(x0, x1, ab + n * 272 + lane * 8);
    const uint32_t hv = __ldg((const uint32_t*)(p.h + (size_t)(nb0 + n) * 8) + lane);
    float y0 = 0.f, y1 = 0.f;
    dot(hv, p.wh, 32, y0, y1); dot(pack_bf16(__uint_as_float(x0), __uint_as_float(x1)), p.wh + 64 * 64, 32, y0, y1);
    ((uint32_t*)p.out)[(size_t)(nb0 + n) * 32 + lane] = u2(__hadd2(b2(hv), b2(pack_bf16(silu(y0), silu(y1)))));
    if (lane < 3) p.out[(size_t)p.N * 64 + (size_t)(nb0 + n) * 3 + lane] = (uint16_t)pack_bf16(bf_lo(__ldg(p.pos + (size_t)(nb0 + n) * 3 + lane)) + __uint_as_float(lds32(ab + n * 272 + 256 + lane * 4)), 0.f);
  }
}

__global__ void __launch_bounds__(NTHR, 1) egnn_kernel(const __grid_constant__ Params p, const __grid_constant__ Maps maps) {
  const uint64_t tmb = (uint64_t)&maps;
  extern __shared__ __align__(1024) unsigned char smraw[];
  const int tid = threadIdx.x, cta = blockIdx.x * CTAM % G;
  const int e0 = cta * p.EPC, n4 = max(0, min(p.EPC, p.E - e0)) >> 2;
  STAMP(0);
  if (tid == NWK) {
#pragma unroll 1
    for (int k = 0; k < NCH; k++) { const int nb = max(0, min(NWK, n4 - k * NWK)) * 16;
      mbar_init(sb + BAR_DST + k * 8, 1);
      asm volatile("fence.mbarrier_init.release.cluster;" ::: "memory");
      mbar_expect(sb + BAR_DST + k * 8, nb);
      if (nb) bulk_load(sb + OFF_DST + k * NWK * 16, (const char*)(p.dst + e0) + k * NWK * 16, nb, sb + BAR_DST + k * 8); }
  }
  const int lane = tid & 31, wid = __shfl_sync(~0u, tid >> 5, 0), w = wid & 3;
  asm volatile("{.reg .pred p; setp.eq.u32 p, %2, 384; @p cp.async.cg.shared.global [%0], [%1], 16;}" :: "r"(sb + OFF_LEN - 192 + (tid >> 1)), "l"(p.sync), "r"(tid & 415) : "memory");

  auto first_node = [&](int c) { return (int)((c * p.inv + 0xFFFFFFFFull) >> 32); };
  const int node0 = first_node(cta), nloc = min(first_node(cta + 1), p.N) - node0;
  const uint32_t ealo = (uint32_t)(uint64_t)p.ea;
  const int epad = min(e0, p.E - 1);
  if (wid >= 12) {
    const int t = tid - 384;
    auto load_h = [&](int b) { mbar_expect(sb + BAR_T + b * 8, 8192); tma_load(sb + OFF_H + b * 8192, tmb + TM_H, node0 + b * 64, sb + BAR_T + b * 8); };
    uint32_t pv[9], ev = 0;
#pragma unroll
    for (int i = 0; i < 3; i++) { const uint16_t* pp = p.pos + (size_t)(node0 + t + 128 * i) * 3;
      pv[3 * i] = pv[3 * i + 1] = pv[3 * i + 2] = 0;
      asm volatile("{.reg .pred p; setp.lt.s32 p, %4, %5;\n @p ld.global.nc.u16 %0, [%3];\n @p ld.global.nc.u16 %1, [%3+2];\n @p ld.global.nc.u16 %2, [%3+4];}"
        : "+r"(pv[3 * i]), "+r"(pv[3 * i + 1]), "+r"(pv[3 * i + 2]) : "l"(pp), "r"(t + 128 * i), "r"(p.N - node0)); }
    asm volatile("{.reg .pred p; setp.lt.u32 p, %3, 8; @p ld.global.nc.u32 %0, [%1]; @p st.global.v4.u32 [%2], {%4, %4, %4, %4};}"
      : "+r"(ev) : "l"((const uint32_t*)(p.ea + (size_t)epad * 2) + t), "l"(p.q + (size_t)(p.N + cta * PADM) * 128 + t * 16), "r"(t), "r"(0xF700F700u) : "memory");
    asm volatile("cp.async.wait_all;" ::: "memory");
    __syncwarp();
    const uint32_t e = lds32(sb + OFF_LEN + 8 + w * 16) + 1;
    {
      const uint32_t tg = (1 + e % 3) << 30, v = ((tg >> 16) + 512 + (lane & 7) * 4) * 0x10001u;
      if (t == 0) sts32(sb + OFF_MISC + 32, e);
#pragma unroll
      for (int i = 0; i < 9; i++) sts128(sb + OFF_SA + t * 16 + i * 2048, v, v + 0x10001u, v + 0x20002u, v + 0x30003u);
      bar_sync(6, NTHR);
      mbar_arrive(sb + BAR_EP, lane == 0);
#pragma unroll
      for (int i = 0; i < 17; i++) sts128(sb + OFF_SB + t * 16 + i * 2048, tg, tg, tg, tg); }
    uint32_t mp = 0;
#pragma unroll
    for (int i = 0; i < 3; i++) { sts64(sb + OFF_POS + (t + 128 * i) * 8, pv[3 * i] | (pv[3 * i + 1] << 16), pv[3 * i + 2]); mp = mag2(mag2(mp, pv[3 * i] | (pv[3 * i + 1] << 16)), pv[3 * i + 2]); }
    proxy_fence();
    __syncwarp();
    mbar_arrive(sb + BAR_PS, lane == 0);
    mbar_wait(sb + BAR_W);
    {
      uint32_t v[4], u[4]; const int r = t >> 3, c = t & 7;
      lds128(v, sb + OFF_WS + 128 + t * 16); lds128(u, sb + OFF_WS + c * 16);
      const uint32_t x = lds32(sb + OFF_WS + 2176 + lane * 4);
      sts128(sb + OFF_W3 + r * 128 + ((c ^ (r & 7)) << 4), b2h(v[0], .5f), b2h(v[1], .5f), b2h(v[2], .5f), b2h(v[3], .5f));
      const float s = ((r & 1) || r == 6) ? 0.f : .5f;
      if (t < 64) sts128(sb + OFF_WD + r * 128 + ((c ^ r) << 4), b2h(u[0], s), b2h(u[1], s), b2h(u[2], s), b2h(u[3], s));
      if (t < 32) sts32(sb + OFF_WX + (t & 3) * 32 + (t >> 2) * 4, b2h(x, 1.f));
      const uint32_t m3 = __reduce_max_sync(~0u, magr(mag2(mag2(mag2(mag2(0, v[0]), v[1]), v[2]), v[3]))), md = __reduce_max_sync(~0u, magr(mag2(mag2(mag2(mag2(0, u[0]), u[1]), u[2]), u[3])));
      if (wbad(m3, 0x4000) || wbad(md, 0x4000) || wbad(__reduce_max_sync(~0u, magr(mag2(0, x))), 0x4700) || magr(mp) >= 0x4200 || magr(mag2(0, ev)) >= 0x4380) sts32(sb + OFF_MISC + 8, 1);
    }
    if (w == 1) {
#pragma unroll 1
      for (int b = 0; b < 3; b++) { mbar_wait(sb + BAR_SRC + b * 8); if (lane == 0) load_h(b); }
    }
    bar_sync(3, 128);
    const uint32_t frag = (w * 16 + (lane & 15)) * 128 + (((lane >> 4) ^ (lane & 7)) << 4);
    uint32_t mq = 0;
#pragma unroll 1
    for (int b = 0; b < 6; b++) {
      float acc[32];
      const uint64_t da = DHI | (((sb + OFF_H) >> 4) + b * 512), db = DHI | ((sb + OFF_W) >> 4);
      const uint32_t v0 = lds16(sb + OFF_POS + b * 512 + w * 128 + lane * 2), v1 = lds16(sb + OFF_POS + 64 + b * 512 + w * 128 + lane * 2);
      mbar_wait(sb + BAR_T + b * 8);
      if (b == 0) STAMP(25);
      if (b == 5) STAMP(26);
      wg_fence();
      ss64<0>(acc, da, db); ss64<1>(acc, da + 2, db + 128); ss64<1>(acc, da + 4, db + 256); ss64<1>(acc, da + 6, db + 384);
      wg_commit();
      if (b == 0) mbar_wait(sb + BAR_AW);
      if (t == 32 && b < 3) load_h(b + 3);
      __syncwarp();
      uint32_t ff[6], fg[6];
#pragma unroll
      for (int j = 0; j < 6; j++) { ff[j] = (__byte_perm((j & 1) ? v1 : v0, 0, 0x4140) >> (3 * (j >> 1))) & 0x00070007u; fg[j] = __vsub2(0x00040004u, ff[j]);
        asm volatile("" : "+r"(ff[j]), "+r"(fg[j])); }
      wg_wait0(); fence_regs(acc);
      uint32_t o[16];
#pragma unroll
      for (int j = 0; j < 16; j++) o[j] = pack_f16(.5f * acc[2 * j], .5f * acc[2 * j + 1]);
#pragma unroll
      for (int j = 0; j < 6; j++) {
        const uint32_t m = o[j] & 0x7FFF7FFFu; mq = __vmaxu2(mq, m);
        o[j] = (__viaddmax_s16x2(m, fg[j], 0) & 0xFFF8FFF8u) | ff[j] | (o[j] & 0x80008000u); }
      if (b == 4) mbar_wait(sb + BAR_AX);
      const uint32_t qs = sb + OFF_SA + b * 8192;
#pragma unroll
      for (int j = 0; j < 4; j++) stsm4((qs + frag) ^ (j << 5), o[4 * j], o[4 * j + 1], o[4 * j + 2], o[4 * j + 3]);
      proxy_fence();
      __syncwarp();
      if (lane == 0 && b * 64 + w * 16 < nloc) tma_store(tmb + TM_Q, 0, node0 + b * 64 + w * 16, qs + w * 2048);
    }
    if (lane == 0) bulk_commit();
    { const uint32_t m = __reduce_max_sync(~0u, magr(mq)); if (lane == 0) sts32(sb + OFF_MISC + 16 + w * 4, m); }
    asm volatile("setmaxnreg.dec.sync.aligned.u32 56;");
    bulk_wait();
    bar_sync(3, 128);
    if (w == 0) {
      STAMP(18);
      uint32_t mv[4]; lds128(mv, sb + OFF_MISC + 16);
      const uint32_t mx = max(max(mv[0], mv[1]), max(mv[2], mv[3]));
      mbar_arrive(sb + BAR_QR, lane == 0);
      STAMP(19);
      if (lane == 0) {
        if (nloc > 0 && (mx >= 0x7BF0 || mx < 0x1400)) asm volatile("st.relaxed.gpu.global.u32 [%0+4], %1;" :: "l"(p.sync), "r"(e) : "memory");
        asm volatile("red.release.gpu.global.add.u32 [%0], 1;" :: "l"(p.sync) : "memory");
      }
      __syncwarp();
      uint32_t c, f; int spin = 0;
      do { asm volatile("ld.acquire.gpu.global.v2.u32 {%0, %1}, [%2];" : "=r"(c), "=r"(f) : "l"(p.sync) : "memory"); trap_if(++spin > 4000000); } while (__any_sync(~0u, (int)(c - e * G) < 0));
      if (f == e) sts32(sb + OFF_MISC + 8, 1);
      if (cta == 0 && lane == 0) asm volatile("st.relaxed.gpu.global.u32 [%0+8], %1;" :: "l"(p.sync), "r"(e) : "memory");
      STAMP(20);
      __syncwarp();
      mbar_arrive(sb + BAR_QP, lane == 0);
    }
    if (w == 2) {
      const uint32_t tg = (1 + e % 3) << 30;
      hint_wait(p.sync + 5, e * G);
      if (lane == 0) { mbar_expect(sb + BAR_HB, XPAD);
#pragma unroll 1
        for (int o = 0; o < 4; o++) bulk_load(sb + OFF_XB + o * (G * 64), (const char*)p.xb + (size_t)(cta * 4 + o) * (G * 64), G * 64, sb + BAR_HB); }
      STAMP(21);
      bar_sync(7, 384);
      sts32(sb + OFF_XB + XPAD, tg + p.N + cta * PADM);
      const uint32_t nx = __shfl_sync(~0u, lds32(sb + OFF_MISC + 8) ? 0 : lds32(sb + OFF_MISC + 4), 0);
#pragma unroll 1
      for (uint32_t k = 0; k < nx; k += 32) {
        const uint32_t i = min(k + lane, nx - 1), xr = lds32(sb + OFF_EXT + i * 4), row = (xr >> 9) & 255;
        const uint32_t v = ext_get(p.xe + (cta * G + row) * 32 + ((xr >> 17) & 31), e), x = lds32(sb + OFF_CNT + (xr & 511) * 4) + (xr >> 22) * 16;
        sts32(sb + OFF_XB + XPAD + 4 + i * 4, v); sts16(sb + OFF_TS + x, XPAD + 4 + i * 4);
        sts32(sb + OFF_TE + x * 2, mad16(v, 0x2000u, ealo - (tg >> 11) + row * p.EPC * 32));
      }
      __syncwarp();
      mbar_arrive(sb + BAR_HB, lane == 0);
    }
    if (w == 1) {
      const uint32_t nb = (p.E / G) & ~15u;
#pragma unroll 1
      for (int i = 0; i < PFN; i++) {
        if (lane == 0 && nb) asm volatile("cp.async.bulk.prefetch.L2.global [%0], %1;" :: "l"((const char*)p.ea + (size_t)(i * G + cta) * nb), "r"(nb) : "memory");
        __nanosleep(PFNS); }
    }
    if (w == 3) {
      if (lane == 0) { mbar_expect(sb + BAR_U, 16384); tma_load(sb + OFF_W, tmb + TM_WH, 0, sb + BAR_U); }
      __syncwarp();
      bar_sync(4, 416);
      if (lane == 0) tma_load(sb + OFF_W + 8192, tmb + TM_WH, 64, sb + BAR_U);
    }
    bar_sync(3, 128);
    mbar_wait(sb + BAR_U);
    uint32_t mh = 0;
#pragma unroll 1
    for (int i = t; i < 1024; i += 128) {
      uint32_t v[4]; const uint32_t r = (i >> 3) & 7, j = (i ^ r) & 7;
#pragma unroll
      for (int k = 0; k < 4; k++) v[k] = lds32(sb + OFF_W + (i >> 3) * 128 + ((((j & 4) + k) ^ r) << 4) + (j & 3) * 4);
      __syncwarp();
      if (i < 512) sts128(sb + OFF_W + i * 16, hhalf(v[0]), hhalf(v[1]), hhalf(v[2]), hhalf(v[3]));
      else { sts128(sb + OFF_W + i * 16, b2h(v[0], .5f), b2h(v[1], .5f), b2h(v[2], .5f), b2h(v[3], .5f)); mh = mag2(mag2(mag2(mag2(mh, v[0]), v[1]), v[2]), v[3]); } }
    if (wbad(__reduce_max_sync(~0u, magr(mh)), 0x4700)) sts32(sb + OFF_MISC + 12, 1);
    proxy_fence();
    __syncwarp();
    mbar_arrive(sb + BAR_WH, lane == 0);
    if (!__shfl_sync(~0u, lds32(sb + OFF_MISC + 8), 0)) {
      mbar_wait(sb + BAR_WH);
      float chk = 0.f;
#pragma unroll 1
      for (uint32_t todo = UORD; todo; todo >>= 4) {
        const uint32_t nd = lds16(sb + OFF_GP + (todo & 3) * 1024 + w * 256 + (lane & 15) * 8 + 6), hb = (todo >> 3) & 1;
        const uint64_t b1 = DHI | (((sb + OFF_W) >> 4) + hb * 4);
        uint32_t f[8]; float acc[16];
#pragma unroll
        for (int j = 0; j < 8; j += 2) {
          const uint32_t a = j < 4 ? sb + OFF_H + nd * 128 + (((nd & 7) << 4) ^ (lane & 16)) : sb + OFF_P2 + (todo & 3) * 8192 + frag;
          if (j == 4) mbar_wait(sb + BAR_M + (todo & 3) * 8);
          ldsm4(f, a ^ ((j & 3) << 5)); ldsm4(f + 4, a ^ ((j & 3) << 5) ^ 32);
          wg_fence();
          if (j == 0) rs32b<0>(acc, f, b1); else if (j < 4) rs32b<1>(acc, f, b1 + 128 * j); else rs32h(acc, f, b1 + 128 * j);
          if (j < 4) rs32b<1>(acc, f + 4, b1 + 128 * j + 128); else rs32h(acc, f + 4, b1 + 128 * j + 128);
          wg_commit(); wg_wait0(); fence_regs(acc);
        }
        chk = fmaf(acc[0], 0.f, fmaf(acc[2], 0.f, chk));
#pragma unroll
        for (int k = 0; k < 2; k++) {
          const uint32_t o = __shfl_sync(~0u, nd, (lane >> 2) + 8 * k) * 128 + (lane & 3) * 16 + hb * 64;
          uint32_t x[4]; lds128(x, sb + OFF_H + (o ^ ((o >> 3) & 0x70)));
#pragma unroll
          for (int i = 0; i < 4; i++) x[i] = u2(__hadd2(b2(x[i]), b2(pack_bf16(silu_h(acc[4 * i + 2 * k]), silu_h(acc[4 * i + 2 * k + 1])))));
          if (o < nloc * 128) *(uint4*)((char*)p.out + (size_t)node0 * 128 + o) = make_uint4(x[0], x[1], x[2], x[3]);
        }
        __nanosleep(DEFNS);
      }
      uint32_t pa_[9];
#pragma unroll
      for (int k = 0; k < 9; k++) { const uint32_t i = t + 128 * k, n = (i * 43691u) >> 17; pa_[k] = lds16(sb + OFF_INV + n * 2) + (i - 3 * n) * 2; }
      uint16_t* po = p.out + (size_t)p.N * 64 + node0 * 3 + t;
      mbar_wait(sb + BAR_X);
#pragma unroll
      for (int k = 0; k < 9; k++) pa_[k] = lds16(sb + OFF_GP + pa_[k]);
#pragma unroll
      for (int k = 0; k < 9; k++) if (t + 128 * k < nloc * 3) po[128 * k] = pa_[k];
      asm volatile("{.reg .pred p, q; setp.neu.f32 p, %0, 0f00000000; bar.red.or.pred q, 5, 512, p;}" :: "f"(chk) : "memory");
    }
    return;
  }

  if (tid == 320) {
    mbar_init(sb + BAR_W, 1);
    asm volatile("fence.mbarrier_init.release.cluster;" ::: "memory");
    mbar_expect(sb + BAR_W, 2 * 8192 + 2304);
    tma_load(sb + OFF_W, tmb + TM_WE, 64, sb + BAR_W); tma_load(sb + OFF_W + 8192, tmb + TM_WE, 0, sb + BAR_W);
    bulk_load(sb + OFF_WS, p.we + 128 * 64, 2176, sb + BAR_W); bulk_load(sb + OFF_WS + 2176, p.wx, 128, sb + BAR_W);
  }
  if (tid == 288) {
#pragma unroll
    for (int a = BAR_SRC; a < BAR_END; a += 8) if (a != BAR_W) mbar_init(sb + a, a == BAR_X ? 12 : a >= BAR_WH || a == BAR_PS || a == BAR_EP ? 4 : a == BAR_HB ? 2 : 1);
    asm volatile("fence.mbarrier_init.release.cluster;" ::: "memory");
    asm volatile("prefetch.tensormap [%0];" :: "l"(tmb + TM_XA)); asm volatile("prefetch.tensormap [%0];" :: "l"(tmb + TM_H));
    asm volatile("prefetch.tensormap [%0];" :: "l"(tmb + TM_XB)); asm volatile("prefetch.tensormap [%0];" :: "l"(tmb + TM_Q));
  }
  {
    if (tid < 144) { const uint32_t z = (tid >> 3) == 16 ? 0x8000u : 0u; sts128(sb + OFF_CNT + tid * 16, z, z, z, z); }
    else if (tid <= 144 + G) sts32(sb + OFF_BC + (tid - 144) * 4, ((tid - 144) & 31) * 4);
    const uint32_t sp = XPAD * 0x10001u, em = first_node(G);
    if (wid < 7) {
#pragma unroll
      for (int i = 0; i < 4; i++) sts128(sb + OFF_TS + tid * 16 + i * 3584, sp, sp, sp, sp);
    }
    static_assert(SCAP * 32 == 4 * 3584, "fill");
#pragma unroll 1
    for (int i = n4 + tid; i < 1536; i += 384) sts128(sb + OFF_DST + i * 16, em, em, em, em);
    if (tid == 321) sts128(sb + OFF_MISC, 0, 0, p.force_slow, 0);
  }
  bar_arrive(6, NTHR);
  bar_sync(0, 384);
  uint32_t ep, tag, eb0, pk[12], r0[12], r1[12], cb;
  uint2 vb[12];
  auto get_tag = [&]() { mbar_wait(sb + BAR_EP); ep = lds32(sb + OFF_MISC + 32); tag = (1 + ep % 3) << 30; eb0 = ealo - (tag >> 11); };
  if (wid == 11) {
    trap_if(sb != (uint32_t)__cvta_generic_to_shared(smraw));
#pragma unroll 1
    for (int k = 0; k < 3; k++) { const int nb = max(0, min(8192, n4 * 16 - k * 8192));
      mbar_wait(sb + BAR_DST + (k ? k + 1 : 0) * 8);
      if (lane == 0) { mbar_expect(sb + BAR_SRC + k * 8, nb);
        if (nb) bulk_load(sb + OFF_SRCI + k * 8192, (const char*)(p.src + e0) + k * 8192, nb, sb + BAR_SRC + k * 8); } }
    get_tag();
    mbar_wait(sb + BAR_PS);
    bar_sync(12, 384);
    uint32_t xm = 0;
#pragma unroll
    for (int k = 0; k < 5; k++) xm |= (lds32(sb + OFF_BC + min(lane + 32 * k, G - 1) * 4) >= (65 << 9) && lane + 32 * k < G) << k;
    auto ext_send = [&](int pl) {
      uint32_t x = xm;
      for (uint32_t m; (m = __ballot_sync(~0u, x));) {
        const uint32_t l = __ffs(m) - 1, j = l + 32 * (__ffs(__shfl_sync(~0u, x, l)) - 1);
        if (lane == l) x &= x - 1;
        const uint32_t e = min(lds16(sb + OFF_AX + j * 128 + ((4 * l + 2 * lane) & 126)), 6143u);
        if (pl) st_ext(p.xe + (j * G + cta) * 32 + lane, lds32(sb + OFF_SRCI + e * 4) + tag + (e << 16), ep);
        else { const uint32_t cn = lds32(sb + OFF_BC + j * 4) >> 9, v = cn > 96 ? 1 : lane + 64 < cn ? 512 | (lds32(sb + OFF_DST + e * 4) & 511) : 0;
          asm volatile("red.shared.xor.b32 [%0], %1;" :: "r"(sb + OFF_SA + j * 128 + ((l + lane) & 31) * 4), "r"(((v & 63) << 10) | ((v >> 6) << 26)) : "memory"); }
      }
    };
    if (__any_sync(~0u, xm)) { ext_send(0); proxy_fence(); __syncwarp(); }
    if (lane == 0) { tma_store(tmb + TM_XA, cta * 64, 0, sb + OFF_SA); bulk_commit(); mbar_arrive(sb + BAR_AI); bulk_wait(); hint_signal(p.sync + 4); mbar_arrive(sb + BAR_AW); STAMP(16); }
    __syncwarp();
    bar_sync(13, 384);
    ext_send(1);
    mbar_arrive(sb + BAR_AX, lane == 0);
    mbar_wait(sb + BAR_HA);
    __nanosleep(BDEL);
    if (lane == 0) {
#pragma unroll 1
      for (int r = 0; r < G; r += BROWS) { tma_store(tmb + TM_XB, cta * 64, r, sb + OFF_SB + r * 256); bulk_commit(); bulk_wait(); }
      hint_signal(p.sync + 5);
      STAMP(17);
    }
    __syncwarp();
  } else {
    {
      uint32_t d[4 * NCH], jj[4 * NCH], rr[4 * NCH];
      auto count = [&](int k) {
        mbar_wait(sb + BAR_DST + k * 8);
        lds128(d + 4 * k, sb + OFF_DST + (tid + NWK * k) * 16);
#pragma unroll
        for (int i = 4 * k; i < 4 * k + 4; i++) { jj[i] = d[i] * p.magic; rr[i] = atoms_add(__dp4a(jj[i], 0x04000000u, sb + OFF_BC), 0x202u); }
      };
      auto place = [&](int k) {
#pragma unroll
        for (int i = 4 * k; i < 4 * k + 4; i++) {
          const uint32_t o = __dp4a(jj[i], 0x80000000u, rr[i] & 0x807Eu);
          d[i] = (d[i] & 511) | (tag >> 16);
          asm("{.reg .pred p; setp.ge.u32 p, %1, 0x8000; @p add.u32 %0, %2, %3;}" : "+r"(d[i]) : "r"(o), "r"(tid * 4), "r"(NWK * k * 4 + (i & 3)));
          sts16(sb + OFF_SA + o, d[i]); jj[i] = __viaddmin_u32(o, o, G * 256);
        }
      };
      count(0); STAMP(1); count(1); get_tag(); place(0); count(2); place(1); count(3); place(2);
      if (wid < 4) { count(4); STAMP(15); place(3); place(4); } else place(3);
      proxy_fence();
      bar_arrive(12, 384);
      STAMP(2);
      mbar_wait(sb + BAR_AI);
      mbar_wait(sb + BAR_SRC); mbar_wait(sb + BAR_SRC + 8); mbar_wait(sb + BAR_SRC + 16);
      STAMP(12);
#pragma unroll
      for (int k = 0; k < NCH; k++) lds128(d + 4 * k, sb + OFF_SRCI + (tid + NWK * k) * 16);
      const uint32_t tb = tag + (tid << 18);
#pragma unroll
      for (int i = 0; i < 4 * NCH; i++) if (i < 4 * NCH - 4 || wid < 4) sts32(sb + OFF_SB + jj[i], d[i] + tb + ((NWK * (i >> 2) * 4 + (i & 3)) << 16));
      proxy_fence();
      bar_arrive(13, 384);
      STAMP(3);
    }
    const uint32_t rot = (lane + cta) & 31;
    cb = sb + OFF_CNT - (tag >> 14);
    {
      const uint32_t* xa = (const uint32_t*)(p.xa + (cta * G + wid) * 8) + rot;
      if (wid < 8) { const uint32_t e_ = ealo + epad * 32;
        mbar_wait(sb + BAR_AX);
#pragma unroll
        for (int i = 0; i < 7; i++) sts128(sb + OFF_TE + tid * 16 + i * 4096, e_, e_, e_, e_); }
      static_assert(SCAP * 64 == 7 * 4096, "fill");
      if (wid == 10) { hint_wait(p.sync + 4, ep * G); mbar_arrive(sb + BAR_HA, lane == 0); }
      mbar_wait(sb + BAR_HA);
      STAMP(14);
      const uint32_t tp = tag | (tag >> 16);
      uint32_t st;
#pragma unroll 1
      for (int spin = 0;; spin++) {
        st = 0;
#pragma unroll
        for (int k = 0; k < 12; k++) asm volatile("ld.relaxed.gpu.global.u32 %0, [%1];" : "=r"(pk[k]) : "l"(xa + k * 352) : "memory");
#pragma unroll
        for (int k = 0; k < 12; k++) st |= pk[k] ^ tp;
        st = __reduce_or_sync(~0u, st);
        if (!(st >> 30)) break;
        trap_if(spin > 2000000);
      }
      if (st & 0x3C00FC00u) {
#pragma unroll 1
        for (;;) {
          uint32_t x = 0, row = 0;
#pragma unroll
          for (int k = 0; k < 12; k++) { const uint32_t y = (pk[k] ^ tp) & 0x3C00FC00u; if (!x && y) { x = y; row = wid + 11 * k; pk[k] ^= y; } }
          if (!__any_sync(~0u, x)) break;
          const uint32_t n = ((x >> 10) & 63) | ((x >> 20) & 0x1C0);
          if (x >> 29) {
            const uint32_t r = atoms_add(sb + OFF_CNT + n * 4, 16), idx = atoms_add(sb + OFF_MISC + 4, 1);
            if (idx < 256) sts32(sb + OFF_EXT + idx * 4, n | (row << 9) | (lane << 17) | (min(r >> 4, 255u) << 22));
            else x = 1;
          }
          if (x && !(x >> 29)) sts32(sb + OFF_MISC + 8, 1);
          __syncwarp();
        }
      }
#pragma unroll
      for (int k = 0; k < 12; k++) { r0[k] = mad16(pk[k], 0x0004u, cb); r1[k] = mad16(pk[k], 0x0400u, cb); vb[k].x = atoms_add(r0[k], 16); vb[k].y = atoms_add(r1[k], 16); }
    }
    STAMP(4);
    if (wid >= 6) bar_arrive(11, NWK);
    if (wid < 6) {
      uint32_t ca[2], ky[2], dr[2], sq[2], ps[4];
#pragma unroll
      for (int i = 0; i < 2; i++) { ca[i] = sb + OFF_CNT + ((node0 + tid + 192 * i) & 511) * 4; lds64(ps[2 * i], ps[2 * i + 1], sb + OFF_POS + (tid + 192 * i) * 8); ps[2 * i + 1] |= (tid + 192 * i) << 16; }
      bar_sync(11, NWK);
      STAMP(5);
#pragma unroll
      for (int i = 0; i < 2; i++) ky[i] = (lds32(ca[i]) + 16) >> 5;
      if (max(ky[0], ky[1]) > 31) sts32(sb + OFF_MISC + 8, 1);
#pragma unroll
      for (int i = 0; i < 2; i++) { ky[i] = min(ky[i], 31u); dr[i] = atoms_add(sb + OFF_DH + ky[i] * 4, 1); }
      bar_sync(10, 192);
      const uint32_t hv = lds32(sb + OFF_DH + lane * 4);
      uint32_t inc = hv;
#pragma unroll
      for (int o = 1; o < 32; o <<= 1) asm("{.reg .pred p; .reg .b32 y; shfl.sync.down.b32 y|p, %0, %1, 31, -1; @p add.u32 %0, %0, y;}" : "+r"(inc) : "r"(o));
#pragma unroll
      for (int i = 0; i < 2; i++) {
        const uint32_t pos = __shfl_sync(~0u, inc - hv, ky[i]) + dr[i];
        const uint32_t ak = (uint32_t)(QCODE >> ((pos >> 5) * 4)) & 15, l = (pos >> 3) & 3;
        sq[i] = (ak >> 2) * 16 + ((QREV >> (pos >> 5) & 1) ? 3 - l : l) * 4 + (ak & 3);
        dr[i] = pos & 7;
        asm volatile("{.reg .pred p; setp.eq.u32 p, %2, 0; @p st.shared.u8 [%0], %1;}" :: "r"(sb + OFF_LEN + sq[i]), "r"(max(ky[i], 1u)), "r"(dr[i]) : "memory");
        sts64(sb + OFF_GP + sq[i] * 64 + dr[i] * 8, ps[2 * i], ps[2 * i + 1]);
        sts16(sb + OFF_INV + (tid + 192 * i) * 2, sq[i] * 64 + dr[i] * 8);
      }
      bar_sync(10, 192);
      const uint32_t ln = lds32(sb + OFF_LEN + min(lane, 11) * 4), tot = __dp4a(ln, 0x01010101u, 0u);
      inc = tot;
#pragma unroll
      for (int o = 1; o < 16; o <<= 1) asm("{.reg .pred p; .reg .b32 y; shfl.sync.up.b32 y|p, %0, %1, 0, -1; @p add.u32 %0, %0, y;}" : "+r"(inc) : "r"(o));
      if (wid == 1) sts32(sb + OFF_CNT + 2048 + lane * 4, 0);
      if (tid < 12) { sts32(sb + OFF_LEN + 64 + tid * 4, inc - tot); if (inc > SCAP - 12) sts32(sb + OFF_MISC + 8, 1); }
#pragma unroll
      for (int i = 0; i < 2; i++) sts32(ca[i], __dp4a(__shfl_sync(~0u, ln, sq[i] >> 2), 0x00010101u >> (24 - 8 * (sq[i] & 3)), __shfl_sync(~0u, inc - tot, sq[i] >> 2)) * 32 + dr[i] * 2);
    }
    bar_arrive(7, 384);
  }
  bar_sync(1, 384);
  STAMP(6);
  if (wid != 11 && !__shfl_sync(~0u, lds32(sb + OFF_MISC + 8), 0)) {
#pragma unroll
    for (int k = 0; k < 12; k++) { r0[k] = lds32(r0[k]); r1[k] = lds32(r1[k]); }
#pragma unroll
    for (int k = 0; k < 12; k++) { r0[k] += vb[k].x; r1[k] += vb[k].y; }
  } else {
#pragma unroll
    for (int k = 0; k < 12; k++) r0[k] = r1[k] = 0x8000;
  }
  auto put_ids = [&]() {
    const uint32_t id = wid * 256 + ((lane + cta) & 31) * 8;
    auto put = [&](uint32_t x, uint32_t v) { asm volatile("{.reg .pred p; setp.lt.u32 p, %0, 0x8000; @p st.shared.u16 [%0+%2], %1;}" :: "r"(x), "h"((uint16_t)v), "n"(sb + OFF_TS) : "memory"); };
#pragma unroll
    for (int k = 0; k < 12; k++) { put(pk[k] & 0xFFFF, id + k * 2816); put(pk[k] >> 16, id + k * 2816 + 4); }
  };
  STAMP(7);
  mbar_wait(sb + BAR_QR);
  asm volatile("setmaxnreg.inc.sync.aligned.u32 152;");
#pragma unroll
  for (int k = 0; k < 12; k++) asm volatile("prmt.b32 %0, %1, %2, 0x5410;" : "=r"(pk[k]) : "r"(r0[k]), "r"(r1[k]));
  uint32_t pa[8], sp[8], pq[16]; float chk = 0.f;
  {
    uint32_t hf[32], mp = 0; float a0[32], a1[32];
    const uint32_t an = sb + OFF_GP + wid * 256 + (lane & 15) * 8 + 6, n0 = lds16(an), n1 = lds16(an + 128);
#pragma unroll
    for (int j = 0; j < 8; j++) { const uint32_t nd = j < 4 ? n0 : n1; ldsm4(hf + 4 * j, (sb + OFF_H + nd * 128 + (((nd & 7) << 4) ^ (lane & 16))) ^ ((j & 3) << 5)); }
    const uint64_t db = DHI | ((sb + OFF_W + 8192) >> 4);
    wg_fence();
    rs64b<0>(a0, hf[0], hf[1], hf[2], hf[3], db); rs64b<1>(a0, hf[4], hf[5], hf[6], hf[7], db + 128); rs64b<1>(a0, hf[8], hf[9], hf[10], hf[11], db + 256); rs64b<1>(a0, hf[12], hf[13], hf[14], hf[15], db + 384);
    wg_commit();
    rs64b<0>(a1, hf[16], hf[17], hf[18], hf[19], db); rs64b<1>(a1, hf[20], hf[21], hf[22], hf[23], db + 128); rs64b<1>(a1, hf[24], hf[25], hf[26], hf[27], db + 256); rs64b<1>(a1, hf[28], hf[29], hf[30], hf[31], db + 384);
    wg_commit();
    put_ids();
    asm volatile("wgmma.wait_group.sync.aligned 1;" ::: "memory"); fence_regs(a0);
#pragma unroll
    for (int j = 0; j < 8; j++) { const uint32_t x = pack_f16(.5f * a0[4 * j], .5f * a0[4 * j + 1]), y = pack_f16(.5f * a0[4 * j + 2], .5f * a0[4 * j + 3]); mp = hmag(hmag(mp, x), y);
      asm volatile("movmatrix.sync.aligned.m8n8.trans.b16 %0, %1;" : "=r"(pa[j]) : "r"(x)); asm volatile("movmatrix.sync.aligned.m8n8.trans.b16 %0, %1;" : "=r"(sp[j]) : "r"(y)); }
    wg_wait0(); fence_regs(a1);
    bar_arrive(4, 416);
#pragma unroll
    for (int j = 0; j < 16; j++) { pq[j] = pack_f16(.5f * a1[2 * j], .5f * a1[2 * j + 1]); mp = hmag(mp, pq[j]); }
    if (magr(mp) >= 0x7000) chk = __int_as_float(0x7FC00000);
  }
  if (wid == 0) STAMP(23);
  uint32_t bad;
  {
    const uint32_t ring = sb + OFF_RING + wid * STG, p2 = sb + OFF_P2 + wid * 2048;
    uint32_t lens = __shfl_sync(~0u, lds32(sb + OFF_LEN + wid * 4), 0);
    uint32_t rem = __dp4a(lens, 0x20202020u, 0u);
    const uint32_t base = min(lds32(sb + OFF_LEN + 64 + wid * 4), SCAP);
    uint32_t a_s = sb + OFF_TS + base * 32 + (lane >> 3) * 8, a_e = sb + OFF_TE + base * 64 + (lane >> 1) * 4;
    uint32_t k0 = (uint32_t)(uint64_t)p.q + (((lane & 7) ^ ((lane >> 1) & 4)) << 4), k1 = k0 ^ 16, k2 = k0 ^ 32, k3 = k0 ^ 48, ke = ((lane ^ (lane >> 3)) & 1) << 4;
    uint32_t dst0 = ring + (lane >> 3) * 640 + (lane & 7) * 16;
    const uint32_t qhi = (uint32_t)((uint64_t)p.q >> 32), ehi = (uint32_t)((uint64_t)p.ea >> 32);
    uint32_t s0, s1, ev, to = 0, so = 12 * STG;
    auto tl_ = [&]() { lds64(s0, s1, a_s + to); asm volatile("ld.shared.u32 %0, [%1]; add.u32 %1, %1, 64;" : "=&r"(ev), "+r"(a_e) :: "memory"); to += 32; };
#define CPQ(LH, x, k, off) "dp2a." LH ".u32.u32 lo, " x ", 0x80000080, " k "; mov.b64 a, {lo, %7}; @p cp.async.cg.shared.global [%0+" #off "], [a], 16;\n"
#define CPE "or.b32 lo, %10, %11; mov.b64 a, {lo, %12}; @p cp.async.cg.shared.global [%0+512], [a], 16;\n"
#define CPA(BODY) asm volatile("{.reg .b32 lo; .reg .b64 a; .reg .pred p; setp.le.u32 p, %8, %9;\n" BODY "}" \
      :: "r"(dst0 + so), "r"(s0), "r"(s1), "r"(k0), "r"(k1), "r"(k2), "r"(k3), "r"(qhi), "r"(to), "r"(rem), "r"(ev), "r"(ke), "r"(ehi) : "memory")
#define CPQ4 CPQ("lo", "%1", "%3", 0) CPQ("hi", "%1", "%4", 128) CPQ("lo", "%2", "%5", 256) CPQ("hi", "%2", "%6", 384) "cp.async.commit_group;"
    auto issue = [&]() { CPA(CPE CPQ4); so = so == (NST - 1) * 12 * STG ? 0 : so + 12 * STG; };
    const int g = lane >> 2, qd = lane & 3;
    const uint32_t sw = ((lane >> 4) ^ (lane & 7)) << 4, fr = (lane & 15) * 128 + sw;
    uint32_t qa0 = ring + (g & 3) * 640 + qd * 128 + sw, qa1 = qa0 ^ 32, qa2 = qa0 ^ 64, qa3 = qa0 ^ 96;
    uint32_t eadr = ring + 512 + (g & 3) * 640 + qd * 32 + ((((lane >> 4) ^ g) & 1) << 4);
    uint32_t oh0 = g == 2 * qd ? 0x3C00u : g == 2 * qd + 1 ? 0x3C000000u : 0u, oh1 = oh0;
    uint32_t a_g = sb + OFF_GP + wid * 256 + lane * 2;
    asm volatile("shfl.sync.idx.b32 %0, %0, %1, 31, -1;" : "+r"(oh1) : "r"(lane));
    uint32_t w3[16], wv[8], bp[16], sum[8], Y[16], M[16], own, ownp, dpk, tl[16], th[16];
    float pacc = 0.f;
    auto wload = [&]() {
#pragma unroll
      for (int j = 0; j < 4; j++) ldsm4t(w3 + 4 * j, (sb + OFF_W3 + fr) ^ (j << 5));
      lds128(wv, sb + OFF_WX + (a_g & 6) * 16); lds128(wv + 4, sb + OFF_WX + 16 + (a_g & 6) * 16);
    };
    auto hload = [&](uint32_t (&hf)[16], uint32_t nd) {
      const uint32_t hrow = sb + OFF_H + nd * 128 + (((nd & 7) << 4) ^ ((a_g >> 1) & 16));
#pragma unroll
      for (int j = 0; j < 4; j++) ldsm4(hf + 4 * j, hrow ^ (j << 5));
      return hrow;
    };
    { uint32_t wd[8]; const uint32_t a = sb + OFF_WD + (lane & 7) * 128 + ((((lane >> 3) ^ lane) & 7) << 4);
      ldsm4t(wd, a); ldsm4t(wd + 4, a ^ 64);
#pragma unroll
      for (int j = 0; j < 8; j++) { bp[2 * j] = wd[j]; bp[2 * j + 1] = pa[j]; } }
    own = lds16(a_g) * 0x10001u;
    wload();
    if (__shfl_sync(~0u, lds32(sb + OFF_MISC + 8), 0)) rem = 0;
    auto resolve = [&](auto NBK, uint32_t o) {
      constexpr int NB = decltype(NBK)::value;
      uint32_t id[NB], c0[NB], c1[NB]; const uint32_t a = base * 32 + o + lane * 4;
#pragma unroll
      for (int i = 0; i < NB; i++) { id[i] = lds32(sb + OFF_TS + a + i * 128); if (o + lane * 4 + i * 128 >= rem) id[i] = XPAD * 0x10001u; }
      uint32_t st = 0;
#pragma unroll
      for (int i = 0; i < NB; i++) { c0[i] = lds32(sb + OFF_XB + (id[i] & 0xFFFF)); c1[i] = lds32(sb + OFF_XB + (id[i] >> 16)); }
#pragma unroll
      for (int i = 0; i < NB; i++) st |= (c0[i] ^ tag) | (c1[i] ^ tag);
      for (int spin = 0; __any_sync(~0u, st >> 30); spin++) {
        st = 0; trap_if(spin > 2000000);
#pragma unroll
        for (int i = 0; i < NB; i++) {
          asm volatile("{.reg .pred p, q; setp.lt.u32 p, %4, %6; setp.lt.u32 q, %5, %6; @p ld.relaxed.gpu.global.u32 %0, [%2]; @q ld.relaxed.gpu.global.u32 %1, [%3];}"
            : "+r"(c0[i]), "+r"(c1[i]) : "l"((const char*)p.xb + cta * XPAD + (id[i] & 0xFFFF)), "l"((const char*)p.xb + cta * XPAD + (id[i] >> 16)), "r"(id[i] & 0xFFFF), "r"(id[i] >> 16), "n"(XPAD) : "memory");
          st |= (c0[i] ^ tag) | (c1[i] ^ tag); }
      }
#pragma unroll
      for (int i = 0; i < NB; i++) { const uint32_t j0 = (id[i] >> 8) & 255, j1 = id[i] >> 24;
        asm volatile("{.reg .pred p, q, r; setp.lt.u32 p, %5, %9; setp.lt.u32 q, %6, %9; setp.lt.u32 r, %7, %8;\n"
          "@p st.shared.u32 [%0], %2; @q st.shared.u32 [%0+4], %3; @r st.shared.u32 [%1], %4;}"
          :: "r"(sb + OFF_TE + 2 * a + i * 256), "r"(sb + OFF_TS + a + i * 128), "r"(mad16(c0[i], 0x2000u, eb0 + j0 * p.EPC * 32)), "r"(mad16(c1[i], 0x2000u, eb0 + j1 * p.EPC * 32)),
             "r"(__byte_perm(c0[i], c1[i], 0x5410)), "r"(j0), "r"(j1), "r"(o + lane * 4 + i * 128), "r"(rem), "n"(G) : "memory"); }
    };
    bar_sync(2, 384);
    if (wid == 0) STAMP(27);
    mbar_wait(sb + BAR_HB);
    if (wid == 0) STAMP(22);
#pragma unroll 1
    for (uint32_t o = 0, go = 0; go < 32 * NST; o += 128 * RNB) {
      if (o < rem) { resolve(IC<RNB>(), o);
        asm volatile("{.reg .pred p; mbarrier.test_wait.parity.shared::cta.b64 p, [%1], 0; vote.sync.all.pred p, p, -1; selp.u32 %0, %2, 0, p;}" : "=r"(go) : "r"(sb + BAR_QP), "n"(32 * NST - 32) : "memory"); }
      else { bar_sync(8, 384); mbar_wait(sb + BAR_QP); go = 32 * NST; if (wid == 0) STAMP(24); }
      __syncwarp();
#pragma unroll 1
      while (to < go) { tl_(); issue(); if (to == 32) STAMP(13); }
    }
    bad = __shfl_sync(~0u, lds32(sb + OFF_MISC + 8), 0);
   if (!bad) {
#pragma unroll
    for (int j = 0; j < 4; j++) stsm4((p2 + fr) ^ (j << 5), pq[4 * j], pq[4 * j + 1], pq[4 * j + 2], pq[4 * j + 3]);
    auto body = [&](auto MODE) {
      constexpr int mode = decltype(MODE)::value;
      uint32_t T[16], ef[4], q0, q1, x0, x1, x2; float e0_, e1_, cs[4];
      auto mu = [&](int j) {
#pragma unroll
        for (int i = 2 * j; i < 2 * j + 2; i++) asm volatile("{.reg .b16 l, h; mov.b32 {l, h}, %2; tanh.approx.f16 l, l; tanh.approx.f16 h, h; cvt.u32.u16 %0, l; cvt.u32.u16 %1, h;}" : "=r"(tl[i]), "=r"(th[i]) : "r"(Y[i])); };
      auto fi = [&](int j) {
#pragma unroll
        for (int i = 2 * j; i < 2 * j + 2; i++) asm volatile("{.reg .b32 t; prmt.b32 t, %2, %3, 0x5410; fma.rn.f16x2 %0, %1, t, %1;}" : "=r"(M[i]) : "r"(Y[i]), "r"(tl[i]), "r"(th[i])); };
      auto ad = [&](int j) { asm volatile("add.rn.f16x2 %0, %0, %1; add.rn.f16x2 %0, %0, %2;" : "+r"(sum[j]) : "r"(M[2 * j]), "r"(M[2 * j + 1])); };
      auto he = [&](int j) { asm volatile("mma.sync.aligned.m16n8k16.row.col.f16.f16.f16.f16 {%0,%1}, {%2,%3,%4,%5}, {%6,%7}, {%0,%1};" : "+r"(T[2 * j]), "+r"(T[2 * j + 1]) : "r"(ef[0]), "r"(ef[1]), "r"(ef[2]), "r"(ef[3]), "r"(w3[2 * j]), "r"(w3[2 * j + 1])); };
      auto hs = [&](int j) { asm volatile("mma.sync.aligned.m16n8k16.row.col.f16.f16.f16.f16 {%0,%1}, {%2,%3,%4,%5}, {%6,%7}, {%8,%9};" : "=r"(Y[2 * j]), "=r"(Y[2 * j + 1]) : "r"(q0), "r"(q1), "r"(oh0), "r"(oh1), "r"(bp[2 * j]), "r"(bp[2 * j + 1]), "r"(T[2 * j]), "r"(T[2 * j + 1])); };
      auto hc = [&](int j) {
        if (j) asm volatile("mma.sync.aligned.m16n8k16.row.col.f32.f16.f16.f32 {%0,%1,%2,%3}, {%4,%5,%6,%7}, {%8,%9}, {%0,%1,%2,%3};" : "+f"(cs[0]), "+f"(cs[1]), "+f"(cs[2]), "+f"(cs[3]) : "r"(M[4 * j]), "r"(M[4 * j + 1]), "r"(M[4 * j + 2]), "r"(M[4 * j + 3]), "r"(wv[2 * j]), "r"(wv[2 * j + 1]));
        else asm volatile("mma.sync.aligned.m16n8k16.row.col.f32.f16.f16.f32 {%0,%1,%2,%3}, {%4,%5,%6,%7}, {%8,%9}, {%10,%10,%10,%10};" : "=f"(cs[0]), "=f"(cs[1]), "=f"(cs[2]), "=f"(cs[3]) : "r"(M[0]), "r"(M[1]), "r"(M[2]), "r"(M[3]), "r"(wv[0]), "r"(wv[1]), "f"(0.f)); };
      auto cv = [&](int i) { asm volatile("{.reg .b32 a, b; shl.b32 a, %0, 16; and.b32 b, %0, 0xFFFF0000; cvt.rn.f16x2.f32 %0, b, a;}" : "+r"(ef[i])); };
      auto un = [&]() { asm volatile("shl.b32 %0, %2, 16; and.b32 %1, %2, 0xFFFF0000;" : "=&f"(e0_), "=&f"(e1_) : "r"(dpk)); };
      auto ex0 = [&]() { asm volatile("prmt.b32 %0, %3, %4, 0x6420; prmt.b32 %1, %5, %6, 0x6420; prmt.b32 %2, %7, %8, 0x6420;" : "=&r"(x0), "=&r"(x1), "=&r"(x2) : "r"(T[0]), "r"(T[1]), "r"(T[2]), "r"(T[3]), "r"(T[4]), "r"(T[5])); };
      auto ex1 = [&]() { asm volatile("{.reg .b32 a, b; shl.b32 a, %2, 3; shl.b32 b, %3, 6; lop3.b32 a, %1, a, 0x38383838, 0xD8; lop3.b32 a, a, b, 0xC0C0C0C0, 0xD8; sub.rn.bf16x2 %0, %4, a;}" : "=r"(dpk) : "r"(x0), "r"(x1), "r"(x2), "r"(own)); };
      auto ex2 = [&]() { asm volatile("{.reg .b32 a, b, d, u; .reg .b16 l, h; shl.b32 a, %2, 16; and.b32 b, %2, 0xFFFF0000; cvt.rn.f16x2.f32 d, b, a; mul.rn.f16x2 %0, d, d; mov.b32 {l, h}, d; mov.b32 u, {h, h}; mul.rn.f16x2 %1, u, u;}" : "=&r"(q0), "=&r"(q1) : "r"(dpk)); };
      auto pf = [&]() { asm volatile("fma.rn.f32 %0, %1, %2, %0; fma.rn.f32 %0, %3, %4, %0;" : "+f"(pacc) : "f"(cs[0]), "f"(e0_), "f"(cs[2]), "f"(e1_)); };
      if (mode == 2) { LASTSEQ return; }
      asm volatile("cp.async.wait_group %0;" :: "n"(NST - 1) : "memory");
      __syncwarp();
      if (mode == 1) STAMP(8);
      ldsm4(ef, eadr + so); ldsm4(T, qa0 + so); ldsm4(T + 4, qa1 + so); ldsm4(T + 8, qa2 + so); ldsm4(T + 12, qa3 + so);
      if (mode == 1) {
        tl_(); issue();
        cv(0); cv(1); cv(2); cv(3); ex0(); ex1(); ex2();
#pragma unroll
        for (int j = 0; j < 8; j++) { he(j); hs(j); }
        FIRSTSEQ return;
      }
      BODYSEQ
    };
#pragma unroll
    for (int j = 0; j < 8; j++) sum[j] = 0;
    body(IC<1>());
    int cnt = (lens & 255) - 1;
    auto pload = [&](uint32_t (&x)[8], uint32_t o) { const uint32_t l = a_g >> 1, a = p2 + o + (l & 7) * 128 + (((((l >> 3) & 3) ^ l) & 7) << 4); ldsm4t(x, a); ldsm4t(x + 4, a ^ 64); };
    auto flush = [&]() {
      asm volatile("{.reg .pred p; setp.ne.u32 p, %2, 6; @p st.shared.u16 [%0+-64], %1;}" :: "r"(a_g), "h"((uint16_t)pack_bf16(bf_hi(ownp) + pacc, 0.f)), "r"(a_g & 6) : "memory");
      chk = fmaf(pacc, 0.f, chk); pacc = 0.f; };
    constexpr uint64_t b1 = DHI | ((sb + OFF_W) >> 4), b2_ = b1 + 512;
    auto mma_h = [&](float (&acc)[32], uint32_t (&hf)[16]) {
      rs64b<0>(acc, hf[0], hf[1], hf[2], hf[3], b1); rs64b<1>(acc, hf[4], hf[5], hf[6], hf[7], b1 + 128); rs64b<1>(acc, hf[8], hf[9], hf[10], hf[11], b1 + 256); rs64b<1>(acc, hf[12], hf[13], hf[14], hf[15], b1 + 384); };
    auto mma_m = [&](float (&acc)[32]) {
      rs64h<1>(acc, sp[0], sum[0], sp[1], sum[1], b2_); rs64h<1>(acc, sp[2], sum[2], sp[3], sum[3], b2_ + 128); rs64h<1>(acc, sp[4], sum[4], sp[5], sum[5], b2_ + 256); rs64h<1>(acc, sp[6], sum[6], sp[7], sum[7], b2_ + 384);
      wg_commit(); wg_wait0(); fence_regs(acc);
      STAMP(10);
      chk = fmaf(acc[0], 0.f, fmaf(acc[2], 0.f, chk)); };
    auto roff = [&](uint32_t nd, int r) { return __shfl_sync(~0u, nd, ((a_g >> 3) & 7) + 8 * r) * 128 + (a_g & 6) * 8; };
    auto radr = [&](uint32_t o, int k) { return sb + OFF_H + (o ^ ((o >> 3) & 0x70) ^ ((k >> 1) << 6)); };
    auto fin = [&](float (&acc)[32], uint32_t* x, int k) {
#pragma unroll
      for (int i = 0; i < 4; i++) { const int c = 16 * (k >> 1) + 4 * i + 2 * (k & 1); x[i] = u2(__hadd2(b2(x[i]), b2(pack_bf16(silu_h(acc[c]), silu_h(acc[c + 1]))))); } };
#pragma unroll 1
    for (int t = 0;; t++) {
#pragma unroll 1
      for (; cnt > 0; cnt--) { body(IC<0>());
      }
      if (!(t & 1)) {
        ownp = own; a_g += 64;
        if (t == 6) break;
        own = lds16(a_g) * 0x10001u;
        if (t == 2) { const uint32_t a = ((a_g & 16) ? p2 : sb + OFF_WD) + ((a_g << 6) & 0x380) + (qa0 & 0x70);
#pragma unroll
          for (int j = 0; j < 4; j++) ldsm4t(bp + 4 * j, a ^ (j << 5));
        } else {
#pragma unroll
          for (int j = 0; j < 8; j++) bp[2 * j + 1] = sp[j];
        }
        lens >>= 8; cnt = 1;
        continue;
      }
      cnt = (lens & 255) - 1;
      flush();
      if (t == 3) {
        uint32_t x[8];
        pload(x, 1024);
        __syncwarp();
#pragma unroll
        for (int j = 0; j < 4; j++) stsm4((p2 + ((a_g << 6) & 0x780) + (qa0 & 0x70)) ^ (j << 5), sp[2 * j], sum[2 * j], sp[2 * j + 1], sum[2 * j + 1]);
#pragma unroll
        for (int j = 0; j < 8; j++) sum[j] = x[j];
        __syncwarp();
        mbar_arrive(sb + BAR_M + (wid >> 2) * 8, (a_g & 62) == 0);
      }
#pragma unroll
      for (int j = 0; j < 8; j++) { sp[j] = sum[j]; asm volatile("mov.b32 %0, 0;" : "=r"(sum[j])); }
    }
    {
      uint32_t hf[16], v[16]; float acc[32];
      const uint32_t nd = lds16(sb + OFF_GP + wid * 256 + (lane & 15) * 8 + 134), o[2] = {roff(nd, 0), roff(nd, 1)};
      hload(hf, nd);
#pragma unroll
      for (int k = 0; k < 4; k++) lds128(v + 4 * k, radr(o[k & 1], k));
      mbar_wait(sb + BAR_WH);
      wg_fence(); mma_h(acc, hf); wg_commit();
      body(IC<2>());
      STAMP(9);
      flush();
      __syncwarp();
      mbar_arrive(sb + BAR_X, lane == 0);
      wg_fence();
      mma_m(acc);
#pragma unroll
      for (int k = 0; k < 4; k++) { fin(acc, v + 4 * k, k);
        asm volatile("{.reg .pred p; setp.lt.u32 p, %5, %6; @p st.global.v4.b32 [%0], {%1,%2,%3,%4};}" :: "l"((const char*)p.out + (size_t)node0 * 128 + o[k & 1] + (k >> 1) * 64), "r"(v[4 * k]), "r"(v[4 * k + 1]), "r"(v[4 * k + 2]), "r"(v[4 * k + 3]), "r"(o[k & 1]), "r"(nloc * 128) : "memory"); }
    }
    asm volatile("{.reg .pred p, q; setp.neu.f32 p, %1, 0f00000000; setp.ne.or.u32 p, %2, 0, p; bar.red.or.pred q, 5, 512, p; selp.u32 %0, 1, 0, q;}" : "=r"(bad) : "f"(chk), "r"(lds32(sb + OFF_MISC + 12)) : "memory");
    STAMP(11);
   } else { asm volatile("cp.async.wait_all;" ::: "memory"); bar_sync(5, 384); }
  }
  if (bad) slow_path(p, wid, lane, node0, nloc);
}

}

typedef CUresult (*EncodeFn)(CUtensorMap*, CUtensorMapDataType, cuuint32_t, void*, const cuuint64_t*, const cuuint64_t*, const cuuint32_t*, const cuuint32_t*,
                             CUtensorMapInterleave, CUtensorMapSwizzle, CUtensorMapL2promotion, CUtensorMapFloatOOBfill);

extern "C" void kernel_launch(void* const* d_in, const int* in_sizes, int n_in, void* d_out, int out_size) {
  Params p; Maps maps;
  p.h = (const uint4*)d_in[0]; p.pos = (const uint16_t*)d_in[1]; p.ea = (const uint4*)d_in[2];
  p.src = (const int*)d_in[3]; p.dst = (const int*)d_in[4];
  p.we = (const uint16_t*)d_in[5]; p.wx = (const uint16_t*)d_in[6]; p.wh = (const uint16_t*)d_in[7];
  p.out = (uint16_t*)d_out;
  p.N = in_sizes[0] / 64; p.E = in_sizes[3];
  p.EPC = ((p.E + G * 4 - 1) / (G * 4)) * 4;
  p.magic = (uint32_t)(((uint64_t)G << 24) / (uint64_t)p.N);
  p.inv = (1ull << 56) / p.magic;
  const uint64_t ea0 = (uint64_t)d_in[2], ea1 = ea0 + (uint64_t)p.E * 32 - 1;
  p.force_slow = ((ea0 >> 32) != (ea1 >> 32)) || (ea0 & 31) || (p.E & 3);
  void* qp = nullptr;
  cudaGetSymbolAddress(&qp, g_q);
  p.q = (char*)qp;
  if (((uint64_t)p.q >> 32) != (((uint64_t)p.q + QBYTES) >> 32)) p.q += QBYTES;
  cudaGetSymbolAddress((void**)&p.sync, g_sync); cudaGetSymbolAddress((void**)&p.xe, g_xe);
  cudaGetSymbolAddress((void**)&p.xa, g_xa); cudaGetSymbolAddress((void**)&p.xb, g_xb);
  const int df[10] = {18, 250, 900, 500, 250, 59, 0xff2, 0xD5C4E6};
  for (int i = 0; i < 10; i++) p.tune[i] = df[i];
  p.qcode = 0x890145a6273bull;
  p.ctam = p.tune[5];
  void* fn = nullptr; cudaDriverEntryPointQueryResult qr;
  cudaGetDriverEntryPoint("cuTensorMapEncodeTiled", &fn, cudaEnableDefault, &qr);
  auto mk = [&](CUtensorMap* tm, void* base, int rows, int box = 64) {
    const cuuint64_t dim[2] = {64, (cuuint64_t)rows}, str[1] = {128}; const cuuint32_t bx[2] = {64, (cuuint32_t)box}, es[2] = {1, 1};
    ((EncodeFn)fn)(tm, CU_TENSOR_MAP_DATA_TYPE_BFLOAT16, 2, base, dim, str, bx, es, CU_TENSOR_MAP_INTERLEAVE_NONE, CU_TENSOR_MAP_SWIZZLE_128B,
                   CU_TENSOR_MAP_L2_PROMOTION_NONE, CU_TENSOR_MAP_FLOAT_OOB_FILL_NONE);
  };
  mk(&maps.m[TM_H / 128], d_in[0], p.N); mk(&maps.m[TM_WE / 128], d_in[5], 145); mk(&maps.m[TM_WH / 128], d_in[7], 128); mk(&maps.m[TM_Q / 128], p.q, p.N, 16);
  for (int k = 0; k < 2; k++) {
    void* xp = (void*)(k ? p.xb : p.xa);
    const cuuint64_t dim[2] = {(cuuint64_t)G * 64, (cuuint64_t)G}, str[1] = {(cuuint64_t)G * (128 << k)}; const cuuint32_t bx[2] = {64, (cuuint32_t)(k ? BROWS : G)}, es[2] = {1, 1};
    ((EncodeFn)fn)(&maps.m[TM_XA / 128 + k], k ? CU_TENSOR_MAP_DATA_TYPE_UINT32 : CU_TENSOR_MAP_DATA_TYPE_UINT16, 2, xp, dim, str, bx, es, CU_TENSOR_MAP_INTERLEAVE_NONE,
                   CU_TENSOR_MAP_SWIZZLE_NONE, CU_TENSOR_MAP_L2_PROMOTION_NONE, CU_TENSOR_MAP_FLOAT_OOB_FILL_NONE);
  }
  cudaFuncSetAttribute(egnn_kernel, cudaFuncAttributeMaxDynamicSharedMemorySize, SMEM);
  egnn_kernel<<<G, NTHR, SMEM>>>(p, maps);
}
```

```cpp
#include <cuda_runtime.h>
#include <cuda_bf16.h>
#include <cuda_fp16.h>
#include <cuda.h>
#include <stdint.h>
#pragma nv_diag_suppress 549

#define PFN p.tune[0]
#define PFB p.tune[3]
#define PFNS p.tune[1]
#define BDEL p.tune[2]
#define DEFNS p.tune[4]
#define CTAM p.ctam
#define QREV p.tune[6]
#define UORD p.tune[7]
#define QCODE p.qcode
#define FIRSTSEQ mu(0); mu(1); fi(0); mu(2); fi(1);
#define BODYSEQ hc(0); fi(2); tl_(); mu(3); un(); ad(1); ad(0); cv(0); mu(4); cv(2); fi(3); cv(1); ex0(); ex1(); cv(3); he(0); fi(4); he(1); \
  mu(5); hc(1); mu(6); fi(5); he(2); ad(2); ex2(); hs(0); ad(3); hs(1); fi(6); mu(7); issue(); hc(2); he(3); hs(3); fi(7); mu(0); \
  hs(2); he(4); he(5); ad(5); ad(4); hs(4); fi(0); he(6); mu(1); hc(3); he(7); fi(1); ad(6); hs(7); hs(5); ad(7); hs(6); mu(2); \
  pf();
#define LASTSEQ hc(0); fi(2); mu(3); un(); ad(1); ad(0); mu(4); fi(3); fi(4); mu(5); hc(1); mu(6); fi(5); ad(2); ad(3); fi(6); mu(7); hc(2); \
  fi(7); ad(5); ad(4); hc(3); ad(6); ad(7); pf();
namespace {

constexpr int G = 132;
constexpr int NTHR = 512, NWK = 352, NCH = 5;
constexpr int NST = 3, STG = 2560;
constexpr int BROWS = 44, RNB = 2, PADM = 33;
constexpr int SCAP = 448;

constexpr int OFF_H = 0;
constexpr int OFF_W = 49152;
constexpr int OFF_WD = OFF_W + 16384;
constexpr int OFF_W3 = OFF_WD + 1024;
constexpr int OFF_P2 = OFF_W3 + 2048;
constexpr int OFF_RING = OFF_P2 + 24576;
constexpr int OFF_TE = OFF_RING + 12 * NST * STG;
constexpr int OFF_TS = OFF_TE + SCAP * 64;
constexpr int OFF_INV = OFF_TS - 768;
constexpr int OFF_GP = OFF_TS + SCAP * 32;
constexpr int OFF_WX = OFF_GP + 3072;
constexpr int OFF_LEN = OFF_WX + 128;
constexpr int OFF_MISC = OFF_LEN + 128;
constexpr int OFF_BAR = OFF_MISC + 48;
constexpr int SMEM = OFF_BAR + 256;
static_assert(SMEM <= 232448, "smem");
constexpr uint32_t sb = 1024;
constexpr int OFF_SRCI = OFF_TE;
constexpr int OFF_SB = OFF_RING, OFF_SA = OFF_SB + 34816, OFF_AX = OFF_SA + 32768, OFF_DST = OFF_H + 24576;
constexpr int OFF_WS = OFF_AX + 17408;
constexpr int OFF_BC = OFF_WS + 2304;
constexpr int OFF_CNT = OFF_P2;
constexpr int OFF_DH = OFF_CNT + 2176;
constexpr int OFF_POS = OFF_DH + 128;
constexpr int OFF_EXT = OFF_POS + 3072;
constexpr int OFF_XB = OFF_EXT + 1024, XPAD = G * 256;
static_assert(OFF_XB + XPAD + 1028 <= OFF_RING + 12 * STG && OFF_XB % 128 == 0 && OFF_BC + 544 <= OFF_TE && OFF_P2 % 1024 == 0 && OFF_SA % 1024 == 0 && SCAP * 64 >= 24576, "staging");
constexpr int BAR_DST = OFF_BAR, BAR_SRC = BAR_DST + 40, BAR_T = BAR_SRC + 24, BAR_W = BAR_T + 48, BAR_PS = BAR_W + 8, BAR_AW = BAR_PS + 8,
              BAR_QP = BAR_AW + 8, BAR_QR = BAR_QP + 8, BAR_HA = BAR_QR + 8, BAR_EP = BAR_HA + 8, BAR_AX = BAR_EP + 8, BAR_AI = BAR_AX + 8, BAR_HB = BAR_AI + 8, BAR_U = BAR_HB + 8, BAR_WH = BAR_U + 8, BAR_M = BAR_WH + 8, BAR_X = BAR_M + 24, BAR_END = BAR_X + 8;
static_assert(BAR_END <= OFF_BAR + 256, "barriers");
constexpr uint32_t QBYTES = 8u << 20;

__device__ __align__(256) uint4 g_xa[G * G * 8];
__device__ __align__(256) uint4 g_xb[G * G * 16];
__device__ __align__(256) uint2 g_xe[G * G * 32];
__device__ __align__(256) uint4 g_q[2 * QBYTES / 16];
__device__ __align__(256) uint32_t g_sync[8];
#define STAMP(k)

struct Maps { CUtensorMap m[6]; };
constexpr int TM_H = 0, TM_WE = 128, TM_WH = 256, TM_Q = 384, TM_XA = 512, TM_XB = 640;
struct Params {
  const int* dst; uint32_t* sync; int E, EPC, N, ctam; unsigned long long inv; uint32_t magic; int force_slow;
  const int* src; const uint16_t* pos; const uint4* ea; const uint16_t* we; const uint16_t* wx; char* q;
  const uint4* xa; const uint4* xb; uint2* xe; uint16_t* out; const uint4* h; const uint16_t* wh;
  int tune[10]; unsigned long long qcode;
};
template<int V> struct IC { static constexpr int value = V; };

#define R32(d) "+f"(d[0]),"+f"(d[1]),"+f"(d[2]),"+f"(d[3]),"+f"(d[4]),"+f"(d[5]),"+f"(d[6]),"+f"(d[7]),"+f"(d[8]),"+f"(d[9]),"+f"(d[10]),"+f"(d[11]),"+f"(d[12]),"+f"(d[13]),"+f"(d[14]),"+f"(d[15]),"+f"(d[16]),"+f"(d[17]),"+f"(d[18]),"+f"(d[19]),"+f"(d[20]),"+f"(d[21]),"+f"(d[22]),"+f"(d[23]),"+f"(d[24]),"+f"(d[25]),"+f"(d[26]),"+f"(d[27]),"+f"(d[28]),"+f"(d[29]),"+f"(d[30]),"+f"(d[31])
#define S32 "{%0,%1,%2,%3,%4,%5,%6,%7,%8,%9,%10,%11,%12,%13,%14,%15,%16,%17,%18,%19,%20,%21,%22,%23,%24,%25,%26,%27,%28,%29,%30,%31}"
#define DI __device__ __forceinline__

constexpr uint64_t DHI = ((uint64_t)(1024 >> 4) << 32) | (1ull << 62);
template<int SD> DI void rs64b(float (&d)[32], uint32_t a0, uint32_t a1, uint32_t a2, uint32_t a3, uint64_t db) {
  asm volatile("wgmma.mma_async.sync.aligned.m64n64k16.f32.bf16.bf16 " S32 ", {%32,%33,%34,%35}, %36, %37, 1, 1, 1;" : R32(d) : "r"(a0), "r"(a1), "r"(a2), "r"(a3), "l"(db), "n"(SD)); }
template<int SD> DI void rs64h(float (&d)[32], uint32_t a0, uint32_t a1, uint32_t a2, uint32_t a3, uint64_t db) {
  asm volatile("wgmma.mma_async.sync.aligned.m64n64k16.f32.f16.f16 " S32 ", {%32,%33,%34,%35}, %36, %37, 1, 1, 1;" : R32(d) : "r"(a0), "r"(a1), "r"(a2), "r"(a3), "l"(db), "n"(SD)); }
template<int SD> DI void ss64(float (&d)[32], uint64_t da, uint64_t db) {
  asm volatile("wgmma.mma_async.sync.aligned.m64n64k16.f32.bf16.bf16 " S32 ", %32, %33, %34, 1, 1, 0, 1;" : R32(d) : "l"(da), "l"(db), "n"(SD)); }
#define R16(d) "+f"(d[0]),"+f"(d[1]),"+f"(d[2]),"+f"(d[3]),"+f"(d[4]),"+f"(d[5]),"+f"(d[6]),"+f"(d[7]),"+f"(d[8]),"+f"(d[9]),"+f"(d[10]),"+f"(d[11]),"+f"(d[12]),"+f"(d[13]),"+f"(d[14]),"+f"(d[15])
#define S16 "{%0,%1,%2,%3,%4,%5,%6,%7,%8,%9,%10,%11,%12,%13,%14,%15}"
template<int SD> DI void rs32b(float (&d)[16], const uint32_t* a, uint64_t db) {
  asm volatile("wgmma.mma_async.sync.aligned.m64n32k16.f32.bf16.bf16 " S16 ", {%16,%17,%18,%19}, %20, %21, 1, 1, 1;" : R16(d) : "r"(a[0]), "r"(a[1]), "r"(a[2]), "r"(a[3]), "l"(db), "n"(SD)); }
DI void rs32h(float (&d)[16], const uint32_t* a, uint64_t db) {
  asm volatile("wgmma.mma_async.sync.aligned.m64n32k16.f32.f16.f16 " S16 ", {%16,%17,%18,%19}, %20, 1, 1, 1, 1;" : R16(d) : "r"(a[0]), "r"(a[1]), "r"(a[2]), "r"(a[3]), "l"(db)); }
DI void fence_regs(float (&d)[16]) { asm volatile("" : R16(d) :: "memory"); }
DI void trap_if(bool c) { asm volatile("{.reg .pred p; setp.eq.u32 p, %0, 0; @p bra.uni LT_%=; trap; LT_%=:}" :: "r"((uint32_t)c)); }
DI void wg_fence() { asm volatile("wgmma.fence.sync.aligned;" ::: "memory"); }
DI void wg_commit() { asm volatile("wgmma.commit_group.sync.aligned;" ::: "memory"); }
DI void wg_wait0() { asm volatile("wgmma.wait_group.sync.aligned 0;" ::: "memory"); }
DI void fence_regs(float (&d)[32]) { asm volatile("" : R32(d) :: "memory"); }
DI void proxy_fence() { asm volatile("fence.proxy.async.shared::cta;" ::: "memory"); }
DI uint64_t pol_first() { uint64_t r; asm("createpolicy.fractional.L2::evict_first.b64 %0, 1.0;" : "=l"(r)); return r; }
DI float tanh_ap(float x) { float y; asm("tanh.approx.f32 %0, %1;" : "=f"(y) : "f"(x)); return y; }
DI float silu_h(float y) { return fmaf(y, tanh_ap(y), y); }
DI uint32_t pack_bf16(float lo, float hi) { uint32_t r; asm("cvt.rn.bf16x2.f32 %0, %1, %2;" : "=r"(r) : "f"(hi), "f"(lo)); return r; }
DI uint32_t pack_f16(float lo, float hi) { uint32_t r; asm("cvt.rn.f16x2.f32 %0, %1, %2;" : "=r"(r) : "f"(hi), "f"(lo)); return r; }
DI float bf_lo(uint32_t v) { return __uint_as_float(v << 16); }
DI float bf_hi(uint32_t v) { return __uint_as_float(v & 0xFFFF0000u); }
DI uint32_t b2h(uint32_t v, float s) { return pack_f16(s * bf_lo(v), s * bf_hi(v)); }
DI void mbar_wait(uint32_t bar, uint32_t parity = 0) {
  asm volatile("{.reg .pred p, q; .reg .u32 c; mov.u32 c, 0;\n"
    "LW_%=: mbarrier.try_wait.parity.shared::cta.b64 p, [%0], %1;\n add.u32 c, c, 1; setp.lt.and.u32 q, c, 0x200000, !p;\n @q bra.uni LW_%=;}" :: "r"(bar), "r"(parity) : "memory");
}
DI void mbar_arrive(uint32_t bar, int p = 1) { asm volatile("{.reg .pred p; setp.ne.b32 p, %1, 0; @p mbarrier.arrive.shared::cta.b64 _, [%0];}" :: "r"(bar), "r"(p) : "memory"); }
DI void bar_sync(int id, int n) { asm volatile("bar.sync %0, %1;" :: "r"(id), "r"(n) : "memory"); }
DI void bar_arrive(int id, int n) { asm volatile("bar.arrive %0, %1;" :: "r"(id), "r"(n) : "memory"); }
DI __nv_bfloat162 b2(uint32_t v) { return *(__nv_bfloat162*)&v; }
DI uint32_t u2(__nv_bfloat162 v) { return *(uint32_t*)&v; }
DI uint32_t hsq(uint32_t v) { return u2(__hmul2(b2(v), b2(v))); }
DI uint32_t hsub(uint32_t a, uint32_t b) { return u2(__hsub2(b2(a), b2(b))); }
DI uint32_t hhalf(uint32_t v) { return u2(__hmul2(b2(v), __floats2bfloat162_rn(0.5f, 0.5f))); }
DI uint32_t mag2(uint32_t m, uint32_t v) { return __vmaxu2(m, v & 0x7FFF7FFFu); }
DI uint32_t hmag(uint32_t m, uint32_t v) { const __half2 r = __hmax2(*(const __half2*)&m, __habs2(*(const __half2*)&v)); return *(const uint32_t*)&r; }
DI uint32_t magr(uint32_t m) { return max(m & 0xFFFF, m >> 16); }
DI void sts128(uint32_t a, uint32_t x, uint32_t y, uint32_t z, uint32_t w) { asm volatile("st.shared.v4.u32 [%0], {%1,%2,%3,%4};" :: "r"(a), "r"(x), "r"(y), "r"(z), "r"(w) : "memory"); }
DI void sts64(uint32_t a, uint32_t x, uint32_t y) { asm volatile("st.shared.v2.u32 [%0], {%1,%2};" :: "r"(a), "r"(x), "r"(y) : "memory"); }
DI void sts32(uint32_t a, uint32_t x) { asm volatile("st.shared.u32 [%0], %1;" :: "r"(a), "r"(x) : "memory"); }
DI void sts16(uint32_t a, uint32_t x) { asm volatile("st.shared.u16 [%0], %1;" :: "r"(a), "h"((uint16_t)x) : "memory"); }
DI void lds128(uint32_t* v, uint32_t a) { asm volatile("ld.shared.v4.u32 {%0, %1, %2, %3}, [%4];" : "=r"(v[0]), "=r"(v[1]), "=r"(v[2]), "=r"(v[3]) : "r"(a) : "memory"); }
DI void lds64(uint32_t& x, uint32_t& y, uint32_t a) { asm volatile("ld.shared.v2.u32 {%0, %1}, [%2];" : "=r"(x), "=r"(y) : "r"(a) : "memory"); }
DI uint32_t lds32(uint32_t a) { uint32_t x; asm volatile("ld.shared.u32 %0, [%1];" : "=r"(x) : "r"(a) : "memory"); return x; }
DI uint32_t lds16(uint32_t a) { uint32_t x; asm volatile("ld.shared.u16 %0, [%1];" : "=r"(x) : "r"(a) : "memory"); return x; }
DI uint32_t atoms_add(uint32_t a, uint32_t v) { uint32_t r; asm volatile("atom.shared.add.u32 %0, [%1], %2;" : "=r"(r) : "r"(a), "r"(v) : "memory"); return r; }
DI void bulk_load(uint32_t dst, const void* src, uint32_t bytes, uint32_t bar) {
  asm volatile("cp.async.bulk.shared::cluster.global.mbarrier::complete_tx::bytes.L2::cache_hint [%0], [%1], %2, [%3], %4;" :: "r"(dst), "l"(src), "r"(bytes), "r"(bar), "l"(pol_first()) : "memory"); }
DI void mbar_expect(uint32_t bar, uint32_t bytes) { asm volatile("mbarrier.arrive.expect_tx.shared::cta.b64 _, [%0], %1;" :: "r"(bar), "r"(bytes) : "memory"); }
DI void mbar_init(uint32_t bar, int n) { asm volatile("mbarrier.init.shared::cta.b64 [%0], %1;" :: "r"(bar), "r"(n) : "memory"); }
DI void tma_load(uint32_t dst, uint64_t tm, int row, uint32_t bar) {
  asm volatile("cp.async.bulk.tensor.2d.shared::cluster.global.mbarrier::complete_tx::bytes.L2::cache_hint [%0], [%1, {%3, %4}], [%2], %5;" :: "r"(dst), "l"(tm), "r"(bar), "r"(0), "r"(row), "l"(pol_first()) : "memory"); }
DI void tma_store(uint64_t tm, int col, int row, uint32_t src) {
  asm volatile("cp.async.bulk.tensor.2d.global.shared::cta.bulk_group [%0, {%2, %3}], [%1];" :: "l"(tm), "r"(src), "r"(col), "r"(row) : "memory"); }
DI void bulk_commit() { asm volatile("cp.async.bulk.commit_group;" ::: "memory"); }
DI uint2 ld_poll2(const void* a) { uint2 v; asm volatile("ld.relaxed.gpu.global.v2.u32 {%0, %1}, [%2];" : "=r"(v.x), "=r"(v.y) : "l"(a) : "memory"); return v; }
DI void st_ext(uint2* a, uint32_t v, uint32_t ep) { asm volatile("st.relaxed.gpu.global.v2.u32 [%0], {%1, %2};" :: "l"(a), "r"(v), "r"(ep) : "memory"); }
DI uint32_t ext_get(const uint2* a, uint32_t ep) { uint2 v; int spin = 0; do { v = ld_poll2(a); trap_if(++spin > 4000000); } while (__any_sync(~0u, v.y != ep)); return v.x; }
DI void bulk_wait() { asm volatile("cp.async.bulk.wait_group 0;" ::: "memory"); }
DI void hint_signal(uint32_t* c) { asm volatile("red.relaxed.gpu.global.add.u32 [%0], 1;" :: "l"(c) : "memory"); }
DI void hint_wait(const uint32_t* c, uint32_t target) { uint32_t v; int spin = 0;
  do { asm volatile("ld.relaxed.gpu.global.u32 %0, [%1];" : "=r"(v) : "l"(c) : "memory"); trap_if(++spin > 4000000); } while (__any_sync(~0u, (int)(v - target) < 0)); }
DI void stsm4(uint32_t a, uint32_t x, uint32_t y, uint32_t z, uint32_t w) { asm volatile("stmatrix.sync.aligned.m8n8.x4.shared.b16 [%0], {%1,%2,%3,%4};" :: "r"(a), "r"(x), "r"(y), "r"(z), "r"(w) : "memory"); }
DI void ldsm4(uint32_t* v, uint32_t a) { asm volatile("ldmatrix.sync.aligned.m8n8.x4.shared.b16 {%0,%1,%2,%3}, [%4];" : "=r"(v[0]), "=r"(v[1]), "=r"(v[2]), "=r"(v[3]) : "r"(a) : "memory"); }
DI void ldsm4t(uint32_t* v, uint32_t a) { asm volatile("ldmatrix.sync.aligned.m8n8.x4.trans.shared.b16 {%0,%1,%2,%3}, [%4];" : "=r"(v[0]), "=r"(v[1]), "=r"(v[2]), "=r"(v[3]) : "r"(a) : "memory"); }
DI uint32_t mad16(uint32_t x, uint32_t m, uint32_t c) { uint32_t r; asm("dp2a.lo.u32.u32 %0, %1, %2, %3;" : "=r"(r) : "r"(x), "r"(m), "r"(c)); return r; }
DI bool wbad(uint32_t m, uint32_t hi) { return m > hi || (m && m < 0x3980); }

__device__ __noinline__ void slow_path(const Params& p, int wid, int lane, int node0, int nloc) {
  const uint32_t ab = sb + OFF_P2 + wid * 8704;
  for (int i = lane; i < 32 * 68; i += 32) sts32(ab + i * 4, 0);
  __syncwarp();
  const uint32_t wdv = __ldg((const uint32_t*)(p.we + 128 * 64) + lane), wxv = __ldg((const uint32_t*)p.wx + lane);
  const int nb0 = node0 + wid * 32, cntn = max(0, min(32, nloc - wid * 32));
  auto dot = [&](uint32_t hv, const uint16_t* w, int K2, float& y0, float& y1) {
#pragma unroll 4
    for (int k = 0; k < K2; k++) {
      const uint32_t hk = __shfl_sync(~0u, hv, k), wa = __ldg((const uint32_t*)(w + 2 * k * 64) + lane), wb = __ldg((const uint32_t*)(w + (2 * k + 1) * 64) + lane);
      y0 = fmaf(bf_lo(hk), bf_lo(wa), fmaf(bf_hi(hk), bf_lo(wb), y0)); y1 = fmaf(bf_lo(hk), bf_hi(wa), fmaf(bf_hi(hk), bf_hi(wb), y1));
    }
  };
  auto silu = [](float x) { return x / (1.f + __expf(-x)); };
#pragma unroll 1
  for (int base = 0; base < p.E; base += 32) {
    const int e = base + lane;
    const uint32_t dl = e < p.E ? (uint32_t)(__ldg(p.dst + e) - nb0) : 0xFFFFFFFFu;
    uint32_t mk = __ballot_sync(~0u, dl < (uint32_t)cntn);
    while (mk) {
      const int l = __ffs(mk) - 1; mk &= mk - 1;
      const int ee = base + l, n = __shfl_sync(~0u, dl, l), s = __ldg(p.src + ee);
      const uint16_t *po = p.pos + (size_t)(nb0 + n) * 3, *pp = p.pos + (size_t)s * 3;
      const uint32_t dxy = hsub(__ldg(po) | (__ldg(po + 1) << 16), __ldg(pp) | (__ldg(pp + 1) << 16)), dz = hsub(__ldg(po + 2), __ldg(pp + 2));
      const uint32_t sq = hsq(dxy); const float d2 = bf_lo(sq) + bf_hi(sq) + bf_lo(hsq(dz));
      float y0 = d2 * bf_lo(wdv), y1 = d2 * bf_hi(wdv);
      dot(__ldg((const uint32_t*)(p.h + (size_t)(nb0 + n) * 8) + lane), p.we, 32, y0, y1);
      dot(__ldg((const uint32_t*)(p.h + (size_t)s * 8) + lane), p.we + 64 * 64, 32, y0, y1);
      dot(__ldg((const uint32_t*)(p.ea + (size_t)ee * 2) + (lane & 7)), p.we + 129 * 64, 8, y0, y1);
      const uint32_t mm = pack_bf16(silu(y0), silu(y1));
      float c = bf_lo(mm) * bf_lo(wxv) + bf_hi(mm) * bf_hi(wxv);
#pragma unroll
      for (int o = 16; o; o >>= 1) c += __shfl_xor_sync(~0u, c, o);
      const uint32_t a = ab + n * 272;
      uint32_t x0, x1; lds64(x0, x1, a + lane * 8);
      sts64(a + lane * 8, __float_as_uint(__uint_as_float(x0) + bf_lo(mm)), __float_as_uint(__uint_as_float(x1) + bf_hi(mm)));
      if (lane < 3) { const float df = lane == 0 ? bf_lo(dxy) : lane == 1 ? bf_hi(dxy) : bf_lo(dz); sts32(a + 256 + lane * 4, __float_as_uint(fmaf(c, df, __uint_as_float(lds32(a + 256 + lane * 4))))); }
    }
  }
  __syncwarp();
#pragma unroll 1
  for (int n = 0; n < cntn; n++) {
    uint32_t x0, x1; lds64(x0, x1, ab + n * 272 + lane * 8);
    const uint32_t hv = __ldg((const uint32_t*)(p.h + (size_t)(nb0 + n) * 8) + lane);
    float y0 = 0.f, y1 = 0.f;
    dot(hv, p.wh, 32, y0, y1); dot(pack_bf16(__uint_as_float(x0), __uint_as_float(x1)), p.wh + 64 * 64, 32, y0, y1);
    ((uint32_t*)p.out)[(size_t)(nb0 + n) * 32 + lane] = u2(__hadd2(b2(hv), b2(pack_bf16(silu(y0), silu(y1)))));
    if (lane < 3) p.out[(size_t)p.N * 64 + (size_t)(nb0 + n) * 3 + lane] = (uint16_t)pack_bf16(bf_lo(__ldg(p.pos + (size_t)(nb0 + n) * 3 + lane)) + __uint_as_float(lds32(ab + n * 272 + 256 + lane * 4)), 0.f);
  }
}

__global__ void __launch_bounds__(NTHR, 1) egnn_kernel(const __grid_constant__ Params p, const __grid_constant__ Maps maps) {
  const uint64_t tmb = (uint64_t)&maps;
  extern __shared__ __align__(1024) unsigned char smraw[];
  const int tid = threadIdx.x, cta = blockIdx.x * CTAM % G;
  const int e0 = cta * p.EPC, n4 = max(0, min(p.EPC, p.E - e0)) >> 2;
  STAMP(0);
  if (tid == NWK) {
#pragma unroll 1
    for (int k = 0; k < NCH; k++) { const int nb = max(0, min(NWK, n4 - k * NWK)) * 16;
      mbar_init(sb + BAR_DST + k * 8, 1);
      asm volatile("fence.mbarrier_init.release.cluster;" ::: "memory");
      mbar_expect(sb + BAR_DST + k * 8, nb);
      if (nb) bulk_load(sb + OFF_DST + k * NWK * 16, (const char*)(p.dst + e0) + k * NWK * 16, nb, sb + BAR_DST + k * 8); }
  }
  const int lane = tid & 31, wid = __shfl_sync(~0u, tid >> 5, 0), w = wid & 3;
  asm volatile("{.reg .pred p; setp.eq.u32 p, %2, 384; @p cp.async.cg.shared.global [%0], [%1], 16;}" :: "r"(sb + OFF_LEN - 192 + (tid >> 1)), "l"(p.sync), "r"(tid & 415) : "memory");

  auto first_node = [&](int c) { return (int)((c * p.inv + 0xFFFFFFFFull) >> 32); };
  const int node0 = first_node(cta), nloc = min(first_node(cta + 1), p.N) - node0;
  const uint32_t ealo = (uint32_t)(uint64_t)p.ea;
  const int epad = min(e0, p.E - 1);
  if (wid >= 12) {
    const int t = tid - 384;
    auto load_h = [&](int b) { mbar_expect(sb + BAR_T + b * 8, 8192); tma_load(sb + OFF_H + b * 8192, tmb + TM_H, node0 + b * 64, sb + BAR_T + b * 8); };
    uint32_t pv[9], ev = 0;
#pragma unroll
    for (int i = 0; i < 3; i++) { const uint16_t* pp = p.pos + (size_t)(node0 + t + 128 * i) * 3;
      pv[3 * i] = pv[3 * i + 1] = pv[3 * i + 2] = 0;
      asm volatile("{.reg .pred p; setp.lt.s32 p, %4, %5;\n @p ld.global.nc.u16 %0, [%3];\n @p ld.global.nc.u16 %1, [%3+2];\n @p ld.global.nc.u16 %2, [%3+4];}"
        : "+r"(pv[3 * i]), "+r"(pv[3 * i + 1]), "+r"(pv[3 * i + 2]) : "l"(pp), "r"(t + 128 * i), "r"(p.N - node0)); }
    asm volatile("{.reg .pred p; setp.lt.u32 p, %3, 8; @p ld.global.nc.u32 %0, [%1]; @p st.global.v4.u32 [%2], {%4, %4, %4, %4};}"
      : "+r"(ev) : "l"((const uint32_t*)(p.ea + (size_t)epad * 2) + t), "l"(p.q + (size_t)(p.N + cta * PADM) * 128 + t * 16), "r"(t), "r"(0xF700F700u) : "memory");
    asm volatile("cp.async.wait_all;" ::: "memory");
    __syncwarp();
    const uint32_t e = lds32(sb + OFF_LEN + 8 + w * 16) + 1;
    {
      const uint32_t tg = (1 + e % 3) << 30, v = ((tg >> 16) + 512 + (lane & 7) * 4) * 0x10001u;
      if (t == 0) sts32(sb + OFF_MISC + 32, e);
#pragma unroll
      for (int i = 0; i < 9; i++) sts128(sb + OFF_SA + t * 16 + i * 2048, v, v + 0x10001u, v + 0x20002u, v + 0x30003u);
      bar_sync(6, NTHR);
      mbar_arrive(sb + BAR_EP, lane == 0);
#pragma unroll
      for (int i = 0; i < 17; i++) sts128(sb + OFF_SB + t * 16 + i * 2048, tg, tg, tg, tg); }
    uint32_t mp = 0;
#pragma unroll
    for (int i = 0; i < 3; i++) { sts64(sb + OFF_POS + (t + 128 * i) * 8, pv[3 * i] | (pv[3 * i + 1] << 16), pv[3 * i + 2]); mp = mag2(mag2(mp, pv[3 * i] | (pv[3 * i + 1] << 16)), pv[3 * i + 2]); }
    proxy_fence();
    __syncwarp();
    mbar_arrive(sb + BAR_PS, lane == 0);
    mbar_wait(sb + BAR_W);
    {
      uint32_t v[4], u[4]; const int r = t >> 3, c = t & 7;
      lds128(v, sb + OFF_WS + 128 + t * 16); lds128(u, sb + OFF_WS + c * 16);
      const uint32_t x = lds32(sb + OFF_WS + 2176 + lane * 4);
      sts128(sb + OFF_W3 + r * 128 + ((c ^ (r & 7)) << 4), b2h(v[0], .5f), b2h(v[1], .5f), b2h(v[2], .5f), b2h(v[3], .5f));
      const float s = ((r & 1) || r == 6) ? 0.f : .5f;
      if (t < 64) sts128(sb + OFF_WD + r * 128 + ((c ^ r) << 4), b2h(u[0], s), b2h(u[1], s), b2h(u[2], s), b2h(u[3], s));
      if (t < 32) sts32(sb + OFF_WX + (t & 3) * 32 + (t >> 2) * 4, b2h(x, 1.f));
      const uint32_t m3 = __reduce_max_sync(~0u, magr(mag2(mag2(mag2(mag2(0, v[0]), v[1]), v[2]), v[3]))), md = __reduce_max_sync(~0u, magr(mag2(mag2(mag2(mag2(0, u[0]), u[1]), u[2]), u[3])));
      if (wbad(m3, 0x4000) || wbad(md, 0x4000) || wbad(__reduce_max_sync(~0u, magr(mag2(0, x))), 0x4700) || magr(mp) >= 0x4200 || magr(mag2(0, ev)) >= 0x4380) sts32(sb + OFF_MISC + 8, 1);
    }
    if (w == 1) {
#pragma unroll 1
      for (int b = 0; b < 3; b++) { mbar_wait(sb + BAR_SRC + b * 8); if (lane == 0) load_h(b); }
    }
    bar_sync(3, 128);
    const uint32_t frag = (w * 16 + (lane & 15)) * 128 + (((lane >> 4) ^ (lane & 7)) << 4);
    uint32_t mq = 0;
#pragma unroll 1
    for (int b = 0; b < 6; b++) {
      float acc[32];
      const uint64_t da = DHI | (((sb + OFF_H) >> 4) + b * 512), db = DHI | ((sb + OFF_W) >> 4);
      const uint32_t v0 = lds16(sb + OFF_POS + b * 512 + w * 128 + lane * 2), v1 = lds16(sb + OFF_POS + 64 + b * 512 + w * 128 + lane * 2);
      mbar_wait(sb + BAR_T + b * 8);
      if (b == 0) STAMP(25);
      if (b == 5) STAMP(26);
      wg_fence();
      ss64<0>(acc, da, db); ss64<1>(acc, da + 2, db + 128); ss64<1>(acc, da + 4, db + 256); ss64<1>(acc, da + 6, db + 384);
      wg_commit();
      if (b == 0) mbar_wait(sb + BAR_AW);
      if (t == 32 && b < 3) load_h(b + 3);
      __syncwarp();
      uint32_t ff[6], fg[6];
#pragma unroll
      for (int j = 0; j < 6; j++) { ff[j] = (__byte_perm((j & 1) ? v1 : v0, 0, 0x4140) >> (3 * (j >> 1))) & 0x00070007u; fg[j] = __vsub2(0x00040004u, ff[j]);
        asm volatile("" : "+r"(ff[j]), "+r"(fg[j])); }
      wg_wait0(); fence_regs(acc);
      uint32_t o[16];
#pragma unroll
      for (int j = 0; j < 16; j++) o[j] = pack_f16(.5f * acc[2 * j], .5f * acc[2 * j + 1]);
#pragma unroll
      for (int j = 0; j < 6; j++) {
        const uint32_t m = o[j] & 0x7FFF7FFFu; mq = __vmaxu2(mq, m);
        o[j] = (__viaddmax_s16x2(m, fg[j], 0) & 0xFFF8FFF8u) | ff[j] | (o[j] & 0x80008000u); }
      if (b == 4) mbar_wait(sb + BAR_AX);
      const uint32_t qs = sb + OFF_SA + b * 8192;
#pragma unroll
      for (int j = 0; j < 4; j++) stsm4((qs + frag) ^ (j << 5), o[4 * j], o[4 * j + 1], o[4 * j + 2], o[4 * j + 3]);
      proxy_fence();
      __syncwarp();
      if (lane == 0 && b * 64 + w * 16 < nloc) tma_store(tmb + TM_Q, 0, node0 + b * 64 + w * 16, qs + w * 2048);
    }
    if (lane == 0) bulk_commit();
    { const uint32_t m = __reduce_max_sync(~0u, magr(mq)); if (lane == 0) sts32(sb + OFF_MISC + 16 + w * 4, m); }
    asm volatile("setmaxnreg.dec.sync.aligned.u32 56;");
    bulk_wait();
    bar_sync(3, 128);
    if (w == 0) {
      STAMP(18);
      uint32_t mv[4]; lds128(mv, sb + OFF_MISC + 16);
      const uint32_t mx = max(max(mv[0], mv[1]), max(mv[2], mv[3]));
      mbar_arrive(sb + BAR_QR, lane == 0);
      STAMP(19);
      if (lane == 0) {
        if (nloc > 0 && (mx >= 0x7BF0 || mx < 0x1400)) asm volatile("st.relaxed.gpu.global.u32 [%0+4], %1;" :: "l"(p.sync), "r"(e) : "memory");
        asm volatile("red.release.gpu.global.add.u32 [%0], 1;" :: "l"(p.sync) : "memory");
      }
      __syncwarp();
      uint32_t c, f; int spin = 0;
      do { asm volatile("ld.acquire.gpu.global.v2.u32 {%0, %1}, [%2];" : "=r"(c), "=r"(f) : "l"(p.sync) : "memory"); trap_if(++spin > 4000000); } while (__any_sync(~0u, (int)(c - e * G) < 0));
      if (f == e) sts32(sb + OFF_MISC + 8, 1);
      if (cta == 0 && lane == 0) asm volatile("st.relaxed.gpu.global.u32 [%0+8], %1;" :: "l"(p.sync), "r"(e) : "memory");
      STAMP(20);
      __syncwarp();
      mbar_arrive(sb + BAR_QP, lane == 0);
    }
    if (w == 2) {
      const uint32_t tg = (1 + e % 3) << 30;
      hint_wait(p.sync + 5, e * G);
      if (lane == 0) { mbar_expect(sb + BAR_HB, XPAD);
#pragma unroll 1
        for (int o = 0; o < 4; o++) bulk_load(sb + OFF_XB + o * (G * 64), (const char*)p.xb + (size_t)(cta * 4 + o) * (G * 64), G * 64, sb + BAR_HB); }
      STAMP(21);
      bar_sync(7, 384);
      sts32(sb + OFF_XB + XPAD, tg + p.N + cta * PADM);
      const uint32_t nx = __shfl_sync(~0u, lds32(sb + OFF_MISC + 8) ? 0 : lds32(sb + OFF_MISC + 4), 0);
#pragma unroll 1
      for (uint32_t k = 0; k < nx; k += 32) {
        const uint32_t i = min(k + lane, nx - 1), xr = lds32(sb + OFF_EXT + i * 4), row = (xr >> 9) & 255;
        const uint32_t v = ext_get(p.xe + (cta * G + row) * 32 + ((xr >> 17) & 31), e), x = lds32(sb + OFF_CNT + (xr & 511) * 4) + (xr >> 22) * 16;
        sts32(sb + OFF_XB + XPAD + 4 + i * 4, v); sts16(sb + OFF_TS + x, XPAD + 4 + i * 4);
        sts32(sb + OFF_TE + x * 2, mad16(v, 0x2000u, ealo - (tg >> 11) + row * p.EPC * 32));
      }
      __syncwarp();
      mbar_arrive(sb + BAR_HB, lane == 0);
    }
    if (w == 1) {
      const uint32_t nb = min(PFB, p.E / G * 32 / max(PFN, 1)) & ~127u;
#pragma unroll 1
      for (int i = 0; i < PFN; i++) {
        if (lane == 0 && nb) asm volatile("cp.async.bulk.prefetch.L2.global [%0], %1;" :: "l"((const char*)p.ea + (size_t)(i * G + cta) * nb), "r"(nb) : "memory");
        __nanosleep(PFNS); }
    }
    if (w == 3) {
      if (lane == 0) { mbar_expect(sb + BAR_U, 16384); tma_load(sb + OFF_W, tmb + TM_WH, 0, sb + BAR_U); }
      __syncwarp();
      bar_sync(4, 416);
      if (lane == 0) tma_load(sb + OFF_W + 8192, tmb + TM_WH, 64, sb + BAR_U);
    }
    bar_sync(3, 128);
    mbar_wait(sb + BAR_U);
    uint32_t mh = 0;
#pragma unroll 1
    for (int i = t; i < 1024; i += 128) {
      uint32_t v[4]; const uint32_t r = (i >> 3) & 7, j = (i ^ r) & 7;
#pragma unroll
      for (int k = 0; k < 4; k++) v[k] = lds32(sb + OFF_W + (i >> 3) * 128 + ((((j & 4) + k) ^ r) << 4) + (j & 3) * 4);
      __syncwarp();
      if (i < 512) sts128(sb + OFF_W + i * 16, hhalf(v[0]), hhalf(v[1]), hhalf(v[2]), hhalf(v[3]));
      else { sts128(sb + OFF_W + i * 16, b2h(v[0], .5f), b2h(v[1], .5f), b2h(v[2], .5f), b2h(v[3], .5f)); mh = mag2(mag2(mag2(mag2(mh, v[0]), v[1]), v[2]), v[3]); } }
    if (wbad(__reduce_max_sync(~0u, magr(mh)), 0x4700)) sts32(sb + OFF_MISC + 12, 1);
    proxy_fence();
    __syncwarp();
    mbar_arrive(sb + BAR_WH, lane == 0);
    if (!__shfl_sync(~0u, lds32(sb + OFF_MISC + 8), 0)) {
      mbar_wait(sb + BAR_WH);
      float chk = 0.f;
#pragma unroll 1
      for (uint32_t todo = UORD; todo; todo >>= 4) {
        const uint32_t nd = lds16(sb + OFF_GP + (todo & 3) * 1024 + w * 256 + (lane & 15) * 8 + 6), hb = (todo >> 3) & 1;
        const uint64_t b1 = DHI | (((sb + OFF_W) >> 4) + hb * 4);
        uint32_t f[8]; float acc[16];
#pragma unroll
        for (int j = 0; j < 8; j += 2) {
          const uint32_t a = j < 4 ? sb + OFF_H + nd * 128 + (((nd & 7) << 4) ^ (lane & 16)) : sb + OFF_P2 + (todo & 3) * 8192 + frag;
          if (j == 4) mbar_wait(sb + BAR_M + (todo & 3) * 8);
          ldsm4(f, a ^ ((j & 3) << 5)); ldsm4(f + 4, a ^ ((j & 3) << 5) ^ 32);
          wg_fence();
          if (j == 0) rs32b<0>(acc, f, b1); else if (j < 4) rs32b<1>(acc, f, b1 + 128 * j); else rs32h(acc, f, b1 + 128 * j);
          if (j < 4) rs32b<1>(acc, f + 4, b1 + 128 * j + 128); else rs32h(acc, f + 4, b1 + 128 * j + 128);
          wg_commit(); wg_wait0(); fence_regs(acc);
        }
        chk = fmaf(acc[0], 0.f, fmaf(acc[2], 0.f, chk));
#pragma unroll
        for (int k = 0; k < 2; k++) {
          const uint32_t o = __shfl_sync(~0u, nd, (lane >> 2) + 8 * k) * 128 + (lane & 3) * 16 + hb * 64;
          uint32_t x[4]; lds128(x, sb + OFF_H + (o ^ ((o >> 3) & 0x70)));
#pragma unroll
          for (int i = 0; i < 4; i++) x[i] = u2(__hadd2(b2(x[i]), b2(pack_bf16(silu_h(acc[4 * i + 2 * k]), silu_h(acc[4 * i + 2 * k + 1])))));
          if (o < nloc * 128) *(uint4*)((char*)p.out + (size_t)node0 * 128 + o) = make_uint4(x[0], x[1], x[2], x[3]);
        }
        __nanosleep(DEFNS);
      }
      uint32_t pa_[9];
#pragma unroll
      for (int k = 0; k < 9; k++) { const uint32_t i = t + 128 * k, n = (i * 43691u) >> 17; pa_[k] = lds16(sb + OFF_INV + n * 2) + (i - 3 * n) * 2; }
      uint16_t* po = p.out + (size_t)p.N * 64 + node0 * 3 + t;
      mbar_wait(sb + BAR_X);
#pragma unroll
      for (int k = 0; k < 9; k++) pa_[k] = lds16(sb + OFF_GP + pa_[k]);
#pragma unroll
      for (int k = 0; k < 9; k++) if (t + 128 * k < nloc * 3) po[128 * k] = pa_[k];
      asm volatile("{.reg .pred p, q; setp.neu.f32 p, %0, 0f00000000; bar.red.or.pred q, 5, 512, p;}" :: "f"(chk) : "memory");
    }
    return;
  }

  if (tid == 320) {
    mbar_init(sb + BAR_W, 1);
    asm volatile("fence.mbarrier_init.release.cluster;" ::: "memory");
    mbar_expect(sb + BAR_W, 2 * 8192 + 2304);
    tma_load(sb + OFF_W, tmb + TM_WE, 64, sb + BAR_W); tma_load(sb + OFF_W + 8192, tmb + TM_WE, 0, sb + BAR_W);
    bulk_load(sb + OFF_WS, p.we + 128 * 64, 2176, sb + BAR_W); bulk_load(sb + OFF_WS + 2176, p.wx, 128, sb + BAR_W);
  }
  if (tid == 288) {
#pragma unroll
    for (int a = BAR_SRC; a < BAR_END; a += 8) if (a != BAR_W) mbar_init(sb + a, a == BAR_X ? 12 : a >= BAR_WH || a == BAR_PS || a == BAR_EP ? 4 : a == BAR_HB ? 2 : 1);
    asm volatile("fence.mbarrier_init.release.cluster;" ::: "memory");
    asm volatile("prefetch.tensormap [%0];" :: "l"(tmb + TM_XA)); asm volatile("prefetch.tensormap [%0];" :: "l"(tmb + TM_H));
    asm volatile("prefetch.tensormap [%0];" :: "l"(tmb + TM_XB)); asm volatile("prefetch.tensormap [%0];" :: "l"(tmb + TM_Q));
  }
  {
    if (tid < 144) { const uint32_t z = (tid >> 3) == 16 ? 0x8000u : 0u; sts128(sb + OFF_CNT + tid * 16, z, z, z, z); }
    else if (tid <= 144 + G) sts32(sb + OFF_BC + (tid - 144) * 4, ((tid - 144) & 31) * 4);
    const uint32_t sp = XPAD * 0x10001u, em = first_node(G);
    if (wid < 7) {
#pragma unroll
      for (int i = 0; i < 4; i++) sts128(sb + OFF_TS + tid * 16 + i * 3584, sp, sp, sp, sp);
    }
    static_assert(SCAP * 32 == 4 * 3584, "fill");
#pragma unroll 1
    for (int i = n4 + tid; i < 1536; i += 384) sts128(sb + OFF_DST + i * 16, em, em, em, em);
    if (tid == 321) sts128(sb + OFF_MISC, 0, 0, p.force_slow, 0);
  }
  bar_arrive(6, NTHR);
  bar_sync(0, 384);
  uint32_t ep, tag, eb0, pk[12], r0[12], r1[12], cb;
  uint2 vb[12];
  auto get_tag = [&]() { mbar_wait(sb + BAR_EP); ep = lds32(sb + OFF_MISC + 32); tag = (1 + ep % 3) << 30; eb0 = ealo - (tag >> 11); };
  if (wid == 11) {
    trap_if(sb != (uint32_t)__cvta_generic_to_shared(smraw));
#pragma unroll 1
    for (int k = 0; k < 3; k++) { const int nb = max(0, min(8192, n4 * 16 - k * 8192));
      mbar_wait(sb + BAR_DST + (k ? k + 1 : 0) * 8);
      if (lane == 0) { mbar_expect(sb + BAR_SRC + k * 8, nb);
        if (nb) bulk_load(sb + OFF_SRCI + k * 8192, (const char*)(p.src + e0) + k * 8192, nb, sb + BAR_SRC + k * 8); } }
    get_tag();
    mbar_wait(sb + BAR_PS);
    bar_sync(12, 384);
    uint32_t xm = 0;
#pragma unroll
    for (int k = 0; k < 5; k++) xm |= (lds32(sb + OFF_BC + min(lane + 32 * k, G - 1) * 4) >= (65 << 9) && lane + 32 * k < G) << k;
    auto ext_send = [&](int pl) {
      uint32_t x = xm;
      for (uint32_t m; (m = __ballot_sync(~0u, x));) {
        const uint32_t l = __ffs(m) - 1, j = l + 32 * (__ffs(__shfl_sync(~0u, x, l)) - 1);
        if (lane == l) x &= x - 1;
        const uint32_t e = min(lds16(sb + OFF_AX + j * 128 + ((4 * l + 2 * lane) & 126)), 6143u);
        if (pl) st_ext(p.xe + (j * G + cta) * 32 + lane, lds32(sb + OFF_SRCI + e * 4) + tag + (e << 16), ep);
        else { const uint32_t cn = lds32(sb + OFF_BC + j * 4) >> 9, v = cn > 96 ? 1 : lane + 64 < cn ? 512 | (lds32(sb + OFF_DST + e * 4) & 511) : 0;
          asm volatile("red.shared.xor.b32 [%0], %1;" :: "r"(sb + OFF_SA + j * 128 + ((l + lane) & 31) * 4), "r"(((v & 63) << 10) | ((v >> 6) << 26)) : "memory"); }
      }
    };
    if (__any_sync(~0u, xm)) { ext_send(0); proxy_fence(); __syncwarp(); }
    if (lane == 0) { tma_store(tmb + TM_XA, cta * 64, 0, sb + OFF_SA); bulk_commit(); mbar_arrive(sb + BAR_AI); bulk_wait(); hint_signal(p.sync + 4); mbar_arrive(sb + BAR_AW); STAMP(16); }
    __syncwarp();
    bar_sync(13, 384);
    ext_send(1);
    mbar_arrive(sb + BAR_AX, lane == 0);
    mbar_wait(sb + BAR_HA);
    __nanosleep(BDEL);
    if (lane == 0) {
#pragma unroll 1
      for (int r = 0; r < G; r += BROWS) { tma_store(tmb + TM_XB, cta * 64, r, sb + OFF_SB + r * 256); bulk_commit(); bulk_wait(); }
      hint_signal(p.sync + 5);
      STAMP(17);
    }
    __syncwarp();
  } else {
    {
      uint32_t d[4 * NCH], jj[4 * NCH], rr[4 * NCH];
      auto count = [&](int k) {
        mbar_wait(sb + BAR_DST + k * 8);
        lds128(d + 4 * k, sb + OFF_DST + (tid + NWK * k) * 16);
#pragma unroll
        for (int i = 4 * k; i < 4 * k + 4; i++) { jj[i] = d[i] * p.magic; rr[i] = atoms_add(__dp4a(jj[i], 0x04000000u, sb + OFF_BC), 0x202u); }
      };
      auto place = [&](int k) {
#pragma unroll
        for (int i = 4 * k; i < 4 * k + 4; i++) {
          const uint32_t o = __dp4a(jj[i], 0x80000000u, rr[i] & 0x807Eu);
          d[i] = (d[i] & 511) | (tag >> 16);
          asm("{.reg .pred p; setp.ge.u32 p, %1, 0x8000; @p add.u32 %0, %2, %3;}" : "+r"(d[i]) : "r"(o), "r"(tid * 4), "r"(NWK * k * 4 + (i & 3)));
          sts16(sb + OFF_SA + o, d[i]); jj[i] = __viaddmin_u32(o, o, G * 256);
        }
      };
      count(0); STAMP(1); count(1); get_tag(); place(0); count(2); place(1); count(3); place(2);
      if (wid < 4) { count(4); STAMP(15); place(3); place(4); } else place(3);
      proxy_fence();
      bar_arrive(12, 384);
      STAMP(2);
      mbar_wait(sb + BAR_AI);
      mbar_wait(sb + BAR_SRC); mbar_wait(sb + BAR_SRC + 8); mbar_wait(sb + BAR_SRC + 16);
      STAMP(12);
#pragma unroll
      for (int k = 0; k < NCH; k++) lds128(d + 4 * k, sb + OFF_SRCI + (tid + NWK * k) * 16);
      const uint32_t tb = tag + (tid << 18);
#pragma unroll
      for (int i = 0; i < 4 * NCH; i++) if (i < 4 * NCH - 4 || wid < 4) sts32(sb + OFF_SB + jj[i], d[i] + tb + ((NWK * (i >> 2) * 4 + (i & 3)) << 16));
      proxy_fence();
      bar_arrive(13, 384);
      STAMP(3);
    }
    const uint32_t rot = (lane + cta) & 31;
    cb = sb + OFF_CNT - (tag >> 14);
    {
      const uint32_t* xa = (const uint32_t*)(p.xa + (cta * G + wid) * 8) + rot;
      if (wid < 8) { const uint32_t e_ = ealo + epad * 32;
        mbar_wait(sb + BAR_AX);
#pragma unroll
        for (int i = 0; i < 7; i++) sts128(sb + OFF_TE + tid * 16 + i * 4096, e_, e_, e_, e_); }
      static_assert(SCAP * 64 == 7 * 4096, "fill");
      if (wid == 10) { hint_wait(p.sync + 4, ep * G); mbar_arrive(sb + BAR_HA, lane == 0); }
      mbar_wait(sb + BAR_HA);
      STAMP(14);
      const uint32_t tp = tag | (tag >> 16);
      uint32_t st;
#pragma unroll 1
      for (int spin = 0;; spin++) {
        st = 0;
#pragma unroll
        for (int k = 0; k < 12; k++) asm volatile("ld.relaxed.gpu.global.u32 %0, [%1];" : "=r"(pk[k]) : "l"(xa + k * 352) : "memory");
#pragma unroll
        for (int k = 0; k < 12; k++) st |= pk[k] ^ tp;
        st = __reduce_or_sync(~0u, st);
        if (!(st >> 30)) break;
        trap_if(spin > 2000000);
      }
      if (st & 0x3C00FC00u) {
#pragma unroll 1
        for (;;) {
          uint32_t x = 0, row = 0;
#pragma unroll
          for (int k = 0; k < 12; k++) { const uint32_t y = (pk[k] ^ tp) & 0x3C00FC00u; if (!x && y) { x = y; row = wid + 11 * k; pk[k] ^= y; } }
          if (!__any_sync(~0u, x)) break;
          const uint32_t n = ((x >> 10) & 63) | ((x >> 20) & 0x1C0);
          if (x >> 29) {
            const uint32_t r = atoms_add(sb + OFF_CNT + n * 4, 16), idx = atoms_add(sb + OFF_MISC + 4, 1);
            if (idx < 256) sts32(sb + OFF_EXT + idx * 4, n | (row << 9) | (lane << 17) | (min(r >> 4, 255u) << 22));
            else x = 1;
          }
          if (x && !(x >> 29)) sts32(sb + OFF_MISC + 8, 1);
          __syncwarp();
        }
      }
#pragma unroll
      for (int k = 0; k < 12; k++) { r0[k] = mad16(pk[k], 0x0004u, cb); r1[k] = mad16(pk[k], 0x0400u, cb); vb[k].x = atoms_add(r0[k], 16); vb[k].y = atoms_add(r1[k], 16); }
    }
    STAMP(4);
    if (wid >= 6) bar_arrive(11, NWK);
    if (wid < 6) {
      uint32_t ca[2], ky[2], dr[2], sq[2], ps[4];
#pragma unroll
      for (int i = 0; i < 2; i++) { ca[i] = sb + OFF_CNT + ((node0 + tid + 192 * i) & 511) * 4; lds64(ps[2 * i], ps[2 * i + 1], sb + OFF_POS + (tid + 192 * i) * 8); ps[2 * i + 1] |= (tid + 192 * i) << 16; }
      bar_sync(11, NWK);
      STAMP(5);
#pragma unroll
      for (int i = 0; i < 2; i++) ky[i] = (lds32(ca[i]) + 16) >> 5;
      if (max(ky[0], ky[1]) > 31) sts32(sb + OFF_MISC + 8, 1);
#pragma unroll
      for (int i = 0; i < 2; i++) { ky[i] = min(ky[i], 31u); dr[i] = atoms_add(sb + OFF_DH + ky[i] * 4, 1); }
      bar_sync(10, 192);
      const uint32_t hv = lds32(sb + OFF_DH + lane * 4);
      uint32_t inc = hv;
#pragma unroll
      for (int o = 1; o < 32; o <<= 1) asm("{.reg .pred p; .reg .b32 y; shfl.sync.down.b32 y|p, %0, %1, 31, -1; @p add.u32 %0, %0, y;}" : "+r"(inc) : "r"(o));
#pragma unroll
      for (int i = 0; i < 2; i++) {
        const uint32_t pos = __shfl_sync(~0u, inc - hv, ky[i]) + dr[i];
        const uint32_t ak = (uint32_t)(QCODE >> ((pos >> 5) * 4)) & 15, l = (pos >> 3) & 3;
        sq[i] = (ak >> 2) * 16 + ((QREV >> (pos >> 5) & 1) ? 3 - l : l) * 4 + (ak & 3);
        dr[i] = pos & 7;
        asm volatile("{.reg .pred p; setp.eq.u32 p, %2, 0; @p st.shared.u8 [%0], %1;}" :: "r"(sb + OFF_LEN + sq[i]), "r"(max(ky[i], 1u)), "r"(dr[i]) : "memory");
        sts64(sb + OFF_GP + sq[i] * 64 + dr[i] * 8, ps[2 * i], ps[2 * i + 1]);
        sts16(sb + OFF_INV + (tid + 192 * i) * 2, sq[i] * 64 + dr[i] * 8);
      }
      bar_sync(10, 192);
      const uint32_t ln = lds32(sb + OFF_LEN + min(lane, 11) * 4), tot = __dp4a(ln, 0x01010101u, 0u);
      inc = tot;
#pragma unroll
      for (int o = 1; o < 16; o <<= 1) asm("{.reg .pred p; .reg .b32 y; shfl.sync.up.b32 y|p, %0, %1, 0, -1; @p add.u32 %0, %0, y;}" : "+r"(inc) : "r"(o));
      if (wid == 1) sts32(sb + OFF_CNT + 2048 + lane * 4, 0);
      if (tid < 12) { sts32(sb + OFF_LEN + 64 + tid * 4, inc - tot); if (inc > SCAP - 12) sts32(sb + OFF_MISC + 8, 1); }
#pragma unroll
      for (int i = 0; i < 2; i++) sts32(ca[i], __dp4a(__shfl_sync(~0u, ln, sq[i] >> 2), 0x00010101u >> (24 - 8 * (sq[i] & 3)), __shfl_sync(~0u, inc - tot, sq[i] >> 2)) * 32 + dr[i] * 2);
    }
    bar_arrive(7, 384);
  }
  bar_sync(1, 384);
  STAMP(6);
  if (wid != 11 && !__shfl_sync(~0u, lds32(sb + OFF_MISC + 8), 0)) {
#pragma unroll
    for (int k = 0; k < 12; k++) { r0[k] = lds32(r0[k]); r1[k] = lds32(r1[k]); }
#pragma unroll
    for (int k = 0; k < 12; k++) { r0[k] += vb[k].x; r1[k] += vb[k].y; }
  } else {
#pragma unroll
    for (int k = 0; k < 12; k++) r0[k] = r1[k] = 0x8000;
  }
  auto put_ids = [&]() {
    const uint32_t id = wid * 256 + ((lane + cta) & 31) * 8;
    auto put = [&](uint32_t x, uint32_t v) { asm volatile("{.reg .pred p; setp.lt.u32 p, %0, 0x8000; @p st.shared.u16 [%0+%2], %1;}" :: "r"(x), "h"((uint16_t)v), "n"(sb + OFF_TS) : "memory"); };
#pragma unroll
    for (int k = 0; k < 12; k++) { put(pk[k] & 0xFFFF, id + k * 2816); put(pk[k] >> 16, id + k * 2816 + 4); }
  };
  STAMP(7);
  mbar_wait(sb + BAR_QR);
  asm volatile("setmaxnreg.inc.sync.aligned.u32 152;");
#pragma unroll
  for (int k = 0; k < 12; k++) asm volatile("prmt.b32 %0, %1, %2, 0x5410;" : "=r"(pk[k]) : "r"(r0[k]), "r"(r1[k]));
  uint32_t pa[8], sp[8], pq[16]; float chk = 0.f;
  {
    uint32_t hf[32], mp = 0; float a0[32], a1[32];
    const uint32_t an = sb + OFF_GP + wid * 256 + (lane & 15) * 8 + 6, n0 = lds16(an), n1 = lds16(an + 128);
#pragma unroll
    for (int j = 0; j < 8; j++) { const uint32_t nd = j < 4 ? n0 : n1; ldsm4(hf + 4 * j, (sb + OFF_H + nd * 128 + (((nd & 7) << 4) ^ (lane & 16))) ^ ((j & 3) << 5)); }
    const uint64_t db = DHI | ((sb + OFF_W + 8192) >> 4);
    wg_fence();
    rs64b<0>(a0, hf[0], hf[1], hf[2], hf[3], db); rs64b<1>(a0, hf[4], hf[5], hf[6], hf[7], db + 128); rs64b<1>(a0, hf[8], hf[9], hf[10], hf[11], db + 256); rs64b<1>(a0, hf[12], hf[13], hf[14], hf[15], db + 384);
    wg_commit();
    rs64b<0>(a1, hf[16], hf[17], hf[18], hf[19], db); rs64b<1>(a1, hf[20], hf[21], hf[22], hf[23], db + 128); rs64b<1>(a1, hf[24], hf[25], hf[26], hf[27], db + 256); rs64b<1>(a1, hf[28], hf[29], hf[30], hf[31], db + 384);
    wg_commit();
    put_ids();
    asm volatile("wgmma.wait_group.sync.aligned 1;" ::: "memory"); fence_regs(a0);
#pragma unroll
    for (int j = 0; j < 8; j++) { const uint32_t x = pack_f16(.5f * a0[4 * j], .5f * a0[4 * j + 1]), y = pack_f16(.5f * a0[4 * j + 2], .5f * a0[4 * j + 3]); mp = hmag(hmag(mp, x), y);
      asm volatile("movmatrix.sync.aligned.m8n8.trans.b16 %0, %1;" : "=r"(pa[j]) : "r"(x)); asm volatile("movmatrix.sync.aligned.m8n8.trans.b16 %0, %1;" : "=r"(sp[j]) : "r"(y)); }
    wg_wait0(); fence_regs(a1);
    bar_arrive(4, 416);
#pragma unroll
    for (int j = 0; j < 16; j++) { pq[j] = pack_f16(.5f * a1[2 * j], .5f * a1[2 * j + 1]); mp = hmag(mp, pq[j]); }
    if (magr(mp) >= 0x7000) chk = __int_as_float(0x7FC00000);
  }
  if (wid == 0) STAMP(23);
  uint32_t bad;
  {
    const uint32_t ring = sb + OFF_RING + wid * STG, p2 = sb + OFF_P2 + wid * 2048;
    uint32_t lens = __shfl_sync(~0u, lds32(sb + OFF_LEN + wid * 4), 0);
    uint32_t rem = __dp4a(lens, 0x20202020u, 0u);
    const uint32_t base = min(lds32(sb + OFF_LEN + 64 + wid * 4), SCAP);
    uint32_t a_s = sb + OFF_TS + base * 32 + (lane >> 3) * 8, a_e = sb + OFF_TE + base * 64 + (lane >> 1) * 4;
    uint32_t k0 = (uint32_t)(uint64_t)p.q + (((lane & 7) ^ ((lane >> 1) & 4)) << 4), k1 = k0 ^ 16, k2 = k0 ^ 32, k3 = k0 ^ 48, ke = ((lane ^ (lane >> 3)) & 1) << 4;
    uint32_t dst0 = ring + (lane >> 3) * 640 + (lane & 7) * 16;
    const uint32_t qhi = (uint32_t)((uint64_t)p.q >> 32), ehi = (uint32_t)((uint64_t)p.ea >> 32);
    uint32_t s0, s1, ev, to = 0, so = 12 * STG;
    auto tl_ = [&]() { lds64(s0, s1, a_s + to); asm volatile("ld.shared.u32 %0, [%1]; add.u32 %1, %1, 64;" : "=&r"(ev), "+r"(a_e) :: "memory"); to += 32; };
#define CPQ(LH, x, k, off) "dp2a." LH ".u32.u32 lo, " x ", 0x80000080, " k "; mov.b64 a, {lo, %7}; @p cp.async.cg.shared.global [%0+" #off "], [a], 16;\n"
    uint64_t pe; asm volatile("createpolicy.fractional.L2::evict_normal.b64 %0, 1.0;" : "=l"(pe));
    uint32_t one = __shfl_sync(~0u, lane, 1);
#define CPE "or.b32 lo, %10, %11; mov.b64 a, {lo, %12}; @p cp.async.cg.shared.global.L2::cache_hint [%0+512], [a], 16, %13;\n"
#define CPA(BODY) asm volatile("{.reg .b32 lo; .reg .b64 a; .reg .pred p; setp.le.u32 p, %8, %9;\n" BODY "}" \
      :: "r"(so * one + dst0), "r"(s0), "r"(s1), "r"(k0), "r"(k1), "r"(k2), "r"(k3), "r"(qhi), "r"(to), "r"(rem), "r"(ev), "r"(ke), "r"(ehi), "l"(pe) : "memory")
#define CPQ4 CPQ("lo", "%1", "%3", 0) CPQ("hi", "%1", "%4", 128) CPQ("lo", "%2", "%5", 256) CPQ("hi", "%2", "%6", 384) "cp.async.commit_group;"
    auto issue = [&]() { CPA(CPE CPQ4); so = so == (NST - 1) * 12 * STG ? 0 : so + 12 * STG; };
    const int g = lane >> 2, qd = lane & 3;
    const uint32_t sw = ((lane >> 4) ^ (lane & 7)) << 4, fr = (lane & 15) * 128 + sw;
    uint32_t qa0 = ring + (g & 3) * 640 + qd * 128 + sw, qa1 = qa0 ^ 32, qa2 = qa0 ^ 64, qa3 = qa0 ^ 96;
    uint32_t eadr = ring + 512 + (g & 3) * 640 + qd * 32 + ((((lane >> 4) ^ g) & 1) << 4);
    uint32_t oh0 = g == 2 * qd ? 0x3C00u : g == 2 * qd + 1 ? 0x3C000000u : 0u, oh1 = oh0;
    uint32_t a_g = sb + OFF_GP + wid * 256 + lane * 2;
    asm volatile("shfl.sync.idx.b32 %0, %0, %1, 31, -1;" : "+r"(oh1) : "r"(lane));
    uint32_t w3[16], wv[8], bp[16], sum[8], Y[16], M[16], own, ownp, dpk, tl[16], th[16];
    float pacc = 0.f;
    auto wload = [&]() {
#pragma unroll
      for (int j = 0; j < 4; j++) ldsm4t(w3 + 4 * j, (sb + OFF_W3 + fr) ^ (j << 5));
      lds128(wv, sb + OFF_WX + (a_g & 6) * 16); lds128(wv + 4, sb + OFF_WX + 16 + (a_g & 6) * 16);
    };
    auto hload = [&](uint32_t (&hf)[16], uint32_t nd) {
      const uint32_t hrow = sb + OFF_H + nd * 128 + (((nd & 7) << 4) ^ ((a_g >> 1) & 16));
#pragma unroll
      for (int j = 0; j < 4; j++) ldsm4(hf + 4 * j, hrow ^ (j << 5));
      return hrow;
    };
    { uint32_t wd[8]; const uint32_t a = sb + OFF_WD + (lane & 7) * 128 + ((((lane >> 3) ^ lane) & 7) << 4);
      ldsm4t(wd, a); ldsm4t(wd + 4, a ^ 64);
#pragma unroll
      for (int j = 0; j < 8; j++) { bp[2 * j] = wd[j]; bp[2 * j + 1] = pa[j]; } }
    own = lds16(a_g) * 0x10001u;
    wload();
    if (__shfl_sync(~0u, lds32(sb + OFF_MISC + 8), 0)) rem = 0;
    auto resolve = [&](auto NBK, uint32_t o) {
      constexpr int NB = decltype(NBK)::value;
      uint32_t id[NB], c0[NB], c1[NB]; const uint32_t a = base * 32 + o + lane * 4;
#pragma unroll
      for (int i = 0; i < NB; i++) { id[i] = lds32(sb + OFF_TS + a + i * 128); if (o + lane * 4 + i * 128 >= rem) id[i] = XPAD * 0x10001u; }
      uint32_t st = 0;
#pragma unroll
      for (int i = 0; i < NB; i++) { c0[i] = lds32(sb + OFF_XB + (id[i] & 0xFFFF)); c1[i] = lds32(sb + OFF_XB + (id[i] >> 16)); }
#pragma unroll
      for (int i = 0; i < NB; i++) st |= (c0[i] ^ tag) | (c1[i] ^ tag);
      for (int spin = 0; __any_sync(~0u, st >> 30); spin++) {
        st = 0; trap_if(spin > 2000000);
#pragma unroll
        for (int i = 0; i < NB; i++) {
          asm volatile("{.reg .pred p, q; setp.lt.u32 p, %4, %6; setp.lt.u32 q, %5, %6; @p ld.relaxed.gpu.global.u32 %0, [%2]; @q ld.relaxed.gpu.global.u32 %1, [%3];}"
            : "+r"(c0[i]), "+r"(c1[i]) : "l"((const char*)p.xb + cta * XPAD + (id[i] & 0xFFFF)), "l"((const char*)p.xb + cta * XPAD + (id[i] >> 16)), "r"(id[i] & 0xFFFF), "r"(id[i] >> 16), "n"(XPAD) : "memory");
          st |= (c0[i] ^ tag) | (c1[i] ^ tag); }
      }
#pragma unroll
      for (int i = 0; i < NB; i++) { const uint32_t j0 = (id[i] >> 8) & 255, j1 = id[i] >> 24;
        asm volatile("{.reg .pred p, q, r; setp.lt.u32 p, %5, %9; setp.lt.u32 q, %6, %9; setp.lt.u32 r, %7, %8;\n"
          "@p st.shared.u32 [%0], %2; @q st.shared.u32 [%0+4], %3; @r st.shared.u32 [%1], %4;}"
          :: "r"(sb + OFF_TE + 2 * a + i * 256), "r"(sb + OFF_TS + a + i * 128), "r"(mad16(c0[i], 0x2000u, eb0 + j0 * p.EPC * 32)), "r"(mad16(c1[i], 0x2000u, eb0 + j1 * p.EPC * 32)),
             "r"(__byte_perm(c0[i], c1[i], 0x5410)), "r"(j0), "r"(j1), "r"(o + lane * 4 + i * 128), "r"(rem), "n"(G) : "memory"); }
    };
    bar_sync(2, 384);
    if (wid == 0) STAMP(27);
    mbar_wait(sb + BAR_HB);
    if (wid == 0) STAMP(22);
#pragma unroll 1
    for (uint32_t o = 0, go = 0; go < 32 * NST; o += 128 * RNB) {
      if (o < rem) { resolve(IC<RNB>(), o);
        asm volatile("{.reg .pred p; mbarrier.test_wait.parity.shared::cta.b64 p, [%1], 0; vote.sync.all.pred p, p, -1; selp.u32 %0, %2, 0, p;}" : "=r"(go) : "r"(sb + BAR_QP), "n"(32 * NST - 32) : "memory"); }
      else { bar_sync(8, 384); mbar_wait(sb + BAR_QP); go = 32 * NST; if (wid == 0) STAMP(24); }
      __syncwarp();
#pragma unroll 1
      while (to < go) { tl_(); issue(); if (to == 32) STAMP(13); }
    }
    bad = __shfl_sync(~0u, lds32(sb + OFF_MISC + 8), 0);
   if (!bad) {
#pragma unroll
    for (int j = 0; j < 4; j++) stsm4((p2 + fr) ^ (j << 5), pq[4 * j], pq[4 * j + 1], pq[4 * j + 2], pq[4 * j + 3]);
    auto body = [&](auto MODE) {
      constexpr int mode = decltype(MODE)::value;
      uint32_t T[16], ef[4], q0, q1, x0, x1, x2; float e0_, e1_, cs[4];
      auto mu = [&](int j) {
#pragma unroll
        for (int i = 2 * j; i < 2 * j + 2; i++) asm volatile("{.reg .b16 l, h; mov.b32 {l, h}, %2; tanh.approx.f16 l, l; tanh.approx.f16 h, h; cvt.u32.u16 %0, l; cvt.u32.u16 %1, h;}" : "=r"(tl[i]), "=r"(th[i]) : "r"(Y[i])); };
      auto fi = [&](int j) {
#pragma unroll
        for (int i = 2 * j; i < 2 * j + 2; i++) asm volatile("{.reg .b32 t; prmt.b32 t, %2, %3, 0x5410; fma.rn.f16x2 %0, %1, t, %1;}" : "=r"(M[i]) : "r"(Y[i]), "r"(tl[i]), "r"(th[i])); };
      auto ad = [&](int j) { asm volatile("add.rn.f16x2 %0, %0, %1; add.rn.f16x2 %0, %0, %2;" : "+r"(sum[j]) : "r"(M[2 * j]), "r"(M[2 * j + 1])); };
      auto he = [&](int j) { asm volatile("mma.sync.aligned.m16n8k16.row.col.f16.f16.f16.f16 {%0,%1}, {%2,%3,%4,%5}, {%6,%7}, {%0,%1};" : "+r"(T[2 * j]), "+r"(T[2 * j + 1]) : "r"(ef[0]), "r"(ef[1]), "r"(ef[2]), "r"(ef[3]), "r"(w3[2 * j]), "r"(w3[2 * j + 1])); };
      auto hs = [&](int j) { asm volatile("mma.sync.aligned.m16n8k16.row.col.f16.f16.f16.f16 {%0,%1}, {%2,%3,%4,%5}, {%6,%7}, {%8,%9};" : "=r"(Y[2 * j]), "=r"(Y[2 * j + 1]) : "r"(q0), "r"(q1), "r"(oh0), "r"(oh1), "r"(bp[2 * j]), "r"(bp[2 * j + 1]), "r"(T[2 * j]), "r"(T[2 * j + 1])); };
      auto hc = [&](int j) {
        if (j) asm volatile("mma.sync.aligned.m16n8k16.row.col.f32.f16.f16.f32 {%0,%1,%2,%3}, {%4,%5,%6,%7}, {%8,%9}, {%0,%1,%2,%3};" : "+f"(cs[0]), "+f"(cs[1]), "+f"(cs[2]), "+f"(cs[3]) : "r"(M[4 * j]), "r"(M[4 * j + 1]), "r"(M[4 * j + 2]), "r"(M[4 * j + 3]), "r"(wv[2 * j]), "r"(wv[2 * j + 1]));
        else asm volatile("mma.sync.aligned.m16n8k16.row.col.f32.f16.f16.f32 {%0,%1,%2,%3}, {%4,%5,%6,%7}, {%8,%9}, {%10,%10,%10,%10};" : "=f"(cs[0]), "=f"(cs[1]), "=f"(cs[2]), "=f"(cs[3]) : "r"(M[0]), "r"(M[1]), "r"(M[2]), "r"(M[3]), "r"(wv[0]), "r"(wv[1]), "f"(0.f)); };
      auto cv = [&](int i) { asm volatile("{.reg .b32 a, b; shl.b32 a, %0, 16; and.b32 b, %0, 0xFFFF0000; cvt.rn.f16x2.f32 %0, b, a;}" : "+r"(ef[i])); };
      auto un = [&]() { asm volatile("shl.b32 %0, %2, 16; and.b32 %1, %2, 0xFFFF0000;" : "=&f"(e0_), "=&f"(e1_) : "r"(dpk)); };
      auto ex0 = [&]() { asm volatile("prmt.b32 %0, %3, %4, 0x6420; prmt.b32 %1, %5, %6, 0x6420; prmt.b32 %2, %7, %8, 0x6420;" : "=&r"(x0), "=&r"(x1), "=&r"(x2) : "r"(T[0]), "r"(T[1]), "r"(T[2]), "r"(T[3]), "r"(T[4]), "r"(T[5])); };
      auto ex1 = [&]() { asm volatile("{.reg .b32 a, b; shl.b32 a, %2, 3; shl.b32 b, %3, 6; lop3.b32 a, %1, a, 0x38383838, 0xD8; lop3.b32 a, a, b, 0xC0C0C0C0, 0xD8; sub.rn.bf16x2 %0, %4, a;}" : "=r"(dpk) : "r"(x0), "r"(x1), "r"(x2), "r"(own)); };
      auto ex2 = [&]() { asm volatile("{.reg .b32 a, b, d, u; .reg .b16 l, h; shl.b32 a, %2, 16; and.b32 b, %2, 0xFFFF0000; cvt.rn.f16x2.f32 d, b, a; mul.rn.f16x2 %0, d, d; mov.b32 {l, h}, d; mov.b32 u, {h, h}; mul.rn.f16x2 %1, u, u;}" : "=&r"(q0), "=&r"(q1) : "r"(dpk)); };
      auto pf = [&]() { asm volatile("fma.rn.f32 %0, %1, %2, %0; fma.rn.f32 %0, %3, %4, %0;" : "+f"(pacc) : "f"(cs[0]), "f"(e0_), "f"(cs[2]), "f"(e1_)); };
      if (mode == 2) { LASTSEQ return; }
      asm volatile("cp.async.wait_group %0;" :: "n"(NST - 1) : "memory");
      __syncwarp();
      if (mode == 1) STAMP(8);
      ldsm4(ef, eadr + so); ldsm4(T, qa0 + so); ldsm4(T + 4, qa1 + so); ldsm4(T + 8, qa2 + so); ldsm4(T + 12, qa3 + so);
      if (mode == 1) {
        tl_(); issue();
        cv(0); cv(1); cv(2); cv(3); ex0(); ex1(); ex2();
#pragma unroll
        for (int j = 0; j < 8; j++) { he(j); hs(j); }
        FIRSTSEQ return;
      }
      BODYSEQ
    };
#pragma unroll
    for (int j = 0; j < 8; j++) sum[j] = 0;
    body(IC<1>());
    int cnt = (lens & 255) - 1;
    auto pload = [&](uint32_t (&x)[8], uint32_t o) { const uint32_t l = a_g >> 1, a = p2 + o + (l & 7) * 128 + (((((l >> 3) & 3) ^ l) & 7) << 4); ldsm4t(x, a); ldsm4t(x + 4, a ^ 64); };
    auto flush = [&]() {
      asm volatile("{.reg .pred p; setp.ne.u32 p, %2, 6; @p st.shared.u16 [%0+-64], %1;}" :: "r"(a_g), "h"((uint16_t)pack_bf16(bf_hi(ownp) + pacc, 0.f)), "r"(a_g & 6) : "memory");
      chk = fmaf(pacc, 0.f, chk); pacc = 0.f; };
    constexpr uint64_t b1 = DHI | ((sb + OFF_W) >> 4), b2_ = b1 + 512;
    auto mma_h = [&](float (&acc)[32], uint32_t (&hf)[16]) {
      rs64b<0>(acc, hf[0], hf[1], hf[2], hf[3], b1); rs64b<1>(acc, hf[4], hf[5], hf[6], hf[7], b1 + 128); rs64b<1>(acc, hf[8], hf[9], hf[10], hf[11], b1 + 256); rs64b<1>(acc, hf[12], hf[13], hf[14], hf[15], b1 + 384); };
    auto mma_m = [&](float (&acc)[32]) {
      rs64h<1>(acc, sp[0], sum[0], sp[1], sum[1], b2_); rs64h<1>(acc, sp[2], sum[2], sp[3], sum[3], b2_ + 128); rs64h<1>(acc, sp[4], sum[4], sp[5], sum[5], b2_ + 256); rs64h<1>(acc, sp[6], sum[6], sp[7], sum[7], b2_ + 384);
      wg_commit(); wg_wait0(); fence_regs(acc);
      STAMP(10);
      chk = fmaf(acc[0], 0.f, fmaf(acc[2], 0.f, chk)); };
    auto roff = [&](uint32_t nd, int r) { return __shfl_sync(~0u, nd, ((a_g >> 3) & 7) + 8 * r) * 128 + (a_g & 6) * 8; };
    auto radr = [&](uint32_t o, int k) { return sb + OFF_H + (o ^ ((o >> 3) & 0x70) ^ ((k >> 1) << 6)); };
    auto fin = [&](float (&acc)[32], uint32_t* x, int k) {
#pragma unroll
      for (int i = 0; i < 4; i++) { const int c = 16 * (k >> 1) + 4 * i + 2 * (k & 1); x[i] = u2(__hadd2(b2(x[i]), b2(pack_bf16(silu_h(acc[c]), silu_h(acc[c + 1]))))); } };
#pragma unroll 1
    for (int t = 0;; t++) {
#pragma unroll 1
      for (; cnt > 0; cnt--) { body(IC<0>());
      }
      if (!(t & 1)) {
        ownp = own; a_g += 64;
        if (t == 6) break;
        pe = pol_first();
        own = lds16(a_g) * 0x10001u;
        if (t == 2) { const uint32_t a = ((a_g & 16) ? p2 : sb + OFF_WD) + ((a_g << 6) & 0x380) + (qa0 & 0x70);
#pragma unroll
          for (int j = 0; j < 4; j++) ldsm4t(bp + 4 * j, a ^ (j << 5));
        } else {
#pragma unroll
          for (int j = 0; j < 8; j++) bp[2 * j + 1] = sp[j];
        }
        lens >>= 8; cnt = 1;
        continue;
      }
      cnt = (lens & 255) - 1;
      flush();
      if (t == 3) {
        uint32_t x[8];
        pload(x, 1024);
        __syncwarp();
#pragma unroll
        for (int j = 0; j < 4; j++) stsm4((p2 + ((a_g << 6) & 0x780) + (qa0 & 0x70)) ^ (j << 5), sp[2 * j], sum[2 * j], sp[2 * j + 1], sum[2 * j + 1]);
#pragma unroll
        for (int j = 0; j < 8; j++) sum[j] = x[j];
        __syncwarp();
        mbar_arrive(sb + BAR_M + (wid >> 2) * 8, (a_g & 62) == 0);
      }
#pragma unroll
      for (int j = 0; j < 8; j++) { sp[j] = sum[j]; asm volatile("mov.b32 %0, 0;" : "=r"(sum[j])); }
    }
    {
      uint32_t hf[16], v[16]; float acc[32];
      const uint32_t nd = lds16(sb + OFF_GP + wid * 256 + (lane & 15) * 8 + 134), o[2] = {roff(nd, 0), roff(nd, 1)};
      hload(hf, nd);
#pragma unroll
      for (int k = 0; k < 4; k++) lds128(v + 4 * k, radr(o[k & 1], k));
      mbar_wait(sb + BAR_WH);
      wg_fence(); mma_h(acc, hf); wg_commit();
      body(IC<2>());
      STAMP(9);
      flush();
      __syncwarp();
      mbar_arrive(sb + BAR_X, lane == 0);
      wg_fence();
      mma_m(acc);
#pragma unroll
      for (int k = 0; k < 4; k++) { fin(acc, v + 4 * k, k);
        asm volatile("{.reg .pred p; setp.lt.u32 p, %5, %6; @p st.global.v4.b32 [%0], {%1,%2,%3,%4};}" :: "l"((const char*)p.out + (size_t)node0 * 128 + o[k & 1] + (k >> 1) * 64), "r"(v[4 * k]), "r"(v[4 * k + 1]), "r"(v[4 * k + 2]), "r"(v[4 * k + 3]), "r"(o[k & 1]), "r"(nloc * 128) : "memory"); }
    }
    asm volatile("{.reg .pred p, q; setp.neu.f32 p, %1, 0f00000000; setp.ne.or.u32 p, %2, 0, p; bar.red.or.pred q, 5, 512, p; selp.u32 %0, 1, 0, q;}" : "=r"(bad) : "f"(chk), "r"(lds32(sb + OFF_MISC + 12)) : "memory");
    STAMP(11);
   } else { asm volatile("cp.async.wait_all;" ::: "memory"); bar_sync(5, 384); }
  }
  if (bad) slow_path(p, wid, lane, node0, nloc);
}

}

typedef CUresult (*EncodeFn)(CUtensorMap*, CUtensorMapDataType, cuuint32_t, void*, const cuuint64_t*, const cuuint64_t*, const cuuint32_t*, const cuuint32_t*,
                             CUtensorMapInterleave, CUtensorMapSwizzle, CUtensorMapL2promotion, CUtensorMapFloatOOBfill);

extern "C" void kernel_launch(void* const* d_in, const int* in_sizes, int n_in, void* d_out, int out_size) {
  Params p; Maps maps;
  p.h = (const uint4*)d_in[0]; p.pos = (const uint16_t*)d_in[1]; p.ea = (const uint4*)d_in[2];
  p.src = (const int*)d_in[3]; p.dst = (const int*)d_in[4];
  p.we = (const uint16_t*)d_in[5]; p.wx = (const uint16_t*)d_in[6]; p.wh = (const uint16_t*)d_in[7];
  p.out = (uint16_t*)d_out;
  p.N = in_sizes[0] / 64; p.E = in_sizes[3];
  p.EPC = ((p.E + G * 4 - 1) / (G * 4)) * 4;
  p.magic = (uint32_t)(((uint64_t)G << 24) / (uint64_t)p.N);
  p.inv = (1ull << 56) / p.magic;
  const uint64_t ea0 = (uint64_t)d_in[2], ea1 = ea0 + (uint64_t)p.E * 32 - 1;
  p.force_slow = ((ea0 >> 32) != (ea1 >> 32)) || (ea0 & 31) || (p.E & 3);
  void* qp = nullptr;
  cudaGetSymbolAddress(&qp, g_q);
  p.q = (char*)qp;
  if (((uint64_t)p.q >> 32) != (((uint64_t)p.q + QBYTES) >> 32)) p.q += QBYTES;
  cudaGetSymbolAddress((void**)&p.sync, g_sync); cudaGetSymbolAddress((void**)&p.xe, g_xe);
  cudaGetSymbolAddress((void**)&p.xa, g_xa); cudaGetSymbolAddress((void**)&p.xb, g_xb);
  const int df[10] = {34, 120, 900, 3072, 0, 17, 0xff2, 0xD5C4E6};
  for (int i = 0; i < 10; i++) p.tune[i] = df[i];
  p.qcode = 0x890145a6273bull;
  p.ctam = p.tune[5];
  void* fn = nullptr; cudaDriverEntryPointQueryResult qr;
  cudaGetDriverEntryPoint("cuTensorMapEncodeTiled", &fn, cudaEnableDefault, &qr);
  auto mk = [&](CUtensorMap* tm, void* base, int rows, int box = 64) {
    const cuuint64_t dim[2] = {64, (cuuint64_t)rows}, str[1] = {128}; const cuuint32_t bx[2] = {64, (cuuint32_t)box}, es[2] = {1, 1};
    ((EncodeFn)fn)(tm, CU_TENSOR_MAP_DATA_TYPE_BFLOAT16, 2, base, dim, str, bx, es, CU_TENSOR_MAP_INTERLEAVE_NONE, CU_TENSOR_MAP_SWIZZLE_128B,
                   CU_TENSOR_MAP_L2_PROMOTION_NONE, CU_TENSOR_MAP_FLOAT_OOB_FILL_NONE);
  };
  mk(&maps.m[TM_H / 128], d_in[0], p.N); mk(&maps.m[TM_WE / 128], d_in[5], 145); mk(&maps.m[TM_WH / 128], d_in[7], 128); mk(&maps.m[TM_Q / 128], p.q, p.N, 16);
  for (int k = 0; k < 2; k++) {
    void* xp = (void*)(k ? p.xb : p.xa);
    const cuuint64_t dim[2] = {(cuuint64_t)G * 64, (cuuint64_t)G}, str[1] = {(cuuint64_t)G * (128 << k)}; const cuuint32_t bx[2] = {64, (cuuint32_t)(k ? BROWS : G)}, es[2] = {1, 1};
    ((EncodeFn)fn)(&maps.m[TM_XA / 128 + k], k ? CU_TENSOR_MAP_DATA_TYPE_UINT32 : CU_TENSOR_MAP_DATA_TYPE_UINT16, 2, xp, dim, str, bx, es, CU_TENSOR_MAP_INTERLEAVE_NONE,
                   CU_TENSOR_MAP_SWIZZLE_NONE, CU_TENSOR_MAP_L2_PROMOTION_NONE, CU_TENSOR_MAP_FLOAT_OOB_FILL_NONE);
  }
  cudaFuncSetAttribute(egnn_kernel, cudaFuncAttributeMaxDynamicSharedMemorySize, SMEM);
  egnn_kernel<<<G, NTHR, SMEM>>>(p, maps);
}
```

```cpp
#include <cuda_runtime.h>
#include <cuda_bf16.h>
#include <cuda_fp16.h>
#include <cuda.h>
#include <stdint.h>
#pragma nv_diag_suppress 549

#define PFN p.tune[0]
#define PFB p.tune[3]
#define PFNS p.tune[1]
#define PFE p.tune[8]
#define BDEL p.tune[2]
#define DEFNS p.tune[4]
#define CTAM p.ctam
#define QREV p.tune[6]
#define UORD p.tune[7]
#define QCODE p.qcode
#define FIRSTSEQ mu(0); mu(1); fi(0); mu(2); fi(1);
#define BODYSEQ hc(0); fi(2); tl_(); mu(3); un(); ad(1); ad(0); cv(0); mu(4); cv(2); fi(3); cv(1); ex0(); ex1(); cv(3); he(0); fi(4); he(1); \
  mu(5); hc(1); mu(6); fi(5); he(2); ad(2); ex2(); hs(0); ad(3); hs(1); fi(6); mu(7); issue(); hc(2); he(3); hs(3); fi(7); mu(0); \
  hs(2); he(4); he(5); ad(5); ad(4); hs(4); fi(0); he(6); mu(1); hc(3); he(7); fi(1); ad(6); hs(7); hs(5); ad(7); hs(6); mu(2); \
  pf();
#define LASTSEQ hc(0); fi(2); mu(3); un(); ad(1); ad(0); mu(4); fi(3); fi(4); mu(5); hc(1); mu(6); fi(5); ad(2); ad(3); fi(6); mu(7); hc(2); \
  fi(7); ad(5); ad(4); hc(3); ad(6); ad(7); pf();
namespace {

constexpr int G = 132;
constexpr int NTHR = 512, NWK = 352, NCH = 5;
constexpr int NST = 3, STG = 2560;
constexpr int BROWS = 44, RNB = 2, PADM = 33;
constexpr int SCAP = 448;

constexpr int OFF_H = 0;
constexpr int OFF_W = 49152;
constexpr int OFF_WD = OFF_W + 16384;
constexpr int OFF_W3 = OFF_WD + 1024;
constexpr int OFF_P2 = OFF_W3 + 2048;
constexpr int OFF_RING = OFF_P2 + 24576;
constexpr int OFF_TE = OFF_RING + 12 * NST * STG;
constexpr int OFF_TS = OFF_TE + SCAP * 64;
constexpr int OFF_INV = OFF_TS - 768;
constexpr int OFF_GP = OFF_TS + SCAP * 32;
constexpr int OFF_WX = OFF_GP + 3072;
constexpr int OFF_LEN = OFF_WX + 128;
constexpr int OFF_MISC = OFF_LEN + 128;
constexpr int OFF_BAR = OFF_MISC + 48;
constexpr int SMEM = OFF_BAR + 256;
static_assert(SMEM <= 232448, "smem");
constexpr uint32_t sb = 1024;
constexpr int OFF_SRCI = OFF_TE;
constexpr int OFF_SB = OFF_RING, OFF_SA = OFF_SB + 34816, OFF_AX = OFF_SA + 32768, OFF_DST = OFF_H + 24576;
constexpr int OFF_WS = OFF_AX + 17408;
constexpr int OFF_BC = OFF_WS + 2304;
constexpr int OFF_CNT = OFF_P2;
constexpr int OFF_DH = OFF_CNT + 2176;
constexpr int OFF_POS = OFF_DH + 128;
constexpr int OFF_EXT = OFF_POS + 3072;
constexpr int OFF_XB = OFF_EXT + 1024, XPAD = G * 256;
static_assert(OFF_XB + XPAD + 1028 <= OFF_RING + 12 * STG && OFF_XB % 128 == 0 && OFF_BC + 544 <= OFF_TE && OFF_P2 % 1024 == 0 && OFF_SA % 1024 == 0 && SCAP * 64 >= 24576, "staging");
constexpr int BAR_DST = OFF_BAR, BAR_SRC = BAR_DST + 40, BAR_T = BAR_SRC + 24, BAR_W = BAR_T + 48, BAR_PS = BAR_W + 8, BAR_AW = BAR_PS + 8,
              BAR_QP = BAR_AW + 8, BAR_QR = BAR_QP + 8, BAR_HA = BAR_QR + 8, BAR_EP = BAR_HA + 8, BAR_AX = BAR_EP + 8, BAR_AI = BAR_AX + 8, BAR_HB = BAR_AI + 8, BAR_U = BAR_HB + 8, BAR_WH = BAR_U + 8, BAR_M = BAR_WH + 8, BAR_X = BAR_M + 24, BAR_END = BAR_X + 8;
static_assert(BAR_END <= OFF_BAR + 256, "barriers");
constexpr uint32_t QBYTES = 8u << 20;

__device__ __align__(256) uint4 g_xa[G * G * 8];
__device__ __align__(256) uint4 g_xb[G * G * 16];
__device__ __align__(256) uint2 g_xe[G * G * 32];
__device__ __align__(256) uint4 g_q[2 * QBYTES / 16];
__device__ __align__(256) uint32_t g_sync[8];
#define STAMP(k)

struct Maps { CUtensorMap m[6]; };
constexpr int TM_H = 0, TM_WE = 128, TM_WH = 256, TM_Q = 384, TM_XA = 512, TM_XB = 640;
struct Params {
  const int* dst; uint32_t* sync; int E, EPC, N, ctam; unsigned long long inv; uint32_t magic; int force_slow;
  const int* src; const uint16_t* pos; const uint4* ea; const uint16_t* we; const uint16_t* wx; char* q;
  const uint4* xa; const uint4* xb; uint2* xe; uint16_t* out; const uint4* h; const uint16_t* wh;
  int tune[10]; unsigned long long qcode;
};
template<int V> struct IC { static constexpr int value = V; };

#define R32(d) "+f"(d[0]),"+f"(d[1]),"+f"(d[2]),"+f"(d[3]),"+f"(d[4]),"+f"(d[5]),"+f"(d[6]),"+f"(d[7]),"+f"(d[8]),"+f"(d[9]),"+f"(d[10]),"+f"(d[11]),"+f"(d[12]),"+f"(d[13]),"+f"(d[14]),"+f"(d[15]),"+f"(d[16]),"+f"(d[17]),"+f"(d[18]),"+f"(d[19]),"+f"(d[20]),"+f"(d[21]),"+f"(d[22]),"+f"(d[23]),"+f"(d[24]),"+f"(d[25]),"+f"(d[26]),"+f"(d[27]),"+f"(d[28]),"+f"(d[29]),"+f"(d[30]),"+f"(d[31])
#define S32 "{%0,%1,%2,%3,%4,%5,%6,%7,%8,%9,%10,%11,%12,%13,%14,%15,%16,%17,%18,%19,%20,%21,%22,%23,%24,%25,%26,%27,%28,%29,%30,%31}"
#define DI __device__ __forceinline__

constexpr uint64_t DHI = ((uint64_t)(1024 >> 4) << 32) | (1ull << 62);
template<int SD> DI void rs64b(float (&d)[32], uint32_t a0, uint32_t a1, uint32_t a2, uint32_t a3, uint64_t db) {
  asm volatile("wgmma.mma_async.sync.aligned.m64n64k16.f32.bf16.bf16 " S32 ", {%32,%33,%34,%35}, %36, %37, 1, 1, 1;" : R32(d) : "r"(a0), "r"(a1), "r"(a2), "r"(a3), "l"(db), "n"(SD)); }
template<int SD> DI void rs64h(float (&d)[32], uint32_t a0, uint32_t a1, uint32_t a2, uint32_t a3, uint64_t db) {
  asm volatile("wgmma.mma_async.sync.aligned.m64n64k16.f32.f16.f16 " S32 ", {%32,%33,%34,%35}, %36, %37, 1, 1, 1;" : R32(d) : "r"(a0), "r"(a1), "r"(a2), "r"(a3), "l"(db), "n"(SD)); }
template<int SD> DI void ss64(float (&d)[32], uint64_t da, uint64_t db) {
  asm volatile("wgmma.mma_async.sync.aligned.m64n64k16.f32.bf16.bf16 " S32 ", %32, %33, %34, 1, 1, 0, 1;" : R32(d) : "l"(da), "l"(db), "n"(SD)); }
#define R16(d) "+f"(d[0]),"+f"(d[1]),"+f"(d[2]),"+f"(d[3]),"+f"(d[4]),"+f"(d[5]),"+f"(d[6]),"+f"(d[7]),"+f"(d[8]),"+f"(d[9]),"+f"(d[10]),"+f"(d[11]),"+f"(d[12]),"+f"(d[13]),"+f"(d[14]),"+f"(d[15])
#define S16 "{%0,%1,%2,%3,%4,%5,%6,%7,%8,%9,%10,%11,%12,%13,%14,%15}"
template<int SD> DI void rs32b(float (&d)[16], const uint32_t* a, uint64_t db) {
  asm volatile("wgmma.mma_async.sync.aligned.m64n32k16.f32.bf16.bf16 " S16 ", {%16,%17,%18,%19}, %20, %21, 1, 1, 1;" : R16(d) : "r"(a[0]), "r"(a[1]), "r"(a[2]), "r"(a[3]), "l"(db), "n"(SD)); }
DI void rs32h(float (&d)[16], const uint32_t* a, uint64_t db) {
  asm volatile("wgmma.mma_async.sync.aligned.m64n32k16.f32.f16.f16 " S16 ", {%16,%17,%18,%19}, %20, 1, 1, 1, 1;" : R16(d) : "r"(a[0]), "r"(a[1]), "r"(a[2]), "r"(a[3]), "l"(db)); }
DI void fence_regs(float (&d)[16]) { asm volatile("" : R16(d) :: "memory"); }
DI void trap_if(bool c) { asm volatile("{.reg .pred p; setp.eq.u32 p, %0, 0; @p bra.uni LT_%=; trap; LT_%=:}" :: "r"((uint32_t)c)); }
DI void wg_fence() { asm volatile("wgmma.fence.sync.aligned;" ::: "memory"); }
DI void wg_commit() { asm volatile("wgmma.commit_group.sync.aligned;" ::: "memory"); }
DI void wg_wait0() { asm volatile("wgmma.wait_group.sync.aligned 0;" ::: "memory"); }
DI void fence_regs(float (&d)[32]) { asm volatile("" : R32(d) :: "memory"); }
DI void proxy_fence() { asm volatile("fence.proxy.async.shared::cta;" ::: "memory"); }
DI uint64_t pol_first() { uint64_t r; asm("createpolicy.fractional.L2::evict_first.b64 %0, 1.0;" : "=l"(r)); return r; }
DI float tanh_ap(float x) { float y; asm("tanh.approx.f32 %0, %1;" : "=f"(y) : "f"(x)); return y; }
DI float silu_h(float y) { return fmaf(y, tanh_ap(y), y); }
DI uint32_t pack_bf16(float lo, float hi) { uint32_t r; asm("cvt.rn.bf16x2.f32 %0, %1, %2;" : "=r"(r) : "f"(hi), "f"(lo)); return r; }
DI uint32_t pack_f16(float lo, float hi) { uint32_t r; asm("cvt.rn.f16x2.f32 %0, %1, %2;" : "=r"(r) : "f"(hi), "f"(lo)); return r; }
DI float bf_lo(uint32_t v) { return __uint_as_float(v << 16); }
DI float bf_hi(uint32_t v) { return __uint_as_float(v & 0xFFFF0000u); }
DI uint32_t b2h(uint32_t v, float s) { return pack_f16(s * bf_lo(v), s * bf_hi(v)); }
DI void mbar_wait(uint32_t bar, uint32_t parity = 0) {
  asm volatile("{.reg .pred p, q; .reg .u32 c; mov.u32 c, 0;\n"
    "LW_%=: mbarrier.try_wait.parity.shared::cta.b64 p, [%0], %1;\n add.u32 c, c, 1; setp.lt.and.u32 q, c, 0x200000, !p;\n @q bra.uni LW_%=;}" :: "r"(bar), "r"(parity) : "memory");
}
DI void mbar_arrive(uint32_t bar, int p = 1) { asm volatile("{.reg .pred p; setp.ne.b32 p, %1, 0; @p mbarrier.arrive.shared::cta.b64 _, [%0];}" :: "r"(bar), "r"(p) : "memory"); }
DI void bar_sync(int id, int n) { asm volatile("bar.sync %0, %1;" :: "r"(id), "r"(n) : "memory"); }
DI void bar_arrive(int id, int n) { asm volatile("bar.arrive %0, %1;" :: "r"(id), "r"(n) : "memory"); }
DI __nv_bfloat162 b2(uint32_t v) { return *(__nv_bfloat162*)&v; }
DI uint32_t u2(__nv_bfloat162 v) { return *(uint32_t*)&v; }
DI uint32_t hsq(uint32_t v) { return u2(__hmul2(b2(v), b2(v))); }
DI uint32_t hsub(uint32_t a, uint32_t b) { return u2(__hsub2(b2(a), b2(b))); }
DI uint32_t hhalf(uint32_t v) { return u2(__hmul2(b2(v), __floats2bfloat162_rn(0.5f, 0.5f))); }
DI uint32_t mag2(uint32_t m, uint32_t v) { return __vmaxu2(m, v & 0x7FFF7FFFu); }
DI uint32_t hmag(uint32_t m, uint32_t v) { const __half2 r = __hmax2(*(const __half2*)&m, __habs2(*(const __half2*)&v)); return *(const uint32_t*)&r; }
DI uint32_t magr(uint32_t m) { return max(m & 0xFFFF, m >> 16); }
DI void sts128(uint32_t a, uint32_t x, uint32_t y, uint32_t z, uint32_t w) { asm volatile("st.shared.v4.u32 [%0], {%1,%2,%3,%4};" :: "r"(a), "r"(x), "r"(y), "r"(z), "r"(w) : "memory"); }
DI void sts64(uint32_t a, uint32_t x, uint32_t y) { asm volatile("st.shared.v2.u32 [%0], {%1,%2};" :: "r"(a), "r"(x), "r"(y) : "memory"); }
DI void sts32(uint32_t a, uint32_t x) { asm volatile("st.shared.u32 [%0], %1;" :: "r"(a), "r"(x) : "memory"); }
DI void sts16(uint32_t a, uint32_t x) { asm volatile("st.shared.u16 [%0], %1;" :: "r"(a), "h"((uint16_t)x) : "memory"); }
DI void lds128(uint32_t* v, uint32_t a) { asm volatile("ld.shared.v4.u32 {%0, %1, %2, %3}, [%4];" : "=r"(v[0]), "=r"(v[1]), "=r"(v[2]), "=r"(v[3]) : "r"(a) : "memory"); }
DI void lds64(uint32_t& x, uint32_t& y, uint32_t a) { asm volatile("ld.shared.v2.u32 {%0, %1}, [%2];" : "=r"(x), "=r"(y) : "r"(a) : "memory"); }
DI uint32_t lds32(uint32_t a) { uint32_t x; asm volatile("ld.shared.u32 %0, [%1];" : "=r"(x) : "r"(a) : "memory"); return x; }
DI uint32_t lds16(uint32_t a) { uint32_t x; asm volatile("ld.shared.u16 %0, [%1];" : "=r"(x) : "r"(a) : "memory"); return x; }
DI uint32_t atoms_add(uint32_t a, uint32_t v) { uint32_t r; asm volatile("atom.shared.add.u32 %0, [%1], %2;" : "=r"(r) : "r"(a), "r"(v) : "memory"); return r; }
DI void bulk_load(uint32_t dst, const void* src, uint32_t bytes, uint32_t bar) {
  asm volatile("cp.async.bulk.shared::cluster.global.mbarrier::complete_tx::bytes.L2::cache_hint [%0], [%1], %2, [%3], %4;" :: "r"(dst), "l"(src), "r"(bytes), "r"(bar), "l"(pol_first()) : "memory"); }
DI void mbar_expect(uint32_t bar, uint32_t bytes) { asm volatile("mbarrier.arrive.expect_tx.shared::cta.b64 _, [%0], %1;" :: "r"(bar), "r"(bytes) : "memory"); }
DI void mbar_init(uint32_t bar, int n) { asm volatile("mbarrier.init.shared::cta.b64 [%0], %1;" :: "r"(bar), "r"(n) : "memory"); }
DI void tma_load(uint32_t dst, uint64_t tm, int row, uint32_t bar) {
  asm volatile("cp.async.bulk.tensor.2d.shared::cluster.global.mbarrier::complete_tx::bytes.L2::cache_hint [%0], [%1, {%3, %4}], [%2], %5;" :: "r"(dst), "l"(tm), "r"(bar), "r"(0), "r"(row), "l"(pol_first()) : "memory"); }
DI void tma_store(uint64_t tm, int col, int row, uint32_t src) {
  asm volatile("cp.async.bulk.tensor.2d.global.shared::cta.bulk_group [%0, {%2, %3}], [%1];" :: "l"(tm), "r"(src), "r"(col), "r"(row) : "memory"); }
DI void bulk_commit() { asm volatile("cp.async.bulk.commit_group;" ::: "memory"); }
DI uint2 ld_poll2(const void* a) { uint2 v; asm volatile("ld.relaxed.gpu.global.v2.u32 {%0, %1}, [%2];" : "=r"(v.x), "=r"(v.y) : "l"(a) : "memory"); return v; }
DI void st_ext(uint2* a, uint32_t v, uint32_t ep) { asm volatile("st.relaxed.gpu.global.v2.u32 [%0], {%1, %2};" :: "l"(a), "r"(v), "r"(ep) : "memory"); }
DI uint32_t ext_get(const uint2* a, uint32_t ep) { uint2 v; int spin = 0; do { v = ld_poll2(a); trap_if(++spin > 4000000); } while (__any_sync(~0u, v.y != ep)); return v.x; }
DI void bulk_wait() { asm volatile("cp.async.bulk.wait_group 0;" ::: "memory"); }
DI void hint_signal(uint32_t* c) { asm volatile("red.relaxed.gpu.global.add.u32 [%0], 1;" :: "l"(c) : "memory"); }
DI void hint_wait(const uint32_t* c, uint32_t target) { uint32_t v; int spin = 0;
  do { asm volatile("ld.relaxed.gpu.global.u32 %0, [%1];" : "=r"(v) : "l"(c) : "memory"); trap_if(++spin > 4000000); } while (__any_sync(~0u, (int)(v - target) < 0)); }
DI void stsm4(uint32_t a, uint32_t x, uint32_t y, uint32_t z, uint32_t w) { asm volatile("stmatrix.sync.aligned.m8n8.x4.shared.b16 [%0], {%1,%2,%3,%4};" :: "r"(a), "r"(x), "r"(y), "r"(z), "r"(w) : "memory"); }
DI void ldsm4(uint32_t* v, uint32_t a) { asm volatile("ldmatrix.sync.aligned.m8n8.x4.shared.b16 {%0,%1,%2,%3}, [%4];" : "=r"(v[0]), "=r"(v[1]), "=r"(v[2]), "=r"(v[3]) : "r"(a) : "memory"); }
DI void ldsm4t(uint32_t* v, uint32_t a) { asm volatile("ldmatrix.sync.aligned.m8n8.x4.trans.shared.b16 {%0,%1,%2,%3}, [%4];" : "=r"(v[0]), "=r"(v[1]), "=r"(v[2]), "=r"(v[3]) : "r"(a) : "memory"); }
DI uint32_t mad16(uint32_t x, uint32_t m, uint32_t c) { uint32_t r; asm("dp2a.lo.u32.u32 %0, %1, %2, %3;" : "=r"(r) : "r"(x), "r"(m), "r"(c)); return r; }
DI bool wbad(uint32_t m, uint32_t hi) { return m > hi || (m && m < 0x3980); }

__device__ __noinline__ void slow_path(const Params& p, int wid, int lane, int node0, int nloc) {
  const uint32_t ab = sb + OFF_P2 + wid * 8704;
  for (int i = lane; i < 32 * 68; i += 32) sts32(ab + i * 4, 0);
  __syncwarp();
  const uint32_t wdv = __ldg((const uint32_t*)(p.we + 128 * 64) + lane), wxv = __ldg((const uint32_t*)p.wx + lane);
  const int nb0 = node0 + wid * 32, cntn = max(0, min(32, nloc - wid * 32));
  auto dot = [&](uint32_t hv, const uint16_t* w, int K2, float& y0, float& y1) {
#pragma unroll 4
    for (int k = 0; k < K2; k++) {
      const uint32_t hk = __shfl_sync(~0u, hv, k), wa = __ldg((const uint32_t*)(w + 2 * k * 64) + lane), wb = __ldg((const uint32_t*)(w + (2 * k + 1) * 64) + lane);
      y0 = fmaf(bf_lo(hk), bf_lo(wa), fmaf(bf_hi(hk), bf_lo(wb), y0)); y1 = fmaf(bf_lo(hk), bf_hi(wa), fmaf(bf_hi(hk), bf_hi(wb), y1));
    }
  };
  auto silu = [](float x) { return x / (1.f + __expf(-x)); };
#pragma unroll 1
  for (int base = 0; base < p.E; base += 32) {
    const int e = base + lane;
    const uint32_t dl = e < p.E ? (uint32_t)(__ldg(p.dst + e) - nb0) : 0xFFFFFFFFu;
    uint32_t mk = __ballot_sync(~0u, dl < (uint32_t)cntn);
    while (mk) {
      const int l = __ffs(mk) - 1; mk &= mk - 1;
      const int ee = base + l, n = __shfl_sync(~0u, dl, l), s = __ldg(p.src + ee);
      const uint16_t *po = p.pos + (size_t)(nb0 + n) * 3, *pp = p.pos + (size_t)s * 3;
      const uint32_t dxy = hsub(__ldg(po) | (__ldg(po + 1) << 16), __ldg(pp) | (__ldg(pp + 1) << 16)), dz = hsub(__ldg(po + 2), __ldg(pp + 2));
      const uint32_t sq = hsq(dxy); const float d2 = bf_lo(sq) + bf_hi(sq) + bf_lo(hsq(dz));
      float y0 = d2 * bf_lo(wdv), y1 = d2 * bf_hi(wdv);
      dot(__ldg((const uint32_t*)(p.h + (size_t)(nb0 + n) * 8) + lane), p.we, 32, y0, y1);
      dot(__ldg((const uint32_t*)(p.h + (size_t)s * 8) + lane), p.we + 64 * 64, 32, y0, y1);
      dot(__ldg((const uint32_t*)(p.ea + (size_t)ee * 2) + (lane & 7)), p.we + 129 * 64, 8, y0, y1);
      const uint32_t mm = pack_bf16(silu(y0), silu(y1));
      float c = bf_lo(mm) * bf_lo(wxv) + bf_hi(mm) * bf_hi(wxv);
#pragma unroll
      for (int o = 16; o; o >>= 1) c += __shfl_xor_sync(~0u, c, o);
      const uint32_t a = ab + n * 272;
      uint32_t x0, x1; lds64(x0, x1, a + lane * 8);
      sts64(a + lane * 8, __float_as_uint(__uint_as_float(x0) + bf_lo(mm)), __float_as_uint(__uint_as_float(x1) + bf_hi(mm)));
      if (lane < 3) { const float df = lane == 0 ? bf_lo(dxy) : lane == 1 ? bf_hi(dxy) : bf_lo(dz); sts32(a + 256 + lane * 4, __float_as_uint(fmaf(c, df, __uint_as_float(lds32(a + 256 + lane * 4))))); }
    }
  }
  __syncwarp();
#pragma unroll 1
  for (int n = 0; n < cntn; n++) {
    uint32_t x0, x1; lds64(x0, x1, ab + n * 272 + lane * 8);
    const uint32_t hv = __ldg((const uint32_t*)(p.h + (size_t)(nb0 + n) * 8) + lane);
    float y0 = 0.f, y1 = 0.f;
    dot(hv, p.wh, 32, y0, y1); dot(pack_bf16(__uint_as_float(x0), __uint_as_float(x1)), p.wh + 64 * 64, 32, y0, y1);
    ((uint32_t*)p.out)[(size_t)(nb0 + n) * 32 + lane] = u2(__hadd2(b2(hv), b2(pack_bf16(silu(y0), silu(y1)))));
    if (lane < 3) p.out[(size_t)p.N * 64 + (size_t)(nb0 + n) * 3 + lane] = (uint16_t)pack_bf16(bf_lo(__ldg(p.pos + (size_t)(nb0 + n) * 3 + lane)) + __uint_as_float(lds32(ab + n * 272 + 256 + lane * 4)), 0.f);
  }
}

__global__ void __launch_bounds__(NTHR, 1) egnn_kernel(const __grid_constant__ Params p, const __grid_constant__ Maps maps) {
  const uint64_t tmb = (uint64_t)&maps;
  extern __shared__ __align__(1024) unsigned char smraw[];
  const int tid = threadIdx.x, cta = blockIdx.x * CTAM % G;
  const int e0 = cta * p.EPC, n4 = max(0, min(p.EPC, p.E - e0)) >> 2;
  STAMP(0);
  if (tid == NWK) {
#pragma unroll 1
    for (int k = 0; k < NCH; k++) { const int nb = max(0, min(NWK, n4 - k * NWK)) * 16;
      mbar_init(sb + BAR_DST + k * 8, 1);
      asm volatile("fence.mbarrier_init.release.cluster;" ::: "memory");
      mbar_expect(sb + BAR_DST + k * 8, nb);
      if (nb) bulk_load(sb + OFF_DST + k * NWK * 16, (const char*)(p.dst + e0) + k * NWK * 16, nb, sb + BAR_DST + k * 8); }
  }
  const int lane = tid & 31, wid = __shfl_sync(~0u, tid >> 5, 0), w = wid & 3;
  asm volatile("{.reg .pred p; setp.eq.u32 p, %2, 384; @p cp.async.cg.shared.global [%0], [%1], 16;}" :: "r"(sb + OFF_LEN - 192 + (tid >> 1)), "l"(p.sync), "r"(tid & 415) : "memory");

  auto first_node = [&](int c) { return (int)((c * p.inv + 0xFFFFFFFFull) >> 32); };
  const int node0 = first_node(cta), nloc = min(first_node(cta + 1), p.N) - node0;
  const uint32_t ealo = (uint32_t)(uint64_t)p.ea;
  const int epad = min(e0, p.E - 1);
  if (wid >= 12) {
    const int t = tid - 384;
    auto load_h = [&](int b) { mbar_expect(sb + BAR_T + b * 8, 8192); tma_load(sb + OFF_H + b * 8192, tmb + TM_H, node0 + b * 64, sb + BAR_T + b * 8); };
    uint32_t pv[9], ev = 0;
#pragma unroll
    for (int i = 0; i < 3; i++) { const uint16_t* pp = p.pos + (size_t)(node0 + t + 128 * i) * 3;
      pv[3 * i] = pv[3 * i + 1] = pv[3 * i + 2] = 0;
      asm volatile("{.reg .pred p; setp.lt.s32 p, %4, %5;\n @p ld.global.nc.u16 %0, [%3];\n @p ld.global.nc.u16 %1, [%3+2];\n @p ld.global.nc.u16 %2, [%3+4];}"
        : "+r"(pv[3 * i]), "+r"(pv[3 * i + 1]), "+r"(pv[3 * i + 2]) : "l"(pp), "r"(t + 128 * i), "r"(p.N - node0)); }
    asm volatile("{.reg .pred p; setp.lt.u32 p, %3, 8; @p ld.global.nc.u32 %0, [%1]; @p st.global.v4.u32 [%2], {%4, %4, %4, %4};}"
      : "+r"(ev) : "l"((const uint32_t*)(p.ea + (size_t)epad * 2) + t), "l"(p.q + (size_t)(p.N + cta * PADM) * 128 + t * 16), "r"(t), "r"(0xF700F700u) : "memory");
    asm volatile("cp.async.wait_all;" ::: "memory");
    __syncwarp();
    const uint32_t e = lds32(sb + OFF_LEN + 8 + w * 16) + 1;
    {
      const uint32_t tg = (1 + e % 3) << 30, v = ((tg >> 16) + 512 + (lane & 7) * 4) * 0x10001u;
      if (t == 0) sts32(sb + OFF_MISC + 32, e);
#pragma unroll
      for (int i = 0; i < 9; i++) sts128(sb + OFF_SA + t * 16 + i * 2048, v, v + 0x10001u, v + 0x20002u, v + 0x30003u);
      bar_sync(6, NTHR);
      mbar_arrive(sb + BAR_EP, lane == 0);
#pragma unroll
      for (int i = 0; i < 17; i++) sts128(sb + OFF_SB + t * 16 + i * 2048, tg, tg, tg, tg); }
    uint32_t mp = 0;
#pragma unroll
    for (int i = 0; i < 3; i++) { sts64(sb + OFF_POS + (t + 128 * i) * 8, pv[3 * i] | (pv[3 * i + 1] << 16), pv[3 * i + 2]); mp = mag2(mag2(mp, pv[3 * i] | (pv[3 * i + 1] << 16)), pv[3 * i + 2]); }
    proxy_fence();
    __syncwarp();
    mbar_arrive(sb + BAR_PS, lane == 0);
    mbar_wait(sb + BAR_W);
    {
      uint32_t v[4], u[4]; const int r = t >> 3, c = t & 7;
      lds128(v, sb + OFF_WS + 128 + t * 16); lds128(u, sb + OFF_WS + c * 16);
      const uint32_t x = lds32(sb + OFF_WS + 2176 + lane * 4);
      sts128(sb + OFF_W3 + r * 128 + ((c ^ (r & 7)) << 4), b2h(v[0], .5f), b2h(v[1], .5f), b2h(v[2], .5f), b2h(v[3], .5f));
      const float s = ((r & 1) || r == 6) ? 0.f : .5f;
      if (t < 64) sts128(sb + OFF_WD + r * 128 + ((c ^ r) << 4), b2h(u[0], s), b2h(u[1], s), b2h(u[2], s), b2h(u[3], s));
      if (t < 32) sts32(sb + OFF_WX + (t & 3) * 32 + (t >> 2) * 4, b2h(x, 1.f));
      const uint32_t m3 = __reduce_max_sync(~0u, magr(mag2(mag2(mag2(mag2(0, v[0]), v[1]), v[2]), v[3]))), md = __reduce_max_sync(~0u, magr(mag2(mag2(mag2(mag2(0, u[0]), u[1]), u[2]), u[3])));
      if (wbad(m3, 0x4000) || wbad(md, 0x4000) || wbad(__reduce_max_sync(~0u, magr(mag2(0, x))), 0x4700) || magr(mp) >= 0x4200 || magr(mag2(0, ev)) >= 0x4380) sts32(sb + OFF_MISC + 8, 1);
    }
    if (w == 1) {
#pragma unroll 1
      for (int b = 0; b < 3; b++) { mbar_wait(sb + BAR_SRC + b * 8); if (lane == 0) load_h(b); }
    }
    bar_sync(3, 128);
    const uint32_t frag = (w * 16 + (lane & 15)) * 128 + (((lane >> 4) ^ (lane & 7)) << 4);
    uint32_t mq = 0; int pfi = 0;
    auto prefetch_e = [&]() {
      const uint32_t nb = PFB;
      if (lane == 0 && nb) asm volatile("cp.async.bulk.prefetch.L2.global [%0], %1;" :: "l"((const char*)p.ea + (size_t)(pfi * G + cta) * nb), "r"(nb) : "memory");
      pfi++; };
#pragma unroll 1
    for (int b = 0; b < 6; b++) {
      float acc[32];
      const uint64_t da = DHI | (((sb + OFF_H) >> 4) + b * 512), db = DHI | ((sb + OFF_W) >> 4);
      const uint32_t v0 = lds16(sb + OFF_POS + b * 512 + w * 128 + lane * 2), v1 = lds16(sb + OFF_POS + 64 + b * 512 + w * 128 + lane * 2);
      mbar_wait(sb + BAR_T + b * 8);
      if (b == 0) STAMP(25);
      if (b == 5) STAMP(26);
      wg_fence();
      ss64<0>(acc, da, db); ss64<1>(acc, da + 2, db + 128); ss64<1>(acc, da + 4, db + 256); ss64<1>(acc, da + 6, db + 384);
      wg_commit();
      if (b == 0) mbar_wait(sb + BAR_AW);
      if (t == 32 && b < 3) load_h(b + 3);
      if (w == 1) for (int k = PFE >> (4 * b) & 15; k > 0; k--) prefetch_e();
      __syncwarp();
      uint32_t ff[6], fg[6];
#pragma unroll
      for (int j = 0; j < 6; j++) { ff[j] = (__byte_perm((j & 1) ? v1 : v0, 0, 0x4140) >> (3 * (j >> 1))) & 0x00070007u; fg[j] = __vsub2(0x00040004u, ff[j]);
        asm volatile("" : "+r"(ff[j]), "+r"(fg[j])); }
      wg_wait0(); fence_regs(acc);
      uint32_t o[16];
#pragma unroll
      for (int j = 0; j < 16; j++) o[j] = pack_f16(.5f * acc[2 * j], .5f * acc[2 * j + 1]);
#pragma unroll
      for (int j = 0; j < 6; j++) {
        const uint32_t m = o[j] & 0x7FFF7FFFu; mq = __vmaxu2(mq, m);
        o[j] = (__viaddmax_s16x2(m, fg[j], 0) & 0xFFF8FFF8u) | ff[j] | (o[j] & 0x80008000u); }
      if (b == 4) mbar_wait(sb + BAR_AX);
      const uint32_t qs = sb + OFF_SA + b * 8192;
#pragma unroll
      for (int j = 0; j < 4; j++) stsm4((qs + frag) ^ (j << 5), o[4 * j], o[4 * j + 1], o[4 * j + 2], o[4 * j + 3]);
      proxy_fence();
      __syncwarp();
      if (lane == 0 && b * 64 + w * 16 < nloc) tma_store(tmb + TM_Q, 0, node0 + b * 64 + w * 16, qs + w * 2048);
    }
    if (lane == 0) bulk_commit();
    { const uint32_t m = __reduce_max_sync(~0u, magr(mq)); if (lane == 0) sts32(sb + OFF_MISC + 16 + w * 4, m); }
    asm volatile("setmaxnreg.dec.sync.aligned.u32 56;");
    bulk_wait();
    bar_sync(3, 128);
    if (w == 0) {
      STAMP(18);
      uint32_t mv[4]; lds128(mv, sb + OFF_MISC + 16);
      const uint32_t mx = max(max(mv[0], mv[1]), max(mv[2], mv[3]));
      mbar_arrive(sb + BAR_QR, lane == 0);
      STAMP(19);
      if (lane == 0) {
        if (nloc > 0 && (mx >= 0x7BF0 || mx < 0x1400)) asm volatile("st.relaxed.gpu.global.u32 [%0+4], %1;" :: "l"(p.sync), "r"(e) : "memory");
        asm volatile("red.release.gpu.global.add.u32 [%0], 1;" :: "l"(p.sync) : "memory");
      }
      __syncwarp();
      uint32_t c, f; int spin = 0;
      do { asm volatile("ld.acquire.gpu.global.v2.u32 {%0, %1}, [%2];" : "=r"(c), "=r"(f) : "l"(p.sync) : "memory"); trap_if(++spin > 4000000); } while (__any_sync(~0u, (int)(c - e * G) < 0));
      if (f == e) sts32(sb + OFF_MISC + 8, 1);
      if (cta == 0 && lane == 0) asm volatile("st.relaxed.gpu.global.u32 [%0+8], %1;" :: "l"(p.sync), "r"(e) : "memory");
      STAMP(20);
      __syncwarp();
      mbar_arrive(sb + BAR_QP, lane == 0);
    }
    if (w == 2) {
      const uint32_t tg = (1 + e % 3) << 30;
      hint_wait(p.sync + 5, e * G);
      if (lane == 0) { mbar_expect(sb + BAR_HB, XPAD);
#pragma unroll 1
        for (int o = 0; o < 4; o++) bulk_load(sb + OFF_XB + o * (G * 64), (const char*)p.xb + (size_t)(cta * 4 + o) * (G * 64), G * 64, sb + BAR_HB); }
      STAMP(21);
      bar_sync(7, 384);
      sts32(sb + OFF_XB + XPAD, tg + p.N + cta * PADM);
      const uint32_t nx = __shfl_sync(~0u, lds32(sb + OFF_MISC + 8) ? 0 : lds32(sb + OFF_MISC + 4), 0);
#pragma unroll 1
      for (uint32_t k = 0; k < nx; k += 32) {
        const uint32_t i = min(k + lane, nx - 1), xr = lds32(sb + OFF_EXT + i * 4), row = (xr >> 9) & 255;
        const uint32_t v = ext_get(p.xe + (cta * G + row) * 32 + ((xr >> 17) & 31), e), x = lds32(sb + OFF_CNT + (xr & 511) * 4) + (xr >> 22) * 16;
        sts32(sb + OFF_XB + XPAD + 4 + i * 4, v); sts16(sb + OFF_TS + x, XPAD + 4 + i * 4);
        sts32(sb + OFF_TE + x * 2, mad16(v, 0x2000u, ealo - (tg >> 11) + row * p.EPC * 32));
      }
      __syncwarp();
      mbar_arrive(sb + BAR_HB, lane == 0);
    }
    if (w == 1) {
#pragma unroll 1
      while (pfi < PFN) { prefetch_e(); __nanosleep(PFNS); }
    }
    if (w == 3) {
      if (lane == 0) { mbar_expect(sb + BAR_U, 16384); tma_load(sb + OFF_W, tmb + TM_WH, 0, sb + BAR_U); }
      __syncwarp();
      bar_sync(4, 416);
      if (lane == 0) tma_load(sb + OFF_W + 8192, tmb + TM_WH, 64, sb + BAR_U);
    }
    bar_sync(3, 128);
    mbar_wait(sb + BAR_U);
    uint32_t mh = 0;
#pragma unroll 1
    for (int i = t; i < 1024; i += 128) {
      uint32_t v[4]; const uint32_t r = (i >> 3) & 7, j = (i ^ r) & 7;
#pragma unroll
      for (int k = 0; k < 4; k++) v[k] = lds32(sb + OFF_W + (i >> 3) * 128 + ((((j & 4) + k) ^ r) << 4) + (j & 3) * 4);
      __syncwarp();
      if (i < 512) sts128(sb + OFF_W + i * 16, hhalf(v[0]), hhalf(v[1]), hhalf(v[2]), hhalf(v[3]));
      else { sts128(sb + OFF_W + i * 16, b2h(v[0], .5f), b2h(v[1], .5f), b2h(v[2], .5f), b2h(v[3], .5f)); mh = mag2(mag2(mag2(mag2(mh, v[0]), v[1]), v[2]), v[3]); } }
    if (wbad(__reduce_max_sync(~0u, magr(mh)), 0x4700)) sts32(sb + OFF_MISC + 12, 1);
    proxy_fence();
    __syncwarp();
    mbar_arrive(sb + BAR_WH, lane == 0);
    if (!__shfl_sync(~0u, lds32(sb + OFF_MISC + 8), 0)) {
      mbar_wait(sb + BAR_WH);
      float chk = 0.f;
#pragma unroll 1
      for (uint32_t todo = UORD; todo; todo >>= 4) {
        const uint32_t nd = lds16(sb + OFF_GP + (todo & 3) * 1024 + w * 256 + (lane & 15) * 8 + 6), hb = (todo >> 3) & 1;
        const uint64_t b1 = DHI | (((sb + OFF_W) >> 4) + hb * 4);
        uint32_t f[8]; float acc[16];
#pragma unroll
        for (int j = 0; j < 8; j += 2) {
          const uint32_t a = j < 4 ? sb + OFF_H + nd * 128 + (((nd & 7) << 4) ^ (lane & 16)) : sb + OFF_P2 + (todo & 3) * 8192 + frag;
          if (j == 4) mbar_wait(sb + BAR_M + (todo & 3) * 8);
          ldsm4(f, a ^ ((j & 3) << 5)); ldsm4(f + 4, a ^ ((j & 3) << 5) ^ 32);
          wg_fence();
          if (j == 0) rs32b<0>(acc, f, b1); else if (j < 4) rs32b<1>(acc, f, b1 + 128 * j); else rs32h(acc, f, b1 + 128 * j);
          if (j < 4) rs32b<1>(acc, f + 4, b1 + 128 * j + 128); else rs32h(acc, f + 4, b1 + 128 * j + 128);
          wg_commit(); wg_wait0(); fence_regs(acc);
        }
        chk = fmaf(acc[0], 0.f, fmaf(acc[2], 0.f, chk));
#pragma unroll
        for (int k = 0; k < 2; k++) {
          const uint32_t o = __shfl_sync(~0u, nd, (lane >> 2) + 8 * k) * 128 + (lane & 3) * 16 + hb * 64;
          uint32_t x[4]; lds128(x, sb + OFF_H + (o ^ ((o >> 3) & 0x70)));
#pragma unroll
          for (int i = 0; i < 4; i++) x[i] = u2(__hadd2(b2(x[i]), b2(pack_bf16(silu_h(acc[4 * i + 2 * k]), silu_h(acc[4 * i + 2 * k + 1])))));
          if (o < nloc * 128) *(uint4*)((char*)p.out + (size_t)node0 * 128 + o) = make_uint4(x[0], x[1], x[2], x[3]);
        }
        __nanosleep(DEFNS);
      }
      uint32_t pa_[9];
#pragma unroll
      for (int k = 0; k < 9; k++) { const uint32_t i = t + 128 * k, n = (i * 43691u) >> 17; pa_[k] = lds16(sb + OFF_INV + n * 2) + (i - 3 * n) * 2; }
      uint16_t* po = p.out + (size_t)p.N * 64 + node0 * 3 + t;
      mbar_wait(sb + BAR_X);
#pragma unroll
      for (int k = 0; k < 9; k++) pa_[k] = lds16(sb + OFF_GP + pa_[k]);
#pragma unroll
      for (int k = 0; k < 9; k++) if (t + 128 * k < nloc * 3) po[128 * k] = pa_[k];
      asm volatile("{.reg .pred p, q; setp.neu.f32 p, %0, 0f00000000; bar.red.or.pred q, 5, 512, p;}" :: "f"(chk) : "memory");
    }
    return;
  }

  if (tid == 320) {
    mbar_init(sb + BAR_W, 1);
    asm volatile("fence.mbarrier_init.release.cluster;" ::: "memory");
    mbar_expect(sb + BAR_W, 2 * 8192 + 2304);
    tma_load(sb + OFF_W, tmb + TM_WE, 64, sb + BAR_W); tma_load(sb + OFF_W + 8192, tmb + TM_WE, 0, sb + BAR_W);
    bulk_load(sb + OFF_WS, p.we + 128 * 64, 2176, sb + BAR_W); bulk_load(sb + OFF_WS + 2176, p.wx, 128, sb + BAR_W);
  }
  if (tid == 288) {
#pragma unroll
    for (int a = BAR_SRC; a < BAR_END; a += 8) if (a != BAR_W) mbar_init(sb + a, a == BAR_X ? 12 : a >= BAR_WH || a == BAR_PS || a == BAR_EP ? 4 : a == BAR_HB ? 2 : 1);
    asm volatile("fence.mbarrier_init.release.cluster;" ::: "memory");
    asm volatile("prefetch.tensormap [%0];" :: "l"(tmb + TM_XA)); asm volatile("prefetch.tensormap [%0];" :: "l"(tmb + TM_H));
    asm volatile("prefetch.tensormap [%0];" :: "l"(tmb + TM_XB)); asm volatile("prefetch.tensormap [%0];" :: "l"(tmb + TM_Q));
  }
  {
    if (tid < 144) { const uint32_t z = (tid >> 3) == 16 ? 0x8000u : 0u; sts128(sb + OFF_CNT + tid * 16, z, z, z, z); }
    else if (tid <= 144 + G) sts32(sb + OFF_BC + (tid - 144) * 4, ((tid - 144) & 31) * 4);
    const uint32_t sp = XPAD * 0x10001u, em = first_node(G);
    if (wid < 7) {
#pragma unroll
      for (int i = 0; i < 4; i++) sts128(sb + OFF_TS + tid * 16 + i * 3584, sp, sp, sp, sp);
    }
    static_assert(SCAP * 32 == 4 * 3584, "fill");
#pragma unroll 1
    for (int i = n4 + tid; i < 1536; i += 384) sts128(sb + OFF_DST + i * 16, em, em, em, em);
    if (tid == 321) sts128(sb + OFF_MISC, 0, 0, p.force_slow, 0);
  }
  bar_arrive(6, NTHR);
  bar_sync(0, 384);
  uint32_t ep, tag, eb0, pk[12], r0[12], r1[12], cb;
  uint2 vb[12];
  auto get_tag = [&]() { mbar_wait(sb + BAR_EP); ep = lds32(sb + OFF_MISC + 32); tag = (1 + ep % 3) << 30; eb0 = ealo - (tag >> 11); };
  if (wid == 11) {
    trap_if(sb != (uint32_t)__cvta_generic_to_shared(smraw));
#pragma unroll 1
    for (int k = 0; k < 3; k++) { const int nb = max(0, min(8192, n4 * 16 - k * 8192));
      mbar_wait(sb + BAR_DST + (k ? k + 1 : 0) * 8);
      if (lane == 0) { mbar_expect(sb + BAR_SRC + k * 8, nb);
        if (nb) bulk_load(sb + OFF_SRCI + k * 8192, (const char*)(p.src + e0) + k * 8192, nb, sb + BAR_SRC + k * 8); } }
    proxy_fence();
    get_tag();
    mbar_wait(sb + BAR_PS);
    bar_sync(12, 384);
    uint32_t xm = 0;
#pragma unroll
    for (int k = 0; k < 5; k++) xm |= (lds32(sb + OFF_BC + min(lane + 32 * k, G - 1) * 4) >= (65 << 9) && lane + 32 * k < G) << k;
    auto ext_send = [&](int pl) {
      uint32_t x = xm;
      for (uint32_t m; (m = __ballot_sync(~0u, x));) {
        const uint32_t l = __ffs(m) - 1, j = l + 32 * (__ffs(__shfl_sync(~0u, x, l)) - 1);
        if (lane == l) x &= x - 1;
        const uint32_t e = min(lds16(sb + OFF_AX + j * 128 + ((4 * l + 2 * lane) & 126)), 6143u);
        if (pl) st_ext(p.xe + (j * G + cta) * 32 + lane, lds32(sb + OFF_SRCI + e * 4) + tag + (e << 16), ep);
        else { const uint32_t cn = lds32(sb + OFF_BC + j * 4) >> 9, v = cn > 96 ? 1 : lane + 64 < cn ? 512 | (lds32(sb + OFF_DST + e * 4) & 511) : 0;
          asm volatile("red.shared.xor.b32 [%0], %1;" :: "r"(sb + OFF_SA + j * 128 + ((l + lane) & 31) * 4), "r"(((v & 63) << 10) | ((v >> 6) << 26)) : "memory"); }
      }
    };
    if (__any_sync(~0u, xm)) { ext_send(0); proxy_fence(); __syncwarp(); }
    if (lane == 0) { tma_store(tmb + TM_XA, cta * 64, 0, sb + OFF_SA); bulk_commit(); mbar_arrive(sb + BAR_AI); bulk_wait(); hint_signal(p.sync + 4); mbar_arrive(sb + BAR_AW); STAMP(16); }
    __syncwarp();
    bar_sync(13, 384);
    ext_send(1);
    mbar_arrive(sb + BAR_AX, lane == 0);
    mbar_wait(sb + BAR_HA);
    __nanosleep(BDEL);
    if (lane == 0) {
#pragma unroll 1
      for (int r = 0; r < G; r += BROWS) { tma_store(tmb + TM_XB, cta * 64, r, sb + OFF_SB + r * 256); bulk_commit(); bulk_wait(); }
      hint_signal(p.sync + 5);
      STAMP(17);
    }
    __syncwarp();
  } else {
    {
      uint32_t d[4 * NCH], jj[4 * NCH], rr[4 * NCH];
      auto count = [&](int k) {
        mbar_wait(sb + BAR_DST + k * 8);
        lds128(d + 4 * k, sb + OFF_DST + (tid + NWK * k) * 16);
#pragma unroll
        for (int i = 4 * k; i < 4 * k + 4; i++) { jj[i] = d[i] * p.magic; rr[i] = atoms_add(__dp4a(jj[i], 0x04000000u, sb + OFF_BC), 0x202u); }
      };
      auto place = [&](int k) {
#pragma unroll
        for (int i = 4 * k; i < 4 * k + 4; i++) {
          const uint32_t o = __dp4a(jj[i], 0x80000000u, rr[i] & 0x807Eu);
          d[i] = (d[i] & 511) | (tag >> 16);
          asm("{.reg .pred p; setp.ge.u32 p, %1, 0x8000; @p add.u32 %0, %2, %3;}" : "+r"(d[i]) : "r"(o), "r"(tid * 4), "r"(NWK * k * 4 + (i & 3)));
          sts16(sb + OFF_SA + o, d[i]); jj[i] = __viaddmin_u32(o, o, G * 256);
        }
      };
      count(0); STAMP(1); count(1); get_tag(); place(0); count(2); place(1); count(3); place(2);
      if (wid < 4) { count(4); STAMP(15); place(3); place(4); } else place(3);
      proxy_fence();
      bar_arrive(12, 384);
      STAMP(2);
      mbar_wait(sb + BAR_AI);
      mbar_wait(sb + BAR_SRC); mbar_wait(sb + BAR_SRC + 8); mbar_wait(sb + BAR_SRC + 16);
      STAMP(12);
#pragma unroll
      for (int k = 0; k < NCH; k++) lds128(d + 4 * k, sb + OFF_SRCI + (tid + NWK * k) * 16);
      const uint32_t tb = tag + (tid << 18);
#pragma unroll
      for (int i = 0; i < 4 * NCH; i++) if (i < 4 * NCH - 4 || wid < 4) sts32(sb + OFF_SB + jj[i], d[i] + tb + ((NWK * (i >> 2) * 4 + (i & 3)) << 16));
      proxy_fence();
      bar_arrive(13, 384);
      STAMP(3);
    }
    const uint32_t rot = (lane + cta) & 31;
    cb = sb + OFF_CNT - (tag >> 14);
    {
      const uint32_t* xa = (const uint32_t*)(p.xa + (cta * G + wid) * 8) + rot;
      if (wid < 8) { const uint32_t e_ = ealo + epad * 32;
        mbar_wait(sb + BAR_AX);
#pragma unroll
        for (int i = 0; i < 7; i++) sts128(sb + OFF_TE + tid * 16 + i * 4096, e_, e_, e_, e_); }
      static_assert(SCAP * 64 == 7 * 4096, "fill");
      if (wid == 10) { hint_wait(p.sync + 4, ep * G); mbar_arrive(sb + BAR_HA, lane == 0); }
      mbar_wait(sb + BAR_HA);
      STAMP(14);
      const uint32_t tp = tag | (tag >> 16);
      uint32_t st;
#pragma unroll 1
      for (int spin = 0;; spin++) {
        st = 0;
#pragma unroll
        for (int k = 0; k < 12; k++) asm volatile("ld.relaxed.gpu.global.u32 %0, [%1];" : "=r"(pk[k]) : "l"(xa + k * 352) : "memory");
#pragma unroll
        for (int k = 0; k < 12; k++) st |= pk[k] ^ tp;
        st = __reduce_or_sync(~0u, st);
        if (!(st >> 30)) break;
        trap_if(spin > 2000000);
      }
      if (st & 0x3C00FC00u) {
#pragma unroll 1
        for (;;) {
          uint32_t x = 0, row = 0;
#pragma unroll
          for (int k = 0; k < 12; k++) { const uint32_t y = (pk[k] ^ tp) & 0x3C00FC00u; if (!x && y) { x = y; row = wid + 11 * k; pk[k] ^= y; } }
          if (!__any_sync(~0u, x)) break;
          const uint32_t n = ((x >> 10) & 63) | ((x >> 20) & 0x1C0);
          if (x >> 29) {
            const uint32_t r = atoms_add(sb + OFF_CNT + n * 4, 16), idx = atoms_add(sb + OFF_MISC + 4, 1);
            if (idx < 256) sts32(sb + OFF_EXT + idx * 4, n | (row << 9) | (lane << 17) | (min(r >> 4, 255u) << 22));
            else x = 1;
          }
          if (x && !(x >> 29)) sts32(sb + OFF_MISC + 8, 1);
          __syncwarp();
        }
      }
#pragma unroll
      for (int k = 0; k < 12; k++) { r0[k] = mad16(pk[k], 0x0004u, cb); r1[k] = mad16(pk[k], 0x0400u, cb); vb[k].x = atoms_add(r0[k], 16); vb[k].y = atoms_add(r1[k], 16); }
    }
    STAMP(4);
    if (wid >= 6) bar_arrive(11, NWK);
    if (wid < 6) {
      uint32_t ca[2], ky[2], dr[2], sq[2], ps[4];
#pragma unroll
      for (int i = 0; i < 2; i++) { ca[i] = sb + OFF_CNT + ((node0 + tid + 192 * i) & 511) * 4; lds64(ps[2 * i], ps[2 * i + 1], sb + OFF_POS + (tid + 192 * i) * 8); ps[2 * i + 1] |= (tid + 192 * i) << 16; }
      bar_sync(11, NWK);
      STAMP(5);
#pragma unroll
      for (int i = 0; i < 2; i++) ky[i] = (lds32(ca[i]) + 16) >> 5;
      if (max(ky[0], ky[1]) > 31) sts32(sb + OFF_MISC + 8, 1);
#pragma unroll
      for (int i = 0; i < 2; i++) { ky[i] = min(ky[i], 31u); dr[i] = atoms_add(sb + OFF_DH + ky[i] * 4, 1); }
      bar_sync(10, 192);
      const uint32_t hv = lds32(sb + OFF_DH + lane * 4);
      uint32_t inc = hv;
#pragma unroll
      for (int o = 1; o < 32; o <<= 1) asm("{.reg .pred p; .reg .b32 y; shfl.sync.down.b32 y|p, %0, %1, 31, -1; @p add.u32 %0, %0, y;}" : "+r"(inc) : "r"(o));
#pragma unroll
      for (int i = 0; i < 2; i++) {
        const uint32_t pos = __shfl_sync(~0u, inc - hv, ky[i]) + dr[i];
        const uint32_t ak = (uint32_t)(QCODE >> ((pos >> 5) * 4)) & 15, l = (pos >> 3) & 3;
        sq[i] = (ak >> 2) * 16 + ((QREV >> (pos >> 5) & 1) ? 3 - l : l) * 4 + (ak & 3);
        dr[i] = pos & 7;
        asm volatile("{.reg .pred p; setp.eq.u32 p, %2, 0; @p st.shared.u8 [%0], %1;}" :: "r"(sb + OFF_LEN + sq[i]), "r"(max(ky[i], 1u)), "r"(dr[i]) : "memory");
        sts64(sb + OFF_GP + sq[i] * 64 + dr[i] * 8, ps[2 * i], ps[2 * i + 1]);
        sts16(sb + OFF_INV + (tid + 192 * i) * 2, sq[i] * 64 + dr[i] * 8);
      }
      bar_sync(10, 192);
      const uint32_t ln = lds32(sb + OFF_LEN + min(lane, 11) * 4), tot = __dp4a(ln, 0x01010101u, 0u);
      inc = tot;
#pragma unroll
      for (int o = 1; o < 16; o <<= 1) asm("{.reg .pred p; .reg .b32 y; shfl.sync.up.b32 y|p, %0, %1, 0, -1; @p add.u32 %0, %0, y;}" : "+r"(inc) : "r"(o));
      if (wid == 1) sts32(sb + OFF_CNT + 2048 + lane * 4, 0);
      if (tid < 12) { sts32(sb + OFF_LEN + 64 + tid * 4, inc - tot); if (inc > SCAP - 12) sts32(sb + OFF_MISC + 8, 1); }
#pragma unroll
      for (int i = 0; i < 2; i++) sts32(ca[i], __dp4a(__shfl_sync(~0u, ln, sq[i] >> 2), 0x00010101u >> (24 - 8 * (sq[i] & 3)), __shfl_sync(~0u, inc - tot, sq[i] >> 2)) * 32 + dr[i] * 2);
    }
    bar_arrive(7, 384);
  }
  bar_sync(1, 384);
  STAMP(6);
  if (wid != 11 && !__shfl_sync(~0u, lds32(sb + OFF_MISC + 8), 0)) {
#pragma unroll
    for (int k = 0; k < 12; k++) { r0[k] = lds32(r0[k]); r1[k] = lds32(r1[k]); }
#pragma unroll
    for (int k = 0; k < 12; k++) { r0[k] += vb[k].x; r1[k] += vb[k].y; }
  } else {
#pragma unroll
    for (int k = 0; k < 12; k++) r0[k] = r1[k] = 0x8000;
  }
  auto put_ids = [&]() {
    const uint32_t id = wid * 256 + ((lane + cta) & 31) * 8;
    auto put = [&](uint32_t x, uint32_t v) { asm volatile("{.reg .pred p; setp.lt.u32 p, %0, 0x8000; @p st.shared.u16 [%0+%2], %1;}" :: "r"(x), "h"((uint16_t)v), "n"(sb + OFF_TS) : "memory"); };
#pragma unroll
    for (int k = 0; k < 12; k++) { put(pk[k] & 0xFFFF, id + k * 2816); put(pk[k] >> 16, id + k * 2816 + 4); }
  };
  STAMP(7);
  mbar_wait(sb + BAR_QR);
  asm volatile("setmaxnreg.inc.sync.aligned.u32 152;");
#pragma unroll
  for (int k = 0; k < 12; k++) asm volatile("prmt.b32 %0, %1, %2, 0x5410;" : "=r"(pk[k]) : "r"(r0[k]), "r"(r1[k]));
  uint32_t pa[8], sp[8], pq[16]; float chk = 0.f;
  {
    uint32_t hf[32], mp = 0; float a0[32], a1[32];
    const uint32_t an = sb + OFF_GP + wid * 256 + (lane & 15) * 8 + 6, n0 = lds16(an), n1 = lds16(an + 128);
#pragma unroll
    for (int j = 0; j < 8; j++) { const uint32_t nd = j < 4 ? n0 : n1; ldsm4(hf + 4 * j, (sb + OFF_H + nd * 128 + (((nd & 7) << 4) ^ (lane & 16))) ^ ((j & 3) << 5)); }
    const uint64_t db = DHI | ((sb + OFF_W + 8192) >> 4);
    wg_fence();
    rs64b<0>(a0, hf[0], hf[1], hf[2], hf[3], db); rs64b<1>(a0, hf[4], hf[5], hf[6], hf[7], db + 128); rs64b<1>(a0, hf[8], hf[9], hf[10], hf[11], db + 256); rs64b<1>(a0, hf[12], hf[13], hf[14], hf[15], db + 384);
    wg_commit();
    rs64b<0>(a1, hf[16], hf[17], hf[18], hf[19], db); rs64b<1>(a1, hf[20], hf[21], hf[22], hf[23], db + 128); rs64b<1>(a1, hf[24], hf[25], hf[26], hf[27], db + 256); rs64b<1>(a1, hf[28], hf[29], hf[30], hf[31], db + 384);
    wg_commit();
    put_ids();
    asm volatile("wgmma.wait_group.sync.aligned 1;" ::: "memory"); fence_regs(a0);
#pragma unroll
    for (int j = 0; j < 8; j++) { const uint32_t x = pack_f16(.5f * a0[4 * j], .5f * a0[4 * j + 1]), y = pack_f16(.5f * a0[4 * j + 2], .5f * a0[4 * j + 3]); mp = hmag(hmag(mp, x), y);
      asm volatile("movmatrix.sync.aligned.m8n8.trans.b16 %0, %1;" : "=r"(pa[j]) : "r"(x)); asm volatile("movmatrix.sync.aligned.m8n8.trans.b16 %0, %1;" : "=r"(sp[j]) : "r"(y)); }
    wg_wait0(); fence_regs(a1);
    bar_arrive(4, 416);
#pragma unroll
    for (int j = 0; j < 16; j++) { pq[j] = pack_f16(.5f * a1[2 * j], .5f * a1[2 * j + 1]); mp = hmag(mp, pq[j]); }
    if (magr(mp) >= 0x7000) chk = __int_as_float(0x7FC00000);
  }
  if (wid == 0) STAMP(23);
  uint32_t bad;
  {
    const uint32_t ring = sb + OFF_RING + wid * STG, p2 = sb + OFF_P2 + wid * 2048;
    uint32_t lens = __shfl_sync(~0u, lds32(sb + OFF_LEN + wid * 4), 0);
    uint32_t rem = __dp4a(lens, 0x20202020u, 0u);
    const uint32_t base = min(lds32(sb + OFF_LEN + 64 + wid * 4), SCAP);
    uint32_t a_s = sb + OFF_TS + base * 32 + (lane >> 3) * 8, a_e = sb + OFF_TE + base * 64 + (lane >> 1) * 4;
    uint32_t k0 = (uint32_t)(uint64_t)p.q + (((lane & 7) ^ ((lane >> 1) & 4)) << 4), k1 = k0 ^ 16, k2 = k0 ^ 32, k3 = k0 ^ 48, ke = ((lane ^ (lane >> 3)) & 1) << 4;
    uint32_t dst0 = ring + (lane >> 3) * 640 + (lane & 7) * 16;
    const uint32_t qhi = (uint32_t)((uint64_t)p.q >> 32), ehi = (uint32_t)((uint64_t)p.ea >> 32);
    uint32_t s0, s1, ev, to = 0, so = 12 * STG;
    auto tl_ = [&]() { lds64(s0, s1, a_s + to); asm volatile("ld.shared.u32 %0, [%1]; add.u32 %1, %1, 64;" : "=&r"(ev), "+r"(a_e) :: "memory"); to += 32; };
#define CPQ(LH, x, k, off) "dp2a." LH ".u32.u32 lo, " x ", 0x80000080, " k "; mov.b64 a, {lo, %7}; @p cp.async.cg.shared.global [%0+" #off "], [a], 16;\n"
    uint64_t pe; asm volatile("createpolicy.fractional.L2::evict_normal.b64 %0, 1.0;" : "=l"(pe));
    uint32_t one = __shfl_sync(~0u, lane, 1);
#define CPE "or.b32 lo, %10, %11; mov.b64 a, {lo, %12}; @p cp.async.cg.shared.global.L2::cache_hint [%0+512], [a], 16, %13;\n"
#define CPA(BODY) asm volatile("{.reg .b32 lo; .reg .b64 a; .reg .pred p; setp.le.u32 p, %8, %9;\n" BODY "}" \
      :: "r"(so * one + dst0), "r"(s0), "r"(s1), "r"(k0), "r"(k1), "r"(k2), "r"(k3), "r"(qhi), "r"(to), "r"(rem), "r"(ev), "r"(ke), "r"(ehi), "l"(pe) : "memory")
#define CPQ4 CPQ("lo", "%1", "%3", 0) CPQ("hi", "%1", "%4", 128) CPQ("lo", "%2", "%5", 256) CPQ("hi", "%2", "%6", 384) "cp.async.commit_group;"
    auto issue = [&]() { CPA(CPE CPQ4); so = so == (NST - 1) * 12 * STG ? 0 : so + 12 * STG; };
    const int g = lane >> 2, qd = lane & 3;
    const uint32_t sw = ((lane >> 4) ^ (lane & 7)) << 4, fr = (lane & 15) * 128 + sw;
    uint32_t qa0 = ring + (g & 3) * 640 + qd * 128 + sw, qa1 = qa0 ^ 32, qa2 = qa0 ^ 64, qa3 = qa0 ^ 96;
    uint32_t eadr = ring + 512 + (g & 3) * 640 + qd * 32 + ((((lane >> 4) ^ g) & 1) << 4);
    uint32_t oh0 = g == 2 * qd ? 0x3C00u : g == 2 * qd + 1 ? 0x3C000000u : 0u, oh1 = oh0;
    uint32_t a_g = sb + OFF_GP + wid * 256 + lane * 2;
    asm volatile("shfl.sync.idx.b32 %0, %0, %1, 31, -1;" : "+r"(oh1) : "r"(lane));
    uint32_t w3[16], wv[8], bp[16], sum[8], Y[16], M[16], own, ownp, dpk, tl[16], th[16];
    float pacc = 0.f;
    auto wload = [&]() {
#pragma unroll
      for (int j = 0; j < 4; j++) ldsm4t(w3 + 4 * j, (sb + OFF_W3 + fr) ^ (j << 5));
      lds128(wv, sb + OFF_WX + (a_g & 6) * 16); lds128(wv + 4, sb + OFF_WX + 16 + (a_g & 6) * 16);
    };
    auto hload = [&](uint32_t (&hf)[16], uint32_t nd) {
      const uint32_t hrow = sb + OFF_H + nd * 128 + (((nd & 7) << 4) ^ ((a_g >> 1) & 16));
#pragma unroll
      for (int j = 0; j < 4; j++) ldsm4(hf + 4 * j, hrow ^ (j << 5));
      return hrow;
    };
    { uint32_t wd[8]; const uint32_t a = sb + OFF_WD + (lane & 7) * 128 + ((((lane >> 3) ^ lane) & 7) << 4);
      ldsm4t(wd, a); ldsm4t(wd + 4, a ^ 64);
#pragma unroll
      for (int j = 0; j < 8; j++) { bp[2 * j] = wd[j]; bp[2 * j + 1] = pa[j]; } }
    own = lds16(a_g) * 0x10001u;
    wload();
    if (__shfl_sync(~0u, lds32(sb + OFF_MISC + 8), 0)) rem = 0;
    auto resolve = [&](auto NBK, uint32_t o) {
      constexpr int NB = decltype(NBK)::value;
      uint32_t id[NB], c0[NB], c1[NB]; const uint32_t a = base * 32 + o + lane * 4;
#pragma unroll
      for (int i = 0; i < NB; i++) { id[i] = lds32(sb + OFF_TS + a + i * 128); if (o + lane * 4 + i * 128 >= rem) id[i] = XPAD * 0x10001u; }
      uint32_t st = 0;
#pragma unroll
      for (int i = 0; i < NB; i++) { c0[i] = lds32(sb + OFF_XB + (id[i] & 0xFFFF)); c1[i] = lds32(sb + OFF_XB + (id[i] >> 16)); }
#pragma unroll
      for (int i = 0; i < NB; i++) st |= (c0[i] ^ tag) | (c1[i] ^ tag);
      for (int spin = 0; __any_sync(~0u, st >> 30); spin++) {
        st = 0; trap_if(spin > 2000000);
#pragma unroll
        for (int i = 0; i < NB; i++) {
          asm volatile("{.reg .pred p, q; setp.lt.u32 p, %4, %6; setp.lt.u32 q, %5, %6; @p ld.relaxed.gpu.global.u32 %0, [%2]; @q ld.relaxed.gpu.global.u32 %1, [%3];}"
            : "+r"(c0[i]), "+r"(c1[i]) : "l"((const char*)p.xb + cta * XPAD + (id[i] & 0xFFFF)), "l"((const char*)p.xb + cta * XPAD + (id[i] >> 16)), "r"(id[i] & 0xFFFF), "r"(id[i] >> 16), "n"(XPAD) : "memory");
          st |= (c0[i] ^ tag) | (c1[i] ^ tag); }
      }
#pragma unroll
      for (int i = 0; i < NB; i++) { const uint32_t j0 = (id[i] >> 8) & 255, j1 = id[i] >> 24;
        asm volatile("{.reg .pred p, q, r; setp.lt.u32 p, %5, %9; setp.lt.u32 q, %6, %9; setp.lt.u32 r, %7, %8;\n"
          "@p st.shared.u32 [%0], %2; @q st.shared.u32 [%0+4], %3; @r st.shared.u32 [%1], %4;}"
          :: "r"(sb + OFF_TE + 2 * a + i * 256), "r"(sb + OFF_TS + a + i * 128), "r"(mad16(c0[i], 0x2000u, eb0 + j0 * p.EPC * 32)), "r"(mad16(c1[i], 0x2000u, eb0 + j1 * p.EPC * 32)),
             "r"(__byte_perm(c0[i], c1[i], 0x5410)), "r"(j0), "r"(j1), "r"(o + lane * 4 + i * 128), "r"(rem), "n"(G) : "memory"); }
    };
    bar_sync(2, 384);
    if (wid == 0) STAMP(27);
    mbar_wait(sb + BAR_HB);
    if (wid == 0) STAMP(22);
#pragma unroll 1
    for (uint32_t o = 0, go = 0; go < 32 * NST; o += 128 * RNB) {
      if (o < rem) { resolve(IC<RNB>(), o);
        asm volatile("{.reg .pred p; mbarrier.test_wait.parity.shared::cta.b64 p, [%1], 0; vote.sync.all.pred p, p, -1; selp.u32 %0, %2, 0, p;}" : "=r"(go) : "r"(sb + BAR_QP), "n"(32 * NST - 32) : "memory"); }
      else { bar_sync(8, 384); mbar_wait(sb + BAR_QP); go = 32 * NST; if (wid == 0) STAMP(24); }
      __syncwarp();
#pragma unroll 1
      while (to < go) { tl_(); issue(); if (to == 32) STAMP(13); }
    }
    bad = __shfl_sync(~0u, lds32(sb + OFF_MISC + 8), 0);
   if (!bad) {
#pragma unroll
    for (int j = 0; j < 4; j++) stsm4((p2 + fr) ^ (j << 5), pq[4 * j], pq[4 * j + 1], pq[4 * j + 2], pq[4 * j + 3]);
    auto body = [&](auto MODE) {
      constexpr int mode = decltype(MODE)::value;
      uint32_t T[16], ef[4], q0, q1, x0, x1, x2; float e0_, e1_, cs[4];
      auto mu = [&](int j) {
#pragma unroll
        for (int i = 2 * j; i < 2 * j + 2; i++) asm volatile("{.reg .b16 l, h; mov.b32 {l, h}, %2; tanh.approx.f16 l, l; tanh.approx.f16 h, h; cvt.u32.u16 %0, l; cvt.u32.u16 %1, h;}" : "=r"(tl[i]), "=r"(th[i]) : "r"(Y[i])); };
      auto fi = [&](int j) {
#pragma unroll
        for (int i = 2 * j; i < 2 * j + 2; i++) asm volatile("{.reg .b32 t; prmt.b32 t, %2, %3, 0x5410; fma.rn.f16x2 %0, %1, t, %1;}" : "=r"(M[i]) : "r"(Y[i]), "r"(tl[i]), "r"(th[i])); };
      auto ad = [&](int j) { asm volatile("add.rn.f16x2 %0, %0, %1; add.rn.f16x2 %0, %0, %2;" : "+r"(sum[j]) : "r"(M[2 * j]), "r"(M[2 * j + 1])); };
      auto he = [&](int j) { asm volatile("mma.sync.aligned.m16n8k16.row.col.f16.f16.f16.f16 {%0,%1}, {%2,%3,%4,%5}, {%6,%7}, {%0,%1};" : "+r"(T[2 * j]), "+r"(T[2 * j + 1]) : "r"(ef[0]), "r"(ef[1]), "r"(ef[2]), "r"(ef[3]), "r"(w3[2 * j]), "r"(w3[2 * j + 1])); };
      auto hs = [&](int j) { asm volatile("mma.sync.aligned.m16n8k16.row.col.f16.f16.f16.f16 {%0,%1}, {%2,%3,%4,%5}, {%6,%7}, {%8,%9};" : "=r"(Y[2 * j]), "=r"(Y[2 * j + 1]) : "r"(q0), "r"(q1), "r"(oh0), "r"(oh1), "r"(bp[2 * j]), "r"(bp[2 * j + 1]), "r"(T[2 * j]), "r"(T[2 * j + 1])); };
      auto hc = [&](int j) {
        if (j) asm volatile("mma.sync.aligned.m16n8k16.row.col.f32.f16.f16.f32 {%0,%1,%2,%3}, {%4,%5,%6,%7}, {%8,%9}, {%0,%1,%2,%3};" : "+f"(cs[0]), "+f"(cs[1]), "+f"(cs[2]), "+f"(cs[3]) : "r"(M[4 * j]), "r"(M[4 * j + 1]), "r"(M[4 * j + 2]), "r"(M[4 * j + 3]), "r"(wv[2 * j]), "r"(wv[2 * j + 1]));
        else asm volatile("mma.sync.aligned.m16n8k16.row.col.f32.f16.f16.f32 {%0,%1,%2,%3}, {%4,%5,%6,%7}, {%8,%9}, {%10,%10,%10,%10};" : "=f"(cs[0]), "=f"(cs[1]), "=f"(cs[2]), "=f"(cs[3]) : "r"(M[0]), "r"(M[1]), "r"(M[2]), "r"(M[3]), "r"(wv[0]), "r"(wv[1]), "f"(0.f)); };
      auto cv = [&](int i) { asm volatile("{.reg .b32 a, b; shl.b32 a, %0, 16; and.b32 b, %0, 0xFFFF0000; cvt.rn.f16x2.f32 %0, b, a;}" : "+r"(ef[i])); };
      auto un = [&]() { asm volatile("shl.b32 %0, %2, 16; and.b32 %1, %2, 0xFFFF0000;" : "=&f"(e0_), "=&f"(e1_) : "r"(dpk)); };
      auto ex0 = [&]() { asm volatile("prmt.b32 %0, %3, %4, 0x6420; prmt.b32 %1, %5, %6, 0x6420; prmt.b32 %2, %7, %8, 0x6420;" : "=&r"(x0), "=&r"(x1), "=&r"(x2) : "r"(T[0]), "r"(T[1]), "r"(T[2]), "r"(T[3]), "r"(T[4]), "r"(T[5])); };
      auto ex1 = [&]() { asm volatile("{.reg .b32 a, b; shl.b32 a, %2, 3; shl.b32 b, %3, 6; lop3.b32 a, %1, a, 0x38383838, 0xD8; lop3.b32 a, a, b, 0xC0C0C0C0, 0xD8; sub.rn.bf16x2 %0, %4, a;}" : "=r"(dpk) : "r"(x0), "r"(x1), "r"(x2), "r"(own)); };
      auto ex2 = [&]() { asm volatile("{.reg .b32 a, b, d, u; .reg .b16 l, h; shl.b32 a, %2, 16; and.b32 b, %2, 0xFFFF0000; cvt.rn.f16x2.f32 d, b, a; mul.rn.f16x2 %0, d, d; mov.b32 {l, h}, d; mov.b32 u, {h, h}; mul.rn.f16x2 %1, u, u;}" : "=&r"(q0), "=&r"(q1) : "r"(dpk)); };
      auto pf = [&]() { asm volatile("fma.rn.f32 %0, %1, %2, %0; fma.rn.f32 %0, %3, %4, %0;" : "+f"(pacc) : "f"(cs[0]), "f"(e0_), "f"(cs[2]), "f"(e1_)); };
      if (mode == 2) { LASTSEQ return; }
      asm volatile("cp.async.wait_group %0;" :: "n"(NST - 1) : "memory");
      __syncwarp();
      if (mode == 1) STAMP(8);
      ldsm4(ef, eadr + so); ldsm4(T, qa0 + so); ldsm4(T + 4, qa1 + so); ldsm4(T + 8, qa2 + so); ldsm4(T + 12, qa3 + so);
      if (mode == 1) {
        tl_(); issue();
        cv(0); cv(1); cv(2); cv(3); ex0(); ex1(); ex2();
#pragma unroll
        for (int j = 0; j < 8; j++) { he(j); hs(j); }
        FIRSTSEQ return;
      }
      BODYSEQ
    };
#pragma unroll
    for (int j = 0; j < 8; j++) sum[j] = 0;
    body(IC<1>());
    int cnt = (lens & 255) - 1;
    auto pload = [&](uint32_t (&x)[8], uint32_t o) { const uint32_t l = a_g >> 1, a = p2 + o + (l & 7) * 128 + (((((l >> 3) & 3) ^ l) & 7) << 4); ldsm4t(x, a); ldsm4t(x + 4, a ^ 64); };
    auto flush = [&]() {
      asm volatile("{.reg .pred p; setp.ne.u32 p, %2, 6; @p st.shared.u16 [%0+-64], %1;}" :: "r"(a_g), "h"((uint16_t)pack_bf16(bf_hi(ownp) + pacc, 0.f)), "r"(a_g & 6) : "memory");
      chk = fmaf(pacc, 0.f, chk); pacc = 0.f; };
    constexpr uint64_t b1 = DHI | ((sb + OFF_W) >> 4), b2_ = b1 + 512;
    auto mma_h = [&](float (&acc)[32], uint32_t (&hf)[16]) {
      rs64b<0>(acc, hf[0], hf[1], hf[2], hf[3], b1); rs64b<1>(acc, hf[4], hf[5], hf[6], hf[7], b1 + 128); rs64b<1>(acc, hf[8], hf[9], hf[10], hf[11], b1 + 256); rs64b<1>(acc, hf[12], hf[13], hf[14], hf[15], b1 + 384); };
    auto mma_m = [&](float (&acc)[32]) {
      rs64h<1>(acc, sp[0], sum[0], sp[1], sum[1], b2_); rs64h<1>(acc, sp[2], sum[2], sp[3], sum[3], b2_ + 128); rs64h<1>(acc, sp[4], sum[4], sp[5], sum[5], b2_ + 256); rs64h<1>(acc, sp[6], sum[6], sp[7], sum[7], b2_ + 384);
      wg_commit(); wg_wait0(); fence_regs(acc);
      STAMP(10);
      chk = fmaf(acc[0], 0.f, fmaf(acc[2], 0.f, chk)); };
    auto roff = [&](uint32_t nd, int r) { return __shfl_sync(~0u, nd, ((a_g >> 3) & 7) + 8 * r) * 128 + (a_g & 6) * 8; };
    auto radr = [&](uint32_t o, int k) { return sb + OFF_H + (o ^ ((o >> 3) & 0x70) ^ ((k >> 1) << 6)); };
    auto fin = [&](float (&acc)[32], uint32_t* x, int k) {
#pragma unroll
      for (int i = 0; i < 4; i++) { const int c = 16 * (k >> 1) + 4 * i + 2 * (k & 1); x[i] = u2(__hadd2(b2(x[i]), b2(pack_bf16(silu_h(acc[c]), silu_h(acc[c + 1]))))); } };
#pragma unroll 1
    for (int t = 0;; t++) {
#pragma unroll 1
      for (; cnt > 0; cnt--) { body(IC<0>());
      }
      if (!(t & 1)) {
        ownp = own; a_g += 64;
        if (t == 6) break;
        pe = pol_first();
        own = lds16(a_g) * 0x10001u;
        if (t == 2) { const uint32_t a = ((a_g & 16) ? p2 : sb + OFF_WD) + ((a_g << 6) & 0x380) + (qa0 & 0x70);
#pragma unroll
          for (int j = 0; j < 4; j++) ldsm4t(bp + 4 * j, a ^ (j << 5));
        } else {
#pragma unroll
          for (int j = 0; j < 8; j++) bp[2 * j + 1] = sp[j];
        }
        lens >>= 8; cnt = 1;
        continue;
      }
      cnt = (lens & 255) - 1;
      flush();
      if (t == 3) {
        uint32_t x[8];
        pload(x, 1024);
        __syncwarp();
#pragma unroll
        for (int j = 0; j < 4; j++) stsm4((p2 + ((a_g << 6) & 0x780) + (qa0 & 0x70)) ^ (j << 5), sp[2 * j], sum[2 * j], sp[2 * j + 1], sum[2 * j + 1]);
#pragma unroll
        for (int j = 0; j < 8; j++) sum[j] = x[j];
        __syncwarp();
        mbar_arrive(sb + BAR_M + (wid >> 2) * 8, (a_g & 62) == 0);
      }
#pragma unroll
      for (int j = 0; j < 8; j++) { sp[j] = sum[j]; asm volatile("mov.b32 %0, 0;" : "=r"(sum[j])); }
    }
    {
      uint32_t hf[16], v[16]; float acc[32];
      const uint32_t nd = lds16(sb + OFF_GP + wid * 256 + (lane & 15) * 8 + 134), o[2] = {roff(nd, 0), roff(nd, 1)};
      hload(hf, nd);
#pragma unroll
      for (int k = 0; k < 4; k++) lds128(v + 4 * k, radr(o[k & 1], k));
      mbar_wait(sb + BAR_WH);
      wg_fence(); mma_h(acc, hf); wg_commit();
      body(IC<2>());
      STAMP(9);
      flush();
      __syncwarp();
      mbar_arrive(sb + BAR_X, lane == 0);
      wg_fence();
      mma_m(acc);
#pragma unroll
      for (int k = 0; k < 4; k++) { fin(acc, v + 4 * k, k);
        asm volatile("{.reg .pred p; setp.lt.u32 p, %5, %6; @p st.global.v4.b32 [%0], {%1,%2,%3,%4};}" :: "l"((const char*)p.out + (size_t)node0 * 128 + o[k & 1] + (k >> 1) * 64), "r"(v[4 * k]), "r"(v[4 * k + 1]), "r"(v[4 * k + 2]), "r"(v[4 * k + 3]), "r"(o[k & 1]), "r"(nloc * 128) : "memory"); }
    }
    asm volatile("{.reg .pred p, q; setp.neu.f32 p, %1, 0f00000000; setp.ne.or.u32 p, %2, 0, p; bar.red.or.pred q, 5, 512, p; selp.u32 %0, 1, 0, q;}" : "=r"(bad) : "f"(chk), "r"(lds32(sb + OFF_MISC + 12)) : "memory");
    STAMP(11);
   } else { asm volatile("cp.async.wait_all;" ::: "memory"); bar_sync(5, 384); }
  }
  if (bad) slow_path(p, wid, lane, node0, nloc);
}

}

typedef CUresult (*EncodeFn)(CUtensorMap*, CUtensorMapDataType, cuuint32_t, void*, const cuuint64_t*, const cuuint64_t*, const cuuint32_t*, const cuuint32_t*,
                             CUtensorMapInterleave, CUtensorMapSwizzle, CUtensorMapL2promotion, CUtensorMapFloatOOBfill);

extern "C" void kernel_launch(void* const* d_in, const int* in_sizes, int n_in, void* d_out, int out_size) {
  Params p; Maps maps;
  p.h = (const uint4*)d_in[0]; p.pos = (const uint16_t*)d_in[1]; p.ea = (const uint4*)d_in[2];
  p.src = (const int*)d_in[3]; p.dst = (const int*)d_in[4];
  p.we = (const uint16_t*)d_in[5]; p.wx = (const uint16_t*)d_in[6]; p.wh = (const uint16_t*)d_in[7];
  p.out = (uint16_t*)d_out;
  p.N = in_sizes[0] / 64; p.E = in_sizes[3];
  p.EPC = ((p.E + G * 4 - 1) / (G * 4)) * 4;
  p.magic = (uint32_t)(((uint64_t)G << 24) / (uint64_t)p.N);
  p.inv = (1ull << 56) / p.magic;
  const uint64_t ea0 = (uint64_t)d_in[2], ea1 = ea0 + (uint64_t)p.E * 32 - 1;
  p.force_slow = ((ea0 >> 32) != (ea1 >> 32)) || (ea0 & 31) || (p.E & 3);
  void* qp = nullptr;
  cudaGetSymbolAddress(&qp, g_q);
  p.q = (char*)qp;
  if (((uint64_t)p.q >> 32) != (((uint64_t)p.q + QBYTES) >> 32)) p.q += QBYTES;
  cudaGetSymbolAddress((void**)&p.sync, g_sync); cudaGetSymbolAddress((void**)&p.xe, g_xe);
  cudaGetSymbolAddress((void**)&p.xa, g_xa); cudaGetSymbolAddress((void**)&p.xb, g_xb);
  const int df[10] = {34, 120, 900, 3072, 0, 17, 0xff2, 0xD5C4E6, 0x422000};
  for (int i = 0; i < 10; i++) p.tune[i] = df[i];
  p.qcode = 0x890145a6273bull;
  p.ctam = p.tune[5];
  if ((long long)PFB * PFN > (long long)(p.E / G) * 32) PFB = (p.E / G * 32 / PFN) & ~127;
  void* fn = nullptr; cudaDriverEntryPointQueryResult qr;
  cudaGetDriverEntryPoint("cuTensorMapEncodeTiled", &fn, cudaEnableDefault, &qr);
  auto mk = [&](CUtensorMap* tm, void* base, int rows, int box = 64) {
    const cuuint64_t dim[2] = {64, (cuuint64_t)rows}, str[1] = {128}; const cuuint32_t bx[2] = {64, (cuuint32_t)box}, es[2] = {1, 1};
    ((EncodeFn)fn)(tm, CU_TENSOR_MAP_DATA_TYPE_BFLOAT16, 2, base, dim, str, bx, es, CU_TENSOR_MAP_INTERLEAVE_NONE, CU_TENSOR_MAP_SWIZZLE_128B,
                   CU_TENSOR_MAP_L2_PROMOTION_NONE, CU_TENSOR_MAP_FLOAT_OOB_FILL_NONE);
  };
  mk(&maps.m[TM_H / 128], d_in[0], p.N); mk(&maps.m[TM_WE / 128], d_in[5], 145); mk(&maps.m[TM_WH / 128], d_in[7], 128); mk(&maps.m[TM_Q / 128], p.q, p.N, 16);
  for (int k = 0; k < 2; k++) {
    void* xp = (void*)(k ? p.xb : p.xa);
    const cuuint64_t dim[2] = {(cuuint64_t)G * 64, (cuuint64_t)G}, str[1] = {(cuuint64_t)G * (128 << k)}; const cuuint32_t bx[2] = {64, (cuuint32_t)(k ? BROWS : G)}, es[2] = {1, 1};
    ((EncodeFn)fn)(&maps.m[TM_XA / 128 + k], k ? CU_TENSOR_MAP_DATA_TYPE_UINT32 : CU_TENSOR_MAP_DATA_TYPE_UINT16, 2, xp, dim, str, bx, es, CU_TENSOR_MAP_INTERLEAVE_NONE,
                   CU_TENSOR_MAP_SWIZZLE_NONE, CU_TENSOR_MAP_L2_PROMOTION_NONE, CU_TENSOR_MAP_FLOAT_OOB_FILL_NONE);
  }
  cudaFuncSetAttribute(egnn_kernel, cudaFuncAttributeMaxDynamicSharedMemorySize, SMEM);
  egnn_kernel<<<G, NTHR, SMEM>>>(p, maps);
}
```

```cpp
#include <cuda_runtime.h>
#include <cuda_bf16.h>
#include <cuda_fp16.h>
#include <cuda.h>
#include <stdint.h>
#pragma nv_diag_suppress 549

#define PFN p.tune[0]
#define PFB p.tune[3]
#define PFNS p.tune[1]
#define PFE p.tune[8]
#define BDEL p.tune[2]
#define DEFNS p.tune[4]
#define CTAM p.ctam
#define QREV p.tune[6]
#define UORD p.tune[7]
#define QCODE p.qcode
#define FIRSTSEQ mu(0); mu(1); fi(0); mu(2); fi(1);
#define BODYSEQ hc(0); fi(2); tl_(); mu(3); un(); ad(1); ad(0); cv(0); mu(4); cv(2); fi(3); cv(1); ex0(); ex1(); cv(3); he(0); fi(4); he(1); \
  mu(5); hc(1); mu(6); fi(5); he(2); ad(2); ex2(); hs(0); ad(3); hs(1); fi(6); mu(7); issue(); hc(2); he(3); hs(3); fi(7); mu(0); \
  hs(2); he(4); he(5); ad(5); ad(4); hs(4); fi(0); he(6); mu(1); hc(3); he(7); fi(1); ad(6); hs(7); hs(5); ad(7); hs(6); mu(2); \
  pf();
#define LASTSEQ hc(0); fi(2); mu(3); un(); ad(1); ad(0); mu(4); fi(3); fi(4); mu(5); hc(1); mu(6); fi(5); ad(2); ad(3); fi(6); mu(7); hc(2); \
  fi(7); ad(5); ad(4); hc(3); ad(6); ad(7); pf();
namespace {

constexpr int G = 132;
constexpr int NTHR = 512, NWK = 352, NCH = 5;
constexpr int NST = 3, STG = 2560;
constexpr int BROWS = 44, RNB = 2, PADM = 33;
constexpr int SCAP = 448;

constexpr int OFF_H = 0;
constexpr int OFF_W = 49152;
constexpr int OFF_WD = OFF_W + 16384;
constexpr int OFF_W3 = OFF_WD + 1024;
constexpr int OFF_P2 = OFF_W3 + 2048;
constexpr int OFF_RING = OFF_P2 + 24576;
constexpr int OFF_TE = OFF_RING + 12 * NST * STG;
constexpr int OFF_TS = OFF_TE + SCAP * 64;
constexpr int OFF_INV = OFF_TS - 768;
constexpr int OFF_GP = OFF_TS + SCAP * 32;
constexpr int OFF_WX = OFF_GP + 3072;
constexpr int OFF_LEN = OFF_WX + 128;
constexpr int OFF_MISC = OFF_LEN + 128;
constexpr int OFF_BAR = OFF_MISC + 48;
constexpr int SMEM = OFF_BAR + 256;
static_assert(SMEM <= 232448, "smem");
constexpr uint32_t sb = 1024;
constexpr int OFF_SRCI = OFF_TE;
constexpr int OFF_SB = OFF_RING, OFF_SA = OFF_SB + 34816, OFF_AX = OFF_SA + 32768, OFF_DST = OFF_H + 24576;
constexpr int OFF_WS = OFF_AX + 17408;
constexpr int OFF_BC = OFF_WS + 2304;
constexpr int OFF_CNT = OFF_P2;
constexpr int OFF_DH = OFF_CNT + 2176;
constexpr int OFF_POS = OFF_DH + 128;
constexpr int OFF_EXT = OFF_POS + 3072;
constexpr int OFF_XB = OFF_EXT + 1024, XPAD = G * 256;
static_assert(OFF_XB + XPAD + 1028 <= OFF_RING + 12 * STG && OFF_XB % 128 == 0 && OFF_BC + 544 <= OFF_TE && OFF_P2 % 1024 == 0 && OFF_SA % 1024 == 0 && SCAP * 64 >= 24576, "staging");
constexpr int BAR_DST = OFF_BAR, BAR_SRC = BAR_DST + 40, BAR_T = BAR_SRC + 24, BAR_W = BAR_T + 48, BAR_PS = BAR_W + 8, BAR_AW = BAR_PS + 8,
              BAR_QP = BAR_AW + 8, BAR_QR = BAR_QP + 8, BAR_HA = BAR_QR + 8, BAR_EP = BAR_HA + 8, BAR_AX = BAR_EP + 8, BAR_AI = BAR_AX + 8, BAR_HB = BAR_AI + 8, BAR_U = BAR_HB + 8, BAR_WH = BAR_U + 8, BAR_M = BAR_WH + 8, BAR_X = BAR_M + 24, BAR_END = BAR_X + 8;
static_assert(BAR_END <= OFF_BAR + 256, "barriers");
constexpr uint32_t QBYTES = 8u << 20;

__device__ __align__(256) uint4 g_xa[G * G * 8];
__device__ __align__(256) uint4 g_xb[G * G * 16];
__device__ __align__(256) uint2 g_xe[G * G * 32];
__device__ __align__(256) uint4 g_q[2 * QBYTES / 16];
__device__ __align__(256) uint32_t g_sync[8];
#define STAMP(k)

struct Maps { CUtensorMap m[6]; };
constexpr int TM_H = 0, TM_WE = 128, TM_WH = 256, TM_Q = 384, TM_XA = 512, TM_XB = 640;
struct Params {
  const int* dst; uint32_t* sync; int E, EPC, N, ctam; unsigned long long inv; uint32_t magic; int force_slow;
  const int* src; const uint16_t* pos; const uint4* ea; const uint16_t* we; const uint16_t* wx; char* q;
  const uint4* xa; const uint4* xb; uint2* xe; uint16_t* out; const uint4* h; const uint16_t* wh;
  int tune[10]; unsigned long long qcode;
};
template<int V> struct IC { static constexpr int value = V; };

#define R32(d) "+f"(d[0]),"+f"(d[1]),"+f"(d[2]),"+f"(d[3]),"+f"(d[4]),"+f"(d[5]),"+f"(d[6]),"+f"(d[7]),"+f"(d[8]),"+f"(d[9]),"+f"(d[10]),"+f"(d[11]),"+f"(d[12]),"+f"(d[13]),"+f"(d[14]),"+f"(d[15]),"+f"(d[16]),"+f"(d[17]),"+f"(d[18]),"+f"(d[19]),"+f"(d[20]),"+f"(d[21]),"+f"(d[22]),"+f"(d[23]),"+f"(d[24]),"+f"(d[25]),"+f"(d[26]),"+f"(d[27]),"+f"(d[28]),"+f"(d[29]),"+f"(d[30]),"+f"(d[31])
#define S32 "{%0,%1,%2,%3,%4,%5,%6,%7,%8,%9,%10,%11,%12,%13,%14,%15,%16,%17,%18,%19,%20,%21,%22,%23,%24,%25,%26,%27,%28,%29,%30,%31}"
#define DI __device__ __forceinline__

constexpr uint64_t DHI = ((uint64_t)(1024 >> 4) << 32) | (1ull << 62);
template<int SD> DI void rs64b(float (&d)[32], uint32_t a0, uint32_t a1, uint32_t a2, uint32_t a3, uint64_t db) {
  asm volatile("wgmma.mma_async.sync.aligned.m64n64k16.f32.bf16.bf16 " S32 ", {%32,%33,%34,%35}, %36, %37, 1, 1, 1;" : R32(d) : "r"(a0), "r"(a1), "r"(a2), "r"(a3), "l"(db), "n"(SD)); }
template<int SD> DI void rs64h(float (&d)[32], uint32_t a0, uint32_t a1, uint32_t a2, uint32_t a3, uint64_t db) {
  asm volatile("wgmma.mma_async.sync.aligned.m64n64k16.f32.f16.f16 " S32 ", {%32,%33,%34,%35}, %36, %37, 1, 1, 1;" : R32(d) : "r"(a0), "r"(a1), "r"(a2), "r"(a3), "l"(db), "n"(SD)); }
template<int SD> DI void ss64(float (&d)[32], uint64_t da, uint64_t db) {
  asm volatile("wgmma.mma_async.sync.aligned.m64n64k16.f32.bf16.bf16 " S32 ", %32, %33, %34, 1, 1, 0, 1;" : R32(d) : "l"(da), "l"(db), "n"(SD)); }
#define R16(d) "+f"(d[0]),"+f"(d[1]),"+f"(d[2]),"+f"(d[3]),"+f"(d[4]),"+f"(d[5]),"+f"(d[6]),"+f"(d[7]),"+f"(d[8]),"+f"(d[9]),"+f"(d[10]),"+f"(d[11]),"+f"(d[12]),"+f"(d[13]),"+f"(d[14]),"+f"(d[15])
#define S16 "{%0,%1,%2,%3,%4,%5,%6,%7,%8,%9,%10,%11,%12,%13,%14,%15}"
template<int SD> DI void rs32b(float (&d)[16], const uint32_t* a, uint64_t db) {
  asm volatile("wgmma.mma_async.sync.aligned.m64n32k16.f32.bf16.bf16 " S16 ", {%16,%17,%18,%19}, %20, %21, 1, 1, 1;" : R16(d) : "r"(a[0]), "r"(a[1]), "r"(a[2]), "r"(a[3]), "l"(db), "n"(SD)); }
DI void rs32h(float (&d)[16], const uint32_t* a, uint64_t db) {
  asm volatile("wgmma.mma_async.sync.aligned.m64n32k16.f32.f16.f16 " S16 ", {%16,%17,%18,%19}, %20, 1, 1, 1, 1;" : R16(d) : "r"(a[0]), "r"(a[1]), "r"(a[2]), "r"(a[3]), "l"(db)); }
DI void fence_regs(float (&d)[16]) { asm volatile("" : R16(d) :: "memory"); }
DI void trap_if(bool c) { asm volatile("{.reg .pred p; setp.eq.u32 p, %0, 0; @p bra.uni LT_%=; trap; LT_%=:}" :: "r"((uint32_t)c)); }
DI void wg_fence() { asm volatile("wgmma.fence.sync.aligned;" ::: "memory"); }
DI void wg_commit() { asm volatile("wgmma.commit_group.sync.aligned;" ::: "memory"); }
DI void wg_wait0() { asm volatile("wgmma.wait_group.sync.aligned 0;" ::: "memory"); }
DI void fence_regs(float (&d)[32]) { asm volatile("" : R32(d) :: "memory"); }
DI void proxy_fence() { asm volatile("fence.proxy.async.shared::cta;" ::: "memory"); }
DI uint64_t pol_first() { uint64_t r; asm("createpolicy.fractional.L2::evict_first.b64 %0, 1.0;" : "=l"(r)); return r; }
DI float tanh_ap(float x) { float y; asm("tanh.approx.f32 %0, %1;" : "=f"(y) : "f"(x)); return y; }
DI float silu_h(float y) { return fmaf(y, tanh_ap(y), y); }
DI uint32_t pack_bf16(float lo, float hi) { uint32_t r; asm("cvt.rn.bf16x2.f32 %0, %1, %2;" : "=r"(r) : "f"(hi), "f"(lo)); return r; }
DI uint32_t pack_f16(float lo, float hi) { uint32_t r; asm("cvt.rn.f16x2.f32 %0, %1, %2;" : "=r"(r) : "f"(hi), "f"(lo)); return r; }
DI float bf_lo(uint32_t v) { return __uint_as_float(v << 16); }
DI float bf_hi(uint32_t v) { return __uint_as_float(v & 0xFFFF0000u); }
DI uint32_t b2h(uint32_t v, float s) { return pack_f16(s * bf_lo(v), s * bf_hi(v)); }
DI void mbar_wait(uint32_t bar, uint32_t parity = 0) {
  asm volatile("{.reg .pred p, q; .reg .u32 c; mov.u32 c, 0;\n"
    "LW_%=: mbarrier.try_wait.parity.shared::cta.b64 p, [%0], %1;\n add.u32 c, c, 1; setp.lt.and.u32 q, c, 0x200000, !p;\n @q bra.uni LW_%=;}" :: "r"(bar), "r"(parity) : "memory");
}
DI void mbar_arrive(uint32_t bar, int p = 1) { asm volatile("{.reg .pred p; setp.ne.b32 p, %1, 0; @p mbarrier.arrive.shared::cta.b64 _, [%0];}" :: "r"(bar), "r"(p) : "memory"); }
DI void bar_sync(int id, int n) { asm volatile("bar.sync %0, %1;" :: "r"(id), "r"(n) : "memory"); }
DI void bar_arrive(int id, int n) { asm volatile("bar.arrive %0, %1;" :: "r"(id), "r"(n) : "memory"); }
DI __nv_bfloat162 b2(uint32_t v) { return *(__nv_bfloat162*)&v; }
DI uint32_t u2(__nv_bfloat162 v) { return *(uint32_t*)&v; }
DI uint32_t hsq(uint32_t v) { return u2(__hmul2(b2(v), b2(v))); }
DI uint32_t hsub(uint32_t a, uint32_t b) { return u2(__hsub2(b2(a), b2(b))); }
DI uint32_t hhalf(uint32_t v) { return u2(__hmul2(b2(v), __floats2bfloat162_rn(0.5f, 0.5f))); }
DI uint32_t mag2(uint32_t m, uint32_t v) { return __vmaxu2(m, v & 0x7FFF7FFFu); }
DI uint32_t hmag(uint32_t m, uint32_t v) { const __half2 r = __hmax2(*(const __half2*)&m, __habs2(*(const __half2*)&v)); return *(const uint32_t*)&r; }
DI uint32_t magr(uint32_t m) { return max(m & 0xFFFF, m >> 16); }
DI void sts128(uint32_t a, uint32_t x, uint32_t y, uint32_t z, uint32_t w) { asm volatile("st.shared.v4.u32 [%0], {%1,%2,%3,%4};" :: "r"(a), "r"(x), "r"(y), "r"(z), "r"(w) : "memory"); }
DI void sts64(uint32_t a, uint32_t x, uint32_t y) { asm volatile("st.shared.v2.u32 [%0], {%1,%2};" :: "r"(a), "r"(x), "r"(y) : "memory"); }
DI void sts32(uint32_t a, uint32_t x) { asm volatile("st.shared.u32 [%0], %1;" :: "r"(a), "r"(x) : "memory"); }
DI void sts16(uint32_t a, uint32_t x) { asm volatile("st.shared.u16 [%0], %1;" :: "r"(a), "h"((uint16_t)x) : "memory"); }
DI void lds128(uint32_t* v, uint32_t a) { asm volatile("ld.shared.v4.u32 {%0, %1, %2, %3}, [%4];" : "=r"(v[0]), "=r"(v[1]), "=r"(v[2]), "=r"(v[3]) : "r"(a) : "memory"); }
DI void lds64(uint32_t& x, uint32_t& y, uint32_t a) { asm volatile("ld.shared.v2.u32 {%0, %1}, [%2];" : "=r"(x), "=r"(y) : "r"(a) : "memory"); }
DI uint32_t lds32(uint32_t a) { uint32_t x; asm volatile("ld.shared.u32 %0, [%1];" : "=r"(x) : "r"(a) : "memory"); return x; }
DI uint32_t lds16(uint32_t a) { uint32_t x; asm volatile("ld.shared.u16 %0, [%1];" : "=r"(x) : "r"(a) : "memory"); return x; }
DI uint32_t atoms_add(uint32_t a, uint32_t v) { uint32_t r; asm volatile("atom.shared.add.u32 %0, [%1], %2;" : "=r"(r) : "r"(a), "r"(v) : "memory"); return r; }
DI void bulk_load(uint32_t dst, const void* src, uint32_t bytes, uint32_t bar) {
  asm volatile("cp.async.bulk.shared::cluster.global.mbarrier::complete_tx::bytes.L2::cache_hint [%0], [%1], %2, [%3], %4;" :: "r"(dst), "l"(src), "r"(bytes), "r"(bar), "l"(pol_first()) : "memory"); }
DI void mbar_expect(uint32_t bar, uint32_t bytes) { asm volatile("mbarrier.arrive.expect_tx.shared::cta.b64 _, [%0], %1;" :: "r"(bar), "r"(bytes) : "memory"); }
DI void mbar_init(uint32_t bar, int n) { asm volatile("mbarrier.init.shared::cta.b64 [%0], %1;" :: "r"(bar), "r"(n) : "memory"); }
DI void tma_load(uint32_t dst, uint64_t tm, int row, uint32_t bar) {
  asm volatile("cp.async.bulk.tensor.2d.shared::cluster.global.mbarrier::complete_tx::bytes.L2::cache_hint [%0], [%1, {%3, %4}], [%2], %5;" :: "r"(dst), "l"(tm), "r"(bar), "r"(0), "r"(row), "l"(pol_first()) : "memory"); }
DI void tma_store(uint64_t tm, int col, int row, uint32_t src) {
  asm volatile("cp.async.bulk.tensor.2d.global.shared::cta.bulk_group [%0, {%2, %3}], [%1];" :: "l"(tm), "r"(src), "r"(col), "r"(row) : "memory"); }
DI void bulk_commit() { asm volatile("cp.async.bulk.commit_group;" ::: "memory"); }
DI uint2 ld_poll2(const void* a) { uint2 v; asm volatile("ld.relaxed.gpu.global.v2.u32 {%0, %1}, [%2];" : "=r"(v.x), "=r"(v.y) : "l"(a) : "memory"); return v; }
DI void st_ext(uint2* a, uint32_t v, uint32_t ep) { asm volatile("st.relaxed.gpu.global.v2.u32 [%0], {%1, %2};" :: "l"(a), "r"(v), "r"(ep) : "memory"); }
DI uint32_t ext_get(const uint2* a, uint32_t ep) { uint2 v; int spin = 0; do { v = ld_poll2(a); trap_if(++spin > 4000000); } while (__any_sync(~0u, v.y != ep)); return v.x; }
DI void bulk_wait() { asm volatile("cp.async.bulk.wait_group 0;" ::: "memory"); }
DI void hint_signal(uint32_t* c) { asm volatile("red.relaxed.gpu.global.add.u32 [%0], 1;" :: "l"(c) : "memory"); }
DI void hint_wait(const uint32_t* c, uint32_t target) { uint32_t v; int spin = 0;
  do { asm volatile("ld.relaxed.gpu.global.u32 %0, [%1];" : "=r"(v) : "l"(c) : "memory"); trap_if(++spin > 4000000); } while (__any_sync(~0u, (int)(v - target) < 0)); }
DI void stsm4(uint32_t a, uint32_t x, uint32_t y, uint32_t z, uint32_t w) { asm volatile("stmatrix.sync.aligned.m8n8.x4.shared.b16 [%0], {%1,%2,%3,%4};" :: "r"(a), "r"(x), "r"(y), "r"(z), "r"(w) : "memory"); }
DI void ldsm4(uint32_t* v, uint32_t a) { asm volatile("ldmatrix.sync.aligned.m8n8.x4.shared.b16 {%0,%1,%2,%3}, [%4];" : "=r"(v[0]), "=r"(v[1]), "=r"(v[2]), "=r"(v[3]) : "r"(a) : "memory"); }
DI void ldsm4t(uint32_t* v, uint32_t a) { asm volatile("ldmatrix.sync.aligned.m8n8.x4.trans.shared.b16 {%0,%1,%2,%3}, [%4];" : "=r"(v[0]), "=r"(v[1]), "=r"(v[2]), "=r"(v[3]) : "r"(a) : "memory"); }
DI uint32_t mad16(uint32_t x, uint32_t m, uint32_t c) { uint32_t r; asm("dp2a.lo.u32.u32 %0, %1, %2, %3;" : "=r"(r) : "r"(x), "r"(m), "r"(c)); return r; }
DI bool wbad(uint32_t m, uint32_t hi) { return m > hi || (m && m < 0x3980); }

__device__ __noinline__ void slow_path(const Params& p, int wid, int lane, int node0, int nloc) {
  const uint32_t ab = sb + OFF_P2 + wid * 8704;
  for (int i = lane; i < 32 * 68; i += 32) sts32(ab + i * 4, 0);
  __syncwarp();
  const uint32_t wdv = __ldg((const uint32_t*)(p.we + 128 * 64) + lane), wxv = __ldg((const uint32_t*)p.wx + lane);
  const int nb0 = node0 + wid * 32, cntn = max(0, min(32, nloc - wid * 32));
  auto dot = [&](uint32_t hv, const uint16_t* w, int K2, float& y0, float& y1) {
#pragma unroll 4
    for (int k = 0; k < K2; k++) {
      const uint32_t hk = __shfl_sync(~0u, hv, k), wa = __ldg((const uint32_t*)(w + 2 * k * 64) + lane), wb = __ldg((const uint32_t*)(w + (2 * k + 1) * 64) + lane);
      y0 = fmaf(bf_lo(hk), bf_lo(wa), fmaf(bf_hi(hk), bf_lo(wb), y0)); y1 = fmaf(bf_lo(hk), bf_hi(wa), fmaf(bf_hi(hk), bf_hi(wb), y1));
    }
  };
  auto silu = [](float x) { return x / (1.f + __expf(-x)); };
#pragma unroll 1
  for (int base = 0; base < p.E; base += 32) {
    const int e = base + lane;
    const uint32_t dl = e < p.E ? (uint32_t)(__ldg(p.dst + e) - nb0) : 0xFFFFFFFFu;
    uint32_t mk = __ballot_sync(~0u, dl < (uint32_t)cntn);
    while (mk) {
      const int l = __ffs(mk) - 1; mk &= mk - 1;
      const int ee = base + l, n = __shfl_sync(~0u, dl, l), s = __ldg(p.src + ee);
      const uint16_t *po = p.pos + (size_t)(nb0 + n) * 3, *pp = p.pos + (size_t)s * 3;
      const uint32_t dxy = hsub(__ldg(po) | (__ldg(po + 1) << 16), __ldg(pp) | (__ldg(pp + 1) << 16)), dz = hsub(__ldg(po + 2), __ldg(pp + 2));
      const uint32_t sq = hsq(dxy); const float d2 = bf_lo(sq) + bf_hi(sq) + bf_lo(hsq(dz));
      float y0 = d2 * bf_lo(wdv), y1 = d2 * bf_hi(wdv);
      dot(__ldg((const uint32_t*)(p.h + (size_t)(nb0 + n) * 8) + lane), p.we, 32, y0, y1);
      dot(__ldg((const uint32_t*)(p.h + (size_t)s * 8) + lane), p.we + 64 * 64, 32, y0, y1);
      dot(__ldg((const uint32_t*)(p.ea + (size_t)ee * 2) + (lane & 7)), p.we + 129 * 64, 8, y0, y1);
      const uint32_t mm = pack_bf16(silu(y0), silu(y1));
      float c = bf_lo(mm) * bf_lo(wxv) + bf_hi(mm) * bf_hi(wxv);
#pragma unroll
      for (int o = 16; o; o >>= 1) c += __shfl_xor_sync(~0u, c, o);
      const uint32_t a = ab + n * 272;
      uint32_t x0, x1; lds64(x0, x1, a + lane * 8);
      sts64(a + lane * 8, __float_as_uint(__uint_as_float(x0) + bf_lo(mm)), __float_as_uint(__uint_as_float(x1) + bf_hi(mm)));
      if (lane < 3) { const float df = lane == 0 ? bf_lo(dxy) : lane == 1 ? bf_hi(dxy) : bf_lo(dz); sts32(a + 256 + lane * 4, __float_as_uint(fmaf(c, df, __uint_as_float(lds32(a + 256 + lane * 4))))); }
    }
  }
  __syncwarp();
#pragma unroll 1
  for (int n = 0; n < cntn; n++) {
    uint32_t x0, x1; lds64(x0, x1, ab + n * 272 + lane * 8);
    const uint32_t hv = __ldg((const uint32_t*)(p.h + (size_t)(nb0 + n) * 8) + lane);
    float y0 = 0.f, y1 = 0.f;
    dot(hv, p.wh, 32, y0, y1); dot(pack_bf16(__uint_as_float(x0), __uint_as_float(x1)), p.wh + 64 * 64, 32, y0, y1);
    ((uint32_t*)p.out)[(size_t)(nb0 + n) * 32 + lane] = u2(__hadd2(b2(hv), b2(pack_bf16(silu(y0), silu(y1)))));
    if (lane < 3) p.out[(size_t)p.N * 64 + (size_t)(nb0 + n) * 3 + lane] = (uint16_t)pack_bf16(bf_lo(__ldg(p.pos + (size_t)(nb0 + n) * 3 + lane)) + __uint_as_float(lds32(ab + n * 272 + 256 + lane * 4)), 0.f);
  }
}

__global__ void __launch_bounds__(NTHR, 1) egnn_kernel(const __grid_constant__ Params p, const __grid_constant__ Maps maps) {
  const uint64_t tmb = (uint64_t)&maps;
  extern __shared__ __align__(1024) unsigned char smraw[];
  const int tid = threadIdx.x, cta = blockIdx.x * CTAM % G;
  const int e0 = cta * p.EPC, n4 = max(0, min(p.EPC, p.E - e0)) >> 2;
  STAMP(0);
  if (tid == NWK) {
#pragma unroll 1
    for (int k = 0; k < NCH; k++) { const int nb = max(0, min(NWK, n4 - k * NWK)) * 16;
      mbar_init(sb + BAR_DST + k * 8, 1);
      asm volatile("fence.mbarrier_init.release.cluster;" ::: "memory");
      mbar_expect(sb + BAR_DST + k * 8, nb);
      if (nb) bulk_load(sb + OFF_DST + k * NWK * 16, (const char*)(p.dst + e0) + k * NWK * 16, nb, sb + BAR_DST + k * 8); }
  }
  const int lane = tid & 31, wid = __shfl_sync(~0u, tid >> 5, 0), w = wid & 3;
  asm volatile("{.reg .pred p; setp.eq.u32 p, %2, 384; @p cp.async.cg.shared.global [%0], [%1], 16;}" :: "r"(sb + OFF_LEN - 192 + (tid >> 1)), "l"(p.sync), "r"(tid & 415) : "memory");

  auto first_node = [&](int c) { return (int)((c * p.inv + 0xFFFFFFFFull) >> 32); };
  const int node0 = first_node(cta), nloc = min(first_node(cta + 1), p.N) - node0;
  const uint32_t ealo = (uint32_t)(uint64_t)p.ea;
  const int epad = min(e0, p.E - 1);
  if (wid >= 12) {
    const int t = tid - 384;
    auto load_h = [&](int b) { mbar_expect(sb + BAR_T + b * 8, 8192); tma_load(sb + OFF_H + b * 8192, tmb + TM_H, node0 + b * 64, sb + BAR_T + b * 8); };
    uint32_t pv[9], ev = 0;
#pragma unroll
    for (int i = 0; i < 3; i++) { const uint16_t* pp = p.pos + (size_t)(node0 + t + 128 * i) * 3;
      pv[3 * i] = pv[3 * i + 1] = pv[3 * i + 2] = 0;
      asm volatile("{.reg .pred p; setp.lt.s32 p, %4, %5;\n @p ld.global.nc.u16 %0, [%3];\n @p ld.global.nc.u16 %1, [%3+2];\n @p ld.global.nc.u16 %2, [%3+4];}"
        : "+r"(pv[3 * i]), "+r"(pv[3 * i + 1]), "+r"(pv[3 * i + 2]) : "l"(pp), "r"(t + 128 * i), "r"(p.N - node0)); }
    asm volatile("{.reg .pred p; setp.lt.u32 p, %3, 8; @p ld.global.nc.u32 %0, [%1]; @p st.global.v4.u32 [%2], {%4, %4, %4, %4};}"
      : "+r"(ev) : "l"((const uint32_t*)(p.ea + (size_t)epad * 2) + t), "l"(p.q + (size_t)(p.N + cta * PADM) * 128 + t * 16), "r"(t), "r"(0xF700F700u) : "memory");
    asm volatile("cp.async.wait_all;" ::: "memory");
    __syncwarp();
    const uint32_t e = lds32(sb + OFF_LEN + 8 + w * 16) + 1;
    {
      const uint32_t tg = (1 + e % 3) << 30, v = ((tg >> 16) + 512 + (lane & 7) * 4) * 0x10001u;
      if (t == 0) sts32(sb + OFF_MISC + 32, e);
#pragma unroll
      for (int i = 0; i < 9; i++) sts128(sb + OFF_SA + t * 16 + i * 2048, v, v + 0x10001u, v + 0x20002u, v + 0x30003u);
      bar_sync(6, NTHR);
      mbar_arrive(sb + BAR_EP, lane == 0);
#pragma unroll
      for (int i = 0; i < 17; i++) sts128(sb + OFF_SB + t * 16 + i * 2048, tg, tg, tg, tg); }
    uint32_t mp = 0;
#pragma unroll
    for (int i = 0; i < 3; i++) { sts64(sb + OFF_POS + (t + 128 * i) * 8, pv[3 * i] | (pv[3 * i + 1] << 16), pv[3 * i + 2]); mp = mag2(mag2(mp, pv[3 * i] | (pv[3 * i + 1] << 16)), pv[3 * i + 2]); }
    proxy_fence();
    __syncwarp();
    mbar_arrive(sb + BAR_PS, lane == 0);
    mbar_wait(sb + BAR_W);
    {
      uint32_t v[4], u[4]; const int r = t >> 3, c = t & 7;
      lds128(v, sb + OFF_WS + 128 + t * 16); lds128(u, sb + OFF_WS + c * 16);
      const uint32_t x = lds32(sb + OFF_WS + 2176 + lane * 4);
      sts128(sb + OFF_W3 + r * 128 + ((c ^ (r & 7)) << 4), b2h(v[0], .5f), b2h(v[1], .5f), b2h(v[2], .5f), b2h(v[3], .5f));
      const float s = ((r & 1) || r == 6) ? 0.f : .5f;
      if (t < 64) sts128(sb + OFF_WD + r * 128 + ((c ^ r) << 4), b2h(u[0], s), b2h(u[1], s), b2h(u[2], s), b2h(u[3], s));
      if (t < 32) sts32(sb + OFF_WX + (t & 3) * 32 + (t >> 2) * 4, b2h(x, 1.f));
      const uint32_t m3 = __reduce_max_sync(~0u, magr(mag2(mag2(mag2(mag2(0, v[0]), v[1]), v[2]), v[3]))), md = __reduce_max_sync(~0u, magr(mag2(mag2(mag2(mag2(0, u[0]), u[1]), u[2]), u[3])));
      if (wbad(m3, 0x4000) || wbad(md, 0x4000) || wbad(__reduce_max_sync(~0u, magr(mag2(0, x))), 0x4700) || magr(mp) >= 0x4200 || magr(mag2(0, ev)) >= 0x4380) sts32(sb + OFF_MISC + 8, 1);
    }
    if (w == 1) {
#pragma unroll 1
      for (int b = 0; b < 3; b++) { mbar_wait(sb + BAR_SRC + b * 8); if (lane == 0) load_h(b); }
    }
    bar_sync(3, 128);
    const uint32_t frag = (w * 16 + (lane & 15)) * 128 + (((lane >> 4) ^ (lane & 7)) << 4);
    uint32_t mq = 0; int pfi = 0;
    auto prefetch_e = [&]() {
      const uint32_t nb = PFB;
      if (lane == 0 && nb) asm volatile("cp.async.bulk.prefetch.L2.global [%0], %1;" :: "l"((const char*)p.ea + (size_t)(pfi * G + cta) * nb), "r"(nb) : "memory");
      pfi++; };
#pragma unroll 1
    for (int b = 0; b < 6; b++) {
      float acc[32];
      const uint64_t da = DHI | (((sb + OFF_H) >> 4) + b * 512), db = DHI | ((sb + OFF_W) >> 4);
      const uint32_t v0 = lds16(sb + OFF_POS + b * 512 + w * 128 + lane * 2), v1 = lds16(sb + OFF_POS + 64 + b * 512 + w * 128 + lane * 2);
      mbar_wait(sb + BAR_T + b * 8);
      if (b == 0) STAMP(25);
      if (b == 5) STAMP(26);
      wg_fence();
      ss64<0>(acc, da, db); ss64<1>(acc, da + 2, db + 128); ss64<1>(acc, da + 4, db + 256); ss64<1>(acc, da + 6, db + 384);
      wg_commit();
      if (b == 0) mbar_wait(sb + BAR_AW);
      if (t == 32 && b < 3) load_h(b + 3);
      if (w == 1) for (int k = PFE >> (4 * b) & 15; k > 0; k--) prefetch_e();
      __syncwarp();
      uint32_t ff[6], fg[6];
#pragma unroll
      for (int j = 0; j < 6; j++) { ff[j] = (__byte_perm((j & 1) ? v1 : v0, 0, 0x4140) >> (3 * (j >> 1))) & 0x00070007u; fg[j] = __vsub2(0x00040004u, ff[j]);
        asm volatile("" : "+r"(ff[j]), "+r"(fg[j])); }
      wg_wait0(); fence_regs(acc);
      uint32_t o[16];
#pragma unroll
      for (int j = 0; j < 16; j++) o[j] = pack_f16(.5f * acc[2 * j], .5f * acc[2 * j + 1]);
#pragma unroll
      for (int j = 0; j < 6; j++) {
        const uint32_t m = o[j] & 0x7FFF7FFFu; mq = __vmaxu2(mq, m);
        o[j] = (__viaddmax_s16x2(m, fg[j], 0) & 0xFFF8FFF8u) | ff[j] | (o[j] & 0x80008000u); }
      if (b == 4) mbar_wait(sb + BAR_AX);
      const uint32_t qs = sb + OFF_SA + b * 8192;
#pragma unroll
      for (int j = 0; j < 4; j++) stsm4((qs + frag) ^ (j << 5), o[4 * j], o[4 * j + 1], o[4 * j + 2], o[4 * j + 3]);
      proxy_fence();
      __syncwarp();
      if (lane == 0 && b * 64 + w * 16 < nloc) tma_store(tmb + TM_Q, 0, node0 + b * 64 + w * 16, qs + w * 2048);
    }
    if (lane == 0) bulk_commit();
    { const uint32_t m = __reduce_max_sync(~0u, magr(mq)); if (lane == 0) sts32(sb + OFF_MISC + 16 + w * 4, m); }
    asm volatile("setmaxnreg.dec.sync.aligned.u32 56;");
    bulk_wait();
    bar_sync(3, 128);
    if (w == 0) {
      STAMP(18);
      uint32_t mv[4]; lds128(mv, sb + OFF_MISC + 16);
      const uint32_t mx = max(max(mv[0], mv[1]), max(mv[2], mv[3]));
      mbar_arrive(sb + BAR_QR, lane == 0);
      STAMP(19);
      if (lane == 0) {
        if (nloc > 0 && (mx >= 0x7BF0 || mx < 0x1400)) asm volatile("st.relaxed.gpu.global.u32 [%0+4], %1;" :: "l"(p.sync), "r"(e) : "memory");
        asm volatile("red.release.gpu.global.add.u32 [%0], 1;" :: "l"(p.sync) : "memory");
      }
      __syncwarp();
      uint32_t c, f; int spin = 0;
      do { asm volatile("ld.acquire.gpu.global.v2.u32 {%0, %1}, [%2];" : "=r"(c), "=r"(f) : "l"(p.sync) : "memory"); trap_if(++spin > 4000000); } while (__any_sync(~0u, (int)(c - e * G) < 0));
      if (f == e) sts32(sb + OFF_MISC + 8, 1);
      if (cta == 0 && lane == 0) asm volatile("st.relaxed.gpu.global.u32 [%0+8], %1;" :: "l"(p.sync), "r"(e) : "memory");
      STAMP(20);
      __syncwarp();
      mbar_arrive(sb + BAR_QP, lane == 0);
    }
    if (w == 2) {
      const uint32_t tg = (1 + e % 3) << 30;
      hint_wait(p.sync + 5, e * G);
      if (lane == 0) { mbar_expect(sb + BAR_HB, XPAD);
#pragma unroll 1
        for (int o = 0; o < 4; o++) bulk_load(sb + OFF_XB + o * (G * 64), (const char*)p.xb + (size_t)(cta * 4 + o) * (G * 64), G * 64, sb + BAR_HB); }
      STAMP(21);
      bar_sync(7, 384);
      sts32(sb + OFF_XB + XPAD, tg + p.N + cta * PADM);
      const uint32_t nx = __shfl_sync(~0u, lds32(sb + OFF_MISC + 8) ? 0 : lds32(sb + OFF_MISC + 4), 0);
#pragma unroll 1
      for (uint32_t k = 0; k < nx; k += 32) {
        const uint32_t i = min(k + lane, nx - 1), xr = lds32(sb + OFF_EXT + i * 4), row = (xr >> 9) & 255;
        const uint32_t v = ext_get(p.xe + (cta * G + row) * 32 + ((xr >> 17) & 31), e), x = lds32(sb + OFF_CNT + (xr & 511) * 4) + (xr >> 22) * 16;
        sts32(sb + OFF_XB + XPAD + 4 + i * 4, v); sts16(sb + OFF_TS + x, XPAD + 4 + i * 4);
        sts32(sb + OFF_TE + x * 2, mad16(v, 0x2000u, ealo - (tg >> 11) + row * p.EPC * 32));
      }
      __syncwarp();
      mbar_arrive(sb + BAR_HB, lane == 0);
    }
    if (w == 1) {
#pragma unroll 1
      while (pfi < PFN) { prefetch_e(); __nanosleep(PFNS); }
    }
    if (t == 96) { mbar_expect(sb + BAR_U, 8192); tma_load(sb + OFF_W, tmb + TM_WH, 0, sb + BAR_U); }
    __syncwarp();
    bar_sync(4, NTHR);
    const bool fast = !__shfl_sync(~0u, lds32(sb + OFF_MISC + 8), 0);
    if (fast) {
      mp = 0;
#pragma unroll 1
      for (uint32_t todo = UORD; todo; todo >>= 4) {
        const uint32_t nd = lds16(sb + OFF_GP + (todo & 3) * 1024 + w * 256 + (lane & 15) * 8 + 134), hb = (todo >> 3) & 1;
        const uint64_t b1 = DHI | (((sb + OFF_W + 8192) >> 4) + hb * 4);
        uint32_t f[8]; float acc[16];
#pragma unroll
        for (int j = 0; j < 4; j += 2) {
          const uint32_t a = (sb + OFF_H + nd * 128 + (((nd & 7) << 4) ^ (lane & 16))) ^ (j << 5);
          ldsm4(f, a); ldsm4(f + 4, a ^ 32);
          wg_fence();
          if (j == 0) rs32b<0>(acc, f, b1); else rs32b<1>(acc, f, b1 + 256);
          rs32b<1>(acc, f + 4, b1 + 128 * j + 128);
          wg_commit(); wg_wait0(); fence_regs(acc);
        }
#pragma unroll
        for (int j = 0; j < 8; j++) { f[j] = pack_f16(.5f * acc[2 * j], .5f * acc[2 * j + 1]); mp = hmag(mp, f[j]); }
        const uint32_t a = (sb + OFF_P2 + (todo & 3) * 8192 + frag) ^ (hb << 6);
        stsm4(a, f[0], f[1], f[2], f[3]); stsm4(a ^ 32, f[4], f[5], f[6], f[7]);
      }
      if (magr(mp) >= 0x7000) sts32(sb + OFF_MISC + 12, 1);
    }
    bar_sync(3, 128);
    if (t == 96) { mbar_expect(sb + BAR_U, 8192); tma_load(sb + OFF_W + 8192, tmb + TM_WH, 64, sb + BAR_U); }
    __syncwarp();
    mbar_wait(sb + BAR_U);
    uint32_t mh = 0;
#pragma unroll 1
    for (int i = t; i < 1024; i += 128) {
      uint32_t v[4]; const uint32_t r = (i >> 3) & 7, j = (i ^ r) & 7;
#pragma unroll
      for (int k = 0; k < 4; k++) v[k] = lds32(sb + OFF_W + (i >> 3) * 128 + ((((j & 4) + k) ^ r) << 4) + (j & 3) * 4);
      __syncwarp();
      if (i < 512) sts128(sb + OFF_W + i * 16, hhalf(v[0]), hhalf(v[1]), hhalf(v[2]), hhalf(v[3]));
      else { sts128(sb + OFF_W + i * 16, b2h(v[0], .5f), b2h(v[1], .5f), b2h(v[2], .5f), b2h(v[3], .5f)); mh = mag2(mag2(mag2(mag2(mh, v[0]), v[1]), v[2]), v[3]); } }
    if (wbad(__reduce_max_sync(~0u, magr(mh)), 0x4700)) sts32(sb + OFF_MISC + 12, 1);
    proxy_fence();
    __syncwarp();
    mbar_arrive(sb + BAR_WH, lane == 0);
    if (fast) {
      mbar_wait(sb + BAR_WH);
      float chk = 0.f;
#pragma unroll 1
      for (uint32_t todo = UORD; todo; todo >>= 4) {
        const uint32_t nd = lds16(sb + OFF_GP + (todo & 3) * 1024 + w * 256 + (lane & 15) * 8 + 6), hb = (todo >> 3) & 1;
        const uint64_t b1 = DHI | (((sb + OFF_W) >> 4) + hb * 4);
        uint32_t f[8]; float acc[16];
#pragma unroll
        for (int j = 0; j < 8; j += 2) {
          const uint32_t a = j < 4 ? sb + OFF_H + nd * 128 + (((nd & 7) << 4) ^ (lane & 16)) : sb + OFF_P2 + (todo & 3) * 8192 + frag;
          if (j == 4) mbar_wait(sb + BAR_M + (todo & 3) * 8);
          ldsm4(f, a ^ ((j & 3) << 5)); ldsm4(f + 4, a ^ ((j & 3) << 5) ^ 32);
          wg_fence();
          if (j == 0) rs32b<0>(acc, f, b1); else if (j < 4) rs32b<1>(acc, f, b1 + 128 * j); else rs32h(acc, f, b1 + 128 * j);
          if (j < 4) rs32b<1>(acc, f + 4, b1 + 128 * j + 128); else rs32h(acc, f + 4, b1 + 128 * j + 128);
          wg_commit(); wg_wait0(); fence_regs(acc);
        }
        chk = fmaf(acc[0], 0.f, fmaf(acc[2], 0.f, chk));
#pragma unroll
        for (int k = 0; k < 2; k++) {
          const uint32_t o = __shfl_sync(~0u, nd, (lane >> 2) + 8 * k) * 128 + (lane & 3) * 16 + hb * 64;
          uint32_t x[4]; lds128(x, sb + OFF_H + (o ^ ((o >> 3) & 0x70)));
#pragma unroll
          for (int i = 0; i < 4; i++) x[i] = u2(__hadd2(b2(x[i]), b2(pack_bf16(silu_h(acc[4 * i + 2 * k]), silu_h(acc[4 * i + 2 * k + 1])))));
          if (o < nloc * 128) *(uint4*)((char*)p.out + (size_t)node0 * 128 + o) = make_uint4(x[0], x[1], x[2], x[3]);
        }
        __nanosleep(DEFNS);
      }
      uint32_t pa_[9];
#pragma unroll
      for (int k = 0; k < 9; k++) { const uint32_t i = t + 128 * k, n = (i * 43691u) >> 17; pa_[k] = lds16(sb + OFF_INV + n * 2) + (i - 3 * n) * 2; }
      uint16_t* po = p.out + (size_t)p.N * 64 + node0 * 3 + t;
      mbar_wait(sb + BAR_X);
#pragma unroll
      for (int k = 0; k < 9; k++) pa_[k] = lds16(sb + OFF_GP + pa_[k]);
#pragma unroll
      for (int k = 0; k < 9; k++) if (t + 128 * k < nloc * 3) po[128 * k] = pa_[k];
      asm volatile("{.reg .pred p, q; setp.neu.f32 p, %0, 0f00000000; bar.red.or.pred q, 5, 512, p;}" :: "f"(chk) : "memory");
    }
    return;
  }

  if (tid == 320) {
    mbar_init(sb + BAR_W, 1);
    asm volatile("fence.mbarrier_init.release.cluster;" ::: "memory");
    mbar_expect(sb + BAR_W, 2 * 8192 + 2304);
    tma_load(sb + OFF_W, tmb + TM_WE, 64, sb + BAR_W); tma_load(sb + OFF_W + 8192, tmb + TM_WE, 0, sb + BAR_W);
    bulk_load(sb + OFF_WS, p.we + 128 * 64, 2176, sb + BAR_W); bulk_load(sb + OFF_WS + 2176, p.wx, 128, sb + BAR_W);
  }
  if (tid == 288) {
#pragma unroll
    for (int a = BAR_SRC; a < BAR_END; a += 8) if (a != BAR_W) mbar_init(sb + a, a == BAR_X ? 12 : a >= BAR_WH || a == BAR_PS || a == BAR_EP ? 4 : a == BAR_HB || a == BAR_U ? 2 : 1);
    asm volatile("fence.mbarrier_init.release.cluster;" ::: "memory");
    asm volatile("prefetch.tensormap [%0];" :: "l"(tmb + TM_XA)); asm volatile("prefetch.tensormap [%0];" :: "l"(tmb + TM_H));
    asm volatile("prefetch.tensormap [%0];" :: "l"(tmb + TM_XB)); asm volatile("prefetch.tensormap [%0];" :: "l"(tmb + TM_Q));
  }
  {
    if (tid < 144) { const uint32_t z = (tid >> 3) == 16 ? 0x8000u : 0u; sts128(sb + OFF_CNT + tid * 16, z, z, z, z); }
    else if (tid <= 144 + G) sts32(sb + OFF_BC + (tid - 144) * 4, ((tid - 144) & 31) * 4);
    const uint32_t sp = XPAD * 0x10001u, em = first_node(G);
    if (wid < 7) {
#pragma unroll
      for (int i = 0; i < 4; i++) sts128(sb + OFF_TS + tid * 16 + i * 3584, sp, sp, sp, sp);
    }
    static_assert(SCAP * 32 == 4 * 3584, "fill");
#pragma unroll 1
    for (int i = n4 + tid; i < 1536; i += 384) sts128(sb + OFF_DST + i * 16, em, em, em, em);
    if (tid == 321) sts128(sb + OFF_MISC, 0, 0, p.force_slow, 0);
  }
  bar_arrive(6, NTHR);
  bar_sync(0, 384);
  uint32_t ep, tag, eb0, pk[12], r0[12], r1[12], cb;
  uint2 vb[12];
  auto get_tag = [&]() { mbar_wait(sb + BAR_EP); ep = lds32(sb + OFF_MISC + 32); tag = (1 + ep % 3) << 30; eb0 = ealo - (tag >> 11); };
  if (wid == 11) {
    trap_if(sb != (uint32_t)__cvta_generic_to_shared(smraw));
#pragma unroll 1
    for (int k = 0; k < 3; k++) { const int nb = max(0, min(8192, n4 * 16 - k * 8192));
      mbar_wait(sb + BAR_DST + (k ? k + 1 : 0) * 8);
      if (lane == 0) { mbar_expect(sb + BAR_SRC + k * 8, nb);
        if (nb) bulk_load(sb + OFF_SRCI + k * 8192, (const char*)(p.src + e0) + k * 8192, nb, sb + BAR_SRC + k * 8); } }
    proxy_fence();
    get_tag();
    mbar_wait(sb + BAR_PS);
    bar_sync(12, 384);
    uint32_t xm = 0;
#pragma unroll
    for (int k = 0; k < 5; k++) xm |= (lds32(sb + OFF_BC + min(lane + 32 * k, G - 1) * 4) >= (65 << 9) && lane + 32 * k < G) << k;
    auto ext_send = [&](int pl) {
      uint32_t x = xm;
      for (uint32_t m; (m = __ballot_sync(~0u, x));) {
        const uint32_t l = __ffs(m) - 1, j = l + 32 * (__ffs(__shfl_sync(~0u, x, l)) - 1);
        if (lane == l) x &= x - 1;
        const uint32_t e = min(lds16(sb + OFF_AX + j * 128 + ((4 * l + 2 * lane) & 126)), 6143u);
        if (pl) st_ext(p.xe + (j * G + cta) * 32 + lane, lds32(sb + OFF_SRCI + e * 4) + tag + (e << 16), ep);
        else { const uint32_t cn = lds32(sb + OFF_BC + j * 4) >> 9, v = cn > 96 ? 1 : lane + 64 < cn ? 512 | (lds32(sb + OFF_DST + e * 4) & 511) : 0;
          asm volatile("red.shared.xor.b32 [%0], %1;" :: "r"(sb + OFF_SA + j * 128 + ((l + lane) & 31) * 4), "r"(((v & 63) << 10) | ((v >> 6) << 26)) : "memory"); }
      }
    };
    if (__any_sync(~0u, xm)) { ext_send(0); proxy_fence(); __syncwarp(); }
    if (lane == 0) { tma_store(tmb + TM_XA, cta * 64, 0, sb + OFF_SA); bulk_commit(); mbar_arrive(sb + BAR_AI); bulk_wait(); hint_signal(p.sync + 4); mbar_arrive(sb + BAR_AW); STAMP(16); }
    __syncwarp();
    bar_sync(13, 384);
    ext_send(1);
    mbar_arrive(sb + BAR_AX, lane == 0);
    mbar_wait(sb + BAR_HA);
    __nanosleep(BDEL);
    if (lane == 0) {
#pragma unroll 1
      for (int r = 0; r < G; r += BROWS) { tma_store(tmb + TM_XB, cta * 64, r, sb + OFF_SB + r * 256); bulk_commit(); bulk_wait(); }
      hint_signal(p.sync + 5);
      STAMP(17);
    }
    __syncwarp();
  } else {
    {
      uint32_t d[4 * NCH], jj[4 * NCH], rr[4 * NCH];
      auto count = [&](int k) {
        mbar_wait(sb + BAR_DST + k * 8);
        lds128(d + 4 * k, sb + OFF_DST + (tid + NWK * k) * 16);
#pragma unroll
        for (int i = 4 * k; i < 4 * k + 4; i++) { jj[i] = d[i] * p.magic; rr[i] = atoms_add(__dp4a(jj[i], 0x04000000u, sb + OFF_BC), 0x202u); }
      };
      auto place = [&](int k) {
#pragma unroll
        for (int i = 4 * k; i < 4 * k + 4; i++) {
          const uint32_t o = __dp4a(jj[i], 0x80000000u, rr[i] & 0x807Eu);
          d[i] = (d[i] & 511) | (tag >> 16);
          asm("{.reg .pred p; setp.ge.u32 p, %1, 0x8000; @p add.u32 %0, %2, %3;}" : "+r"(d[i]) : "r"(o), "r"(tid * 4), "r"(NWK * k * 4 + (i & 3)));
          sts16(sb + OFF_SA + o, d[i]); jj[i] = __viaddmin_u32(o, o, G * 256);
        }
      };
      count(0); STAMP(1); count(1); get_tag(); place(0); count(2); place(1); count(3); place(2);
      if (wid < 4) { count(4); STAMP(15); place(3); place(4); } else place(3);
      proxy_fence();
      bar_arrive(12, 384);
      STAMP(2);
      mbar_wait(sb + BAR_AI);
      mbar_wait(sb + BAR_SRC); mbar_wait(sb + BAR_SRC + 8); mbar_wait(sb + BAR_SRC + 16);
      STAMP(12);
#pragma unroll
      for (int k = 0; k < NCH; k++) lds128(d + 4 * k, sb + OFF_SRCI + (tid + NWK * k) * 16);
      const uint32_t tb = tag + (tid << 18);
#pragma unroll
      for (int i = 0; i < 4 * NCH; i++) if (i < 4 * NCH - 4 || wid < 4) sts32(sb + OFF_SB + jj[i], d[i] + tb + ((NWK * (i >> 2) * 4 + (i & 3)) << 16));
      proxy_fence();
      bar_arrive(13, 384);
      STAMP(3);
    }
    const uint32_t rot = (lane + cta) & 31;
    cb = sb + OFF_CNT - (tag >> 14);
    {
      const uint32_t* xa = (const uint32_t*)(p.xa + (cta * G + wid) * 8) + rot;
      if (wid < 8) { const uint32_t e_ = ealo + epad * 32;
        mbar_wait(sb + BAR_AX);
#pragma unroll
        for (int i = 0; i < 7; i++) sts128(sb + OFF_TE + tid * 16 + i * 4096, e_, e_, e_, e_); }
      static_assert(SCAP * 64 == 7 * 4096, "fill");
      if (wid == 10) { hint_wait(p.sync + 4, ep * G); mbar_arrive(sb + BAR_HA, lane == 0); }
      mbar_wait(sb + BAR_HA);
      STAMP(14);
      const uint32_t tp = tag | (tag >> 16);
      uint32_t st;
#pragma unroll 1
      for (int spin = 0;; spin++) {
        st = 0;
#pragma unroll
        for (int k = 0; k < 12; k++) asm volatile("ld.relaxed.gpu.global.u32 %0, [%1];" : "=r"(pk[k]) : "l"(xa + k * 352) : "memory");
#pragma unroll
        for (int k = 0; k < 12; k++) st |= pk[k] ^ tp;
        st = __reduce_or_sync(~0u, st);
        if (!(st >> 30)) break;
        trap_if(spin > 2000000);
      }
      if (st & 0x3C00FC00u) {
#pragma unroll 1
        for (;;) {
          uint32_t x = 0, row = 0;
#pragma unroll
          for (int k = 0; k < 12; k++) { const uint32_t y = (pk[k] ^ tp) & 0x3C00FC00u; if (!x && y) { x = y; row = wid + 11 * k; pk[k] ^= y; } }
          if (!__any_sync(~0u, x)) break;
          const uint32_t n = ((x >> 10) & 63) | ((x >> 20) & 0x1C0);
          if (x >> 29) {
            const uint32_t r = atoms_add(sb + OFF_CNT + n * 4, 16), idx = atoms_add(sb + OFF_MISC + 4, 1);
            if (idx < 256) sts32(sb + OFF_EXT + idx * 4, n | (row << 9) | (lane << 17) | (min(r >> 4, 255u) << 22));
            else x = 1;
          }
          if (x && !(x >> 29)) sts32(sb + OFF_MISC + 8, 1);
          __syncwarp();
        }
      }
#pragma unroll
      for (int k = 0; k < 12; k++) { r0[k] = mad16(pk[k], 0x0004u, cb); r1[k] = mad16(pk[k], 0x0400u, cb); vb[k].x = atoms_add(r0[k], 16); vb[k].y = atoms_add(r1[k], 16); }
    }
    STAMP(4);
    if (wid >= 6) bar_arrive(11, NWK);
    if (wid < 6) {
      uint32_t ca[2], ky[2], dr[2], sq[2], ps[4];
#pragma unroll
      for (int i = 0; i < 2; i++) { ca[i] = sb + OFF_CNT + ((node0 + tid + 192 * i) & 511) * 4; lds64(ps[2 * i], ps[2 * i + 1], sb + OFF_POS + (tid + 192 * i) * 8); ps[2 * i + 1] |= (tid + 192 * i) << 16; }
      bar_sync(11, NWK);
      STAMP(5);
#pragma unroll
      for (int i = 0; i < 2; i++) ky[i] = (lds32(ca[i]) + 16) >> 5;
      if (max(ky[0], ky[1]) > 31) sts32(sb + OFF_MISC + 8, 1);
#pragma unroll
      for (int i = 0; i < 2; i++) { ky[i] = min(ky[i], 31u); dr[i] = atoms_add(sb + OFF_DH + ky[i] * 4, 1); }
      bar_sync(10, 192);
      const uint32_t hv = lds32(sb + OFF_DH + lane * 4);
      uint32_t inc = hv;
#pragma unroll
      for (int o = 1; o < 32; o <<= 1) asm("{.reg .pred p; .reg .b32 y; shfl.sync.down.b32 y|p, %0, %1, 31, -1; @p add.u32 %0, %0, y;}" : "+r"(inc) : "r"(o));
#pragma unroll
      for (int i = 0; i < 2; i++) {
        const uint32_t pos = __shfl_sync(~0u, inc - hv, ky[i]) + dr[i];
        const uint32_t ak = (uint32_t)(QCODE >> ((pos >> 5) * 4)) & 15, l = (pos >> 3) & 3;
        sq[i] = (ak >> 2) * 16 + ((QREV >> (pos >> 5) & 1) ? 3 - l : l) * 4 + (ak & 3);
        dr[i] = pos & 7;
        asm volatile("{.reg .pred p; setp.eq.u32 p, %2, 0; @p st.shared.u8 [%0], %1;}" :: "r"(sb + OFF_LEN + sq[i]), "r"(max(ky[i], 1u)), "r"(dr[i]) : "memory");
        sts64(sb + OFF_GP + sq[i] * 64 + dr[i] * 8, ps[2 * i], ps[2 * i + 1]);
        sts16(sb + OFF_INV + (tid + 192 * i) * 2, sq[i] * 64 + dr[i] * 8);
      }
      bar_sync(10, 192);
      const uint32_t ln = lds32(sb + OFF_LEN + min(lane, 11) * 4), tot = __dp4a(ln, 0x01010101u, 0u);
      inc = tot;
#pragma unroll
      for (int o = 1; o < 16; o <<= 1) asm("{.reg .pred p; .reg .b32 y; shfl.sync.up.b32 y|p, %0, %1, 0, -1; @p add.u32 %0, %0, y;}" : "+r"(inc) : "r"(o));
      if (wid == 1) sts32(sb + OFF_CNT + 2048 + lane * 4, 0);
      if (tid < 12) { sts32(sb + OFF_LEN + 64 + tid * 4, inc - tot); if (inc > SCAP - 12) sts32(sb + OFF_MISC + 8, 1); }
#pragma unroll
      for (int i = 0; i < 2; i++) sts32(ca[i], __dp4a(__shfl_sync(~0u, ln, sq[i] >> 2), 0x00010101u >> (24 - 8 * (sq[i] & 3)), __shfl_sync(~0u, inc - tot, sq[i] >> 2)) * 32 + dr[i] * 2);
    }
    bar_arrive(7, 384);
  }
  bar_sync(1, 384);
  STAMP(6);
  if (wid != 11 && !__shfl_sync(~0u, lds32(sb + OFF_MISC + 8), 0)) {
#pragma unroll
    for (int k = 0; k < 12; k++) { r0[k] = lds32(r0[k]); r1[k] = lds32(r1[k]); }
#pragma unroll
    for (int k = 0; k < 12; k++) { r0[k] += vb[k].x; r1[k] += vb[k].y; }
  } else {
#pragma unroll
    for (int k = 0; k < 12; k++) r0[k] = r1[k] = 0x8000;
  }
  auto put_ids = [&]() {
    const uint32_t id = wid * 256 + ((lane + cta) & 31) * 8;
    auto put = [&](uint32_t x, uint32_t v) { asm volatile("{.reg .pred p; setp.lt.u32 p, %0, 0x8000; @p st.shared.u16 [%0+%2], %1;}" :: "r"(x), "h"((uint16_t)v), "n"(sb + OFF_TS) : "memory"); };
#pragma unroll
    for (int k = 0; k < 12; k++) { put(r0[k], id + k * 2816); put(r1[k], id + k * 2816 + 4); }
  };
  STAMP(7);
  mbar_wait(sb + BAR_QR);
  asm volatile("setmaxnreg.inc.sync.aligned.u32 152;");
  uint32_t pa[8], sp[8]; float chk = 0.f;
  {
    uint32_t hf[16], mp = 0; float a0[32];
    const uint32_t nd = lds16(sb + OFF_GP + wid * 256 + (lane & 15) * 8 + 6);
#pragma unroll
    for (int j = 0; j < 4; j++) ldsm4(hf + 4 * j, (sb + OFF_H + nd * 128 + (((nd & 7) << 4) ^ (lane & 16))) ^ (j << 5));
    const uint64_t db = DHI | ((sb + OFF_W + 8192) >> 4);
    wg_fence();
    rs64b<0>(a0, hf[0], hf[1], hf[2], hf[3], db); rs64b<1>(a0, hf[4], hf[5], hf[6], hf[7], db + 128); rs64b<1>(a0, hf[8], hf[9], hf[10], hf[11], db + 256); rs64b<1>(a0, hf[12], hf[13], hf[14], hf[15], db + 384);
    wg_commit();
    put_ids();
    wg_wait0(); fence_regs(a0);
#pragma unroll
    for (int j = 0; j < 8; j++) { const uint32_t x = pack_f16(.5f * a0[4 * j], .5f * a0[4 * j + 1]), y = pack_f16(.5f * a0[4 * j + 2], .5f * a0[4 * j + 3]); mp = hmag(hmag(mp, x), y);
      asm volatile("movmatrix.sync.aligned.m8n8.trans.b16 %0, %1;" : "=r"(pa[j]) : "r"(x)); asm volatile("movmatrix.sync.aligned.m8n8.trans.b16 %0, %1;" : "=r"(sp[j]) : "r"(y)); }
    if (magr(mp) >= 0x7000) chk = 1.f;
  }
  if (wid == 0) STAMP(23);
  uint32_t bad;
  {
    const uint32_t ring = sb + OFF_RING + wid * STG, p2 = sb + OFF_P2 + wid * 2048;
    uint32_t lens = __shfl_sync(~0u, lds32(sb + OFF_LEN + wid * 4), 0);
    uint32_t rem = __dp4a(lens, 0x20202020u, 0u);
    const uint32_t base = min(lds32(sb + OFF_LEN + 64 + wid * 4), SCAP);
    uint32_t a_s = sb + OFF_TS + base * 32 + (lane >> 3) * 8, a_e = sb + OFF_TE + base * 64 + (lane >> 1) * 4;
    uint32_t k0 = (uint32_t)(uint64_t)p.q + (((lane & 7) ^ ((lane >> 1) & 4)) << 4), k1 = k0 ^ 16, k2 = k0 ^ 32, k3 = k0 ^ 48, ke = ((lane ^ (lane >> 3)) & 1) << 4;
    uint32_t dst0 = ring + (lane >> 3) * 640 + (lane & 7) * 16;
    const uint32_t qhi = (uint32_t)((uint64_t)p.q >> 32), ehi = (uint32_t)((uint64_t)p.ea >> 32);
    uint32_t s0, s1, ev, to = 0, so = 12 * STG;
    auto tl_ = [&]() { lds64(s0, s1, a_s + to); asm volatile("ld.shared.u32 %0, [%1]; add.u32 %1, %1, 64;" : "=&r"(ev), "+r"(a_e) :: "memory"); to += 32; };
#define CPQ(LH, x, k, off) "dp2a." LH ".u32.u32 lo, " x ", 0x80000080, " k "; mov.b64 a, {lo, %7}; @p cp.async.cg.shared.global [%0+" #off "], [a], 16;\n"
    uint64_t pe; asm volatile("createpolicy.fractional.L2::evict_normal.b64 %0, 1.0;" : "=l"(pe));
    uint32_t one = __shfl_sync(~0u, lane, 1);
#define CPE "or.b32 lo, %10, %11; mov.b64 a, {lo, %12}; @p cp.async.cg.shared.global.L2::cache_hint [%0+512], [a], 16, %13;\n"
#define CPA(BODY) asm volatile("{.reg .b32 lo; .reg .b64 a; .reg .pred p; setp.le.u32 p, %8, %9;\n" BODY "}" \
      :: "r"(so * one + dst0), "r"(s0), "r"(s1), "r"(k0), "r"(k1), "r"(k2), "r"(k3), "r"(qhi), "r"(to), "r"(rem), "r"(ev), "r"(ke), "r"(ehi), "l"(pe) : "memory")
#define CPQ4 CPQ("lo", "%1", "%3", 0) CPQ("hi", "%1", "%4", 128) CPQ("lo", "%2", "%5", 256) CPQ("hi", "%2", "%6", 384) "cp.async.commit_group;"
    auto issue = [&]() { CPA(CPE CPQ4); so = so == (NST - 1) * 12 * STG ? 0 : so + 12 * STG; };
    const int g = lane >> 2, qd = lane & 3;
    const uint32_t sw = ((lane >> 4) ^ (lane & 7)) << 4, fr = (lane & 15) * 128 + sw;
    uint32_t qa0 = ring + (g & 3) * 640 + qd * 128 + sw, qa1 = qa0 ^ 32, qa2 = qa0 ^ 64, qa3 = qa0 ^ 96;
    uint32_t eadr = ring + 512 + (g & 3) * 640 + qd * 32 + ((((lane >> 4) ^ g) & 1) << 4);
    uint32_t oh0 = g == 2 * qd ? 0x3C00u : g == 2 * qd + 1 ? 0x3C000000u : 0u, oh1 = oh0;
    uint32_t a_g = sb + OFF_GP + wid * 256 + lane * 2;
    asm volatile("shfl.sync.idx.b32 %0, %0, %1, 31, -1;" : "+r"(oh1) : "r"(lane));
    uint32_t w3[16], wv[8], bp[16], sum[8], Y[16], M[16], own, ownp, dpk, tl[16], th[16];
    float pacc = 0.f;
    auto wload = [&]() {
#pragma unroll
      for (int j = 0; j < 4; j++) ldsm4t(w3 + 4 * j, (sb + OFF_W3 + fr) ^ (j << 5));
      lds128(wv, sb + OFF_WX + (a_g & 6) * 16); lds128(wv + 4, sb + OFF_WX + 16 + (a_g & 6) * 16);
    };
    auto hload = [&](uint32_t (&hf)[16], uint32_t nd) {
      const uint32_t hrow = sb + OFF_H + nd * 128 + (((nd & 7) << 4) ^ ((a_g >> 1) & 16));
#pragma unroll
      for (int j = 0; j < 4; j++) ldsm4(hf + 4 * j, hrow ^ (j << 5));
      return hrow;
    };
    { uint32_t wd[8]; const uint32_t a = sb + OFF_WD + (lane & 7) * 128 + ((((lane >> 3) ^ lane) & 7) << 4);
      ldsm4t(wd, a); ldsm4t(wd + 4, a ^ 64);
#pragma unroll
      for (int j = 0; j < 8; j++) { bp[2 * j] = wd[j]; bp[2 * j + 1] = pa[j]; } }
    own = lds16(a_g) * 0x10001u;
    wload();
    if (__shfl_sync(~0u, lds32(sb + OFF_MISC + 8), 0)) rem = 0;
    auto resolve = [&](auto NBK, uint32_t o) {
      constexpr int NB = decltype(NBK)::value;
      uint32_t id[NB], c0[NB], c1[NB]; const uint32_t a = base * 32 + o + lane * 4;
#pragma unroll
      for (int i = 0; i < NB; i++) { id[i] = lds32(sb + OFF_TS + a + i * 128); if (o + lane * 4 + i * 128 >= rem) id[i] = XPAD * 0x10001u; }
      uint32_t st = 0;
#pragma unroll
      for (int i = 0; i < NB; i++) { c0[i] = lds32(sb + OFF_XB + (id[i] & 0xFFFF)); c1[i] = lds32(sb + OFF_XB + (id[i] >> 16)); }
#pragma unroll
      for (int i = 0; i < NB; i++) st |= (c0[i] ^ tag) | (c1[i] ^ tag);
      for (int spin = 0; __any_sync(~0u, st >> 30); spin++) {
        st = 0; trap_if(spin > 2000000);
#pragma unroll
        for (int i = 0; i < NB; i++) {
          asm volatile("{.reg .pred p, q; setp.lt.u32 p, %4, %6; setp.lt.u32 q, %5, %6; @p ld.relaxed.gpu.global.u32 %0, [%2]; @q ld.relaxed.gpu.global.u32 %1, [%3];}"
            : "+r"(c0[i]), "+r"(c1[i]) : "l"((const char*)p.xb + cta * XPAD + (id[i] & 0xFFFF)), "l"((const char*)p.xb + cta * XPAD + (id[i] >> 16)), "r"(id[i] & 0xFFFF), "r"(id[i] >> 16), "n"(XPAD) : "memory");
          st |= (c0[i] ^ tag) | (c1[i] ^ tag); }
      }
#pragma unroll
      for (int i = 0; i < NB; i++) { const uint32_t j0 = (id[i] >> 8) & 255, j1 = id[i] >> 24;
        asm volatile("{.reg .pred p, q, r; setp.lt.u32 p, %5, %9; setp.lt.u32 q, %6, %9; setp.lt.u32 r, %7, %8;\n"
          "@p st.shared.u32 [%0], %2; @q st.shared.u32 [%0+4], %3; @r st.shared.u32 [%1], %4;}"
          :: "r"(sb + OFF_TE + 2 * a + i * 256), "r"(sb + OFF_TS + a + i * 128), "r"(mad16(c0[i], 0x2000u, eb0 + j0 * p.EPC * 32)), "r"(mad16(c1[i], 0x2000u, eb0 + j1 * p.EPC * 32)),
             "r"(__byte_perm(c0[i], c1[i], 0x5410)), "r"(j0), "r"(j1), "r"(o + lane * 4 + i * 128), "r"(rem), "n"(G) : "memory"); }
    };
    bar_sync(2, 384);
    if (wid == 0) STAMP(27);
    mbar_wait(sb + BAR_HB);
    if (wid == 0) STAMP(22);
#pragma unroll 1
    for (uint32_t o = 0, go = 0; go < 32 * NST; o += 128 * RNB) {
      if (o < rem) { resolve(IC<RNB>(), o);
        asm volatile("{.reg .pred p; mbarrier.test_wait.parity.shared::cta.b64 p, [%1], 0; vote.sync.all.pred p, p, -1; selp.u32 %0, %2, 0, p;}" : "=r"(go) : "r"(sb + BAR_QP), "n"(32 * NST - 32) : "memory"); }
      else { bar_arrive(4, NTHR); bar_sync(8, 384); mbar_wait(sb + BAR_QP); go = 32 * NST; if (wid == 0) STAMP(24); }
      __syncwarp();
#pragma unroll 1
      while (to < go) { tl_(); issue(); if (to == 32) STAMP(13); }
    }
    bad = __shfl_sync(~0u, lds32(sb + OFF_MISC + 8), 0);
   if (!bad) {
    auto body = [&](auto MODE) {
      constexpr int mode = decltype(MODE)::value;
      uint32_t T[16], ef[4], q0, q1, x0, x1, x2; float e0_, e1_, cs[4];
      auto mu = [&](int j) {
#pragma unroll
        for (int i = 2 * j; i < 2 * j + 2; i++) asm volatile("{.reg .b16 l, h; mov.b32 {l, h}, %2; tanh.approx.f16 l, l; tanh.approx.f16 h, h; cvt.u32.u16 %0, l; cvt.u32.u16 %1, h;}" : "=r"(tl[i]), "=r"(th[i]) : "r"(Y[i])); };
      auto fi = [&](int j) {
#pragma unroll
        for (int i = 2 * j; i < 2 * j + 2; i++) asm volatile("{.reg .b32 t; prmt.b32 t, %2, %3, 0x5410; fma.rn.f16x2 %0, %1, t, %1;}" : "=r"(M[i]) : "r"(Y[i]), "r"(tl[i]), "r"(th[i])); };
      auto ad = [&](int j) { asm volatile("add.rn.f16x2 %0, %0, %1; add.rn.f16x2 %0, %0, %2;" : "+r"(sum[j]) : "r"(M[2 * j]), "r"(M[2 * j + 1])); };
      auto he = [&](int j) { asm volatile("mma.sync.aligned.m16n8k16.row.col.f16.f16.f16.f16 {%0,%1}, {%2,%3,%4,%5}, {%6,%7}, {%0,%1};" : "+r"(T[2 * j]), "+r"(T[2 * j + 1]) : "r"(ef[0]), "r"(ef[1]), "r"(ef[2]), "r"(ef[3]), "r"(w3[2 * j]), "r"(w3[2 * j + 1])); };
      auto hs = [&](int j) { asm volatile("mma.sync.aligned.m16n8k16.row.col.f16.f16.f16.f16 {%0,%1}, {%2,%3,%4,%5}, {%6,%7}, {%8,%9};" : "=r"(Y[2 * j]), "=r"(Y[2 * j + 1]) : "r"(q0), "r"(q1), "r"(oh0), "r"(oh1), "r"(bp[2 * j]), "r"(bp[2 * j + 1]), "r"(T[2 * j]), "r"(T[2 * j + 1])); };
      auto hc = [&](int j) {
        if (j) asm volatile("mma.sync.aligned.m16n8k16.row.col.f32.f16.f16.f32 {%0,%1,%2,%3}, {%4,%5,%6,%7}, {%8,%9}, {%0,%1,%2,%3};" : "+f"(cs[0]), "+f"(cs[1]), "+f"(cs[2]), "+f"(cs[3]) : "r"(M[4 * j]), "r"(M[4 * j + 1]), "r"(M[4 * j + 2]), "r"(M[4 * j + 3]), "r"(wv[2 * j]), "r"(wv[2 * j + 1]));
        else asm volatile("mma.sync.aligned.m16n8k16.row.col.f32.f16.f16.f32 {%0,%1,%2,%3}, {%4,%5,%6,%7}, {%8,%9}, {%10,%10,%10,%10};" : "=f"(cs[0]), "=f"(cs[1]), "=f"(cs[2]), "=f"(cs[3]) : "r"(M[0]), "r"(M[1]), "r"(M[2]), "r"(M[3]), "r"(wv[0]), "r"(wv[1]), "f"(0.f)); };
      auto cv = [&](int i) { asm volatile("{.reg .b32 a, b; shl.b32 a, %0, 16; and.b32 b, %0, 0xFFFF0000; cvt.rn.f16x2.f32 %0, b, a;}" : "+r"(ef[i])); };
      auto un = [&]() { asm volatile("shl.b32 %0, %2, 16; and.b32 %1, %2, 0xFFFF0000;" : "=&f"(e0_), "=&f"(e1_) : "r"(dpk)); };
      auto ex0 = [&]() { asm volatile("prmt.b32 %0, %3, %4, 0x6420; prmt.b32 %1, %5, %6, 0x6420; prmt.b32 %2, %7, %8, 0x6420;" : "=&r"(x0), "=&r"(x1), "=&r"(x2) : "r"(T[0]), "r"(T[1]), "r"(T[2]), "r"(T[3]), "r"(T[4]), "r"(T[5])); };
      auto ex1 = [&]() { asm volatile("{.reg .b32 a, b; shl.b32 a, %2, 3; shl.b32 b, %3, 6; lop3.b32 a, %1, a, 0x38383838, 0xD8; lop3.b32 a, a, b, 0xC0C0C0C0, 0xD8; sub.rn.bf16x2 %0, %4, a;}" : "=r"(dpk) : "r"(x0), "r"(x1), "r"(x2), "r"(own)); };
      auto ex2 = [&]() { asm volatile("{.reg .b32 a, b, d, u; .reg .b16 l, h; shl.b32 a, %2, 16; and.b32 b, %2, 0xFFFF0000; cvt.rn.f16x2.f32 d, b, a; mul.rn.f16x2 %0, d, d; mov.b32 {l, h}, d; mov.b32 u, {h, h}; mul.rn.f16x2 %1, u, u;}" : "=&r"(q0), "=&r"(q1) : "r"(dpk)); };
      auto pf = [&]() { asm volatile("fma.rn.f32 %0, %1, %2, %0; fma.rn.f32 %0, %3, %4, %0;" : "+f"(pacc) : "f"(cs[0]), "f"(e0_), "f"(cs[2]), "f"(e1_)); };
      if (mode == 2) { LASTSEQ return; }
      asm volatile("cp.async.wait_group %0;" :: "n"(NST - 1) : "memory");
      __syncwarp();
      if (mode == 1) STAMP(8);
      ldsm4(ef, eadr + so); ldsm4(T, qa0 + so); ldsm4(T + 4, qa1 + so); ldsm4(T + 8, qa2 + so); ldsm4(T + 12, qa3 + so);
      if (mode == 1) {
        tl_(); issue();
        cv(0); cv(1); cv(2); cv(3); ex0(); ex1(); ex2();
#pragma unroll
        for (int j = 0; j < 8; j++) { he(j); hs(j); }
        FIRSTSEQ return;
      }
      BODYSEQ
    };
#pragma unroll
    for (int j = 0; j < 8; j++) sum[j] = 0;
    body(IC<1>());
    int cnt = (lens & 255) - 1;
    auto pload = [&](uint32_t (&x)[8], uint32_t o) { const uint32_t l = a_g >> 1, a = p2 + o + (l & 7) * 128 + (((((l >> 3) & 3) ^ l) & 7) << 4); ldsm4t(x, a); ldsm4t(x + 4, a ^ 64); };
    auto flush = [&]() {
      asm volatile("{.reg .pred p; setp.ne.u32 p, %2, 6; @p st.shared.u16 [%0+-64], %1;}" :: "r"(a_g), "h"((uint16_t)pack_bf16(bf_hi(ownp) + pacc, 0.f)), "r"(a_g & 6) : "memory");
      chk = fmaf(pacc, 0.f, chk); pacc = 0.f; };
    constexpr uint64_t b1 = DHI | ((sb + OFF_W) >> 4), b2_ = b1 + 512;
    auto mma_h = [&](float (&acc)[32], uint32_t (&hf)[16]) {
      rs64b<0>(acc, hf[0], hf[1], hf[2], hf[3], b1); rs64b<1>(acc, hf[4], hf[5], hf[6], hf[7], b1 + 128); rs64b<1>(acc, hf[8], hf[9], hf[10], hf[11], b1 + 256); rs64b<1>(acc, hf[12], hf[13], hf[14], hf[15], b1 + 384); };
    auto mma_m = [&](float (&acc)[32]) {
      rs64h<1>(acc, sp[0], sum[0], sp[1], sum[1], b2_); rs64h<1>(acc, sp[2], sum[2], sp[3], sum[3], b2_ + 128); rs64h<1>(acc, sp[4], sum[4], sp[5], sum[5], b2_ + 256); rs64h<1>(acc, sp[6], sum[6], sp[7], sum[7], b2_ + 384);
      wg_commit(); wg_wait0(); fence_regs(acc);
      STAMP(10);
      chk = fmaf(acc[0], 0.f, fmaf(acc[2], 0.f, chk)); };
    auto roff = [&](uint32_t nd, int r) { return __shfl_sync(~0u, nd, ((a_g >> 3) & 7) + 8 * r) * 128 + (a_g & 6) * 8; };
    auto radr = [&](uint32_t o, int k) { return sb + OFF_H + (o ^ ((o >> 3) & 0x70) ^ ((k >> 1) << 6)); };
    auto fin = [&](float (&acc)[32], uint32_t* x, int k) {
#pragma unroll
      for (int i = 0; i < 4; i++) { const int c = 16 * (k >> 1) + 4 * i + 2 * (k & 1); x[i] = u2(__hadd2(b2(x[i]), b2(pack_bf16(silu_h(acc[c]), silu_h(acc[c + 1]))))); } };
#pragma unroll 1
    for (int t = 0;; t++) {
#pragma unroll 1
      for (; cnt > 0; cnt--) { body(IC<0>());
      }
      if (!(t & 1)) {
        ownp = own; a_g += 64;
        if (t == 6) break;
        pe = pol_first();
        own = lds16(a_g) * 0x10001u;
        if (t == 2) { const uint32_t a = ((a_g & 16) ? p2 : sb + OFF_WD) + ((a_g << 6) & 0x380) + (qa0 & 0x70);
          mbar_wait(sb + BAR_U);
#pragma unroll
          for (int j = 0; j < 4; j++) ldsm4t(bp + 4 * j, a ^ (j << 5));
        } else {
#pragma unroll
          for (int j = 0; j < 8; j++) bp[2 * j + 1] = sp[j];
        }
        lens >>= 8; cnt = 1;
        continue;
      }
      cnt = (lens & 255) - 1;
      flush();
      if (t == 3) {
        uint32_t x[8];
        pload(x, 1024);
        __syncwarp();
#pragma unroll
        for (int j = 0; j < 4; j++) stsm4((p2 + ((a_g << 6) & 0x780) + (qa0 & 0x70)) ^ (j << 5), sp[2 * j], sum[2 * j], sp[2 * j + 1], sum[2 * j + 1]);
#pragma unroll
        for (int j = 0; j < 8; j++) sum[j] = x[j];
        __syncwarp();
        mbar_arrive(sb + BAR_M + (wid >> 2) * 8, (a_g & 62) == 0);
      }
#pragma unroll
      for (int j = 0; j < 8; j++) { sp[j] = sum[j]; asm volatile("mov.b32 %0, 0;" : "=r"(sum[j])); }
    }
    {
      uint32_t hf[16], v[16]; float acc[32];
      const uint32_t nd = lds16(sb + OFF_GP + wid * 256 + (lane & 15) * 8 + 134), o[2] = {roff(nd, 0), roff(nd, 1)};
      hload(hf, nd);
#pragma unroll
      for (int k = 0; k < 4; k++) lds128(v + 4 * k, radr(o[k & 1], k));
      mbar_wait(sb + BAR_WH);
      wg_fence(); mma_h(acc, hf); wg_commit();
      body(IC<2>());
      STAMP(9);
      flush();
      __syncwarp();
      mbar_arrive(sb + BAR_X, lane == 0);
      wg_fence();
      mma_m(acc);
#pragma unroll
      for (int k = 0; k < 4; k++) { fin(acc, v + 4 * k, k);
        asm volatile("{.reg .pred p; setp.lt.u32 p, %5, %6; @p st.global.v4.b32 [%0], {%1,%2,%3,%4};}" :: "l"((const char*)p.out + (size_t)node0 * 128 + o[k & 1] + (k >> 1) * 64), "r"(v[4 * k]), "r"(v[4 * k + 1]), "r"(v[4 * k + 2]), "r"(v[4 * k + 3]), "r"(o[k & 1]), "r"(nloc * 128) : "memory"); }
    }
    asm volatile("{.reg .pred p, q; setp.neu.f32 p, %1, 0f00000000; setp.ne.or.u32 p, %2, 0, p; bar.red.or.pred q, 5, 512, p; selp.u32 %0, 1, 0, q;}" : "=r"(bad) : "f"(chk), "r"(lds32(sb + OFF_MISC + 12)) : "memory");
    STAMP(11);
   } else { asm volatile("cp.async.wait_all;" ::: "memory"); bar_sync(5, 384); }
  }
  if (bad) slow_path(p, wid, lane, node0, nloc);
}

}

typedef CUresult (*EncodeFn)(CUtensorMap*, CUtensorMapDataType, cuuint32_t, void*, const cuuint64_t*, const cuuint64_t*, const cuuint32_t*, const cuuint32_t*,
                             CUtensorMapInterleave, CUtensorMapSwizzle, CUtensorMapL2promotion, CUtensorMapFloatOOBfill);

extern "C" void kernel_launch(void* const* d_in, const int* in_sizes, int n_in, void* d_out, int out_size) {
  Params p; Maps maps;
  p.h = (const uint4*)d_in[0]; p.pos = (const uint16_t*)d_in[1]; p.ea = (const uint4*)d_in[2];
  p.src = (const int*)d_in[3]; p.dst = (const int*)d_in[4];
  p.we = (const uint16_t*)d_in[5]; p.wx = (const uint16_t*)d_in[6]; p.wh = (const uint16_t*)d_in[7];
  p.out = (uint16_t*)d_out;
  p.N = in_sizes[0] / 64; p.E = in_sizes[3];
  p.EPC = ((p.E + G * 4 - 1) / (G * 4)) * 4;
  p.magic = (uint32_t)(((uint64_t)G << 24) / (uint64_t)p.N);
  p.inv = (1ull << 56) / p.magic;
  const uint64_t ea0 = (uint64_t)d_in[2], ea1 = ea0 + (uint64_t)p.E * 32 - 1;
  p.force_slow = ((ea0 >> 32) != (ea1 >> 32)) || (ea0 & 31) || (p.E & 3);
  void* qp = nullptr;
  cudaGetSymbolAddress(&qp, g_q);
  p.q = (char*)qp;
  if (((uint64_t)p.q >> 32) != (((uint64_t)p.q + QBYTES) >> 32)) p.q += QBYTES;
  cudaGetSymbolAddress((void**)&p.sync, g_sync); cudaGetSymbolAddress((void**)&p.xe, g_xe);
  cudaGetSymbolAddress((void**)&p.xa, g_xa); cudaGetSymbolAddress((void**)&p.xb, g_xb);
  const int df[10] = {34, 120, 900, 3072, 0, 17, 0xff2, 0xD5C4E6, 0x422000};
  for (int i = 0; i < 10; i++) p.tune[i] = df[i];
  p.qcode = 0x890145a6273bull;
  p.ctam = p.tune[5];
  if ((long long)PFB * PFN > (long long)(p.E / G) * 32) PFB = (p.E / G * 32 / PFN) & ~127;
  void* fn = nullptr; cudaDriverEntryPointQueryResult qr;
  cudaGetDriverEntryPoint("cuTensorMapEncodeTiled", &fn, cudaEnableDefault, &qr);
  auto mk = [&](CUtensorMap* tm, void* base, int rows, int box = 64) {
    const cuuint64_t dim[2] = {64, (cuuint64_t)rows}, str[1] = {128}; const cuuint32_t bx[2] = {64, (cuuint32_t)box}, es[2] = {1, 1};
    ((EncodeFn)fn)(tm, CU_TENSOR_MAP_DATA_TYPE_BFLOAT16, 2, base, dim, str, bx, es, CU_TENSOR_MAP_INTERLEAVE_NONE, CU_TENSOR_MAP_SWIZZLE_128B,
                   CU_TENSOR_MAP_L2_PROMOTION_NONE, CU_TENSOR_MAP_FLOAT_OOB_FILL_NONE);
  };
  mk(&maps.m[TM_H / 128], d_in[0], p.N); mk(&maps.m[TM_WE / 128], d_in[5], 145); mk(&maps.m[TM_WH / 128], d_in[7], 128); mk(&maps.m[TM_Q / 128], p.q, p.N, 16);
  for (int k = 0; k < 2; k++) {
    void* xp = (void*)(k ? p.xb : p.xa);
    const cuuint64_t dim[2] = {(cuuint64_t)G * 64, (cuuint64_t)G}, str[1] = {(cuuint64_t)G * (128 << k)}; const cuuint32_t bx[2] = {64, (cuuint32_t)(k ? BROWS : G)}, es[2] = {1, 1};
    ((EncodeFn)fn)(&maps.m[TM_XA / 128 + k], k ? CU_TENSOR_MAP_DATA_TYPE_UINT32 : CU_TENSOR_MAP_DATA_TYPE_UINT16, 2, xp, dim, str, bx, es, CU_TENSOR_MAP_INTERLEAVE_NONE,
                   CU_TENSOR_MAP_SWIZZLE_NONE, CU_TENSOR_MAP_L2_PROMOTION_NONE, CU_TENSOR_MAP_FLOAT_OOB_FILL_NONE);
  }
  cudaFuncSetAttribute(egnn_kernel, cudaFuncAttributeMaxDynamicSharedMemorySize, SMEM);
  egnn_kernel<<<G, NTHR, SMEM>>>(p, maps);
}
```

```cpp
#include <cuda_runtime.h>
#include <cuda_bf16.h>
#include <cuda_fp16.h>
#include <cuda.h>
#include <stdint.h>
#pragma nv_diag_suppress 549

#define FB 1
#define SPQ 1
#define PFN p.tune[0]
#define PFB p.tune[3]
#define PFNS p.tune[1]
#define PFE p.tune[8]
#define BDEL p.tune[2]
#define DEFNS p.tune[4]
#define CTAM p.ctam
#define QREV p.tune[6]
#define UORD p.tune[7]
#define QCODE p.qcode
#define FIRSTSEQ mu(0); mu(1); fi(0); mu(2); fi(1);
#define BODYSEQ hc(0); fi(2); tl_(); mu(3); un(); ad(1); ad(0); cv(0); mu(4); cv(2); fi(3); cv(1); ex0(); ex1(); cv(3); he(0); fi(4); he(1); \
  mu(5); hc(1); mu(6); fi(5); he(2); ad(2); ex2(); hs(0); ad(3); hs(1); fi(6); mu(7); issue(); hc(2); he(3); hs(3); fi(7); mu(0); \
  hs(2); he(4); he(5); ad(5); ad(4); hs(4); fi(0); he(6); mu(1); hc(3); he(7); fi(1); ad(6); hs(7); hs(5); ad(7); hs(6); mu(2); \
  pf();
#define LASTSEQ hc(0); fi(2); mu(3); un(); ad(1); ad(0); mu(4); fi(3); fi(4); mu(5); hc(1); mu(6); fi(5); ad(2); ad(3); fi(6); mu(7); hc(2); \
  fi(7); ad(5); ad(4); hc(3); ad(6); ad(7); pf();
namespace {

constexpr int G = 132;
constexpr int NTHR = 512, NWK = 352, NCH = 5;
constexpr int NST = 3, STG = 2560;
constexpr int BROWS = 44, RNB = 2, PADM = 33;
constexpr int SCAP = 448;

constexpr int OFF_H = 0;
constexpr int OFF_W = 49152;
constexpr int OFF_WD = OFF_W + 16384;
constexpr int OFF_W3 = OFF_WD + 1024;
constexpr int OFF_P2 = OFF_W3 + 2048;
constexpr int OFF_RING = OFF_P2 + 24576;
constexpr int OFF_TE = OFF_RING + 12 * NST * STG;
constexpr int OFF_TS = OFF_TE + SCAP * 64;
constexpr int OFF_INV = OFF_TS - 768;
constexpr int OFF_GP = OFF_TS + SCAP * 32;
constexpr int OFF_WX = OFF_GP + 3072;
constexpr int OFF_LEN = OFF_WX + 128;
constexpr int OFF_MISC = OFF_LEN + 128;
constexpr int OFF_BAR = OFF_MISC + 48;
constexpr int SMEM = OFF_BAR + 256;
static_assert(SMEM <= 232448, "smem");
constexpr uint32_t sb = 1024;
constexpr int OFF_SRCI = OFF_TE;
constexpr int OFF_SB = OFF_RING, OFF_SA = OFF_SB + 34816, OFF_AX = OFF_SA + 32768, OFF_DST = OFF_H + 24576;
constexpr int OFF_WS = OFF_AX + 17408;
constexpr int OFF_BC = OFF_WS + 2304;
constexpr int OFF_CNT = OFF_P2;
constexpr int OFF_DH = OFF_CNT + 2176;
constexpr int OFF_POS = OFF_DH + 128;
constexpr int OFF_EXT = OFF_POS + 3072;
constexpr int OFF_XB = OFF_EXT + 1024, XPAD = G * 256;
static_assert(OFF_XB + XPAD + 1028 <= OFF_RING + 12 * STG && OFF_XB % 128 == 0 && OFF_BC + 544 <= OFF_TE && OFF_P2 % 1024 == 0 && OFF_SA % 1024 == 0 && SCAP * 64 >= 24576, "staging");
constexpr int BAR_DST = OFF_BAR, BAR_SRC = BAR_DST + 40, BAR_T = BAR_SRC + 24, BAR_W = BAR_T + 48, BAR_PS = BAR_W + 8, BAR_AW = BAR_PS + 8,
              BAR_QP = BAR_AW + 8, BAR_QR = BAR_QP + 8, BAR_HA = BAR_QR + 8, BAR_EP = BAR_HA + 8, BAR_AX = BAR_EP + 8, BAR_AI = BAR_AX + 8, BAR_HB = BAR_AI + 8, BAR_QH = BAR_HB + 8, BAR_U = BAR_QH + 8, BAR_WH = BAR_U + 8, BAR_M = BAR_WH + 8, BAR_X = BAR_M + 24, BAR_RS = BAR_X + 8, BAR_END = BAR_RS + 8;
static_assert(BAR_END <= OFF_BAR + 256, "barriers");
constexpr uint32_t QBYTES = 8u << 20;

__device__ __align__(256) uint4 g_xa[G * G * 8];
__device__ __align__(256) uint4 g_xb[G * G * 16];
__device__ __align__(256) uint2 g_xe[G * G * 32];
__device__ __align__(256) uint4 g_q[2 * QBYTES / 16];
__device__ __align__(256) uint32_t g_sync[8];
#define STAMP(k)

struct Maps { CUtensorMap m[6]; };
constexpr int TM_H = 0, TM_WE = 128, TM_WH = 256, TM_Q = 384, TM_XA = 512, TM_XB = 640;
struct Params {
  const int* dst; uint32_t* sync; int E, EPC, N, ctam; unsigned long long inv; uint32_t magic; int force_slow;
  const int* src; const uint16_t* pos; const uint4* ea; const uint16_t* we; const uint16_t* wx; char* q;
  const uint4* xa; const uint4* xb; uint2* xe; uint16_t* out; const uint4* h; const uint16_t* wh;
  int tune[10]; unsigned long long qcode;
};
template<int V> struct IC { static constexpr int value = V; };

#define R32(d) "+f"(d[0]),"+f"(d[1]),"+f"(d[2]),"+f"(d[3]),"+f"(d[4]),"+f"(d[5]),"+f"(d[6]),"+f"(d[7]),"+f"(d[8]),"+f"(d[9]),"+f"(d[10]),"+f"(d[11]),"+f"(d[12]),"+f"(d[13]),"+f"(d[14]),"+f"(d[15]),"+f"(d[16]),"+f"(d[17]),"+f"(d[18]),"+f"(d[19]),"+f"(d[20]),"+f"(d[21]),"+f"(d[22]),"+f"(d[23]),"+f"(d[24]),"+f"(d[25]),"+f"(d[26]),"+f"(d[27]),"+f"(d[28]),"+f"(d[29]),"+f"(d[30]),"+f"(d[31])
#define S32 "{%0,%1,%2,%3,%4,%5,%6,%7,%8,%9,%10,%11,%12,%13,%14,%15,%16,%17,%18,%19,%20,%21,%22,%23,%24,%25,%26,%27,%28,%29,%30,%31}"
#define DI __device__ __forceinline__

constexpr uint64_t DHI = ((uint64_t)(1024 >> 4) << 32) | (1ull << 62);
template<int SD> DI void rs64b(float (&d)[32], uint32_t a0, uint32_t a1, uint32_t a2, uint32_t a3, uint64_t db) {
  asm volatile("wgmma.mma_async.sync.aligned.m64n64k16.f32.bf16.bf16 " S32 ", {%32,%33,%34,%35}, %36, %37, 1, 1, 1;" : R32(d) : "r"(a0), "r"(a1), "r"(a2), "r"(a3), "l"(db), "n"(SD)); }
template<int SD> DI void rs64h(float (&d)[32], uint32_t a0, uint32_t a1, uint32_t a2, uint32_t a3, uint64_t db) {
  asm volatile("wgmma.mma_async.sync.aligned.m64n64k16.f32.f16.f16 " S32 ", {%32,%33,%34,%35}, %36, %37, 1, 1, 1;" : R32(d) : "r"(a0), "r"(a1), "r"(a2), "r"(a3), "l"(db), "n"(SD)); }
template<int SD> DI void ss64(float (&d)[32], uint64_t da, uint64_t db) {
  asm volatile("wgmma.mma_async.sync.aligned.m64n64k16.f32.bf16.bf16 " S32 ", %32, %33, %34, 1, 1, 0, 1;" : R32(d) : "l"(da), "l"(db), "n"(SD)); }
#define R16(d) "+f"(d[0]),"+f"(d[1]),"+f"(d[2]),"+f"(d[3]),"+f"(d[4]),"+f"(d[5]),"+f"(d[6]),"+f"(d[7]),"+f"(d[8]),"+f"(d[9]),"+f"(d[10]),"+f"(d[11]),"+f"(d[12]),"+f"(d[13]),"+f"(d[14]),"+f"(d[15])
#define S16 "{%0,%1,%2,%3,%4,%5,%6,%7,%8,%9,%10,%11,%12,%13,%14,%15}"
template<int SD> DI void rs32b(float (&d)[16], const uint32_t* a, uint64_t db) {
  asm volatile("wgmma.mma_async.sync.aligned.m64n32k16.f32.bf16.bf16 " S16 ", {%16,%17,%18,%19}, %20, %21, 1, 1, 1;" : R16(d) : "r"(a[0]), "r"(a[1]), "r"(a[2]), "r"(a[3]), "l"(db), "n"(SD)); }
DI void rs32h(float (&d)[16], const uint32_t* a, uint64_t db) {
  asm volatile("wgmma.mma_async.sync.aligned.m64n32k16.f32.f16.f16 " S16 ", {%16,%17,%18,%19}, %20, 1, 1, 1, 1;" : R16(d) : "r"(a[0]), "r"(a[1]), "r"(a[2]), "r"(a[3]), "l"(db)); }
DI void fence_regs(float (&d)[16]) { asm volatile("" : R16(d) :: "memory"); }
DI void trap_if(bool c) { asm volatile("{.reg .pred p; setp.eq.u32 p, %0, 0; @p bra.uni LT_%=; trap; LT_%=:}" :: "r"((uint32_t)c)); }
DI void wg_fence() { asm volatile("wgmma.fence.sync.aligned;" ::: "memory"); }
DI void wg_commit() { asm volatile("wgmma.commit_group.sync.aligned;" ::: "memory"); }
DI void wg_wait0() { asm volatile("wgmma.wait_group.sync.aligned 0;" ::: "memory"); }
DI void fence_regs(float (&d)[32]) { asm volatile("" : R32(d) :: "memory"); }
DI void proxy_fence() { asm volatile("fence.proxy.async.shared::cta;" ::: "memory"); }
DI uint64_t pol_first() { uint64_t r; asm("createpolicy.fractional.L2::evict_first.b64 %0, 1.0;" : "=l"(r)); return r; }
DI float tanh_ap(float x) { float y; asm("tanh.approx.f32 %0, %1;" : "=f"(y) : "f"(x)); return y; }
DI float silu_h(float y) { return fmaf(y, tanh_ap(y), y); }
DI uint32_t pack_bf16(float lo, float hi) { uint32_t r; asm("cvt.rn.bf16x2.f32 %0, %1, %2;" : "=r"(r) : "f"(hi), "f"(lo)); return r; }
DI uint32_t pack_f16(float lo, float hi) { uint32_t r; asm("cvt.rn.f16x2.f32 %0, %1, %2;" : "=r"(r) : "f"(hi), "f"(lo)); return r; }
DI float bf_lo(uint32_t v) { return __uint_as_float(v << 16); }
DI float bf_hi(uint32_t v) { return __uint_as_float(v & 0xFFFF0000u); }
DI uint32_t b2h(uint32_t v, float s) { return pack_f16(s * bf_lo(v), s * bf_hi(v)); }
DI void mbar_wait(uint32_t bar, uint32_t parity = 0) {
  asm volatile("{.reg .pred p, q; .reg .u32 c; mov.u32 c, 0;\n"
    "LW_%=: mbarrier.try_wait.parity.shared::cta.b64 p, [%0], %1;\n add.u32 c, c, 1; setp.lt.and.u32 q, c, 0x200000, !p;\n @q bra.uni LW_%=;}" :: "r"(bar), "r"(parity) : "memory");
}
DI void mbar_arrive(uint32_t bar, int p = 1) { asm volatile("{.reg .pred p; setp.ne.b32 p, %1, 0; @p mbarrier.arrive.shared::cta.b64 _, [%0];}" :: "r"(bar), "r"(p) : "memory"); }
DI void bar_sync(int id, int n) { asm volatile("bar.sync %0, %1;" :: "r"(id), "r"(n) : "memory"); }
DI void bar_arrive(int id, int n) { asm volatile("bar.arrive %0, %1;" :: "r"(id), "r"(n) : "memory"); }
DI __nv_bfloat162 b2(uint32_t v) { return *(__nv_bfloat162*)&v; }
DI uint32_t u2(__nv_bfloat162 v) { return *(uint32_t*)&v; }
DI uint32_t hsq(uint32_t v) { return u2(__hmul2(b2(v), b2(v))); }
DI uint32_t hsub(uint32_t a, uint32_t b) { return u2(__hsub2(b2(a), b2(b))); }
DI uint32_t hhalf(uint32_t v) { return u2(__hmul2(b2(v), __floats2bfloat162_rn(0.5f, 0.5f))); }
DI uint32_t mag2(uint32_t m, uint32_t v) { return __vmaxu2(m, v & 0x7FFF7FFFu); }
DI uint32_t hmag(uint32_t m, uint32_t v) { const __half2 r = __hmax2(*(const __half2*)&m, __habs2(*(const __half2*)&v)); return *(const uint32_t*)&r; }
DI uint32_t magr(uint32_t m) { return max(m & 0xFFFF, m >> 16); }
DI void sts128(uint32_t a, uint32_t x, uint32_t y, uint32_t z, uint32_t w) { asm volatile("st.shared.v4.u32 [%0], {%1,%2,%3,%4};" :: "r"(a), "r"(x), "r"(y), "r"(z), "r"(w) : "memory"); }
DI void sts64(uint32_t a, uint32_t x, uint32_t y) { asm volatile("st.shared.v2.u32 [%0], {%1,%2};" :: "r"(a), "r"(x), "r"(y) : "memory"); }
DI void sts32(uint32_t a, uint32_t x) { asm volatile("st.shared.u32 [%0], %1;" :: "r"(a), "r"(x) : "memory"); }
DI void sts16(uint32_t a, uint32_t x) { asm volatile("st.shared.u16 [%0], %1;" :: "r"(a), "h"((uint16_t)x) : "memory"); }
DI void lds128(uint32_t* v, uint32_t a) { asm volatile("ld.shared.v4.u32 {%0, %1, %2, %3}, [%4];" : "=r"(v[0]), "=r"(v[1]), "=r"(v[2]), "=r"(v[3]) : "r"(a) : "memory"); }
DI void lds64(uint32_t& x, uint32_t& y, uint32_t a) { asm volatile("ld.shared.v2.u32 {%0, %1}, [%2];" : "=r"(x), "=r"(y) : "r"(a) : "memory"); }
DI uint32_t lds32(uint32_t a) { uint32_t x; asm volatile("ld.shared.u32 %0, [%1];" : "=r"(x) : "r"(a) : "memory"); return x; }
DI uint32_t lds16(uint32_t a) { uint32_t x; asm volatile("ld.shared.u16 %0, [%1];" : "=r"(x) : "r"(a) : "memory"); return x; }
DI uint32_t atoms_add(uint32_t a, uint32_t v) { uint32_t r; asm volatile("atom.shared.add.u32 %0, [%1], %2;" : "=r"(r) : "r"(a), "r"(v) : "memory"); return r; }
DI void bulk_load(uint32_t dst, const void* src, uint32_t bytes, uint32_t bar) {
  asm volatile("cp.async.bulk.shared::cluster.global.mbarrier::complete_tx::bytes.L2::cache_hint [%0], [%1], %2, [%3], %4;" :: "r"(dst), "l"(src), "r"(bytes), "r"(bar), "l"(pol_first()) : "memory"); }
DI void mbar_expect(uint32_t bar, uint32_t bytes) { asm volatile("mbarrier.arrive.expect_tx.shared::cta.b64 _, [%0], %1;" :: "r"(bar), "r"(bytes) : "memory"); }
DI void mbar_init(uint32_t bar, int n) { asm volatile("mbarrier.init.shared::cta.b64 [%0], %1;" :: "r"(bar), "r"(n) : "memory"); }
DI void tma_load(uint32_t dst, uint64_t tm, int row, uint32_t bar) {
  asm volatile("cp.async.bulk.tensor.2d.shared::cluster.global.mbarrier::complete_tx::bytes.L2::cache_hint [%0], [%1, {%3, %4}], [%2], %5;" :: "r"(dst), "l"(tm), "r"(bar), "r"(0), "r"(row), "l"(pol_first()) : "memory"); }
DI void tma_store(uint64_t tm, int col, int row, uint32_t src) {
  asm volatile("cp.async.bulk.tensor.2d.global.shared::cta.bulk_group [%0, {%2, %3}], [%1];" :: "l"(tm), "r"(src), "r"(col), "r"(row) : "memory"); }
DI void bulk_commit() { asm volatile("cp.async.bulk.commit_group;" ::: "memory"); }
DI uint2 ld_poll2(const void* a) { uint2 v; asm volatile("ld.relaxed.gpu.global.v2.u32 {%0, %1}, [%2];" : "=r"(v.x), "=r"(v.y) : "l"(a) : "memory"); return v; }
DI void st_ext(uint2* a, uint32_t v, uint32_t ep) { asm volatile("st.relaxed.gpu.global.v2.u32 [%0], {%1, %2};" :: "l"(a), "r"(v), "r"(ep) : "memory"); }
DI uint32_t ext_get(const uint2* a, uint32_t ep) { uint2 v; int spin = 0; do { v = ld_poll2(a); trap_if(++spin > 4000000); } while (__any_sync(~0u, v.y != ep)); return v.x; }
DI void bulk_wait() { asm volatile("cp.async.bulk.wait_group 0;" ::: "memory"); }
DI void hint_signal(uint32_t* c) { asm volatile("red.relaxed.gpu.global.add.u32 [%0], 1;" :: "l"(c) : "memory"); }
DI void hint_wait(const uint32_t* c, uint32_t target) { uint32_t v; int spin = 0;
  do { asm volatile("ld.relaxed.gpu.global.u32 %0, [%1];" : "=r"(v) : "l"(c) : "memory"); trap_if(++spin > 4000000); } while (__any_sync(~0u, (int)(v - target) < 0)); }
DI void stsm4(uint32_t a, uint32_t x, uint32_t y, uint32_t z, uint32_t w) { asm volatile("stmatrix.sync.aligned.m8n8.x4.shared.b16 [%0], {%1,%2,%3,%4};" :: "r"(a), "r"(x), "r"(y), "r"(z), "r"(w) : "memory"); }
DI void ldsm4(uint32_t* v, uint32_t a) { asm volatile("ldmatrix.sync.aligned.m8n8.x4.shared.b16 {%0,%1,%2,%3}, [%4];" : "=r"(v[0]), "=r"(v[1]), "=r"(v[2]), "=r"(v[3]) : "r"(a) : "memory"); }
DI void ldsm4t(uint32_t* v, uint32_t a) { asm volatile("ldmatrix.sync.aligned.m8n8.x4.trans.shared.b16 {%0,%1,%2,%3}, [%4];" : "=r"(v[0]), "=r"(v[1]), "=r"(v[2]), "=r"(v[3]) : "r"(a) : "memory"); }
DI uint32_t mad16(uint32_t x, uint32_t m, uint32_t c) { uint32_t r; asm("dp2a.lo.u32.u32 %0, %1, %2, %3;" : "=r"(r) : "r"(x), "r"(m), "r"(c)); return r; }
DI bool wbad(uint32_t m, uint32_t hi) { return m > hi || (m && m < 0x3980); }

__device__ __noinline__ void slow_path(const Params& p, int wid, int lane, int node0, int nloc) {
  const uint32_t ab = sb + OFF_P2 + wid * 8704;
  for (int i = lane; i < 32 * 68; i += 32) sts32(ab + i * 4, 0);
  __syncwarp();
  const uint32_t wdv = __ldg((const uint32_t*)(p.we + 128 * 64) + lane), wxv = __ldg((const uint32_t*)p.wx + lane);
  const int nb0 = node0 + wid * 32, cntn = max(0, min(32, nloc - wid * 32));
  auto dot = [&](uint32_t hv, const uint16_t* w, int K2, float& y0, float& y1) {
#pragma unroll 4
    for (int k = 0; k < K2; k++) {
      const uint32_t hk = __shfl_sync(~0u, hv, k), wa = __ldg((const uint32_t*)(w + 2 * k * 64) + lane), wb = __ldg((const uint32_t*)(w + (2 * k + 1) * 64) + lane);
      y0 = fmaf(bf_lo(hk), bf_lo(wa), fmaf(bf_hi(hk), bf_lo(wb), y0)); y1 = fmaf(bf_lo(hk), bf_hi(wa), fmaf(bf_hi(hk), bf_hi(wb), y1));
    }
  };
  auto silu = [](float x) { return x / (1.f + __expf(-x)); };
#pragma unroll 1
  for (int base = 0; base < p.E; base += 32) {
    const int e = base + lane;
    const uint32_t dl = e < p.E ? (uint32_t)(__ldg(p.dst + e) - nb0) : 0xFFFFFFFFu;
    uint32_t mk = __ballot_sync(~0u, dl < (uint32_t)cntn);
    while (mk) {
      const int l = __ffs(mk) - 1; mk &= mk - 1;
      const int ee = base + l, n = __shfl_sync(~0u, dl, l), s = __ldg(p.src + ee);
      const uint16_t *po = p.pos + (size_t)(nb0 + n) * 3, *pp = p.pos + (size_t)s * 3;
      const uint32_t dxy = hsub(__ldg(po) | (__ldg(po + 1) << 16), __ldg(pp) | (__ldg(pp + 1) << 16)), dz = hsub(__ldg(po + 2), __ldg(pp + 2));
      const uint32_t sq = hsq(dxy); const float d2 = bf_lo(sq) + bf_hi(sq) + bf_lo(hsq(dz));
      float y0 = d2 * bf_lo(wdv), y1 = d2 * bf_hi(wdv);
      dot(__ldg((const uint32_t*)(p.h + (size_t)(nb0 + n) * 8) + lane), p.we, 32, y0, y1);
      dot(__ldg((const uint32_t*)(p.h + (size_t)s * 8) + lane), p.we + 64 * 64, 32, y0, y1);
      dot(__ldg((const uint32_t*)(p.ea + (size_t)ee * 2) + (lane & 7)), p.we + 129 * 64, 8, y0, y1);
      const uint32_t mm = pack_bf16(silu(y0), silu(y1));
      float c = bf_lo(mm) * bf_lo(wxv) + bf_hi(mm) * bf_hi(wxv);
#pragma unroll
      for (int o = 16; o; o >>= 1) c += __shfl_xor_sync(~0u, c, o);
      const uint32_t a = ab + n * 272;
      uint32_t x0, x1; lds64(x0, x1, a + lane * 8);
      sts64(a + lane * 8, __float_as_uint(__uint_as_float(x0) + bf_lo(mm)), __float_as_uint(__uint_as_float(x1) + bf_hi(mm)));
      if (lane < 3) { const float df = lane == 0 ? bf_lo(dxy) : lane == 1 ? bf_hi(dxy) : bf_lo(dz); sts32(a + 256 + lane * 4, __float_as_uint(fmaf(c, df, __uint_as_float(lds32(a + 256 + lane * 4))))); }
    }
  }
  __syncwarp();
#pragma unroll 1
  for (int n = 0; n < cntn; n++) {
    uint32_t x0, x1; lds64(x0, x1, ab + n * 272 + lane * 8);
    const uint32_t hv = __ldg((const uint32_t*)(p.h + (size_t)(nb0 + n) * 8) + lane);
    float y0 = 0.f, y1 = 0.f;
    dot(hv, p.wh, 32, y0, y1); dot(pack_bf16(__uint_as_float(x0), __uint_as_float(x1)), p.wh + 64 * 64, 32, y0, y1);
    ((uint32_t*)p.out)[(size_t)(nb0 + n) * 32 + lane] = u2(__hadd2(b2(hv), b2(pack_bf16(silu(y0), silu(y1)))));
    if (lane < 3) p.out[(size_t)p.N * 64 + (size_t)(nb0 + n) * 3 + lane] = (uint16_t)pack_bf16(bf_lo(__ldg(p.pos + (size_t)(nb0 + n) * 3 + lane)) + __uint_as_float(lds32(ab + n * 272 + 256 + lane * 4)), 0.f);
  }
}

__global__ void __launch_bounds__(NTHR, 1) egnn_kernel(const __grid_constant__ Params p, const __grid_constant__ Maps maps) {
  const uint64_t tmb = (uint64_t)&maps;
  extern __shared__ __align__(1024) unsigned char smraw[];
  const int tid = threadIdx.x, cta = blockIdx.x * CTAM % G;
  const int e0 = cta * p.EPC, n4 = max(0, min(p.EPC, p.E - e0)) >> 2;
  STAMP(0);
  if (tid == NWK) {
#pragma unroll 1
    for (int k = 0; k < NCH; k++) { const int nb = max(0, min(NWK, n4 - k * NWK)) * 16;
      mbar_init(sb + BAR_DST + k * 8, 1);
      asm volatile("fence.mbarrier_init.release.cluster;" ::: "memory");
      mbar_expect(sb + BAR_DST + k * 8, nb);
      if (nb) bulk_load(sb + OFF_DST + k * NWK * 16, (const char*)(p.dst + e0) + k * NWK * 16, nb, sb + BAR_DST + k * 8); }
  }
  const int lane = tid & 31, wid = __shfl_sync(~0u, tid >> 5, 0), w = wid & 3;
  asm volatile("{.reg .pred p; setp.eq.u32 p, %2, 384; @p cp.async.cg.shared.global [%0], [%1], 16;}" :: "r"(sb + OFF_LEN - 192 + (tid >> 1)), "l"(p.sync), "r"(tid & 415) : "memory");

  auto first_node = [&](int c) { return (int)((c * p.inv + 0xFFFFFFFFull) >> 32); };
  const int node0 = first_node(cta), nloc = min(first_node(cta + 1), p.N) - node0;
  const uint32_t ealo = (uint32_t)(uint64_t)p.ea;
  const int epad = min(e0, p.E - 1);
  if (wid >= 12) {
    const int t = tid - 384;
    auto load_h = [&](int b) { mbar_expect(sb + BAR_T + b * 8, 8192); tma_load(sb + OFF_H + b * 8192, tmb + TM_H, node0 + b * 64, sb + BAR_T + b * 8); };
    uint32_t pv[9], ev = 0;
#pragma unroll
    for (int i = 0; i < 3; i++) { const uint16_t* pp = p.pos + (size_t)(node0 + t + 128 * i) * 3;
      pv[3 * i] = pv[3 * i + 1] = pv[3 * i + 2] = 0;
      asm volatile("{.reg .pred p; setp.lt.s32 p, %4, %5;\n @p ld.global.nc.u16 %0, [%3];\n @p ld.global.nc.u16 %1, [%3+2];\n @p ld.global.nc.u16 %2, [%3+4];}"
        : "+r"(pv[3 * i]), "+r"(pv[3 * i + 1]), "+r"(pv[3 * i + 2]) : "l"(pp), "r"(t + 128 * i), "r"(p.N - node0)); }
    asm volatile("cp.async.wait_all;" ::: "memory");
    __syncwarp();
    const uint32_t e = lds32(sb + OFF_LEN + 8 + w * 16) + 1;
    {
      const uint32_t tg = (1 + e % 3) << 30, v = ((tg >> 16) + 512 + (lane & 7) * 4) * 0x10001u;
      if (t == 0) sts32(sb + OFF_MISC + 32, e);
#pragma unroll
      for (int i = 0; i < 9; i++) sts128(sb + OFF_SA + t * 16 + i * 2048, v, v + 0x10001u, v + 0x20002u, v + 0x30003u);
      bar_sync(6, NTHR);
      mbar_arrive(sb + BAR_EP, lane == 0);
#pragma unroll
      for (int i = 0; i < 17; i++) sts128(sb + OFF_SB + t * 16 + i * 2048, tg, tg, tg, tg); }
    asm volatile("{.reg .pred p; setp.lt.u32 p, %3, 8; @p ld.global.nc.u32 %0, [%1]; @p st.global.v4.u32 [%2], {%4, %4, %4, %4};}"
      : "+r"(ev) : "l"((const uint32_t*)(p.ea + (size_t)epad * 2) + t), "l"(p.q + (size_t)(p.N + cta * PADM) * 128 + t * 16), "r"(t), "r"(0xF700F700u | (e & 1)) : "memory");
    uint32_t mp = 0;
#pragma unroll
    for (int i = 0; i < 3; i++) { sts64(sb + OFF_POS + (t + 128 * i) * 8, pv[3 * i] | (pv[3 * i + 1] << 16), pv[3 * i + 2] | (e & 1) * 0x410000u); mp = mag2(mag2(mp, pv[3 * i] | (pv[3 * i + 1] << 16)), pv[3 * i + 2]); }
    proxy_fence();
    __syncwarp();
    mbar_arrive(sb + BAR_PS, lane == 0);
    mbar_wait(sb + BAR_W);
    {
      uint32_t v[4], u[4]; const int r = t >> 3, c = t & 7;
      lds128(v, sb + OFF_WS + 128 + t * 16); lds128(u, sb + OFF_WS + c * 16);
      const uint32_t x = lds32(sb + OFF_WS + 2176 + lane * 4);
      sts128(sb + OFF_W3 + r * 128 + ((c ^ (r & 7)) << 4), b2h(v[0], .5f), b2h(v[1], .5f), b2h(v[2], .5f), b2h(v[3], .5f));
      const float s = ((r & 1) || r == 6) ? 0.f : .5f;
      if (t < 64) sts128(sb + OFF_WD + r * 128 + ((c ^ r) << 4), b2h(u[0], s), b2h(u[1], s), b2h(u[2], s), b2h(u[3], s));
      if (t < 32) sts32(sb + OFF_WX + (t & 3) * 32 + (t >> 2) * 4, b2h(x, 1.f));
      const uint32_t m3 = __reduce_max_sync(~0u, magr(mag2(mag2(mag2(mag2(0, v[0]), v[1]), v[2]), v[3]))), md = __reduce_max_sync(~0u, magr(mag2(mag2(mag2(mag2(0, u[0]), u[1]), u[2]), u[3])));
      if (wbad(m3, 0x4000) || wbad(md, 0x4000) || wbad(__reduce_max_sync(~0u, magr(mag2(0, x))), 0x4700) || magr(mp) >= 0x4200 || magr(mag2(0, ev)) >= 0x4380) sts32(sb + OFF_MISC + 8, 1);
    }
    if (w == 1) {
#pragma unroll 1
      for (int b = 0; b < 3; b++) { mbar_wait(sb + BAR_SRC + b * 8); if (lane == 0) load_h(b); }
    }
    bar_sync(3, 128);
    const uint32_t frag = (w * 16 + (lane & 15)) * 128 + (((lane >> 4) ^ (lane & 7)) << 4);
    uint32_t mq = 0; int pfi = 0;
    auto prefetch_e = [&]() {
      const uint32_t nb = PFB;
      if (lane == 0 && nb) asm volatile("cp.async.bulk.prefetch.L2.global [%0], %1;" :: "l"((const char*)p.ea + (size_t)(pfi * G + cta) * nb), "r"(nb) : "memory");
      pfi++; };
#pragma unroll 1
    for (int b = 0; b < 6; b++) {
      float acc[32];
      const uint64_t da = DHI | (((sb + OFF_H) >> 4) + b * 512), db = DHI | ((sb + OFF_W) >> 4);
      const uint32_t v0 = lds16(sb + OFF_POS + b * 512 + w * 128 + lane * 2), v1 = lds16(sb + OFF_POS + 64 + b * 512 + w * 128 + lane * 2);
      mbar_wait(sb + BAR_T + b * 8);
      if (b == 0) STAMP(25);
      if (b == 5) STAMP(26);
      wg_fence();
      ss64<0>(acc, da, db); ss64<1>(acc, da + 2, db + 128); ss64<1>(acc, da + 4, db + 256); ss64<1>(acc, da + 6, db + 384);
      wg_commit();
      if (b == 0) mbar_wait(sb + BAR_AW);
      if (t == 32 && b < 3) load_h(b + 3);
      if (w == 1) for (int k = PFE >> (4 * b) & 15; k > 0; k--) prefetch_e();
      __syncwarp();
      uint32_t ff[6], fg[6];
#pragma unroll
      for (int j = 0; j < 6; j++) { ff[j] = (__byte_perm((j & 1) ? v1 : v0, 0, 0x4140) >> (3 * (j >> 1))) & 0x00070007u; fg[j] = __vsub2(0x00040004u, ff[j]);
        asm volatile("" : "+r"(ff[j]), "+r"(fg[j])); }
      wg_wait0(); fence_regs(acc);
      uint32_t o[16];
#pragma unroll
      for (int j = 0; j < 16; j++) o[j] = pack_f16(.5f * acc[2 * j], .5f * acc[2 * j + 1]);
#pragma unroll
      for (int j = 0; j < 6; j++) {
        const uint32_t m = o[j] & 0x7FFF7FFFu; mq = __vmaxu2(mq, m);
        o[j] = (__viaddmax_s16x2(m, fg[j], 0) & 0xFFF8FFF8u) | ff[j] | (o[j] & 0x80008000u); }
      if ((lane & 3) == 3) { o[8] = (o[8] & ~1u) | (e & 1); o[9] = (o[9] & ~1u) | (e & 1); o[12] = (o[12] & ~1u) | (e & 1); o[13] = (o[13] & ~1u) | (e & 1); }
      if (b == 4) mbar_wait(sb + BAR_AX);
      const uint32_t qs = sb + OFF_SA + b * 8192;
#pragma unroll
      for (int j = 0; j < 4; j++) stsm4((qs + frag) ^ (j << 5), o[4 * j], o[4 * j + 1], o[4 * j + 2], o[4 * j + 3]);
      proxy_fence();
      __syncwarp();
      if (lane == 0 && b * 64 + w * 16 < nloc) tma_store(tmb + TM_Q, 0, node0 + b * 64 + w * 16, qs + w * 2048);
    }
    if (lane == 0) bulk_commit();
    { const uint32_t m = __reduce_max_sync(~0u, magr(mq)); if (lane == 0) sts32(sb + OFF_MISC + 16 + w * 4, m); }
    asm volatile("setmaxnreg.dec.sync.aligned.u32 56;");
    bulk_wait();
    bar_sync(3, 128);
    if (w == 0) {
      STAMP(18);
      uint32_t mv[4]; lds128(mv, sb + OFF_MISC + 16);
      const uint32_t mx = max(max(mv[0], mv[1]), max(mv[2], mv[3]));
      mbar_arrive(sb + BAR_QR, lane == 0);
      STAMP(19);
      if (lane == 0) {
        if (nloc > 0 && (mx >= 0x7BF0 || mx < 0x1400)) asm volatile("st.relaxed.gpu.global.u32 [%0+4], %1;" :: "l"(p.sync), "r"(e) : "memory");
        asm volatile("red.release.gpu.global.add.u32 [%0], 1;" :: "l"(p.sync) : "memory");
      }
      __syncwarp();
      uint32_t c, f; int spin = 0;
      do { asm volatile("ld.acquire.gpu.global.v2.u32 {%0, %1}, [%2];" : "=r"(c), "=r"(f) : "l"(p.sync) : "memory"); trap_if(++spin > 4000000); } while (__any_sync(~0u, (int)(c - e * G) < 0));
      if (f == e) sts32(sb + OFF_MISC + 8, 1);
      if (cta == 0 && lane == 0) asm volatile("st.relaxed.gpu.global.u32 [%0+8], %1;" :: "l"(p.sync), "r"(e) : "memory");
      STAMP(20);
      __syncwarp();
      mbar_arrive(sb + BAR_QP, lane == 0);
    }
    if (w == 2) {
      const uint32_t tg = (1 + e % 3) << 30;
      hint_wait(p.sync + 5, e * G);
      if (lane == 0) { mbar_expect(sb + BAR_HB, XPAD);
#pragma unroll 1
        for (int o = 0; o < 4; o++) bulk_load(sb + OFF_XB + o * (G * 64), (const char*)p.xb + (size_t)(cta * 4 + o) * (G * 64), G * 64, sb + BAR_HB); }
      STAMP(21);
      bar_sync(7, 384);
      sts32(sb + OFF_XB + XPAD, tg + p.N + cta * PADM);
      const uint32_t nx = __shfl_sync(~0u, lds32(sb + OFF_MISC + 8) ? 0 : lds32(sb + OFF_MISC + 4), 0);
#pragma unroll 1
      for (uint32_t k = 0; k < nx; k += 32) {
        const uint32_t i = min(k + lane, nx - 1), xr = lds32(sb + OFF_EXT + i * 4), row = (xr >> 9) & 255;
        const uint32_t v = ext_get(p.xe + (cta * G + row) * 32 + ((xr >> 17) & 31), e), x = lds32(sb + OFF_CNT + (xr & 511) * 4) + (xr >> 22) * 16;
        sts32(sb + OFF_XB + XPAD + 4 + i * 4, v); sts16(sb + OFF_TS + x, XPAD + 4 + i * 4);
        sts32(sb + OFF_TE + x * 2, mad16(v, 0x2000u, ealo - (tg >> 11) + row * p.EPC * 32));
      }
      __syncwarp();
      mbar_arrive(sb + BAR_HB, lane == 0);
    }
    if (w == 1) {
#pragma unroll 1
      while (pfi < PFN) { prefetch_e(); __nanosleep(PFNS); }
    }
    if (w == 3) {
      if (lane == 0) { if (SPQ) hint_signal(p.sync + 6); mbar_expect(sb + BAR_U, 8192); tma_load(sb + OFF_W, tmb + TM_WH, 0, sb + BAR_U); }
      __syncwarp();
      if (SPQ) { hint_wait(p.sync + 6, e * G); mbar_arrive(sb + BAR_QH, lane == 0); }
    }
    bar_sync(4, NTHR);
    const bool fast = !__shfl_sync(~0u, lds32(sb + OFF_MISC + 8), 0);
    if (fast) {
      mp = 0;
#pragma unroll 1
      for (uint32_t todo = UORD; todo; todo >>= 4) {
        const uint32_t nd = lds16(sb + OFF_GP + (todo & 3) * 1024 + w * 256 + (lane & 15) * 8 + 134), hb = (todo >> 3) & 1;
        const uint64_t b1 = DHI | (((sb + OFF_W + 8192) >> 4) + hb * 4);
        uint32_t f[8]; float acc[16];
#pragma unroll
        for (int j = 0; j < 4; j += 2) {
          const uint32_t a = (sb + OFF_H + nd * 128 + (((nd & 7) << 4) ^ (lane & 16))) ^ (j << 5);
          ldsm4(f, a); ldsm4(f + 4, a ^ 32);
          wg_fence();
          if (j == 0) rs32b<0>(acc, f, b1); else rs32b<1>(acc, f, b1 + 256);
          rs32b<1>(acc, f + 4, b1 + 128 * j + 128);
          wg_commit(); wg_wait0(); fence_regs(acc);
        }
#pragma unroll
        for (int j = 0; j < 8; j++) { f[j] = pack_f16(.5f * acc[2 * j], .5f * acc[2 * j + 1]); mp = hmag(mp, f[j]); }
        const uint32_t a = (sb + OFF_P2 + (todo & 3) * 8192 + frag) ^ (hb << 6);
        stsm4(a, f[0], f[1], f[2], f[3]); stsm4(a ^ 32, f[4], f[5], f[6], f[7]);
      }
      if (magr(mp) >= 0x7000) sts32(sb + OFF_MISC + 12, 1);
    }
    bar_sync(3, 128);
    if (t == 96) { mbar_expect(sb + BAR_U, 8192); tma_load(sb + OFF_W + 8192, tmb + TM_WH, 64, sb + BAR_U); }
    __syncwarp();
    mbar_wait(sb + BAR_U);
    uint32_t mh = 0;
#pragma unroll 1
    for (int i = t; i < 1024; i += 128) {
      uint32_t v[4]; const uint32_t r = (i >> 3) & 7, j = (i ^ r) & 7;
#pragma unroll
      for (int k = 0; k < 4; k++) v[k] = lds32(sb + OFF_W + (i >> 3) * 128 + ((((j & 4) + k) ^ r) << 4) + (j & 3) * 4);
      __syncwarp();
      if (i < 512) sts128(sb + OFF_W + i * 16, hhalf(v[0]), hhalf(v[1]), hhalf(v[2]), hhalf(v[3]));
      else { sts128(sb + OFF_W + i * 16, b2h(v[0], .5f), b2h(v[1], .5f), b2h(v[2], .5f), b2h(v[3], .5f)); mh = mag2(mag2(mag2(mag2(mh, v[0]), v[1]), v[2]), v[3]); } }
    if (wbad(__reduce_max_sync(~0u, magr(mh)), 0x4700)) sts32(sb + OFF_MISC + 12, 1);
    proxy_fence();
    __syncwarp();
    mbar_arrive(sb + BAR_WH, lane == 0);
    if (fast) {
      mbar_wait(sb + BAR_WH);
      float chk = 0.f;
#pragma unroll 1
      for (uint32_t todo = UORD; todo; todo >>= 4) {
        const uint32_t nd = lds16(sb + OFF_GP + (todo & 3) * 1024 + w * 256 + (lane & 15) * 8 + 6), hb = (todo >> 3) & 1;
        const uint64_t b1 = DHI | (((sb + OFF_W) >> 4) + hb * 4);
        uint32_t f[8]; float acc[16];
#pragma unroll
        for (int j = 0; j < 8; j += 2) {
          const uint32_t a = j < 4 ? sb + OFF_H + nd * 128 + (((nd & 7) << 4) ^ (lane & 16)) : sb + OFF_P2 + (todo & 3) * 8192 + frag;
          if (j == 4) mbar_wait(sb + BAR_M + (todo & 3) * 8);
          ldsm4(f, a ^ ((j & 3) << 5)); ldsm4(f + 4, a ^ ((j & 3) << 5) ^ 32);
          wg_fence();
          if (j == 0) rs32b<0>(acc, f, b1); else if (j < 4) rs32b<1>(acc, f, b1 + 128 * j); else rs32h(acc, f, b1 + 128 * j);
          if (j < 4) rs32b<1>(acc, f + 4, b1 + 128 * j + 128); else rs32h(acc, f + 4, b1 + 128 * j + 128);
          wg_commit(); wg_wait0(); fence_regs(acc);
        }
        chk = fmaf(acc[0], 0.f, fmaf(acc[2], 0.f, chk));
#pragma unroll
        for (int k = 0; k < 2; k++) {
          const uint32_t o = __shfl_sync(~0u, nd, (lane >> 2) + 8 * k) * 128 + (lane & 3) * 16 + hb * 64;
          uint32_t x[4]; lds128(x, sb + OFF_H + (o ^ ((o >> 3) & 0x70)));
#pragma unroll
          for (int i = 0; i < 4; i++) x[i] = u2(__hadd2(b2(x[i]), b2(pack_bf16(silu_h(acc[4 * i + 2 * k]), silu_h(acc[4 * i + 2 * k + 1])))));
          if (o < nloc * 128) *(uint4*)((char*)p.out + (size_t)node0 * 128 + o) = make_uint4(x[0], x[1], x[2], x[3]);
        }
        __nanosleep(DEFNS);
      }
      uint32_t pa_[9];
#pragma unroll
      for (int k = 0; k < 9; k++) { const uint32_t i = t + 128 * k, n = (i * 43691u) >> 17; pa_[k] = lds16(sb + OFF_INV + n * 2) + (i - 3 * n) * 2; }
      uint16_t* po = p.out + (size_t)p.N * 64 + node0 * 3 + t;
      mbar_wait(sb + BAR_X);
#pragma unroll
      for (int k = 0; k < 9; k++) pa_[k] = lds16(sb + OFF_GP + pa_[k]);
#pragma unroll
      for (int k = 0; k < 9; k++) if (t + 128 * k < nloc * 3) po[128 * k] = pa_[k];
      asm volatile("{.reg .pred p, q; setp.neu.f32 p, %0, 0f00000000; bar.red.or.pred q, 5, 512, p;}" :: "f"(chk) : "memory");
    }
    return;
  }

  if (tid == 320) {
    mbar_init(sb + BAR_W, 1);
    asm volatile("fence.mbarrier_init.release.cluster;" ::: "memory");
    mbar_expect(sb + BAR_W, 2 * 8192 + 2304);
    tma_load(sb + OFF_W, tmb + TM_WE, 64, sb + BAR_W); tma_load(sb + OFF_W + 8192, tmb + TM_WE, 0, sb + BAR_W);
    bulk_load(sb + OFF_WS, p.we + 128 * 64, 2176, sb + BAR_W); bulk_load(sb + OFF_WS + 2176, p.wx, 128, sb + BAR_W);
  }
  if (tid == 288) {
#pragma unroll
    for (int a = BAR_SRC; a < BAR_END; a += 8) if (a != BAR_W) mbar_init(sb + a, a >= BAR_X ? 12 : a >= BAR_WH || a == BAR_PS || a == BAR_EP ? 4 : a == BAR_HB || a == BAR_U ? 2 : 1);
    asm volatile("fence.mbarrier_init.release.cluster;" ::: "memory");
    asm volatile("prefetch.tensormap [%0];" :: "l"(tmb + TM_XA)); asm volatile("prefetch.tensormap [%0];" :: "l"(tmb + TM_H));
    asm volatile("prefetch.tensormap [%0];" :: "l"(tmb + TM_XB)); asm volatile("prefetch.tensormap [%0];" :: "l"(tmb + TM_Q));
  }
  {
    if (tid < 144) { const uint32_t z = (tid >> 3) == 16 ? 0x8000u : 0u; sts128(sb + OFF_CNT + tid * 16, z, z, z, z); }
    else if (tid <= 144 + G) sts32(sb + OFF_BC + (tid - 144) * 4, ((tid - 144) & 31) * 4);
    const uint32_t sp = XPAD * 0x10001u, em = first_node(G);
    if (wid < 7) {
#pragma unroll
      for (int i = 0; i < 4; i++) sts128(sb + OFF_TS + tid * 16 + i * 3584, sp, sp, sp, sp);
    }
    static_assert(SCAP * 32 == 4 * 3584, "fill");
#pragma unroll 1
    for (int i = n4 + tid; i < 1536; i += 384) sts128(sb + OFF_DST + i * 16, em, em, em, em);
    if (tid == 321) sts128(sb + OFF_MISC, 0, 0, p.force_slow, 0);
  }
  bar_arrive(6, NTHR);
  bar_sync(0, 384);
  uint32_t ep, tag, eb0, pk[12], r0[12], r1[12], cb;
  uint2 vb[12];
  auto get_tag = [&]() { mbar_wait(sb + BAR_EP); ep = lds32(sb + OFF_MISC + 32); tag = (1 + ep % 3) << 30; eb0 = ealo - (tag >> 11); };
  if (wid == 11) {
    trap_if(sb != (uint32_t)__cvta_generic_to_shared(smraw));
#pragma unroll 1
    for (int k = 0; k < 3; k++) { const int nb = max(0, min(8192, n4 * 16 - k * 8192));
      mbar_wait(sb + BAR_DST + (k ? k + 1 : 0) * 8);
      if (lane == 0) { mbar_expect(sb + BAR_SRC + k * 8, nb);
        if (nb) bulk_load(sb + OFF_SRCI + k * 8192, (const char*)(p.src + e0) + k * 8192, nb, sb + BAR_SRC + k * 8); } }
    proxy_fence();
    get_tag();
    mbar_wait(sb + BAR_PS);
    bar_sync(12, 384);
    uint32_t xm = 0;
#pragma unroll
    for (int k = 0; k < 5; k++) xm |= (lds32(sb + OFF_BC + min(lane + 32 * k, G - 1) * 4) >= (65 << 9) && lane + 32 * k < G) << k;
    auto ext_send = [&](int pl) {
      uint32_t x = xm;
      for (uint32_t m; (m = __ballot_sync(~0u, x));) {
        const uint32_t l = __ffs(m) - 1, j = l + 32 * (__ffs(__shfl_sync(~0u, x, l)) - 1);
        if (lane == l) x &= x - 1;
        const uint32_t e = min(lds16(sb + OFF_AX + j * 128 + ((4 * l + 2 * lane) & 126)), 6143u);
        if (pl) st_ext(p.xe + (j * G + cta) * 32 + lane, lds32(sb + OFF_SRCI + e * 4) + tag + (e << 16), ep);
        else { const uint32_t cn = lds32(sb + OFF_BC + j * 4) >> 9, v = cn > 96 ? 1 : lane + 64 < cn ? 512 | (lds32(sb + OFF_DST + e * 4) & 511) : 0;
          asm volatile("red.shared.xor.b32 [%0], %1;" :: "r"(sb + OFF_SA + j * 128 + ((l + lane) & 31) * 4), "r"(((v & 63) << 10) | ((v >> 6) << 26)) : "memory"); }
      }
    };
    if (__any_sync(~0u, xm)) { ext_send(0); proxy_fence(); __syncwarp(); }
    if (lane == 0) { tma_store(tmb + TM_XA, cta * 64, 0, sb + OFF_SA); bulk_commit(); mbar_arrive(sb + BAR_AI); bulk_wait(); hint_signal(p.sync + 4); mbar_arrive(sb + BAR_AW); STAMP(16); }
    __syncwarp();
    bar_sync(13, 384);
    ext_send(1);
    mbar_arrive(sb + BAR_AX, lane == 0);
    mbar_wait(sb + BAR_HA);
    __nanosleep(BDEL);
    if (lane == 0) {
#pragma unroll 1
      for (int r = 0; r < G; r += BROWS) { tma_store(tmb + TM_XB, cta * 64, r, sb + OFF_SB + r * 256); bulk_commit(); bulk_wait(); }
      hint_signal(p.sync + 5);
      STAMP(17);
    }
    __syncwarp();
  } else {
    {
      uint32_t d[4 * NCH], jj[4 * NCH], rr[4 * NCH];
      auto count = [&](int k) {
        mbar_wait(sb + BAR_DST + k * 8);
        lds128(d + 4 * k, sb + OFF_DST + (tid + NWK * k) * 16);
#pragma unroll
        for (int i = 4 * k; i < 4 * k + 4; i++) { jj[i] = d[i] * p.magic; rr[i] = atoms_add(__dp4a(jj[i], 0x04000000u, sb + OFF_BC), 0x202u); }
      };
      auto place = [&](int k) {
#pragma unroll
        for (int i = 4 * k; i < 4 * k + 4; i++) {
          const uint32_t o = __dp4a(jj[i], 0x80000000u, rr[i] & 0x807Eu);
          d[i] = (d[i] & 511) | (tag >> 16);
          asm("{.reg .pred p; setp.ge.u32 p, %1, 0x8000; @p add.u32 %0, %2, %3;}" : "+r"(d[i]) : "r"(o), "r"(tid * 4), "r"(NWK * k * 4 + (i & 3)));
          sts16(sb + OFF_SA + o, d[i]); jj[i] = __viaddmin_u32(o, o, G * 256);
        }
      };
      count(0); STAMP(1); count(1); get_tag(); place(0); count(2); place(1); count(3); place(2);
      if (wid < 4) { count(4); STAMP(15); place(3); place(4); } else place(3);
      proxy_fence();
      bar_arrive(12, 384);
      STAMP(2);
      mbar_wait(sb + BAR_AI);
      mbar_wait(sb + BAR_SRC); mbar_wait(sb + BAR_SRC + 8); mbar_wait(sb + BAR_SRC + 16);
      STAMP(12);
#pragma unroll
      for (int k = 0; k < NCH; k++) lds128(d + 4 * k, sb + OFF_SRCI + (tid + NWK * k) * 16);
      const uint32_t tb = tag + (tid << 18);
#pragma unroll
      for (int i = 0; i < 4 * NCH; i++) if (i < 4 * NCH - 4 || wid < 4) sts32(sb + OFF_SB + jj[i], d[i] + tb + ((NWK * (i >> 2) * 4 + (i & 3)) << 16));
      proxy_fence();
      bar_arrive(13, 384);
      STAMP(3);
    }
    const uint32_t rot = (lane + cta) & 31;
    cb = sb + OFF_CNT - (tag >> 14);
    {
      const uint32_t* xa = (const uint32_t*)(p.xa + (cta * G + wid) * 8) + rot;
      if (wid < 8) { const uint32_t e_ = ealo + epad * 32;
        mbar_wait(sb + BAR_AX);
#pragma unroll
        for (int i = 0; i < 7; i++) sts128(sb + OFF_TE + tid * 16 + i * 4096, e_, e_, e_, e_); }
      static_assert(SCAP * 64 == 7 * 4096, "fill");
      if (wid == 10) { hint_wait(p.sync + 4, ep * G); mbar_arrive(sb + BAR_HA, lane == 0); }
      mbar_wait(sb + BAR_HA);
      STAMP(14);
      const uint32_t tp = tag | (tag >> 16);
      uint32_t st;
#pragma unroll 1
      for (int spin = 0;; spin++) {
        st = 0;
#pragma unroll
        for (int k = 0; k < 12; k++) asm volatile("ld.relaxed.gpu.global.u32 %0, [%1];" : "=r"(pk[k]) : "l"(xa + k * 352) : "memory");
#pragma unroll
        for (int k = 0; k < 12; k++) st |= pk[k] ^ tp;
        st = __reduce_or_sync(~0u, st);
        if (!(st >> 30)) break;
        trap_if(spin > 2000000);
      }
      if (st & 0x3C00FC00u) {
#pragma unroll 1
        for (;;) {
          uint32_t x = 0, row = 0;
#pragma unroll
          for (int k = 0; k < 12; k++) { const uint32_t y = (pk[k] ^ tp) & 0x3C00FC00u; if (!x && y) { x = y; row = wid + 11 * k; pk[k] ^= y; } }
          if (!__any_sync(~0u, x)) break;
          const uint32_t n = ((x >> 10) & 63) | ((x >> 20) & 0x1C0);
          if (x >> 29) {
            const uint32_t r = atoms_add(sb + OFF_CNT + n * 4, 16), idx = atoms_add(sb + OFF_MISC + 4, 1);
            if (idx < 256) sts32(sb + OFF_EXT + idx * 4, n | (row << 9) | (lane << 17) | (min(r >> 4, 255u) << 22));
            else x = 1;
          }
          if (x && !(x >> 29)) sts32(sb + OFF_MISC + 8, 1);
          __syncwarp();
        }
      }
#pragma unroll
      for (int k = 0; k < 12; k++) { r0[k] = mad16(pk[k], 0x0004u, cb); r1[k] = mad16(pk[k], 0x0400u, cb); vb[k].x = atoms_add(r0[k], 16); vb[k].y = atoms_add(r1[k], 16); }
    }
    STAMP(4);
    if (wid >= 6) bar_arrive(11, NWK);
    if (wid < 6) {
      uint32_t ca[2], ky[2], dr[2], sq[2], ps[4];
#pragma unroll
      for (int i = 0; i < 2; i++) { ca[i] = sb + OFF_CNT + ((node0 + tid + 192 * i) & 511) * 4; lds64(ps[2 * i], ps[2 * i + 1], sb + OFF_POS + (tid + 192 * i) * 8); ps[2 * i + 1] = __byte_perm(ps[2 * i + 1], tid + 192 * i, 0x5410); }
      bar_sync(11, NWK);
      STAMP(5);
#pragma unroll
      for (int i = 0; i < 2; i++) ky[i] = (lds32(ca[i]) + 16) >> 5;
      if (max(ky[0], ky[1]) > 31) sts32(sb + OFF_MISC + 8, 1);
#pragma unroll
      for (int i = 0; i < 2; i++) { ky[i] = min(ky[i], 31u); dr[i] = atoms_add(sb + OFF_DH + ky[i] * 4, 1); }
      bar_sync(10, 192);
      const uint32_t hv = lds32(sb + OFF_DH + lane * 4);
      uint32_t inc = hv;
#pragma unroll
      for (int o = 1; o < 32; o <<= 1) asm("{.reg .pred p; .reg .b32 y; shfl.sync.down.b32 y|p, %0, %1, 31, -1; @p add.u32 %0, %0, y;}" : "+r"(inc) : "r"(o));
#pragma unroll
      for (int i = 0; i < 2; i++) {
        const uint32_t pos = __shfl_sync(~0u, inc - hv, ky[i]) + dr[i];
        const uint32_t ak = (uint32_t)(QCODE >> ((pos >> 5) * 4)) & 15, l = (pos >> 3) & 3;
        sq[i] = (ak >> 2) * 16 + ((QREV >> (pos >> 5) & 1) ? 3 - l : l) * 4 + (ak & 3);
        dr[i] = pos & 7;
        asm volatile("{.reg .pred p; setp.eq.u32 p, %2, 0; @p st.shared.u8 [%0], %1;}" :: "r"(sb + OFF_LEN + sq[i]), "r"(max(ky[i], 1u)), "r"(dr[i]) : "memory");
        sts64(sb + OFF_GP + sq[i] * 64 + dr[i] * 8, ps[2 * i], ps[2 * i + 1]);
        sts16(sb + OFF_INV + (tid + 192 * i) * 2, sq[i] * 64 + dr[i] * 8);
      }
      bar_sync(10, 192);
      const uint32_t ln = lds32(sb + OFF_LEN + min(lane, 11) * 4), tot = __dp4a(ln, 0x01010101u, 0u);
      inc = tot;
#pragma unroll
      for (int o = 1; o < 16; o <<= 1) asm("{.reg .pred p; .reg .b32 y; shfl.sync.up.b32 y|p, %0, %1, 0, -1; @p add.u32 %0, %0, y;}" : "+r"(inc) : "r"(o));
      if (wid == 1) sts32(sb + OFF_CNT + 2048 + lane * 4, 0);
      if (tid < 12) { sts32(sb + OFF_LEN + 64 + tid * 4, inc - tot); if (inc > SCAP - 12) sts32(sb + OFF_MISC + 8, 1); }
#pragma unroll
      for (int i = 0; i < 2; i++) sts32(ca[i], __dp4a(__shfl_sync(~0u, ln, sq[i] >> 2), 0x00010101u >> (24 - 8 * (sq[i] & 3)), __shfl_sync(~0u, inc - tot, sq[i] >> 2)) * 32 + dr[i] * 2);
    }
    bar_arrive(7, 384);
  }
  bar_sync(1, 384);
  STAMP(6);
  if (wid != 11 && !__shfl_sync(~0u, lds32(sb + OFF_MISC + 8), 0)) {
#pragma unroll
    for (int k = 0; k < 12; k++) { r0[k] = lds32(r0[k]); r1[k] = lds32(r1[k]); }
#pragma unroll
    for (int k = 0; k < 12; k++) { r0[k] += vb[k].x; r1[k] += vb[k].y; }
  } else {
#pragma unroll
    for (int k = 0; k < 12; k++) r0[k] = r1[k] = 0x8000;
  }
  auto put_ids = [&]() {
    const uint32_t id = wid * 256 + ((lane + cta) & 31) * 8;
    auto put = [&](uint32_t x, uint32_t v) { asm volatile("{.reg .pred p; setp.lt.u32 p, %0, 0x8000; @p st.shared.u16 [%0+%2], %1;}" :: "r"(x), "h"((uint16_t)v), "n"(sb + OFF_TS) : "memory"); };
#pragma unroll
    for (int k = 0; k < 12; k++) { put(r0[k], id + k * 2816); put(r1[k], id + k * 2816 + 4); }
  };
  STAMP(7);
  mbar_wait(sb + BAR_QR);
  asm volatile("setmaxnreg.inc.sync.aligned.u32 152;");
  uint32_t pa[8], sp[8]; float chk = 0.f;
  {
    uint32_t hf[16], mp = 0; float a0[32];
    const uint32_t nd = lds16(sb + OFF_GP + wid * 256 + (lane & 15) * 8 + 6);
#pragma unroll
    for (int j = 0; j < 4; j++) ldsm4(hf + 4 * j, (sb + OFF_H + nd * 128 + (((nd & 7) << 4) ^ (lane & 16))) ^ (j << 5));
    const uint64_t db = DHI | ((sb + OFF_W + 8192) >> 4);
    wg_fence();
    rs64b<0>(a0, hf[0], hf[1], hf[2], hf[3], db); rs64b<1>(a0, hf[4], hf[5], hf[6], hf[7], db + 128); rs64b<1>(a0, hf[8], hf[9], hf[10], hf[11], db + 256); rs64b<1>(a0, hf[12], hf[13], hf[14], hf[15], db + 384);
    wg_commit();
    put_ids();
    wg_wait0(); fence_regs(a0);
#pragma unroll
    for (int j = 0; j < 8; j++) { const uint32_t x = pack_f16(.5f * a0[4 * j], .5f * a0[4 * j + 1]), y = pack_f16(.5f * a0[4 * j + 2], .5f * a0[4 * j + 3]); mp = hmag(hmag(mp, x), y);
      asm volatile("movmatrix.sync.aligned.m8n8.trans.b16 %0, %1;" : "=r"(pa[j]) : "r"(x)); asm volatile("movmatrix.sync.aligned.m8n8.trans.b16 %0, %1;" : "=r"(sp[j]) : "r"(y)); }
    if (magr(mp) >= 0x7000) chk = 1.f;
  }
  if (wid == 0) STAMP(23);
  uint32_t bad;
  {
    const uint32_t ring = sb + OFF_RING + wid * STG, p2 = sb + OFF_P2 + wid * 2048;
    uint32_t lens = __shfl_sync(~0u, lds32(sb + OFF_LEN + wid * 4), 0);
    uint32_t rem = __dp4a(lens, 0x20202020u, 0u);
    const uint32_t base = min(lds32(sb + OFF_LEN + 64 + wid * 4), SCAP);
    uint32_t a_s = sb + OFF_TS + base * 32 + (lane >> 3) * 8, a_e = sb + OFF_TE + base * 64 + (lane >> 1) * 4;
    uint32_t k0 = (uint32_t)(uint64_t)p.q + (((lane & 7) ^ ((lane >> 1) & 4)) << 4), k1 = k0 ^ 16, k2 = k0 ^ 32, k3 = k0 ^ 48, ke = ((lane ^ (lane >> 3)) & 1) << 4;
    uint32_t dst0 = ring + (lane >> 3) * 640 + (lane & 7) * 16;
    const uint32_t qhi = (uint32_t)((uint64_t)p.q >> 32), ehi = (uint32_t)((uint64_t)p.ea >> 32);
    uint32_t s0, s1, ev, to = 0, so = 12 * STG;
    auto tl_ = [&]() { lds64(s0, s1, a_s + to); asm volatile("ld.shared.u32 %0, [%1]; add.u32 %1, %1, 64;" : "=&r"(ev), "+r"(a_e) :: "memory"); to += 32; };
#define CPQ(LH, x, k, off) "dp2a." LH ".u32.u32 lo, " x ", 0x80000080, " k "; mov.b64 a, {lo, %7}; @p cp.async.cg.shared.global [%0+" #off "], [a], 16;\n"
    uint64_t pe; asm volatile("createpolicy.fractional.L2::evict_normal.b64 %0, 1.0;" : "=l"(pe));
    uint32_t one = __shfl_sync(~0u, lane, 1);
#define CPE "or.b32 lo, %10, %11; mov.b64 a, {lo, %12}; @p cp.async.cg.shared.global.L2::cache_hint [%0+512], [a], 16, %13;\n"
#define CPA(BODY) asm volatile("{.reg .b32 lo; .reg .b64 a; .reg .pred p; setp.le.u32 p, %8, %9;\n" BODY "}" \
      :: "r"(so * one + dst0), "r"(s0), "r"(s1), "r"(k0), "r"(k1), "r"(k2), "r"(k3), "r"(qhi), "r"(to), "r"(rem), "r"(ev), "r"(ke), "r"(ehi), "l"(pe) : "memory")
#define CPQ4 CPQ("lo", "%1", "%3", 0) CPQ("hi", "%1", "%4", 128) CPQ("lo", "%2", "%5", 256) CPQ("hi", "%2", "%6", 384) "cp.async.commit_group;"
    auto issue = [&]() { CPA(CPE CPQ4); so = so == (NST - 1) * 12 * STG ? 0 : so + 12 * STG; };
    const int g = lane >> 2, qd = lane & 3;
    const uint32_t sw = ((lane >> 4) ^ (lane & 7)) << 4, fr = (lane & 15) * 128 + sw;
    uint32_t qa0 = ring + (g & 3) * 640 + qd * 128 + sw, qa1 = qa0 ^ 32, qa2 = qa0 ^ 64, qa3 = qa0 ^ 96;
    uint32_t eadr = ring + 512 + (g & 3) * 640 + qd * 32 + ((((lane >> 4) ^ g) & 1) << 4);
    uint32_t oh0 = g == 2 * qd ? 0x3C00u : g == 2 * qd + 1 ? 0x3C000000u : 0u, oh1 = oh0;
    uint32_t a_g = sb + OFF_GP + wid * 256 + lane * 2;
    asm volatile("shfl.sync.idx.b32 %0, %0, %1, 31, -1;" : "+r"(oh1) : "r"(lane));
    uint32_t w3[16], wv[8], bp[16], sum[8], Y[16], M[16], own, ownp, dpk, tl[16], th[16];
    float pacc = 0.f;
    auto wload = [&]() {
#pragma unroll
      for (int j = 0; j < 4; j++) ldsm4t(w3 + 4 * j, (sb + OFF_W3 + fr) ^ (j << 5));
      lds128(wv, sb + OFF_WX + (a_g & 6) * 16); lds128(wv + 4, sb + OFF_WX + 16 + (a_g & 6) * 16);
    };
    auto hload = [&](uint32_t (&hf)[16], uint32_t nd) {
      const uint32_t hrow = sb + OFF_H + nd * 128 + (((nd & 7) << 4) ^ ((a_g >> 1) & 16));
#pragma unroll
      for (int j = 0; j < 4; j++) ldsm4(hf + 4 * j, hrow ^ (j << 5));
      return hrow;
    };
    { uint32_t wd[8]; const uint32_t a = sb + OFF_WD + (lane & 7) * 128 + ((((lane >> 3) ^ lane) & 7) << 4);
      ldsm4t(wd, a); ldsm4t(wd + 4, a ^ 64);
#pragma unroll
      for (int j = 0; j < 8; j++) { bp[2 * j] = wd[j]; bp[2 * j + 1] = pa[j]; } }
    own = lds16(a_g) * 0x10001u;
    wload();
    if (__shfl_sync(~0u, lds32(sb + OFF_MISC + 8), 0)) rem = 0;
    auto resolve = [&](auto NBK, uint32_t o) {
      constexpr int NB = decltype(NBK)::value;
      uint32_t id[NB], c0[NB], c1[NB]; const uint32_t a = base * 32 + o + lane * 4;
#pragma unroll
      for (int i = 0; i < NB; i++) { id[i] = lds32(sb + OFF_TS + a + i * 128); if (o + lane * 4 + i * 128 >= rem) id[i] = XPAD * 0x10001u; }
      uint32_t st = 0;
#pragma unroll
      for (int i = 0; i < NB; i++) { c0[i] = lds32(sb + OFF_XB + (id[i] & 0xFFFF)); c1[i] = lds32(sb + OFF_XB + (id[i] >> 16)); }
#pragma unroll
      for (int i = 0; i < NB; i++) st |= (c0[i] ^ tag) | (c1[i] ^ tag);
      for (int spin = 0; __any_sync(~0u, st >> 30); spin++) {
        st = 0; trap_if(spin > 2000000);
#pragma unroll
        for (int i = 0; i < NB; i++) {
          asm volatile("{.reg .pred p, q; setp.lt.u32 p, %4, %6; setp.lt.u32 q, %5, %6; @p ld.relaxed.gpu.global.u32 %0, [%2]; @q ld.relaxed.gpu.global.u32 %1, [%3];}"
            : "+r"(c0[i]), "+r"(c1[i]) : "l"((const char*)p.xb + cta * XPAD + (id[i] & 0xFFFF)), "l"((const char*)p.xb + cta * XPAD + (id[i] >> 16)), "r"(id[i] & 0xFFFF), "r"(id[i] >> 16), "n"(XPAD) : "memory");
          st |= (c0[i] ^ tag) | (c1[i] ^ tag); }
      }
#pragma unroll
      for (int i = 0; i < NB; i++) { const uint32_t j0 = (id[i] >> 8) & 255, j1 = id[i] >> 24;
        asm volatile("{.reg .pred p, q, r; setp.lt.u32 p, %5, %9; setp.lt.u32 q, %6, %9; setp.lt.u32 r, %7, %8;\n"
          "@p st.shared.u32 [%0], %2; @q st.shared.u32 [%0+4], %3; @r st.shared.u32 [%1], %4;}"
          :: "r"(sb + OFF_TE + 2 * a + i * 256), "r"(sb + OFF_TS + a + i * 128), "r"(mad16(c0[i], 0x2000u, eb0 + j0 * p.EPC * 32)), "r"(mad16(c1[i], 0x2000u, eb0 + j1 * p.EPC * 32)),
             "r"(__byte_perm(c0[i], c1[i], 0x5410)), "r"(j0), "r"(j1), "r"(o + lane * 4 + i * 128), "r"(rem), "n"(G) : "memory"); }
    };
    bar_sync(2, 384);
    if (wid == 0) STAMP(27);
    mbar_wait(sb + BAR_HB);
    if (wid == 0) STAMP(22);
#pragma unroll 1
    for (uint32_t o = 0, go = 0; !(go & 1); o += 128 * RNB) {
      if (o < rem) { resolve(IC<RNB>(), o);
        asm volatile("{.reg .pred p; mbarrier.test_wait.parity.shared::cta.b64 p, [%1], 0; vote.sync.all.pred p, p, -1; selp.u32 %0, 64, 0, p;}" : "=r"(go) : "r"(sb + (SPQ ? BAR_QH : BAR_QP)) : "memory"); }
      else { bar_arrive(4, NTHR);
        if (FB) { mbar_arrive(sb + BAR_RS, lane == 0); mbar_wait(sb + (SPQ ? BAR_QH : BAR_QP)); go = 63; } else { bar_sync(8, 384); mbar_wait(sb + BAR_QP); go = 95; }
        if (wid == 0) STAMP(24); }
      __syncwarp();
#pragma unroll 1
      while (to < go) { tl_(); issue(); if (to == 32) STAMP(13); }
    }
    mbar_wait(sb + BAR_QP);
    bad = __shfl_sync(~0u, lds32(sb + OFF_MISC + 8), 0);
   if (!bad) {
    auto qcheck = [&](uint32_t o) {
      const uint32_t a = ring + o + (g & 3) * 640 + qd * 128 + ((((lane >> 2) & 4) ^ (lane & 7)) << 4) + 12;
      if (((lds32(a) ^ ep) | (lds32(a ^ 32) ^ ep)) & 1) chk = 1.f; };
    auto body = [&](auto MODE) {
      constexpr int mode = decltype(MODE)::value;
      uint32_t T[16], ef[4], q0, q1, x0, x1, x2; float e0_, e1_, cs[4];
      auto mu = [&](int j) {
#pragma unroll
        for (int i = 2 * j; i < 2 * j + 2; i++) asm volatile("{.reg .b16 l, h; mov.b32 {l, h}, %2; tanh.approx.f16 l, l; tanh.approx.f16 h, h; cvt.u32.u16 %0, l; cvt.u32.u16 %1, h;}" : "=r"(tl[i]), "=r"(th[i]) : "r"(Y[i])); };
      auto fi = [&](int j) {
#pragma unroll
        for (int i = 2 * j; i < 2 * j + 2; i++) asm volatile("{.reg .b32 t; prmt.b32 t, %2, %3, 0x5410; fma.rn.f16x2 %0, %1, t, %1;}" : "=r"(M[i]) : "r"(Y[i]), "r"(tl[i]), "r"(th[i])); };
      auto ad = [&](int j) { asm volatile("add.rn.f16x2 %0, %0, %1; add.rn.f16x2 %0, %0, %2;" : "+r"(sum[j]) : "r"(M[2 * j]), "r"(M[2 * j + 1])); };
      auto he = [&](int j) { asm volatile("mma.sync.aligned.m16n8k16.row.col.f16.f16.f16.f16 {%0,%1}, {%2,%3,%4,%5}, {%6,%7}, {%0,%1};" : "+r"(T[2 * j]), "+r"(T[2 * j + 1]) : "r"(ef[0]), "r"(ef[1]), "r"(ef[2]), "r"(ef[3]), "r"(w3[2 * j]), "r"(w3[2 * j + 1])); };
      auto hs = [&](int j) { asm volatile("mma.sync.aligned.m16n8k16.row.col.f16.f16.f16.f16 {%0,%1}, {%2,%3,%4,%5}, {%6,%7}, {%8,%9};" : "=r"(Y[2 * j]), "=r"(Y[2 * j + 1]) : "r"(q0), "r"(q1), "r"(oh0), "r"(oh1), "r"(bp[2 * j]), "r"(bp[2 * j + 1]), "r"(T[2 * j]), "r"(T[2 * j + 1])); };
      auto hc = [&](int j) {
        if (j) asm volatile("mma.sync.aligned.m16n8k16.row.col.f32.f16.f16.f32 {%0,%1,%2,%3}, {%4,%5,%6,%7}, {%8,%9}, {%0,%1,%2,%3};" : "+f"(cs[0]), "+f"(cs[1]), "+f"(cs[2]), "+f"(cs[3]) : "r"(M[4 * j]), "r"(M[4 * j + 1]), "r"(M[4 * j + 2]), "r"(M[4 * j + 3]), "r"(wv[2 * j]), "r"(wv[2 * j + 1]));
        else asm volatile("mma.sync.aligned.m16n8k16.row.col.f32.f16.f16.f32 {%0,%1,%2,%3}, {%4,%5,%6,%7}, {%8,%9}, {%10,%10,%10,%10};" : "=f"(cs[0]), "=f"(cs[1]), "=f"(cs[2]), "=f"(cs[3]) : "r"(M[0]), "r"(M[1]), "r"(M[2]), "r"(M[3]), "r"(wv[0]), "r"(wv[1]), "f"(0.f)); };
      auto cv = [&](int i) { asm volatile("{.reg .b32 a, b; shl.b32 a, %0, 16; and.b32 b, %0, 0xFFFF0000; cvt.rn.f16x2.f32 %0, b, a;}" : "+r"(ef[i])); };
      auto un = [&]() { asm volatile("shl.b32 %0, %2, 16; and.b32 %1, %2, 0xFFFF0000;" : "=&f"(e0_), "=&f"(e1_) : "r"(dpk)); };
      auto ex0 = [&]() { asm volatile("prmt.b32 %0, %3, %4, 0x6420; prmt.b32 %1, %5, %6, 0x6420; prmt.b32 %2, %7, %8, 0x6420;" : "=&r"(x0), "=&r"(x1), "=&r"(x2) : "r"(T[0]), "r"(T[1]), "r"(T[2]), "r"(T[3]), "r"(T[4]), "r"(T[5])); };
      auto ex1 = [&]() { asm volatile("{.reg .b32 a, b; shl.b32 a, %2, 3; shl.b32 b, %3, 6; lop3.b32 a, %1, a, 0x38383838, 0xD8; lop3.b32 a, a, b, 0xC0C0C0C0, 0xD8; sub.rn.bf16x2 %0, %4, a;}" : "=r"(dpk) : "r"(x0), "r"(x1), "r"(x2), "r"(own)); };
      auto ex2 = [&]() { asm volatile("{.reg .b32 a, b, d, u; .reg .b16 l, h; shl.b32 a, %2, 16; and.b32 b, %2, 0xFFFF0000; cvt.rn.f16x2.f32 d, b, a; mul.rn.f16x2 %0, d, d; mov.b32 {l, h}, d; mov.b32 u, {h, h}; mul.rn.f16x2 %1, u, u;}" : "=&r"(q0), "=&r"(q1) : "r"(dpk)); };
      auto pf = [&]() { asm volatile("fma.rn.f32 %0, %1, %2, %0; fma.rn.f32 %0, %3, %4, %0;" : "+f"(pacc) : "f"(cs[0]), "f"(e0_), "f"(cs[2]), "f"(e1_)); };
      if (mode == 2) { LASTSEQ return; }
      asm volatile("cp.async.wait_group %0;" :: "n"(FB && mode == 1 ? 1 : NST - 1) : "memory");
      __syncwarp();
      if (mode == 1) { STAMP(8); so = 12 * STG; }
      ldsm4(ef, eadr + so); ldsm4(T, qa0 + so); ldsm4(T + 4, qa1 + so); ldsm4(T + 8, qa2 + so); ldsm4(T + 12, qa3 + so);
      if (mode == 1) {
        if (SPQ) qcheck(12 * STG);
        tl_(); if (!FB) issue();
        cv(0); cv(1); cv(2); cv(3); ex0(); ex1(); ex2();
#pragma unroll
        for (int j = 0; j < 8; j++) { he(j); hs(j); }
        FIRSTSEQ
        if (FB) { mbar_wait(sb + BAR_RS); so = 0; issue(); tl_(); issue(); }
        if (SPQ) { asm volatile("cp.async.wait_group %0;" :: "n"(NST - 1) : "memory"); __syncwarp(); qcheck(24 * STG); }
        return;
      }
      BODYSEQ
    };
#pragma unroll
    for (int j = 0; j < 8; j++) sum[j] = 0;
    body(IC<1>());
    int cnt = (lens & 255) - 1;
    auto pload = [&](uint32_t (&x)[8], uint32_t o) { const uint32_t l = a_g >> 1, a = p2 + o + (l & 7) * 128 + (((((l >> 3) & 3) ^ l) & 7) << 4); ldsm4t(x, a); ldsm4t(x + 4, a ^ 64); };
    auto flush = [&]() {
      asm volatile("{.reg .pred p; setp.ne.u32 p, %2, 6; @p st.shared.u16 [%0+-64], %1;}" :: "r"(a_g), "h"((uint16_t)pack_bf16(bf_hi(ownp) + pacc, 0.f)), "r"(a_g & 6) : "memory");
      chk = fmaf(pacc, 0.f, chk); pacc = 0.f; };
    constexpr uint64_t b1 = DHI | ((sb + OFF_W) >> 4), b2_ = b1 + 512;
    auto mma_h = [&](float (&acc)[32], uint32_t (&hf)[16]) {
      rs64b<0>(acc, hf[0], hf[1], hf[2], hf[3], b1); rs64b<1>(acc, hf[4], hf[5], hf[6], hf[7], b1 + 128); rs64b<1>(acc, hf[8], hf[9], hf[10], hf[11], b1 + 256); rs64b<1>(acc, hf[12], hf[13], hf[14], hf[15], b1 + 384); };
    auto mma_m = [&](float (&acc)[32]) {
      rs64h<1>(acc, sp[0], sum[0], sp[1], sum[1], b2_); rs64h<1>(acc, sp[2], sum[2], sp[3], sum[3], b2_ + 128); rs64h<1>(acc, sp[4], sum[4], sp[5], sum[5], b2_ + 256); rs64h<1>(acc, sp[6], sum[6], sp[7], sum[7], b2_ + 384);
      wg_commit(); wg_wait0(); fence_regs(acc);
      STAMP(10);
      chk = fmaf(acc[0], 0.f, fmaf(acc[2], 0.f, chk)); };
    auto roff = [&](uint32_t nd, int r) { return __shfl_sync(~0u, nd, ((a_g >> 3) & 7) + 8 * r) * 128 + (a_g & 6) * 8; };
    auto radr = [&](uint32_t o, int k) { return sb + OFF_H + (o ^ ((o >> 3) & 0x70) ^ ((k >> 1) << 6)); };
    auto fin = [&](float (&acc)[32], uint32_t* x, int k) {
#pragma unroll
      for (int i = 0; i < 4; i++) { const int c = 16 * (k >> 1) + 4 * i + 2 * (k & 1); x[i] = u2(__hadd2(b2(x[i]), b2(pack_bf16(silu_h(acc[c]), silu_h(acc[c + 1]))))); } };
#pragma unroll 1
    for (int t = 0;; t++) {
#pragma unroll 1
      for (; cnt > 0; cnt--) { body(IC<0>());
      }
      if (!(t & 1)) {
        ownp = own; a_g += 64;
        if (t == 6) break;
        pe = pol_first();
        own = lds16(a_g) * 0x10001u;
        if (t == 2) { const uint32_t a = ((a_g & 16) ? p2 : sb + OFF_WD) + ((a_g << 6) & 0x380) + (qa0 & 0x70);
          mbar_wait(sb + BAR_U);
#pragma unroll
          for (int j = 0; j < 4; j++) ldsm4t(bp + 4 * j, a ^ (j << 5));
        } else {
#pragma unroll
          for (int j = 0; j < 8; j++) bp[2 * j + 1] = sp[j];
        }
        lens >>= 8; cnt = 1;
        continue;
      }
      cnt = (lens & 255) - 1;
      flush();
      if (t == 3) {
        uint32_t x[8];
        pload(x, 1024);
        __syncwarp();
#pragma unroll
        for (int j = 0; j < 4; j++) stsm4((p2 + ((a_g << 6) & 0x780) + (qa0 & 0x70)) ^ (j << 5), sp[2 * j], sum[2 * j], sp[2 * j + 1], sum[2 * j + 1]);
#pragma unroll
        for (int j = 0; j < 8; j++) sum[j] = x[j];
        __syncwarp();
        mbar_arrive(sb + BAR_M + (wid >> 2) * 8, (a_g & 62) == 0);
      }
#pragma unroll
      for (int j = 0; j < 8; j++) { sp[j] = sum[j]; asm volatile("mov.b32 %0, 0;" : "=r"(sum[j])); }
    }
    {
      uint32_t hf[16], v[16]; float acc[32];
      const uint32_t nd = lds16(sb + OFF_GP + wid * 256 + (lane & 15) * 8 + 134), o[2] = {roff(nd, 0), roff(nd, 1)};
      hload(hf, nd);
#pragma unroll
      for (int k = 0; k < 4; k++) lds128(v + 4 * k, radr(o[k & 1], k));
      mbar_wait(sb + BAR_WH);
      wg_fence(); mma_h(acc, hf); wg_commit();
      body(IC<2>());
      STAMP(9);
      flush();
      __syncwarp();
      mbar_arrive(sb + BAR_X, lane == 0);
      wg_fence();
      mma_m(acc);
#pragma unroll
      for (int k = 0; k < 4; k++) { fin(acc, v + 4 * k, k);
        asm volatile("{.reg .pred p; setp.lt.u32 p, %5, %6; @p st.global.v4.b32 [%0], {%1,%2,%3,%4};}" :: "l"((const char*)p.out + (size_t)node0 * 128 + o[k & 1] + (k >> 1) * 64), "r"(v[4 * k]), "r"(v[4 * k + 1]), "r"(v[4 * k + 2]), "r"(v[4 * k + 3]), "r"(o[k & 1]), "r"(nloc * 128) : "memory"); }
    }
    asm volatile("{.reg .pred p, q; setp.neu.f32 p, %1, 0f00000000; setp.ne.or.u32 p, %2, 0, p; bar.red.or.pred q, 5, 512, p; selp.u32 %0, 1, 0, q;}" : "=r"(bad) : "f"(chk), "r"(lds32(sb + OFF_MISC + 12)) : "memory");
    STAMP(11);
   } else { asm volatile("cp.async.wait_all;" ::: "memory"); bar_sync(5, 384); }
  }
  if (bad) slow_path(p, wid, lane, node0, nloc);
}

}

typedef CUresult (*EncodeFn)(CUtensorMap*, CUtensorMapDataType, cuuint32_t, void*, const cuuint64_t*, const cuuint64_t*, const cuuint32_t*, const cuuint32_t*,
                             CUtensorMapInterleave, CUtensorMapSwizzle, CUtensorMapL2promotion, CUtensorMapFloatOOBfill);

extern "C" void kernel_launch(void* const* d_in, const int* in_sizes, int n_in, void* d_out, int out_size) {
  Params p; Maps maps;
  p.h = (const uint4*)d_in[0]; p.pos = (const uint16_t*)d_in[1]; p.ea = (const uint4*)d_in[2];
  p.src = (const int*)d_in[3]; p.dst = (const int*)d_in[4];
  p.we = (const uint16_t*)d_in[5]; p.wx = (const uint16_t*)d_in[6]; p.wh = (const uint16_t*)d_in[7];
  p.out = (uint16_t*)d_out;
  p.N = in_sizes[0] / 64; p.E = in_sizes[3];
  p.EPC = ((p.E + G * 4 - 1) / (G * 4)) * 4;
  p.magic = (uint32_t)(((uint64_t)G << 24) / (uint64_t)p.N);
  p.inv = (1ull << 56) / p.magic;
  const uint64_t ea0 = (uint64_t)d_in[2], ea1 = ea0 + (uint64_t)p.E * 32 - 1;
  p.force_slow = ((ea0 >> 32) != (ea1 >> 32)) || (ea0 & 31) || (p.E & 3);
  void* qp = nullptr;
  cudaGetSymbolAddress(&qp, g_q);
  p.q = (char*)qp;
  if (((uint64_t)p.q >> 32) != (((uint64_t)p.q + QBYTES) >> 32)) p.q += QBYTES;
  cudaGetSymbolAddress((void**)&p.sync, g_sync); cudaGetSymbolAddress((void**)&p.xe, g_xe);
  cudaGetSymbolAddress((void**)&p.xa, g_xa); cudaGetSymbolAddress((void**)&p.xb, g_xb);
  const int df[10] = {34, 120, 900, 3072, 0, 17, 0xff2, 0xD5C4E6, 0x422000};
  for (int i = 0; i < 10; i++) p.tune[i] = df[i];
  p.qcode = 0x890145a6273bull;
  p.ctam = p.tune[5];
  if ((long long)PFB * PFN > (long long)(p.E / G) * 32) PFB = (p.E / G * 32 / PFN) & ~127;
  void* fn = nullptr; cudaDriverEntryPointQueryResult qr;
  cudaGetDriverEntryPoint("cuTensorMapEncodeTiled", &fn, cudaEnableDefault, &qr);
  auto mk = [&](CUtensorMap* tm, void* base, int rows, int box = 64) {
    const cuuint64_t dim[2] = {64, (cuuint64_t)rows}, str[1] = {128}; const cuuint32_t bx[2] = {64, (cuuint32_t)box}, es[2] = {1, 1};
    ((EncodeFn)fn)(tm, CU_TENSOR_MAP_DATA_TYPE_BFLOAT16, 2, base, dim, str, bx, es, CU_TENSOR_MAP_INTERLEAVE_NONE, CU_TENSOR_MAP_SWIZZLE_128B,
                   CU_TENSOR_MAP_L2_PROMOTION_NONE, CU_TENSOR_MAP_FLOAT_OOB_FILL_NONE);
  };
  mk(&maps.m[TM_H / 128], d_in[0], p.N); mk(&maps.m[TM_WE / 128], d_in[5], 145); mk(&maps.m[TM_WH / 128], d_in[7], 128); mk(&maps.m[TM_Q / 128], p.q, p.N, 16);
  for (int k = 0; k < 2; k++) {
    void* xp = (void*)(k ? p.xb : p.xa);
    const cuuint64_t dim[2] = {(cuuint64_t)G * 64, (cuuint64_t)G}, str[1] = {(cuuint64_t)G * (128 << k)}; const cuuint32_t bx[2] = {64, (cuuint32_t)(k ? BROWS : G)}, es[2] = {1, 1};
    ((EncodeFn)fn)(&maps.m[TM_XA / 128 + k], k ? CU_TENSOR_MAP_DATA_TYPE_UINT32 : CU_TENSOR_MAP_DATA_TYPE_UINT16, 2, xp, dim, str, bx, es, CU_TENSOR_MAP_INTERLEAVE_NONE,
                   CU_TENSOR_MAP_SWIZZLE_NONE, CU_TENSOR_MAP_L2_PROMOTION_NONE, CU_TENSOR_MAP_FLOAT_OOB_FILL_NONE);
  }
  cudaFuncSetAttribute(egnn_kernel, cudaFuncAttributeMaxDynamicSharedMemorySize, SMEM);
  egnn_kernel<<<G, NTHR, SMEM>>>(p, maps);
}
```

```cpp
#include <cuda_runtime.h>
#include <cuda_bf16.h>
#include <cuda_fp16.h>
#include <cuda.h>
#include <stdint.h>
#pragma nv_diag_suppress 549

#define PFN p.tune[0]
#define PFB p.tune[3]
#define PFNS p.tune[1]
#define PFE p.tune[8]
#define BDEL p.tune[2]
#define DEFNS p.tune[4]
#define CTAM p.ctam
#define QREV p.tune[6]
#define UORD p.tune[7]
#define QCODE p.qcode
#define FIRSTSEQ mu(0); mu(1); fi(0); mu(2); fi(1);
#define BODYSEQ hc(0); fi(2); tl_(); mu(3); un(); ad(1); ad(0); cv(0); mu(4); cv(2); fi(3); cv(1); ex0(); ex1(); cv(3); he(0); fi(4); he(1); \
  mu(5); hc(1); mu(6); fi(5); he(2); ad(2); ex2(); hs(0); ad(3); hs(1); fi(6); mu(7); issue(); hc(2); he(3); hs(3); fi(7); mu(0); \
  hs(2); he(4); he(5); ad(5); ad(4); hs(4); fi(0); he(6); mu(1); hc(3); he(7); fi(1); ad(6); hs(7); hs(5); ad(7); hs(6); mu(2); \
  pf();
#define LASTSEQ hc(0); fi(2); mu(3); un(); ad(1); ad(0); mu(4); fi(3); fi(4); mu(5); hc(1); mu(6); fi(5); ad(2); ad(3); fi(6); mu(7); hc(2); \
  fi(7); ad(5); ad(4); hc(3); ad(6); ad(7); pf();
namespace {

constexpr int G = 132;
constexpr int NTHR = 512, NWK = 352, NCH = 5;
constexpr int NST = 3, STG = 2560;
constexpr int BROWS = 44, RNB = 2, PADM = 33;
constexpr int SCAP = 448;

constexpr int OFF_H = 0;
constexpr int OFF_W = 49152;
constexpr int OFF_WD = OFF_W + 16384;
constexpr int OFF_W3 = OFF_WD + 1024;
constexpr int OFF_P2 = OFF_W3 + 2048;
constexpr int OFF_RING = OFF_P2 + 24576;
constexpr int OFF_TE = OFF_RING + 12 * NST * STG;
constexpr int OFF_TS = OFF_TE + SCAP * 64;
constexpr int OFF_INV = OFF_TS - 768;
constexpr int OFF_GP = OFF_TS + SCAP * 32;
constexpr int OFF_WX = OFF_GP + 3072;
constexpr int OFF_LEN = OFF_WX + 128;
constexpr int OFF_MISC = OFF_LEN + 128;
constexpr int OFF_BAR = OFF_MISC + 48;
constexpr int SMEM = OFF_BAR + 256;
static_assert(SMEM <= 232448, "smem");
constexpr uint32_t sb = 1024;
constexpr int OFF_SRCI = OFF_TE;
constexpr int OFF_SB = OFF_RING, OFF_SA = OFF_SB + 34816, OFF_AX = OFF_SA + 32768, OFF_DST = OFF_H + 24576;
constexpr int OFF_WS = OFF_AX + 17408;
constexpr int OFF_BC = OFF_WS + 2304;
constexpr int OFF_CNT = OFF_P2;
constexpr int OFF_DH = OFF_CNT + 2176;
constexpr int OFF_POS = OFF_DH + 128;
constexpr int OFF_EXT = OFF_POS + 3072;
constexpr int OFF_XB = OFF_EXT + 1024, XPAD = G * 256;
static_assert(OFF_XB + XPAD + 1028 <= OFF_RING + 12 * STG && OFF_XB % 128 == 0 && OFF_BC + 544 <= OFF_TE && OFF_P2 % 1024 == 0 && OFF_SA % 1024 == 0 && SCAP * 64 >= 24576, "staging");
constexpr int BAR_DST = OFF_BAR, BAR_SRC = BAR_DST + 40, BAR_T = BAR_SRC + 24, BAR_W = BAR_T + 48, BAR_PS = BAR_W + 8, BAR_AW = BAR_PS + 8,
              BAR_QP = BAR_AW + 8, BAR_QR = BAR_QP + 8, BAR_HA = BAR_QR + 8, BAR_EP = BAR_HA + 8, BAR_AX = BAR_EP + 8, BAR_AI = BAR_AX + 8, BAR_HB = BAR_AI + 8, BAR_U = BAR_HB + 8, BAR_WH = BAR_U + 8, BAR_M = BAR_WH + 8, BAR_X = BAR_M + 24, BAR_END = BAR_X + 8;
static_assert(BAR_END <= OFF_BAR + 256, "barriers");
constexpr uint32_t QBYTES = 8u << 20;

__device__ __align__(256) uint4 g_xa[G * G * 8];
__device__ __align__(256) uint4 g_xb[G * G * 16];
__device__ __align__(256) uint2 g_xe[G * G * 32];
__device__ __align__(256) uint4 g_q[2 * QBYTES / 16];
__device__ __align__(256) uint32_t g_sync[8];
#define STAMP(k)

struct Maps { CUtensorMap m[6]; };
constexpr int TM_H = 0, TM_WE = 128, TM_WH = 256, TM_Q = 384, TM_XA = 512, TM_XB = 640;
struct Params {
  const int* dst; uint32_t* sync; int E, EPC, N, ctam; unsigned long long inv; uint32_t magic; int force_slow;
  const int* src; const uint16_t* pos; const uint4* ea; const uint16_t* we; const uint16_t* wx; char* q;
  const uint4* xa; const uint4* xb; uint2* xe; uint16_t* out; const uint4* h; const uint16_t* wh;
  int tune[10]; unsigned long long qcode;
};
template<int V> struct IC { static constexpr int value = V; };

#define R32(d) "+f"(d[0]),"+f"(d[1]),"+f"(d[2]),"+f"(d[3]),"+f"(d[4]),"+f"(d[5]),"+f"(d[6]),"+f"(d[7]),"+f"(d[8]),"+f"(d[9]),"+f"(d[10]),"+f"(d[11]),"+f"(d[12]),"+f"(d[13]),"+f"(d[14]),"+f"(d[15]),"+f"(d[16]),"+f"(d[17]),"+f"(d[18]),"+f"(d[19]),"+f"(d[20]),"+f"(d[21]),"+f"(d[22]),"+f"(d[23]),"+f"(d[24]),"+f"(d[25]),"+f"(d[26]),"+f"(d[27]),"+f"(d[28]),"+f"(d[29]),"+f"(d[30]),"+f"(d[31])
#define S32 "{%0,%1,%2,%3,%4,%5,%6,%7,%8,%9,%10,%11,%12,%13,%14,%15,%16,%17,%18,%19,%20,%21,%22,%23,%24,%25,%26,%27,%28,%29,%30,%31}"
#define DI __device__ __forceinline__

constexpr uint64_t DHI = ((uint64_t)(1024 >> 4) << 32) | (1ull << 62);
template<int SD> DI void rs64b(float (&d)[32], uint32_t a0, uint32_t a1, uint32_t a2, uint32_t a3, uint64_t db) {
  asm volatile("wgmma.mma_async.sync.aligned.m64n64k16.f32.bf16.bf16 " S32 ", {%32,%33,%34,%35}, %36, %37, 1, 1, 1;" : R32(d) : "r"(a0), "r"(a1), "r"(a2), "r"(a3), "l"(db), "n"(SD)); }
template<int SD> DI void rs64h(float (&d)[32], uint32_t a0, uint32_t a1, uint32_t a2, uint32_t a3, uint64_t db) {
  asm volatile("wgmma.mma_async.sync.aligned.m64n64k16.f32.f16.f16 " S32 ", {%32,%33,%34,%35}, %36, %37, 1, 1, 1;" : R32(d) : "r"(a0), "r"(a1), "r"(a2), "r"(a3), "l"(db), "n"(SD)); }
template<int SD> DI void ss64(float (&d)[32], uint64_t da, uint64_t db) {
  asm volatile("wgmma.mma_async.sync.aligned.m64n64k16.f32.bf16.bf16 " S32 ", %32, %33, %34, 1, 1, 0, 1;" : R32(d) : "l"(da), "l"(db), "n"(SD)); }
#define R16(d) "+f"(d[0]),"+f"(d[1]),"+f"(d[2]),"+f"(d[3]),"+f"(d[4]),"+f"(d[5]),"+f"(d[6]),"+f"(d[7]),"+f"(d[8]),"+f"(d[9]),"+f"(d[10]),"+f"(d[11]),"+f"(d[12]),"+f"(d[13]),"+f"(d[14]),"+f"(d[15])
#define S16 "{%0,%1,%2,%3,%4,%5,%6,%7,%8,%9,%10,%11,%12,%13,%14,%15}"
template<int SD> DI void rs32b(float (&d)[16], const uint32_t* a, uint64_t db) {
  asm volatile("wgmma.mma_async.sync.aligned.m64n32k16.f32.bf16.bf16 " S16 ", {%16,%17,%18,%19}, %20, %21, 1, 1, 1;" : R16(d) : "r"(a[0]), "r"(a[1]), "r"(a[2]), "r"(a[3]), "l"(db), "n"(SD)); }
DI void rs32h(float (&d)[16], const uint32_t* a, uint64_t db) {
  asm volatile("wgmma.mma_async.sync.aligned.m64n32k16.f32.f16.f16 " S16 ", {%16,%17,%18,%19}, %20, 1, 1, 1, 1;" : R16(d) : "r"(a[0]), "r"(a[1]), "r"(a[2]), "r"(a[3]), "l"(db)); }
DI void fence_regs(float (&d)[16]) { asm volatile("" : R16(d) :: "memory"); }
DI void trap_if(bool c) { asm volatile("{.reg .pred p; setp.eq.u32 p, %0, 0; @p bra.uni LT_%=; trap; LT_%=:}" :: "r"((uint32_t)c)); }
DI void wg_fence() { asm volatile("wgmma.fence.sync.aligned;" ::: "memory"); }
DI void wg_commit() { asm volatile("wgmma.commit_group.sync.aligned;" ::: "memory"); }
DI void wg_wait0() { asm volatile("wgmma.wait_group.sync.aligned 0;" ::: "memory"); }
DI void fence_regs(float (&d)[32]) { asm volatile("" : R32(d) :: "memory"); }
DI void proxy_fence() { asm volatile("fence.proxy.async.shared::cta;" ::: "memory"); }
DI uint64_t pol_first() { uint64_t r; asm("createpolicy.fractional.L2::evict_first.b64 %0, 1.0;" : "=l"(r)); return r; }
DI float tanh_ap(float x) { float y; asm("tanh.approx.f32 %0, %1;" : "=f"(y) : "f"(x)); return y; }
DI float silu_h(float y) { return fmaf(y, tanh_ap(y), y); }
DI uint32_t pack_bf16(float lo, float hi) { uint32_t r; asm("cvt.rn.bf16x2.f32 %0, %1, %2;" : "=r"(r) : "f"(hi), "f"(lo)); return r; }
DI uint32_t pack_f16(float lo, float hi) { uint32_t r; asm("cvt.rn.f16x2.f32 %0, %1, %2;" : "=r"(r) : "f"(hi), "f"(lo)); return r; }
DI float bf_lo(uint32_t v) { return __uint_as_float(v << 16); }
DI float bf_hi(uint32_t v) { return __uint_as_float(v & 0xFFFF0000u); }
DI uint32_t b2h(uint32_t v, float s) { return pack_f16(s * bf_lo(v), s * bf_hi(v)); }
DI void mbar_wait(uint32_t bar, uint32_t parity = 0) {
  asm volatile("{.reg .pred p, q; .reg .u32 c; mov.u32 c, 0;\n"
    "LW_%=: mbarrier.try_wait.parity.shared::cta.b64 p, [%0], %1;\n add.u32 c, c, 1; setp.lt.and.u32 q, c, 0x200000, !p;\n @q bra.uni LW_%=;}" :: "r"(bar), "r"(parity) : "memory");
}
DI void mbar_arrive(uint32_t bar, int p = 1) { asm volatile("{.reg .pred p; setp.ne.b32 p, %1, 0; @p mbarrier.arrive.shared::cta.b64 _, [%0];}" :: "r"(bar), "r"(p) : "memory"); }
DI void bar_sync(int id, int n) { asm volatile("bar.sync %0, %1;" :: "r"(id), "r"(n) : "memory"); }
DI void bar_arrive(int id, int n) { asm volatile("bar.arrive %0, %1;" :: "r"(id), "r"(n) : "memory"); }
DI __nv_bfloat162 b2(uint32_t v) { return *(__nv_bfloat162*)&v; }
DI uint32_t u2(__nv_bfloat162 v) { return *(uint32_t*)&v; }
DI uint32_t hsq(uint32_t v) { return u2(__hmul2(b2(v), b2(v))); }
DI uint32_t hsub(uint32_t a, uint32_t b) { return u2(__hsub2(b2(a), b2(b))); }
DI uint32_t hhalf(uint32_t v) { return u2(__hmul2(b2(v), __floats2bfloat162_rn(0.5f, 0.5f))); }
DI uint32_t mag2(uint32_t m, uint32_t v) { return __vmaxu2(m, v & 0x7FFF7FFFu); }
DI uint32_t hmag(uint32_t m, uint32_t v) { const __half2 r = __hmax2(*(const __half2*)&m, __habs2(*(const __half2*)&v)); return *(const uint32_t*)&r; }
DI uint32_t magr(uint32_t m) { return max(m & 0xFFFF, m >> 16); }
DI void sts128(uint32_t a, uint32_t x, uint32_t y, uint32_t z, uint32_t w) { asm volatile("st.shared.v4.u32 [%0], {%1,%2,%3,%4};" :: "r"(a), "r"(x), "r"(y), "r"(z), "r"(w) : "memory"); }
DI void sts64(uint32_t a, uint32_t x, uint32_t y) { asm volatile("st.shared.v2.u32 [%0], {%1,%2};" :: "r"(a), "r"(x), "r"(y) : "memory"); }
DI void sts32(uint32_t a, uint32_t x) { asm volatile("st.shared.u32 [%0], %1;" :: "r"(a), "r"(x) : "memory"); }
DI void sts16(uint32_t a, uint32_t x) { asm volatile("st.shared.u16 [%0], %1;" :: "r"(a), "h"((uint16_t)x) : "memory"); }
DI void lds128(uint32_t* v, uint32_t a) { asm volatile("ld.shared.v4.u32 {%0, %1, %2, %3}, [%4];" : "=r"(v[0]), "=r"(v[1]), "=r"(v[2]), "=r"(v[3]) : "r"(a) : "memory"); }
DI void lds64(uint32_t& x, uint32_t& y, uint32_t a) { asm volatile("ld.shared.v2.u32 {%0, %1}, [%2];" : "=r"(x), "=r"(y) : "r"(a) : "memory"); }
DI uint32_t lds32(uint32_t a) { uint32_t x; asm volatile("ld.shared.u32 %0, [%1];" : "=r"(x) : "r"(a) : "memory"); return x; }
DI uint32_t lds16(uint32_t a) { uint32_t x; asm volatile("ld.shared.u16 %0, [%1];" : "=r"(x) : "r"(a) : "memory"); return x; }
DI uint32_t atoms_add(uint32_t a, uint32_t v) { uint32_t r; asm volatile("atom.shared.add.u32 %0, [%1], %2;" : "=r"(r) : "r"(a), "r"(v) : "memory"); return r; }
DI void bulk_load(uint32_t dst, const void* src, uint32_t bytes, uint32_t bar) {
  asm volatile("cp.async.bulk.shared::cluster.global.mbarrier::complete_tx::bytes.L2::cache_hint [%0], [%1], %2, [%3], %4;" :: "r"(dst), "l"(src), "r"(bytes), "r"(bar), "l"(pol_first()) : "memory"); }
DI void mbar_expect(uint32_t bar, uint32_t bytes) { asm volatile("mbarrier.arrive.expect_tx.shared::cta.b64 _, [%0], %1;" :: "r"(bar), "r"(bytes) : "memory"); }
DI void mbar_init(uint32_t bar, int n) { asm volatile("mbarrier.init.shared::cta.b64 [%0], %1;" :: "r"(bar), "r"(n) : "memory"); }
DI void tma_load(uint32_t dst, uint64_t tm, int row, uint32_t bar) {
  asm volatile("cp.async.bulk.tensor.2d.shared::cluster.global.mbarrier::complete_tx::bytes.L2::cache_hint [%0], [%1, {%3, %4}], [%2], %5;" :: "r"(dst), "l"(tm), "r"(bar), "r"(0), "r"(row), "l"(pol_first()) : "memory"); }
DI void tma_store(uint64_t tm, int col, int row, uint32_t src) {
  asm volatile("cp.async.bulk.tensor.2d.global.shared::cta.bulk_group [%0, {%2, %3}], [%1];" :: "l"(tm), "r"(src), "r"(col), "r"(row) : "memory"); }
DI void bulk_commit() { asm volatile("cp.async.bulk.commit_group;" ::: "memory"); }
DI uint2 ld_poll2(const void* a) { uint2 v; asm volatile("ld.relaxed.gpu.global.v2.u32 {%0, %1}, [%2];" : "=r"(v.x), "=r"(v.y) : "l"(a) : "memory"); return v; }
DI void st_ext(uint2* a, uint32_t v, uint32_t ep) { asm volatile("st.relaxed.gpu.global.v2.u32 [%0], {%1, %2};" :: "l"(a), "r"(v), "r"(ep) : "memory"); }
DI uint32_t ext_get(const uint2* a, uint32_t ep) { uint2 v; int spin = 0; do { v = ld_poll2(a); trap_if(++spin > 4000000); } while (__any_sync(~0u, v.y != ep)); return v.x; }
DI void bulk_wait() { asm volatile("cp.async.bulk.wait_group 0;" ::: "memory"); }
DI void hint_signal(uint32_t* c) { asm volatile("red.relaxed.gpu.global.add.u32 [%0], 1;" :: "l"(c) : "memory"); }
DI void hint_wait(const uint32_t* c, uint32_t target) { uint32_t v; int spin = 0;
  do { asm volatile("ld.relaxed.gpu.global.u32 %0, [%1];" : "=r"(v) : "l"(c) : "memory"); trap_if(++spin > 4000000); } while (__any_sync(~0u, (int)(v - target) < 0)); }
DI void stsm4(uint32_t a, uint32_t x, uint32_t y, uint32_t z, uint32_t w) { asm volatile("stmatrix.sync.aligned.m8n8.x4.shared.b16 [%0], {%1,%2,%3,%4};" :: "r"(a), "r"(x), "r"(y), "r"(z), "r"(w) : "memory"); }
DI void ldsm4(uint32_t* v, uint32_t a) { asm volatile("ldmatrix.sync.aligned.m8n8.x4.shared.b16 {%0,%1,%2,%3}, [%4];" : "=r"(v[0]), "=r"(v[1]), "=r"(v[2]), "=r"(v[3]) : "r"(a) : "memory"); }
DI void ldsm4t(uint32_t* v, uint32_t a) { asm volatile("ldmatrix.sync.aligned.m8n8.x4.trans.shared.b16 {%0,%1,%2,%3}, [%4];" : "=r"(v[0]), "=r"(v[1]), "=r"(v[2]), "=r"(v[3]) : "r"(a) : "memory"); }
DI uint32_t mad16(uint32_t x, uint32_t m, uint32_t c) { uint32_t r; asm("dp2a.lo.u32.u32 %0, %1, %2, %3;" : "=r"(r) : "r"(x), "r"(m), "r"(c)); return r; }
DI bool wbad(uint32_t m, uint32_t hi) { return m > hi || (m && m < 0x3980); }

__device__ __noinline__ void slow_path(const Params& p, int wid, int lane, int node0, int nloc) {
  const uint32_t ab = sb + OFF_P2 + wid * 8704;
  for (int i = lane; i < 32 * 68; i += 32) sts32(ab + i * 4, 0);
  __syncwarp();
  const uint32_t wdv = __ldg((const uint32_t*)(p.we + 128 * 64) + lane), wxv = __ldg((const uint32_t*)p.wx + lane);
  const int nb0 = node0 + wid * 32, cntn = max(0, min(32, nloc - wid * 32));
  auto dot = [&](uint32_t hv, const uint16_t* w, int K2, float& y0, float& y1) {
#pragma unroll 4
    for (int k = 0; k < K2; k++) {
      const uint32_t hk = __shfl_sync(~0u, hv, k), wa = __ldg((const uint32_t*)(w + 2 * k * 64) + lane), wb = __ldg((const uint32_t*)(w + (2 * k + 1) * 64) + lane);
      y0 = fmaf(bf_lo(hk), bf_lo(wa), fmaf(bf_hi(hk), bf_lo(wb), y0)); y1 = fmaf(bf_lo(hk), bf_hi(wa), fmaf(bf_hi(hk), bf_hi(wb), y1));
    }
  };
  auto silu = [](float x) { return x / (1.f + __expf(-x)); };
#pragma unroll 1
  for (int base = 0; base < p.E; base += 32) {
    const int e = base + lane;
    const uint32_t dl = e < p.E ? (uint32_t)(__ldg(p.dst + e) - nb0) : 0xFFFFFFFFu;
    uint32_t mk = __ballot_sync(~0u, dl < (uint32_t)cntn);
    while (mk) {
      const int l = __ffs(mk) - 1; mk &= mk - 1;
      const int ee = base + l, n = __shfl_sync(~0u, dl, l), s = __ldg(p.src + ee);
      const uint16_t *po = p.pos + (size_t)(nb0 + n) * 3, *pp = p.pos + (size_t)s * 3;
      const uint32_t dxy = hsub(__ldg(po) | (__ldg(po + 1) << 16), __ldg(pp) | (__ldg(pp + 1) << 16)), dz = hsub(__ldg(po + 2), __ldg(pp + 2));
      const uint32_t sq = hsq(dxy); const float d2 = bf_lo(sq) + bf_hi(sq) + bf_lo(hsq(dz));
      float y0 = d2 * bf_lo(wdv), y1 = d2 * bf_hi(wdv);
      dot(__ldg((const uint32_t*)(p.h + (size_t)(nb0 + n) * 8) + lane), p.we, 32, y0, y1);
      dot(__ldg((const uint32_t*)(p.h + (size_t)s * 8) + lane), p.we + 64 * 64, 32, y0, y1);
      dot(__ldg((const uint32_t*)(p.ea + (size_t)ee * 2) + (lane & 7)), p.we + 129 * 64, 8, y0, y1);
      const uint32_t mm = pack_bf16(silu(y0), silu(y1));
      float c = bf_lo(mm) * bf_lo(wxv) + bf_hi(mm) * bf_hi(wxv);
#pragma unroll
      for (int o = 16; o; o >>= 1) c += __shfl_xor_sync(~0u, c, o);
      const uint32_t a = ab + n * 272;
      uint32_t x0, x1; lds64(x0, x1, a + lane * 8);
      sts64(a + lane * 8, __float_as_uint(__uint_as_float(x0) + bf_lo(mm)), __float_as_uint(__uint_as_float(x1) + bf_hi(mm)));
      if (lane < 3) { const float df = lane == 0 ? bf_lo(dxy) : lane == 1 ? bf_hi(dxy) : bf_lo(dz); sts32(a + 256 + lane * 4, __float_as_uint(fmaf(c, df, __uint_as_float(lds32(a + 256 + lane * 4))))); }
    }
  }
  __syncwarp();
#pragma unroll 1
  for (int n = 0; n < cntn; n++) {
    uint32_t x0, x1; lds64(x0, x1, ab + n * 272 + lane * 8);
    const uint32_t hv = __ldg((const uint32_t*)(p.h + (size_t)(nb0 + n) * 8) + lane);
    float y0 = 0.f, y1 = 0.f;
    dot(hv, p.wh, 32, y0, y1); dot(pack_bf16(__uint_as_float(x0), __uint_as_float(x1)), p.wh + 64 * 64, 32, y0, y1);
    ((uint32_t*)p.out)[(size_t)(nb0 + n) * 32 + lane] = u2(__hadd2(b2(hv), b2(pack_bf16(silu(y0), silu(y1)))));
    if (lane < 3) p.out[(size_t)p.N * 64 + (size_t)(nb0 + n) * 3 + lane] = (uint16_t)pack_bf16(bf_lo(__ldg(p.pos + (size_t)(nb0 + n) * 3 + lane)) + __uint_as_float(lds32(ab + n * 272 + 256 + lane * 4)), 0.f);
  }
}

__global__ void __launch_bounds__(NTHR, 1) egnn_kernel(const __grid_constant__ Params p, const __grid_constant__ Maps maps) {
  const uint64_t tmb = (uint64_t)&maps;
  extern __shared__ __align__(1024) unsigned char smraw[];
  const int tid = threadIdx.x, cta = blockIdx.x * CTAM % G;
  const int e0 = cta * p.EPC, n4 = max(0, min(p.EPC, p.E - e0)) >> 2;
  STAMP(0);
  asm volatile("{.reg .pred p; setp.lt.s32 p, %1, %2; setp.lt.and.s32 p, %3, %4, p; @p prefetch.global.L2 [%0];}" :: "l"(p.dst + e0 + tid * 32), "r"(tid), "n"(64), "r"(e0 + tid * 32), "r"(p.E));
  if (tid == NWK) {
#pragma unroll 1
    for (int k = 0; k < NCH; k++) { const int nb = max(0, min(NWK, n4 - k * NWK)) * 16;
      mbar_init(sb + BAR_DST + k * 8, 1);
      asm volatile("fence.mbarrier_init.release.cluster;" ::: "memory");
      mbar_expect(sb + BAR_DST + k * 8, nb);
      if (nb) bulk_load(sb + OFF_DST + k * NWK * 16, (const char*)(p.dst + e0) + k * NWK * 16, nb, sb + BAR_DST + k * 8); }
  }
  const int lane = tid & 31, wid = __shfl_sync(~0u, tid >> 5, 0), w = wid & 3;
  asm volatile("{.reg .pred p; setp.eq.u32 p, %2, 384; @p cp.async.cg.shared.global [%0], [%1], 16;}" :: "r"(sb + OFF_LEN - 192 + (tid >> 1)), "l"(p.sync), "r"(tid & 415) : "memory");

  auto first_node = [&](int c) { return (int)((c * p.inv + 0xFFFFFFFFull) >> 32); };
  const int node0 = first_node(cta), nloc = min(first_node(cta + 1), p.N) - node0;
  const uint32_t ealo = (uint32_t)(uint64_t)p.ea;
  const int epad = min(e0, p.E - 1);
  if (wid >= 12) {
    const int t = tid - 384;
    auto load_h = [&](int b) { mbar_expect(sb + BAR_T + b * 8, 8192); tma_load(sb + OFF_H + b * 8192, tmb + TM_H, node0 + b * 64, sb + BAR_T + b * 8); };
    uint32_t pv[9], ev = 0;
#pragma unroll
    for (int i = 0; i < 3; i++) { const uint16_t* pp = p.pos + (size_t)(node0 + t + 128 * i) * 3;
      pv[3 * i] = pv[3 * i + 1] = pv[3 * i + 2] = 0;
      asm volatile("{.reg .pred p; setp.lt.s32 p, %4, %5;\n @p ld.global.nc.u16 %0, [%3];\n @p ld.global.nc.u16 %1, [%3+2];\n @p ld.global.nc.u16 %2, [%3+4];}"
        : "+r"(pv[3 * i]), "+r"(pv[3 * i + 1]), "+r"(pv[3 * i + 2]) : "l"(pp), "r"(t + 128 * i), "r"(p.N - node0)); }
    asm volatile("{.reg .pred p; setp.lt.u32 p, %3, 8; @p ld.global.nc.u32 %0, [%1]; @p st.global.v4.u32 [%2], {%4, %4, %4, %4};}"
      : "+r"(ev) : "l"((const uint32_t*)(p.ea + (size_t)epad * 2) + t), "l"(p.q + (size_t)(p.N + cta * PADM) * 128 + t * 16), "r"(t), "r"(0xF700F700u) : "memory");
    asm volatile("cp.async.wait_all;" ::: "memory");
    __syncwarp();
    const uint32_t e = lds32(sb + OFF_LEN + 8 + w * 16) + 1;
    {
      const uint32_t tg = (1 + e % 3) << 30, v = ((tg >> 16) + 512 + (lane & 7) * 4) * 0x10001u;
      if (t == 0) sts32(sb + OFF_MISC + 32, e);
#pragma unroll
      for (int i = 0; i < 9; i++) sts128(sb + OFF_SA + t * 16 + i * 2048, v, v + 0x10001u, v + 0x20002u, v + 0x30003u);
      bar_sync(6, NTHR);
      mbar_arrive(sb + BAR_EP, lane == 0);
#pragma unroll
      for (int i = 0; i < 17; i++) sts128(sb + OFF_SB + t * 16 + i * 2048, tg, tg, tg, tg); }
    uint32_t mp = 0;
#pragma unroll
    for (int i = 0; i < 3; i++) { sts64(sb + OFF_POS + (t + 128 * i) * 8, pv[3 * i] | (pv[3 * i + 1] << 16), pv[3 * i + 2]); mp = mag2(mag2(mp, pv[3 * i] | (pv[3 * i + 1] << 16)), pv[3 * i + 2]); }
    proxy_fence();
    __syncwarp();
    mbar_arrive(sb + BAR_PS, lane == 0);
    mbar_wait(sb + BAR_W);
    {
      uint32_t v[4], u[4]; const int r = t >> 3, c = t & 7;
      lds128(v, sb + OFF_WS + 128 + t * 16); lds128(u, sb + OFF_WS + c * 16);
      const uint32_t x = lds32(sb + OFF_WS + 2176 + lane * 4);
      sts128(sb + OFF_W3 + r * 128 + ((c ^ (r & 7)) << 4), b2h(v[0], .5f), b2h(v[1], .5f), b2h(v[2], .5f), b2h(v[3], .5f));
      const float s = ((r & 1) || r == 6) ? 0.f : .5f;
      if (t < 64) sts128(sb + OFF_WD + r * 128 + ((c ^ r) << 4), b2h(u[0], s), b2h(u[1], s), b2h(u[2], s), b2h(u[3], s));
      if (t < 32) sts32(sb + OFF_WX + (t & 3) * 32 + (t >> 2) * 4, b2h(x, 1.f));
      const uint32_t m3 = __reduce_max_sync(~0u, magr(mag2(mag2(mag2(mag2(0, v[0]), v[1]), v[2]), v[3]))), md = __reduce_max_sync(~0u, magr(mag2(mag2(mag2(mag2(0, u[0]), u[1]), u[2]), u[3])));
      if (wbad(m3, 0x4000) || wbad(md, 0x4000) || wbad(__reduce_max_sync(~0u, magr(mag2(0, x))), 0x4700) || magr(mp) >= 0x4200 || magr(mag2(0, ev)) >= 0x4380) sts32(sb + OFF_MISC + 8, 1);
    }
    if (w == 1) {
#pragma unroll 1
      for (int b = 0; b < 3; b++) { mbar_wait(sb + BAR_SRC + b * 8); if (lane == 0) load_h(b); }
    }
    bar_sync(3, 128);
    const uint32_t frag = (w * 16 + (lane & 15)) * 128 + (((lane >> 4) ^ (lane & 7)) << 4);
    uint32_t mq = 0; int pfi = 0;
    auto prefetch_e = [&]() {
      const uint32_t nb = PFB;
      if (lane == 0 && nb) asm volatile("cp.async.bulk.prefetch.L2.global [%0], %1;" :: "l"((const char*)p.ea + (size_t)(pfi * G + cta) * nb), "r"(nb) : "memory");
      pfi++; };
#pragma unroll 1
    for (int b = 0; b < 6; b++) {
      float acc[32];
      const uint64_t da = DHI | (((sb + OFF_H) >> 4) + b * 512), db = DHI | ((sb + OFF_W) >> 4);
      const uint32_t v0 = lds16(sb + OFF_POS + b * 512 + w * 128 + lane * 2), v1 = lds16(sb + OFF_POS + 64 + b * 512 + w * 128 + lane * 2);
      mbar_wait(sb + BAR_T + b * 8);
      if (b == 0) STAMP(25);
      if (b == 5) STAMP(26);
      wg_fence();
      ss64<0>(acc, da, db); ss64<1>(acc, da + 2, db + 128); ss64<1>(acc, da + 4, db + 256); ss64<1>(acc, da + 6, db + 384);
      wg_commit();
      if (b == 0) mbar_wait(sb + BAR_AW);
      if (t == 32 && b < 3) load_h(b + 3);
      if (w == 1) for (int k = PFE >> (4 * b) & 15; k > 0; k--) prefetch_e();
      __syncwarp();
      uint32_t ff[6], fg[6];
#pragma unroll
      for (int j = 0; j < 6; j++) { ff[j] = (__byte_perm((j & 1) ? v1 : v0, 0, 0x4140) >> (3 * (j >> 1))) & 0x00070007u; fg[j] = __vsub2(0x00040004u, ff[j]);
        asm volatile("" : "+r"(ff[j]), "+r"(fg[j])); }
      wg_wait0(); fence_regs(acc);
      uint32_t o[16];
#pragma unroll
      for (int j = 0; j < 16; j++) o[j] = pack_f16(.5f * acc[2 * j], .5f * acc[2 * j + 1]);
#pragma unroll
      for (int j = 0; j < 6; j++) {
        const uint32_t m = o[j] & 0x7FFF7FFFu; mq = __vmaxu2(mq, m);
        o[j] = (__viaddmax_s16x2(m, fg[j], 0) & 0xFFF8FFF8u) | ff[j] | (o[j] & 0x80008000u); }
      if (b == 4) mbar_wait(sb + BAR_AX);
      const uint32_t qs = sb + OFF_SA + b * 8192;
#pragma unroll
      for (int j = 0; j < 4; j++) stsm4((qs + frag) ^ (j << 5), o[4 * j], o[4 * j + 1], o[4 * j + 2], o[4 * j + 3]);
      proxy_fence();
      __syncwarp();
      if (lane == 0 && b * 64 + w * 16 < nloc) tma_store(tmb + TM_Q, 0, node0 + b * 64 + w * 16, qs + w * 2048);
    }
    if (lane == 0) bulk_commit();
    { const uint32_t m = __reduce_max_sync(~0u, magr(mq)); if (lane == 0) sts32(sb + OFF_MISC + 16 + w * 4, m); }
    asm volatile("setmaxnreg.dec.sync.aligned.u32 56;");
    bulk_wait();
    bar_sync(3, 128);
    if (w == 0) {
      STAMP(18);
      uint32_t mv[4]; lds128(mv, sb + OFF_MISC + 16);
      const uint32_t mx = max(max(mv[0], mv[1]), max(mv[2], mv[3]));
      mbar_arrive(sb + BAR_QR, lane == 0);
      STAMP(19);
      if (lane == 0) {
        if (nloc > 0 && (mx >= 0x7BF0 || mx < 0x1400)) asm volatile("st.relaxed.gpu.global.u32 [%0+4], %1;" :: "l"(p.sync), "r"(e) : "memory");
        asm volatile("red.release.gpu.global.add.u32 [%0], 1;" :: "l"(p.sync) : "memory");
      }
      __syncwarp();
      uint32_t c, f; int spin = 0;
      do { asm volatile("ld.acquire.gpu.global.v2.u32 {%0, %1}, [%2];" : "=r"(c), "=r"(f) : "l"(p.sync) : "memory"); trap_if(++spin > 4000000); } while (__any_sync(~0u, (int)(c - e * G) < 0));
      if (f == e) sts32(sb + OFF_MISC + 8, 1);
      if (cta == 0 && lane == 0) asm volatile("st.relaxed.gpu.global.u32 [%0+8], %1;" :: "l"(p.sync), "r"(e) : "memory");
      STAMP(20);
      __syncwarp();
      mbar_arrive(sb + BAR_QP, lane == 0);
    }
    if (w == 2) {
      const uint32_t tg = (1 + e % 3) << 30;
      hint_wait(p.sync + 5, e * G);
      if (lane == 0) { mbar_expect(sb + BAR_HB, XPAD);
#pragma unroll 1
        for (int o = 0; o < 4; o++) bulk_load(sb + OFF_XB + o * (G * 64), (const char*)p.xb + (size_t)(cta * 4 + o) * (G * 64), G * 64, sb + BAR_HB); }
      STAMP(21);
      bar_sync(7, 384);
      sts32(sb + OFF_XB + XPAD, tg + p.N + cta * PADM);
      const uint32_t nx = __shfl_sync(~0u, lds32(sb + OFF_MISC + 8) ? 0 : lds32(sb + OFF_MISC + 4), 0);
#pragma unroll 1
      for (uint32_t k = 0; k < nx; k += 32) {
        const uint32_t i = min(k + lane, nx - 1), xr = lds32(sb + OFF_EXT + i * 4), row = (xr >> 9) & 255;
        const uint32_t v = ext_get(p.xe + (cta * G + row) * 32 + ((xr >> 17) & 31), e), x = lds32(sb + OFF_CNT + (xr & 511) * 4) + (xr >> 22) * 16;
        sts32(sb + OFF_XB + XPAD + 4 + i * 4, v); sts16(sb + OFF_TS + x, XPAD + 4 + i * 4);
        sts32(sb + OFF_TE + x * 2, mad16(v, 0x2000u, ealo - (tg >> 11) + row * p.EPC * 32));
      }
      __syncwarp();
      mbar_arrive(sb + BAR_HB, lane == 0);
    }
    if (w == 1) {
#pragma unroll 1
      while (pfi < PFN) { prefetch_e(); __nanosleep(PFNS); }
    }
    if (t == 96) { mbar_expect(sb + BAR_U, 8192); tma_load(sb + OFF_W, tmb + TM_WH, 0, sb + BAR_U); }
    __syncwarp();
    bar_sync(4, NTHR);
    const bool fast = !__shfl_sync(~0u, lds32(sb + OFF_MISC + 8), 0);
    if (fast) {
      mp = 0;
#pragma unroll 1
      for (uint32_t todo = UORD; todo; todo >>= 4) {
        const uint32_t nd = lds16(sb + OFF_GP + (todo & 3) * 1024 + w * 256 + (lane & 15) * 8 + 134), hb = (todo >> 3) & 1;
        const uint64_t b1 = DHI | (((sb + OFF_W + 8192) >> 4) + hb * 4);
        uint32_t f[8]; float acc[16];
#pragma unroll
        for (int j = 0; j < 4; j += 2) {
          const uint32_t a = (sb + OFF_H + nd * 128 + (((nd & 7) << 4) ^ (lane & 16))) ^ (j << 5);
          ldsm4(f, a); ldsm4(f + 4, a ^ 32);
          wg_fence();
          if (j == 0) rs32b<0>(acc, f, b1); else rs32b<1>(acc, f, b1 + 256);
          rs32b<1>(acc, f + 4, b1 + 128 * j + 128);
          wg_commit(); wg_wait0(); fence_regs(acc);
        }
#pragma unroll
        for (int j = 0; j < 8; j++) { f[j] = pack_f16(.5f * acc[2 * j], .5f * acc[2 * j + 1]); mp = hmag(mp, f[j]); }
        const uint32_t a = (sb + OFF_P2 + (todo & 3) * 8192 + frag) ^ (hb << 6);
        stsm4(a, f[0], f[1], f[2], f[3]); stsm4(a ^ 32, f[4], f[5], f[6], f[7]);
      }
      if (magr(mp) >= 0x7000) sts32(sb + OFF_MISC + 12, 1);
    }
    bar_sync(3, 128);
    if (t == 96) { mbar_expect(sb + BAR_U, 8192); tma_load(sb + OFF_W + 8192, tmb + TM_WH, 64, sb + BAR_U); }
    __syncwarp();
    mbar_wait(sb + BAR_U);
    uint32_t mh = 0;
#pragma unroll 1
    for (int i = t; i < 1024; i += 128) {
      uint32_t v[4]; const uint32_t r = (i >> 3) & 7, j = (i ^ r) & 7;
#pragma unroll
      for (int k = 0; k < 4; k++) v[k] = lds32(sb + OFF_W + (i >> 3) * 128 + ((((j & 4) + k) ^ r) << 4) + (j & 3) * 4);
      __syncwarp();
      if (i < 512) sts128(sb + OFF_W + i * 16, hhalf(v[0]), hhalf(v[1]), hhalf(v[2]), hhalf(v[3]));
      else { sts128(sb + OFF_W + i * 16, b2h(v[0], .5f), b2h(v[1], .5f), b2h(v[2], .5f), b2h(v[3], .5f)); mh = mag2(mag2(mag2(mag2(mh, v[0]), v[1]), v[2]), v[3]); } }
    if (wbad(__reduce_max_sync(~0u, magr(mh)), 0x4700)) sts32(sb + OFF_MISC + 12, 1);
    proxy_fence();
    __syncwarp();
    mbar_arrive(sb + BAR_WH, lane == 0);
    if (fast) {
      mbar_wait(sb + BAR_WH);
      float chk = 0.f;
#pragma unroll 1
      for (uint32_t todo = UORD; todo; todo >>= 4) {
        const uint32_t nd = lds16(sb + OFF_GP + (todo & 3) * 1024 + w * 256 + (lane & 15) * 8 + 6), hb = (todo >> 3) & 1;
        const uint64_t b1 = DHI | (((sb + OFF_W) >> 4) + hb * 4);
        uint32_t f[8]; float acc[16];
#pragma unroll
        for (int j = 0; j < 8; j += 2) {
          const uint32_t a = j < 4 ? sb + OFF_H + nd * 128 + (((nd & 7) << 4) ^ (lane & 16)) : sb + OFF_P2 + (todo & 3) * 8192 + frag;
          if (j == 4) mbar_wait(sb + BAR_M + (todo & 3) * 8);
          ldsm4(f, a ^ ((j & 3) << 5)); ldsm4(f + 4, a ^ ((j & 3) << 5) ^ 32);
          wg_fence();
          if (j == 0) rs32b<0>(acc, f, b1); else if (j < 4) rs32b<1>(acc, f, b1 + 128 * j); else rs32h(acc, f, b1 + 128 * j);
          if (j < 4) rs32b<1>(acc, f + 4, b1 + 128 * j + 128); else rs32h(acc, f + 4, b1 + 128 * j + 128);
          wg_commit(); wg_wait0(); fence_regs(acc);
        }
        chk = fmaf(acc[0], 0.f, fmaf(acc[2], 0.f, chk));
#pragma unroll
        for (int k = 0; k < 2; k++) {
          const uint32_t o = __shfl_sync(~0u, nd, (lane >> 2) + 8 * k) * 128 + (lane & 3) * 16 + hb * 64;
          uint32_t x[4]; lds128(x, sb + OFF_H + (o ^ ((o >> 3) & 0x70)));
#pragma unroll
          for (int i = 0; i < 4; i++) x[i] = u2(__hadd2(b2(x[i]), b2(pack_bf16(silu_h(acc[4 * i + 2 * k]), silu_h(acc[4 * i + 2 * k + 1])))));
          if (o < nloc * 128) *(uint4*)((char*)p.out + (size_t)node0 * 128 + o) = make_uint4(x[0], x[1], x[2], x[3]);
        }
        __nanosleep(DEFNS);
      }
      uint32_t pa_[9];
#pragma unroll
      for (int k = 0; k < 9; k++) { const uint32_t i = t + 128 * k, n = (i * 43691u) >> 17; pa_[k] = lds16(sb + OFF_INV + n * 2) + (i - 3 * n) * 2; }
      uint16_t* po = p.out + (size_t)p.N * 64 + node0 * 3 + t;
      mbar_wait(sb + BAR_X);
#pragma unroll
      for (int k = 0; k < 9; k++) pa_[k] = lds16(sb + OFF_GP + pa_[k]);
#pragma unroll
      for (int k = 0; k < 9; k++) if (t + 128 * k < nloc * 3) po[128 * k] = pa_[k];
      asm volatile("{.reg .pred p, q; setp.neu.f32 p, %0, 0f00000000; bar.red.or.pred q, 5, 512, p;}" :: "f"(chk) : "memory");
    }
    return;
  }

  if (tid == 320) {
    mbar_init(sb + BAR_W, 1);
    asm volatile("fence.mbarrier_init.release.cluster;" ::: "memory");
    mbar_expect(sb + BAR_W, 2 * 8192 + 2304);
    tma_load(sb + OFF_W, tmb + TM_WE, 64, sb + BAR_W); tma_load(sb + OFF_W + 8192, tmb + TM_WE, 0, sb + BAR_W);
    bulk_load(sb + OFF_WS, p.we + 128 * 64, 2176, sb + BAR_W); bulk_load(sb + OFF_WS + 2176, p.wx, 128, sb + BAR_W);
  }
  if (tid == 288) {
#pragma unroll
    for (int a = BAR_SRC; a < BAR_END; a += 8) if (a != BAR_W) mbar_init(sb + a, a == BAR_X ? 12 : a >= BAR_WH || a == BAR_PS || a == BAR_EP ? 4 : a == BAR_HB || a == BAR_U ? 2 : 1);
    asm volatile("fence.mbarrier_init.release.cluster;" ::: "memory");
    asm volatile("prefetch.tensormap [%0];" :: "l"(tmb + TM_XA)); asm volatile("prefetch.tensormap [%0];" :: "l"(tmb + TM_H));
    asm volatile("prefetch.tensormap [%0];" :: "l"(tmb + TM_XB)); asm volatile("prefetch.tensormap [%0];" :: "l"(tmb + TM_Q));
  }
  {
    if (tid < 144) sts128(sb + OFF_CNT + tid * 16, 0, 0, 0, 0);
    else if (tid <= 144 + G) sts32(sb + OFF_BC + (tid - 144) * 4, ((tid - 144) & 31) * 4);
    const uint32_t sp = XPAD * 0x10001u, em = first_node(G);
    if (wid < 7) {
#pragma unroll
      for (int i = 0; i < 4; i++) sts128(sb + OFF_TS + tid * 16 + i * 3584, sp, sp, sp, sp);
    }
    static_assert(SCAP * 32 == 4 * 3584, "fill");
#pragma unroll 1
    for (int i = n4 + tid; i < 1536; i += 384) sts128(sb + OFF_DST + i * 16, em, em, em, em);
    if (tid == 321) sts128(sb + OFF_MISC, 0, 0, p.force_slow, 0);
  }
  bar_arrive(6, NTHR);
  bar_sync(0, 384);
  uint32_t ep, tag, eb0, pk[12], r0[12], r1[12], cb;
  uint2 vb[12];
  auto get_tag = [&]() { mbar_wait(sb + BAR_EP); ep = lds32(sb + OFF_MISC + 32); tag = (1 + ep % 3) << 30; eb0 = ealo - (tag >> 11); };
  if (wid == 11) {
    trap_if(sb != (uint32_t)__cvta_generic_to_shared(smraw));
#pragma unroll 1
    for (int k = 0; k < 3; k++) { const int nb = max(0, min(8192, n4 * 16 - k * 8192));
      mbar_wait(sb + BAR_DST + (k ? k + 1 : 0) * 8);
      if (lane == 0) { mbar_expect(sb + BAR_SRC + k * 8, nb);
        if (nb) bulk_load(sb + OFF_SRCI + k * 8192, (const char*)(p.src + e0) + k * 8192, nb, sb + BAR_SRC + k * 8); } }
    proxy_fence();
    get_tag();
    mbar_wait(sb + BAR_PS);
    bar_sync(12, 384);
    uint32_t xm = 0;
#pragma unroll
    for (int k = 0; k < 5; k++) xm |= (lds32(sb + OFF_BC + min(lane + 32 * k, G - 1) * 4) >= (65 << 9) && lane + 32 * k < G) << k;
    auto ext_send = [&](int pl) {
      uint32_t x = xm;
      for (uint32_t m; (m = __ballot_sync(~0u, x));) {
        const uint32_t l = __ffs(m) - 1, j = l + 32 * (__ffs(__shfl_sync(~0u, x, l)) - 1);
        if (lane == l) x &= x - 1;
        const uint32_t e = min(lds16(sb + OFF_AX + j * 128 + ((4 * l + 2 * lane) & 126)), 6143u);
        if (pl) st_ext(p.xe + (j * G + cta) * 32 + lane, lds32(sb + OFF_SRCI + e * 4) + tag + (e << 16), ep);
        else { const uint32_t cn = lds32(sb + OFF_BC + j * 4) >> 9, v = cn > 96 ? 1 : lane + 64 < cn ? 512 | (lds32(sb + OFF_DST + e * 4) & 511) : 0;
          asm volatile("red.shared.xor.b32 [%0], %1;" :: "r"(sb + OFF_SA + j * 128 + ((l + lane) & 31) * 4), "r"(((v & 63) << 10) | ((v >> 6) << 26)) : "memory"); }
      }
    };
    if (__any_sync(~0u, xm)) { ext_send(0); proxy_fence(); __syncwarp(); }
    if (lane == 0) { tma_store(tmb + TM_XA, cta * 64, 0, sb + OFF_SA); bulk_commit(); mbar_arrive(sb + BAR_AI); bulk_wait(); hint_signal(p.sync + 4); mbar_arrive(sb + BAR_AW); STAMP(16); }
    __syncwarp();
    bar_sync(13, 384);
    ext_send(1);
    mbar_arrive(sb + BAR_AX, lane == 0);
    mbar_wait(sb + BAR_HA);
    __nanosleep(BDEL);
    if (lane == 0) {
#pragma unroll 1
      for (int r = 0; r < G; r += BROWS) { tma_store(tmb + TM_XB, cta * 64, r, sb + OFF_SB + r * 256); bulk_commit(); bulk_wait(); }
      hint_signal(p.sync + 5);
      STAMP(17);
    }
    __syncwarp();
  } else {
    {
      uint32_t d[4 * NCH], jj[4 * NCH], rr[4 * NCH];
      auto count = [&](int k) {
        mbar_wait(sb + BAR_DST + k * 8);
        lds128(d + 4 * k, sb + OFF_DST + (tid + NWK * k) * 16);
#pragma unroll
        for (int i = 4 * k; i < 4 * k + 4; i++) { jj[i] = d[i] * p.magic; rr[i] = atoms_add(__dp4a(jj[i], 0x04000000u, sb + OFF_BC), 0x202u); }
      };
      auto place = [&](int k) {
#pragma unroll
        for (int i = 4 * k; i < 4 * k + 4; i++) {
          const uint32_t o = __dp4a(jj[i], 0x80000000u, rr[i] & 0x807Eu);
          d[i] = (d[i] & 511) | (tag >> 16);
          asm("{.reg .pred p; setp.ge.u32 p, %1, 0x8000; @p add.u32 %0, %2, %3;}" : "+r"(d[i]) : "r"(o), "r"(tid * 4), "r"(NWK * k * 4 + (i & 3)));
          sts16(sb + OFF_SA + o, d[i]); jj[i] = __viaddmin_u32(o, o, G * 256);
        }
      };
      count(0); STAMP(1); count(1); get_tag(); place(0); count(2); place(1); count(3); place(2);
      if (wid < 4) { count(4); STAMP(15); place(3); place(4); } else place(3);
      proxy_fence();
      bar_arrive(12, 384);
      STAMP(2);
      mbar_wait(sb + BAR_AI);
      mbar_wait(sb + BAR_SRC); mbar_wait(sb + BAR_SRC + 8); mbar_wait(sb + BAR_SRC + 16);
      STAMP(12);
#pragma unroll
      for (int k = 0; k < NCH; k++) lds128(d + 4 * k, sb + OFF_SRCI + (tid + NWK * k) * 16);
      const uint32_t tb = tag + (tid << 18);
#pragma unroll
      for (int i = 0; i < 4 * NCH; i++) if (i < 4 * NCH - 4 || wid < 4) sts32(sb + OFF_SB + jj[i], d[i] + tb + ((NWK * (i >> 2) * 4 + (i & 3)) << 16));
      proxy_fence();
      bar_arrive(13, 384);
      STAMP(3);
    }
    const uint32_t rot = (lane + cta) & 31;
    cb = sb + OFF_CNT - (tag >> 14);
    {
      const uint32_t* xa = (const uint32_t*)(p.xa + (cta * G + wid) * 8) + rot;
      if (wid < 8) { const uint32_t e_ = ealo + epad * 32;
        mbar_wait(sb + BAR_AX);
#pragma unroll
        for (int i = 0; i < 7; i++) sts128(sb + OFF_TE + tid * 16 + i * 4096, e_, e_, e_, e_); }
      static_assert(SCAP * 64 == 7 * 4096, "fill");
      if (wid == 10) { hint_wait(p.sync + 4, ep * G); mbar_arrive(sb + BAR_HA, lane == 0); }
      mbar_wait(sb + BAR_HA);
      STAMP(14);
      const uint32_t tp = tag | (tag >> 16);
      uint32_t st;
#pragma unroll 1
      for (int spin = 0;; spin++) {
        st = 0;
#pragma unroll
        for (int k = 0; k < 12; k++) asm volatile("ld.relaxed.gpu.global.u32 %0, [%1];" : "=r"(pk[k]) : "l"(xa + k * 352) : "memory");
#pragma unroll
        for (int k = 0; k < 12; k++) st |= pk[k] ^ tp;
        st = __reduce_or_sync(~0u, st);
        if (!(st >> 30)) break;
        trap_if(spin > 2000000);
      }
      if (st & 0x3C00FC00u) {
#pragma unroll 1
        for (;;) {
          uint32_t x = 0, row = 0;
#pragma unroll
          for (int k = 0; k < 12; k++) { const uint32_t y = (pk[k] ^ tp) & 0x3C00FC00u; if (!x && y) { x = y; row = wid + 11 * k; pk[k] ^= y; } }
          if (!__any_sync(~0u, x)) break;
          const uint32_t n = ((x >> 10) & 63) | ((x >> 20) & 0x1C0);
          if (x >> 29) {
            const uint32_t r = atoms_add(sb + OFF_CNT + n * 4, 16), idx = atoms_add(sb + OFF_MISC + 4, 1);
            if (idx < 256) sts32(sb + OFF_EXT + idx * 4, n | (row << 9) | (lane << 17) | (min(r >> 4, 255u) << 22));
            else x = 1;
          }
          if (x && !(x >> 29)) sts32(sb + OFF_MISC + 8, 1);
          __syncwarp();
        }
      }
#pragma unroll
      for (int k = 0; k < 12; k++) { r0[k] = mad16(pk[k], 0x0004u, cb); r1[k] = mad16(pk[k], 0x0400u, cb); vb[k].x = atoms_add(r0[k], 16); vb[k].y = atoms_add(r1[k], 16); }
    }
    STAMP(4);
    if (wid >= 6) bar_arrive(11, NWK);
    if (wid < 6) {
      uint32_t ca[2], ky[2], dr[2], sq[2], ps[4];
#pragma unroll
      for (int i = 0; i < 2; i++) { ca[i] = sb + OFF_CNT + ((node0 + tid + 192 * i) & 511) * 4; lds64(ps[2 * i], ps[2 * i + 1], sb + OFF_POS + (tid + 192 * i) * 8); ps[2 * i + 1] |= (tid + 192 * i) << 16; }
      bar_sync(11, NWK);
      STAMP(5);
#pragma unroll
      for (int i = 0; i < 2; i++) ky[i] = (lds32(ca[i]) + 16) >> 5;
      if (max(ky[0], ky[1]) > 31) sts32(sb + OFF_MISC + 8, 1);
#pragma unroll
      for (int i = 0; i < 2; i++) { ky[i] = min(ky[i], 31u); dr[i] = atoms_add(sb + OFF_DH + ky[i] * 4, 1); }
      bar_sync(10, 192);
      const uint32_t hv = lds32(sb + OFF_DH + lane * 4);
      uint32_t inc = hv;
#pragma unroll
      for (int o = 1; o < 32; o <<= 1) asm("{.reg .pred p; .reg .b32 y; shfl.sync.down.b32 y|p, %0, %1, 31, -1; @p add.u32 %0, %0, y;}" : "+r"(inc) : "r"(o));
#pragma unroll
      for (int i = 0; i < 2; i++) {
        const uint32_t pos = __shfl_sync(~0u, inc - hv, ky[i]) + dr[i];
        const uint32_t ak = (uint32_t)(QCODE >> ((pos >> 5) * 4)) & 15, l = (pos >> 3) & 3;
        sq[i] = (ak >> 2) * 16 + ((QREV >> (pos >> 5) & 1) ? 3 - l : l) * 4 + (ak & 3);
        dr[i] = pos & 7;
        asm volatile("{.reg .pred p; setp.eq.u32 p, %2, 0; @p st.shared.u8 [%0], %1;}" :: "r"(sb + OFF_LEN + sq[i]), "r"(max(ky[i], 1u)), "r"(dr[i]) : "memory");
        sts64(sb + OFF_GP + sq[i] * 64 + dr[i] * 8, ps[2 * i], ps[2 * i + 1]);
        sts16(sb + OFF_INV + (tid + 192 * i) * 2, sq[i] * 64 + dr[i] * 8);
      }
      bar_sync(10, 192);
      const uint32_t ln = lds32(sb + OFF_LEN + min(lane, 11) * 4), tot = __dp4a(ln, 0x01010101u, 0u);
      inc = tot;
#pragma unroll
      for (int o = 1; o < 16; o <<= 1) asm("{.reg .pred p; .reg .b32 y; shfl.sync.up.b32 y|p, %0, %1, 0, -1; @p add.u32 %0, %0, y;}" : "+r"(inc) : "r"(o));
      if (tid < 12) { sts32(sb + OFF_LEN + 64 + tid * 4, inc - tot); if (inc > SCAP - 12) sts32(sb + OFF_MISC + 8, 1); }
#pragma unroll
      for (int i = 0; i < 2; i++) sts32(ca[i], __dp4a(__shfl_sync(~0u, ln, sq[i] >> 2), 0x00010101u >> (24 - 8 * (sq[i] & 3)), __shfl_sync(~0u, inc - tot, sq[i] >> 2)) * 32 + dr[i] * 2);
    }
    bar_arrive(7, 384);
  }
  bar_sync(1, 384);
  STAMP(6);
  if (wid != 11 && !__shfl_sync(~0u, lds32(sb + OFF_MISC + 8), 0)) {
#pragma unroll
    for (int k = 0; k < 12; k++) asm volatile("{.reg .pred p, q; setp.lt.u32 p, %0, %2; setp.lt.u32 q, %1, %2; @p ld.shared.u32 %0, [%0]; @q ld.shared.u32 %1, [%1];}" : "+r"(r0[k]), "+r"(r1[k]) : "n"(sb + OFF_CNT + 2048) : "memory");
#pragma unroll
    for (int k = 0; k < 12; k++) { r0[k] += vb[k].x; r1[k] += vb[k].y; }
  } else {
#pragma unroll
    for (int k = 0; k < 12; k++) r0[k] = r1[k] = 0x8000;
  }
  auto put_ids = [&]() {
    const uint32_t id = wid * 256 + ((lane + cta) & 31) * 8;
    auto put = [&](uint32_t x, uint32_t v) { asm volatile("{.reg .pred p; setp.lt.u32 p, %0, 0x8000; @p st.shared.u16 [%0+%2], %1;}" :: "r"(x), "h"((uint16_t)v), "n"(sb + OFF_TS) : "memory"); };
#pragma unroll
    for (int k = 0; k < 12; k++) { put(r0[k], id + k * 2816); put(r1[k], id + k * 2816 + 4); }
  };
  STAMP(7);
  mbar_wait(sb + BAR_QR);
  asm volatile("setmaxnreg.inc.sync.aligned.u32 152;");
  uint32_t pa[8], sp[8]; float chk = 0.f;
  {
    uint32_t hf[16], mp = 0; float a0[32];
    const uint32_t nd = lds16(sb + OFF_GP + wid * 256 + (lane & 15) * 8 + 6);
#pragma unroll
    for (int j = 0; j < 4; j++) ldsm4(hf + 4 * j, (sb + OFF_H + nd * 128 + (((nd & 7) << 4) ^ (lane & 16))) ^ (j << 5));
    const uint64_t db = DHI | ((sb + OFF_W + 8192) >> 4);
    wg_fence();
    rs64b<0>(a0, hf[0], hf[1], hf[2], hf[3], db); rs64b<1>(a0, hf[4], hf[5], hf[6], hf[7], db + 128); rs64b<1>(a0, hf[8], hf[9], hf[10], hf[11], db + 256); rs64b<1>(a0, hf[12], hf[13], hf[14], hf[15], db + 384);
    wg_commit();
    put_ids();
    wg_wait0(); fence_regs(a0);
#pragma unroll
    for (int j = 0; j < 8; j++) { const uint32_t x = pack_f16(.5f * a0[4 * j], .5f * a0[4 * j + 1]), y = pack_f16(.5f * a0[4 * j + 2], .5f * a0[4 * j + 3]); mp = hmag(hmag(mp, x), y);
      asm volatile("movmatrix.sync.aligned.m8n8.trans.b16 %0, %1;" : "=r"(pa[j]) : "r"(x)); asm volatile("movmatrix.sync.aligned.m8n8.trans.b16 %0, %1;" : "=r"(sp[j]) : "r"(y)); }
    if (magr(mp) >= 0x7000) chk = 1.f;
  }
  if (wid == 0) STAMP(23);
  uint32_t bad;
  {
    const uint32_t ring = sb + OFF_RING + wid * STG, p2 = sb + OFF_P2 + wid * 2048;
    uint32_t lens = __shfl_sync(~0u, lds32(sb + OFF_LEN + wid * 4), 0);
    uint32_t rem = __dp4a(lens, 0x20202020u, 0u);
    const uint32_t base = min(lds32(sb + OFF_LEN + 64 + wid * 4), SCAP);
    uint32_t a_s = sb + OFF_TS + base * 32 + (lane >> 3) * 8, a_e = sb + OFF_TE + base * 64 + (lane >> 1) * 4;
    uint32_t k0 = (uint32_t)(uint64_t)p.q + (((lane & 7) ^ ((lane >> 1) & 4)) << 4), k1 = k0 ^ 16, k2 = k0 ^ 32, k3 = k0 ^ 48, ke = ((lane ^ (lane >> 3)) & 1) << 4;
    uint32_t dst0 = ring + (lane >> 3) * 640 + (lane & 7) * 16;
    const uint32_t qhi = (uint32_t)((uint64_t)p.q >> 32), ehi = (uint32_t)((uint64_t)p.ea >> 32);
    uint32_t s0, s1, ev, to = 0, so = 12 * STG;
    auto tl_ = [&]() { lds64(s0, s1, a_s + to); asm volatile("ld.shared.u32 %0, [%1]; add.u32 %1, %1, 64;" : "=&r"(ev), "+r"(a_e) :: "memory"); to += 32; };
#define CPQ(LH, x, k, off) "dp2a." LH ".u32.u32 lo, " x ", 0x80000080, " k "; mov.b64 a, {lo, %7}; @p cp.async.cg.shared.global [%0+" #off "], [a], 16;\n"
    uint64_t pe; asm volatile("createpolicy.fractional.L2::evict_normal.b64 %0, 1.0;" : "=l"(pe));
    uint32_t one = __shfl_sync(~0u, lane, 1);
#define CPE "or.b32 lo, %10, %11; mov.b64 a, {lo, %12}; @p cp.async.cg.shared.global.L2::cache_hint [%0+512], [a], 16, %13;\n"
#define CPA(BODY) asm volatile("{.reg .b32 lo; .reg .b64 a; .reg .pred p; setp.le.u32 p, %8, %9;\n" BODY "}" \
      :: "r"(so * one + dst0), "r"(s0), "r"(s1), "r"(k0), "r"(k1), "r"(k2), "r"(k3), "r"(qhi), "r"(to), "r"(rem), "r"(ev), "r"(ke), "r"(ehi), "l"(pe) : "memory")
#define CPQ4 CPQ("lo", "%1", "%3", 0) CPQ("hi", "%1", "%4", 128) CPQ("lo", "%2", "%5", 256) CPQ("hi", "%2", "%6", 384) "cp.async.commit_group;"
    auto issue = [&]() { CPA(CPE CPQ4); so = so == (NST - 1) * 12 * STG ? 0 : so + 12 * STG; };
    const int g = lane >> 2, qd = lane & 3;
    const uint32_t sw = ((lane >> 4) ^ (lane & 7)) << 4, fr = (lane & 15) * 128 + sw;
    uint32_t qa0 = ring + (g & 3) * 640 + qd * 128 + sw, qa1 = qa0 ^ 32, qa2 = qa0 ^ 64, qa3 = qa0 ^ 96;
    uint32_t eadr = ring + 512 + (g & 3) * 640 + qd * 32 + ((((lane >> 4) ^ g) & 1) << 4);
    uint32_t oh0 = g == 2 * qd ? 0x3C00u : g == 2 * qd + 1 ? 0x3C000000u : 0u, oh1 = oh0;
    uint32_t a_g = sb + OFF_GP + wid * 256 + lane * 2;
    asm volatile("shfl.sync.idx.b32 %0, %0, %1, 31, -1;" : "+r"(oh1) : "r"(lane));
    uint32_t w3[16], wv[8], bp[16], sum[8], Y[16], M[16], own, ownp, dpk, tl[16], th[16];
    float pacc = 0.f;
    auto wload = [&]() {
#pragma unroll
      for (int j = 0; j < 4; j++) ldsm4t(w3 + 4 * j, (sb + OFF_W3 + fr) ^ (j << 5));
      lds128(wv, sb + OFF_WX + (a_g & 6) * 16); lds128(wv + 4, sb + OFF_WX + 16 + (a_g & 6) * 16);
    };
    auto hload = [&](uint32_t (&hf)[16], uint32_t nd) {
      const uint32_t hrow = sb + OFF_H + nd * 128 + (((nd & 7) << 4) ^ ((a_g >> 1) & 16));
#pragma unroll
      for (int j = 0; j < 4; j++) ldsm4(hf + 4 * j, hrow ^ (j << 5));
      return hrow;
    };
    { uint32_t wd[8]; const uint32_t a = sb + OFF_WD + (lane & 7) * 128 + ((((lane >> 3) ^ lane) & 7) << 4);
      ldsm4t(wd, a); ldsm4t(wd + 4, a ^ 64);
#pragma unroll
      for (int j = 0; j < 8; j++) { bp[2 * j] = wd[j]; bp[2 * j + 1] = pa[j]; } }
    own = lds16(a_g) * 0x10001u;
    wload();
    if (__shfl_sync(~0u, lds32(sb + OFF_MISC + 8), 0)) rem = 0;
    auto resolve = [&](auto NBK, uint32_t o) {
      constexpr int NB = decltype(NBK)::value;
      uint32_t id[NB], c0[NB], c1[NB]; const uint32_t a = base * 32 + o + lane * 4;
#pragma unroll
      for (int i = 0; i < NB; i++) { id[i] = lds32(sb + OFF_TS + a + i * 128); if (o + lane * 4 + i * 128 >= rem) id[i] = XPAD * 0x10001u; }
      uint32_t st = 0;
#pragma unroll
      for (int i = 0; i < NB; i++) { c0[i] = lds32(sb + OFF_XB + (id[i] & 0xFFFF)); c1[i] = lds32(sb + OFF_XB + (id[i] >> 16)); }
#pragma unroll
      for (int i = 0; i < NB; i++) st |= (c0[i] ^ tag) | (c1[i] ^ tag);
      for (int spin = 0; __any_sync(~0u, st >> 30); spin++) {
        st = 0; trap_if(spin > 2000000);
#pragma unroll
        for (int i = 0; i < NB; i++) {
          asm volatile("{.reg .pred p, q; setp.lt.u32 p, %4, %6; setp.lt.u32 q, %5, %6; @p ld.relaxed.gpu.global.u32 %0, [%2]; @q ld.relaxed.gpu.global.u32 %1, [%3];}"
            : "+r"(c0[i]), "+r"(c1[i]) : "l"((const char*)p.xb + cta * XPAD + (id[i] & 0xFFFF)), "l"((const char*)p.xb + cta * XPAD + (id[i] >> 16)), "r"(id[i] & 0xFFFF), "r"(id[i] >> 16), "n"(XPAD) : "memory");
          st |= (c0[i] ^ tag) | (c1[i] ^ tag); }
      }
#pragma unroll
      for (int i = 0; i < NB; i++) { const uint32_t j0 = (id[i] >> 8) & 255, j1 = id[i] >> 24;
        asm volatile("{.reg .pred p, q, r; setp.lt.u32 p, %5, %9; setp.lt.u32 q, %6, %9; setp.lt.u32 r, %7, %8;\n"
          "@p st.shared.u32 [%0], %2; @q st.shared.u32 [%0+4], %3; @r st.shared.u32 [%1], %4;}"
          :: "r"(sb + OFF_TE + 2 * a + i * 256), "r"(sb + OFF_TS + a + i * 128), "r"(mad16(c0[i], 0x2000u, eb0 + j0 * p.EPC * 32)), "r"(mad16(c1[i], 0x2000u, eb0 + j1 * p.EPC * 32)),
             "r"(__byte_perm(c0[i], c1[i], 0x5410)), "r"(j0), "r"(j1), "r"(o + lane * 4 + i * 128), "r"(rem), "n"(G) : "memory"); }
    };
    bar_sync(2, 384);
    if (wid == 0) STAMP(27);
    mbar_wait(sb + BAR_HB);
    if (wid == 0) STAMP(22);
#pragma unroll 1
    for (uint32_t o = 0, go = 0; go < 32 * NST; o += 128 * RNB) {
      if (o < rem) { resolve(IC<RNB>(), o);
        asm volatile("{.reg .pred p; mbarrier.test_wait.parity.shared::cta.b64 p, [%1], 0; vote.sync.all.pred p, p, -1; selp.u32 %0, %2, 0, p;}" : "=r"(go) : "r"(sb + BAR_QP), "n"(32 * NST - 32) : "memory"); }
      else { bar_arrive(4, NTHR); bar_sync(8, 384); mbar_wait(sb + BAR_QP); go = 32 * NST; if (wid == 0) STAMP(24); }
      __syncwarp();
#pragma unroll 1
      while (to < go) { tl_(); issue(); if (to == 32) STAMP(13); }
    }
    bad = __shfl_sync(~0u, lds32(sb + OFF_MISC + 8), 0);
   if (!bad) {
    auto body = [&](auto MODE) {
      constexpr int mode = decltype(MODE)::value;
      uint32_t T[16], ef[4], q0, q1, x0, x1, x2; float e0_, e1_, cs[4];
      auto mu = [&](int j) {
#pragma unroll
        for (int i = 2 * j; i < 2 * j + 2; i++) asm volatile("{.reg .b16 l, h; mov.b32 {l, h}, %2; tanh.approx.f16 l, l; tanh.approx.f16 h, h; cvt.u32.u16 %0, l; cvt.u32.u16 %1, h;}" : "=r"(tl[i]), "=r"(th[i]) : "r"(Y[i])); };
      auto fi = [&](int j) {
#pragma unroll
        for (int i = 2 * j; i < 2 * j + 2; i++) asm volatile("{.reg .b32 t; prmt.b32 t, %2, %3, 0x5410; fma.rn.f16x2 %0, %1, t, %1;}" : "=r"(M[i]) : "r"(Y[i]), "r"(tl[i]), "r"(th[i])); };
      auto ad = [&](int j) { asm volatile("add.rn.f16x2 %0, %0, %1; add.rn.f16x2 %0, %0, %2;" : "+r"(sum[j]) : "r"(M[2 * j]), "r"(M[2 * j + 1])); };
      auto he = [&](int j) { asm volatile("mma.sync.aligned.m16n8k16.row.col.f16.f16.f16.f16 {%0,%1}, {%2,%3,%4,%5}, {%6,%7}, {%0,%1};" : "+r"(T[2 * j]), "+r"(T[2 * j + 1]) : "r"(ef[0]), "r"(ef[1]), "r"(ef[2]), "r"(ef[3]), "r"(w3[2 * j]), "r"(w3[2 * j + 1])); };
      auto hs = [&](int j) { asm volatile("mma.sync.aligned.m16n8k16.row.col.f16.f16.f16.f16 {%0,%1}, {%2,%3,%4,%5}, {%6,%7}, {%8,%9};" : "=r"(Y[2 * j]), "=r"(Y[2 * j + 1]) : "r"(q0), "r"(q1), "r"(oh0), "r"(oh1), "r"(bp[2 * j]), "r"(bp[2 * j + 1]), "r"(T[2 * j]), "r"(T[2 * j + 1])); };
      auto hc = [&](int j) {
        if (j) asm volatile("mma.sync.aligned.m16n8k16.row.col.f32.f16.f16.f32 {%0,%1,%2,%3}, {%4,%5,%6,%7}, {%8,%9}, {%0,%1,%2,%3};" : "+f"(cs[0]), "+f"(cs[1]), "+f"(cs[2]), "+f"(cs[3]) : "r"(M[4 * j]), "r"(M[4 * j + 1]), "r"(M[4 * j + 2]), "r"(M[4 * j + 3]), "r"(wv[2 * j]), "r"(wv[2 * j + 1]));
        else asm volatile("mma.sync.aligned.m16n8k16.row.col.f32.f16.f16.f32 {%0,%1,%2,%3}, {%4,%5,%6,%7}, {%8,%9}, {%10,%10,%10,%10};" : "=f"(cs[0]), "=f"(cs[1]), "=f"(cs[2]), "=f"(cs[3]) : "r"(M[0]), "r"(M[1]), "r"(M[2]), "r"(M[3]), "r"(wv[0]), "r"(wv[1]), "f"(0.f)); };
      auto cv = [&](int i) { asm volatile("{.reg .b32 a, b; shl.b32 a, %0, 16; and.b32 b, %0, 0xFFFF0000; cvt.rn.f16x2.f32 %0, b, a;}" : "+r"(ef[i])); };
      auto un = [&]() { asm volatile("shl.b32 %0, %2, 16; and.b32 %1, %2, 0xFFFF0000;" : "=&f"(e0_), "=&f"(e1_) : "r"(dpk)); };
      auto ex0 = [&]() { asm volatile("prmt.b32 %0, %3, %4, 0x6420; prmt.b32 %1, %5, %6, 0x6420; prmt.b32 %2, %7, %8, 0x6420;" : "=&r"(x0), "=&r"(x1), "=&r"(x2) : "r"(T[0]), "r"(T[1]), "r"(T[2]), "r"(T[3]), "r"(T[4]), "r"(T[5])); };
      auto ex1 = [&]() { asm volatile("{.reg .b32 a, b; shl.b32 a, %2, 3; shl.b32 b, %3, 6; lop3.b32 a, %1, a, 0x38383838, 0xD8; lop3.b32 a, a, b, 0xC0C0C0C0, 0xD8; sub.rn.bf16x2 %0, %4, a;}" : "=r"(dpk) : "r"(x0), "r"(x1), "r"(x2), "r"(own)); };
      auto ex2 = [&]() { asm volatile("{.reg .b32 a, b, d, u; .reg .b16 l, h; shl.b32 a, %2, 16; and.b32 b, %2, 0xFFFF0000; cvt.rn.f16x2.f32 d, b, a; mul.rn.f16x2 %0, d, d; mov.b32 {l, h}, d; mov.b32 u, {h, h}; mul.rn.f16x2 %1, u, u;}" : "=&r"(q0), "=&r"(q1) : "r"(dpk)); };
      auto pf = [&]() { asm volatile("fma.rn.f32 %0, %1, %2, %0; fma.rn.f32 %0, %3, %4, %0;" : "+f"(pacc) : "f"(cs[0]), "f"(e0_), "f"(cs[2]), "f"(e1_)); };
      if (mode == 2) { LASTSEQ return; }
      asm volatile("cp.async.wait_group %0;" :: "n"(NST - 1) : "memory");
      __syncwarp();
      if (mode == 1) STAMP(8);
      ldsm4(ef, eadr + so); ldsm4(T, qa0 + so); ldsm4(T + 4, qa1 + so); ldsm4(T + 8, qa2 + so); ldsm4(T + 12, qa3 + so);
      if (mode == 1) {
        tl_(); issue();
        cv(0); cv(1); cv(2); cv(3); ex0(); ex1(); ex2();
#pragma unroll
        for (int j = 0; j < 8; j++) { he(j); hs(j); }
        FIRSTSEQ return;
      }
      BODYSEQ
    };
#pragma unroll
    for (int j = 0; j < 8; j++) sum[j] = 0;
    body(IC<1>());
    int cnt = (lens & 255) - 1;
    auto pload = [&](uint32_t (&x)[8], uint32_t o) { const uint32_t l = a_g >> 1, a = p2 + o + (l & 7) * 128 + (((((l >> 3) & 3) ^ l) & 7) << 4); ldsm4t(x, a); ldsm4t(x + 4, a ^ 64); };
    auto flush = [&]() {
      asm volatile("{.reg .pred p; setp.ne.u32 p, %2, 6; @p st.shared.u16 [%0+-64], %1;}" :: "r"(a_g), "h"((uint16_t)pack_bf16(bf_hi(ownp) + pacc, 0.f)), "r"(a_g & 6) : "memory");
      chk = fmaf(pacc, 0.f, chk); pacc = 0.f; };
    constexpr uint64_t b1 = DHI | ((sb + OFF_W) >> 4), b2_ = b1 + 512;
    auto mma_h = [&](float (&acc)[32], uint32_t (&hf)[16]) {
      rs64b<0>(acc, hf[0], hf[1], hf[2], hf[3], b1); rs64b<1>(acc, hf[4], hf[5], hf[6], hf[7], b1 + 128); rs64b<1>(acc, hf[8], hf[9], hf[10], hf[11], b1 + 256); rs64b<1>(acc, hf[12], hf[13], hf[14], hf[15], b1 + 384); };
    auto mma_m = [&](float (&acc)[32]) {
      rs64h<1>(acc, sp[0], sum[0], sp[1], sum[1], b2_); rs64h<1>(acc, sp[2], sum[2], sp[3], sum[3], b2_ + 128); rs64h<1>(acc, sp[4], sum[4], sp[5], sum[5], b2_ + 256); rs64h<1>(acc, sp[6], sum[6], sp[7], sum[7], b2_ + 384);
      wg_commit(); wg_wait0(); fence_regs(acc);
      STAMP(10);
      chk = fmaf(acc[0], 0.f, fmaf(acc[2], 0.f, chk)); };
    auto roff = [&](uint32_t nd, int r) { return __shfl_sync(~0u, nd, ((a_g >> 3) & 7) + 8 * r) * 128 + (a_g & 6) * 8; };
    auto radr = [&](uint32_t o, int k) { return sb + OFF_H + (o ^ ((o >> 3) & 0x70) ^ ((k >> 1) << 6)); };
    auto fin = [&](float (&acc)[32], uint32_t* x, int k) {
#pragma unroll
      for (int i = 0; i < 4; i++) { const int c = 16 * (k >> 1) + 4 * i + 2 * (k & 1); x[i] = u2(__hadd2(b2(x[i]), b2(pack_bf16(silu_h(acc[c]), silu_h(acc[c + 1]))))); } };
#pragma unroll 1
    for (int t = 0;; t++) {
#pragma unroll 1
      for (; cnt > 0; cnt--) { body(IC<0>());
      }
      if (!(t & 1)) {
        ownp = own; a_g += 64;
        if (t == 6) break;
        pe = pol_first();
        own = lds16(a_g) * 0x10001u;
        if (t == 2) { const uint32_t a = ((a_g & 16) ? p2 : sb + OFF_WD) + ((a_g << 6) & 0x380) + (qa0 & 0x70);
          mbar_wait(sb + BAR_U);
#pragma unroll
          for (int j = 0; j < 4; j++) ldsm4t(bp + 4 * j, a ^ (j << 5));
        } else {
#pragma unroll
          for (int j = 0; j < 8; j++) bp[2 * j + 1] = sp[j];
        }
        lens >>= 8; cnt = 1;
        continue;
      }
      cnt = (lens & 255) - 1;
      flush();
      if (t == 3) {
        uint32_t x[8];
        pload(x, 1024);
        __syncwarp();
#pragma unroll
        for (int j = 0; j < 4; j++) stsm4((p2 + ((a_g << 6) & 0x780) + (qa0 & 0x70)) ^ (j << 5), sp[2 * j], sum[2 * j], sp[2 * j + 1], sum[2 * j + 1]);
#pragma unroll
        for (int j = 0; j < 8; j++) sum[j] = x[j];
        __syncwarp();
        mbar_arrive(sb + BAR_M + (wid >> 2) * 8, (a_g & 62) == 0);
      }
#pragma unroll
      for (int j = 0; j < 8; j++) { sp[j] = sum[j]; asm volatile("mov.b32 %0, 0;" : "=r"(sum[j])); }
    }
    {
      uint32_t hf[16], v[16]; float acc[32];
      const uint32_t nd = lds16(sb + OFF_GP + wid * 256 + (lane & 15) * 8 + 134), o[2] = {roff(nd, 0), roff(nd, 1)};
      hload(hf, nd);
#pragma unroll
      for (int k = 0; k < 4; k++) lds128(v + 4 * k, radr(o[k & 1], k));
      mbar_wait(sb + BAR_WH);
      wg_fence(); mma_h(acc, hf); wg_commit();
      body(IC<2>());
      STAMP(9);
      flush();
      __syncwarp();
      mbar_arrive(sb + BAR_X, lane == 0);
      wg_fence();
      mma_m(acc);
#pragma unroll
      for (int k = 0; k < 4; k++) { fin(acc, v + 4 * k, k);
        asm volatile("{.reg .pred p; setp.lt.u32 p, %5, %6; @p st.global.v4.b32 [%0], {%1,%2,%3,%4};}" :: "l"((const char*)p.out + (size_t)node0 * 128 + o[k & 1] + (k >> 1) * 64), "r"(v[4 * k]), "r"(v[4 * k + 1]), "r"(v[4 * k + 2]), "r"(v[4 * k + 3]), "r"(o[k & 1]), "r"(nloc * 128) : "memory"); }
    }
    asm volatile("{.reg .pred p, q; setp.neu.f32 p, %1, 0f00000000; setp.ne.or.u32 p, %2, 0, p; bar.red.or.pred q, 5, 512, p; selp.u32 %0, 1, 0, q;}" : "=r"(bad) : "f"(chk), "r"(lds32(sb + OFF_MISC + 12)) : "memory");
    STAMP(11);
   } else { asm volatile("cp.async.wait_all;" ::: "memory"); bar_sync(5, 384); }
  }
  if (bad) slow_path(p, wid, lane, node0, nloc);
}

}

typedef CUresult (*EncodeFn)(CUtensorMap*, CUtensorMapDataType, cuuint32_t, void*, const cuuint64_t*, const cuuint64_t*, const cuuint32_t*, const cuuint32_t*,
                             CUtensorMapInterleave, CUtensorMapSwizzle, CUtensorMapL2promotion, CUtensorMapFloatOOBfill);

extern "C" void kernel_launch(void* const* d_in, const int* in_sizes, int n_in, void* d_out, int out_size) {
  Params p; Maps maps;
  p.h = (const uint4*)d_in[0]; p.pos = (const uint16_t*)d_in[1]; p.ea = (const uint4*)d_in[2];
  p.src = (const int*)d_in[3]; p.dst = (const int*)d_in[4];
  p.we = (const uint16_t*)d_in[5]; p.wx = (const uint16_t*)d_in[6]; p.wh = (const uint16_t*)d_in[7];
  p.out = (uint16_t*)d_out;
  p.N = in_sizes[0] / 64; p.E = in_sizes[3];
  p.EPC = ((p.E + G * 4 - 1) / (G * 4)) * 4;
  p.magic = (uint32_t)(((uint64_t)G << 24) / (uint64_t)p.N);
  p.inv = (1ull << 56) / p.magic;
  const uint64_t ea0 = (uint64_t)d_in[2], ea1 = ea0 + (uint64_t)p.E * 32 - 1;
  p.force_slow = ((ea0 >> 32) != (ea1 >> 32)) || (ea0 & 31) || (p.E & 3);
  void* qp = nullptr;
  cudaGetSymbolAddress(&qp, g_q);
  p.q = (char*)qp;
  if (((uint64_t)p.q >> 32) != (((uint64_t)p.q + QBYTES) >> 32)) p.q += QBYTES;
  cudaGetSymbolAddress((void**)&p.sync, g_sync); cudaGetSymbolAddress((void**)&p.xe, g_xe);
  cudaGetSymbolAddress((void**)&p.xa, g_xa); cudaGetSymbolAddress((void**)&p.xb, g_xb);
  const int df[10] = {34, 120, 900, 3072, 0, 17, 0xff2, 0xD5C4E6, 0x422000};
  for (int i = 0; i < 10; i++) p.tune[i] = df[i];
  p.qcode = 0x890145a6273bull;
  p.ctam = p.tune[5];
  if ((long long)PFB * PFN > (long long)(p.E / G) * 32) PFB = (p.E / G * 32 / PFN) & ~127;
  void* fn = nullptr; cudaDriverEntryPointQueryResult qr;
  cudaGetDriverEntryPoint("cuTensorMapEncodeTiled", &fn, cudaEnableDefault, &qr);
  auto mk = [&](CUtensorMap* tm, void* base, int rows, int box = 64) {
    const cuuint64_t dim[2] = {64, (cuuint64_t)rows}, str[1] = {128}; const cuuint32_t bx[2] = {64, (cuuint32_t)box}, es[2] = {1, 1};
    ((EncodeFn)fn)(tm, CU_TENSOR_MAP_DATA_TYPE_BFLOAT16, 2, base, dim, str, bx, es, CU_TENSOR_MAP_INTERLEAVE_NONE, CU_TENSOR_MAP_SWIZZLE_128B,
                   CU_TENSOR_MAP_L2_PROMOTION_NONE, CU_TENSOR_MAP_FLOAT_OOB_FILL_NONE);
  };
  mk(&maps.m[TM_H / 128], d_in[0], p.N); mk(&maps.m[TM_WE / 128], d_in[5], 145); mk(&maps.m[TM_WH / 128], d_in[7], 128); mk(&maps.m[TM_Q / 128], p.q, p.N, 16);
  for (int k = 0; k < 2; k++) {
    void* xp = (void*)(k ? p.xb : p.xa);
    const cuuint64_t dim[2] = {(cuuint64_t)G * 64, (cuuint64_t)G}, str[1] = {(cuuint64_t)G * (128 << k)}; const cuuint32_t bx[2] = {64, (cuuint32_t)(k ? BROWS : G)}, es[2] = {1, 1};
    ((EncodeFn)fn)(&maps.m[TM_XA / 128 + k], k ? CU_TENSOR_MAP_DATA_TYPE_UINT32 : CU_TENSOR_MAP_DATA_TYPE_UINT16, 2, xp, dim, str, bx, es, CU_TENSOR_MAP_INTERLEAVE_NONE,
                   CU_TENSOR_MAP_SWIZZLE_NONE, CU_TENSOR_MAP_L2_PROMOTION_NONE, CU_TENSOR_MAP_FLOAT_OOB_FILL_NONE);
  }
  cudaFuncSetAttribute(egnn_kernel, cudaFuncAttributeMaxDynamicSharedMemorySize, SMEM);
  egnn_kernel<<<G, NTHR, SMEM>>>(p, maps);
}
```

```cpp
#include <cuda_runtime.h>
#include <cuda_bf16.h>
#include <cuda_fp16.h>
#include <cuda.h>
#include <stdint.h>
#pragma nv_diag_suppress 549

#define PFN p.tune[0]
#define PFB p.tune[3]
#define PFNS p.tune[1]
#define PFE p.tune[8]
#define BT p.tune[9]
#define BDEL p.tune[2]
#define DEFNS p.tune[4]
#define CTAM p.ctam
#define QREV p.tune[6]
#define UORD p.tune[7]
#define QCODE p.qcode
#define FIRSTSEQ mu(0); mu(1); fi(0); mu(2); fi(1);
#define BODYSEQ hc(0); fi(2); tl_(); mu(3); un(); ad(1); ad(0); cv(0); mu(4); cv(2); fi(3); cv(1); ex0(); ex1(); cv(3); he(0); fi(4); he(1); \
  mu(5); hc(1); mu(6); fi(5); he(2); ad(2); ex2(); hs(0); ad(3); hs(1); fi(6); mu(7); issue(); hc(2); he(3); hs(3); fi(7); mu(0); \
  hs(2); he(4); he(5); ad(5); ad(4); hs(4); fi(0); he(6); mu(1); hc(3); he(7); fi(1); ad(6); hs(7); hs(5); ad(7); hs(6); mu(2); \
  pf();
#define LASTSEQ hc(0); fi(2); mu(3); un(); ad(1); ad(0); mu(4); fi(3); fi(4); mu(5); hc(1); mu(6); fi(5); ad(2); ad(3); fi(6); mu(7); hc(2); \
  fi(7); ad(5); ad(4); hc(3); ad(6); ad(7); pf();
namespace {

constexpr int G = 132;
constexpr int NTHR = 512, NWK = 352, NCH = 5;
constexpr int NST = 3, STG = 2560;
constexpr int BROWS = 44, RNB = 2, PADM = 33;
constexpr int SCAP = 448;

constexpr int OFF_H = 0;
constexpr int OFF_W = 49152;
constexpr int OFF_WD = OFF_W + 16384;
constexpr int OFF_W3 = OFF_WD + 1024;
constexpr int OFF_P2 = OFF_W3 + 2048;
constexpr int OFF_RING = OFF_P2 + 24576;
constexpr int OFF_TE = OFF_RING + 12 * NST * STG;
constexpr int OFF_TS = OFF_TE + SCAP * 64;
constexpr int OFF_INV = OFF_TS - 768;
constexpr int OFF_GP = OFF_TS + SCAP * 32;
constexpr int OFF_WX = OFF_GP + 3072;
constexpr int OFF_LEN = OFF_WX + 128;
constexpr int OFF_MISC = OFF_LEN + 128;
constexpr int OFF_BAR = OFF_MISC + 48;
constexpr int SMEM = OFF_BAR + 256;
static_assert(SMEM <= 232448, "smem");
constexpr uint32_t sb = 1024;
constexpr int OFF_SRCI = OFF_TE;
constexpr int OFF_SB = OFF_RING, OFF_SA = OFF_SB + 34816, OFF_AX = OFF_SA + 32768, OFF_DST = OFF_H + 24576;
constexpr int OFF_WS = OFF_AX + 17408;
constexpr int OFF_BC = OFF_WS + 2304;
constexpr int OFF_CNT = OFF_P2;
constexpr int OFF_DH = OFF_CNT + 2176;
constexpr int OFF_POS = OFF_DH + 128;
constexpr int OFF_EXT = OFF_POS + 3072;
constexpr int OFF_XB = OFF_EXT + 1024, XPAD = G * 256;
static_assert(OFF_XB + XPAD + 1028 <= OFF_RING + 12 * STG && OFF_XB % 128 == 0 && OFF_BC + 544 <= OFF_TE && OFF_P2 % 1024 == 0 && OFF_SA % 1024 == 0 && SCAP * 64 >= 24576, "staging");
constexpr int BAR_DST = OFF_BAR, BAR_SRC = BAR_DST + 40, BAR_T = BAR_SRC + 24, BAR_W = BAR_T + 48, BAR_PS = BAR_W + 8, BAR_AW = BAR_PS + 8,
              BAR_QP = BAR_AW + 8, BAR_QR = BAR_QP + 8, BAR_HA = BAR_QR + 8, BAR_EP = BAR_HA + 8, BAR_AX = BAR_EP + 8, BAR_AI = BAR_AX + 8, BAR_HB = BAR_AI + 8, BAR_U = BAR_HB + 8, BAR_WH = BAR_U + 8, BAR_M = BAR_WH + 8, BAR_X = BAR_M + 24, BAR_END = BAR_X + 8;
static_assert(BAR_END <= OFF_BAR + 256, "barriers");
constexpr uint32_t QBYTES = 8u << 20;

__device__ __align__(256) uint4 g_xa[G * G * 8];
__device__ __align__(256) uint4 g_xb[G * G * 16];
__device__ __align__(256) uint2 g_xe[G * G * 32];
__device__ __align__(256) uint4 g_q[2 * QBYTES / 16];
__device__ __align__(256) uint32_t g_sync[8];
#define STAMP(k)

struct Maps { CUtensorMap m[6]; };
constexpr int TM_H = 0, TM_WE = 128, TM_WH = 256, TM_Q = 384, TM_XA = 512, TM_XB = 640;
struct Params {
  const int* dst; uint32_t* sync; int E, EPC, N, ctam; unsigned long long inv; uint32_t magic; int force_slow;
  const int* src; const uint16_t* pos; const uint4* ea; const uint16_t* we; const uint16_t* wx; char* q;
  const uint4* xa; const uint4* xb; uint2* xe; uint16_t* out; const uint4* h; const uint16_t* wh;
  int tune[10]; unsigned long long qcode;
};
template<int V> struct IC { static constexpr int value = V; };

#define R32(d) "+f"(d[0]),"+f"(d[1]),"+f"(d[2]),"+f"(d[3]),"+f"(d[4]),"+f"(d[5]),"+f"(d[6]),"+f"(d[7]),"+f"(d[8]),"+f"(d[9]),"+f"(d[10]),"+f"(d[11]),"+f"(d[12]),"+f"(d[13]),"+f"(d[14]),"+f"(d[15]),"+f"(d[16]),"+f"(d[17]),"+f"(d[18]),"+f"(d[19]),"+f"(d[20]),"+f"(d[21]),"+f"(d[22]),"+f"(d[23]),"+f"(d[24]),"+f"(d[25]),"+f"(d[26]),"+f"(d[27]),"+f"(d[28]),"+f"(d[29]),"+f"(d[30]),"+f"(d[31])
#define S32 "{%0,%1,%2,%3,%4,%5,%6,%7,%8,%9,%10,%11,%12,%13,%14,%15,%16,%17,%18,%19,%20,%21,%22,%23,%24,%25,%26,%27,%28,%29,%30,%31}"
#define DI __device__ __forceinline__

constexpr uint64_t DHI = ((uint64_t)(1024 >> 4) << 32) | (1ull << 62);
template<int SD> DI void rs64b(float (&d)[32], uint32_t a0, uint32_t a1, uint32_t a2, uint32_t a3, uint64_t db) {
  asm volatile("wgmma.mma_async.sync.aligned.m64n64k16.f32.bf16.bf16 " S32 ", {%32,%33,%34,%35}, %36, %37, 1, 1, 1;" : R32(d) : "r"(a0), "r"(a1), "r"(a2), "r"(a3), "l"(db), "n"(SD)); }
template<int SD> DI void rs64h(float (&d)[32], uint32_t a0, uint32_t a1, uint32_t a2, uint32_t a3, uint64_t db) {
  asm volatile("wgmma.mma_async.sync.aligned.m64n64k16.f32.f16.f16 " S32 ", {%32,%33,%34,%35}, %36, %37, 1, 1, 1;" : R32(d) : "r"(a0), "r"(a1), "r"(a2), "r"(a3), "l"(db), "n"(SD)); }
template<int SD> DI void ss64(float (&d)[32], uint64_t da, uint64_t db) {
  asm volatile("wgmma.mma_async.sync.aligned.m64n64k16.f32.bf16.bf16 " S32 ", %32, %33, %34, 1, 1, 0, 1;" : R32(d) : "l"(da), "l"(db), "n"(SD)); }
#define R16(d) "+f"(d[0]),"+f"(d[1]),"+f"(d[2]),"+f"(d[3]),"+f"(d[4]),"+f"(d[5]),"+f"(d[6]),"+f"(d[7]),"+f"(d[8]),"+f"(d[9]),"+f"(d[10]),"+f"(d[11]),"+f"(d[12]),"+f"(d[13]),"+f"(d[14]),"+f"(d[15])
#define S16 "{%0,%1,%2,%3,%4,%5,%6,%7,%8,%9,%10,%11,%12,%13,%14,%15}"
template<int SD> DI void rs32b(float (&d)[16], const uint32_t* a, uint64_t db) {
  asm volatile("wgmma.mma_async.sync.aligned.m64n32k16.f32.bf16.bf16 " S16 ", {%16,%17,%18,%19}, %20, %21, 1, 1, 1;" : R16(d) : "r"(a[0]), "r"(a[1]), "r"(a[2]), "r"(a[3]), "l"(db), "n"(SD)); }
DI void rs32h(float (&d)[16], const uint32_t* a, uint64_t db) {
  asm volatile("wgmma.mma_async.sync.aligned.m64n32k16.f32.f16.f16 " S16 ", {%16,%17,%18,%19}, %20, 1, 1, 1, 1;" : R16(d) : "r"(a[0]), "r"(a[1]), "r"(a[2]), "r"(a[3]), "l"(db)); }
DI void fence_regs(float (&d)[16]) { asm volatile("" : R16(d) :: "memory"); }
DI void trap_if(bool c) { asm volatile("{.reg .pred p; setp.eq.u32 p, %0, 0; @p bra.uni LT_%=; trap; LT_%=:}" :: "r"((uint32_t)c)); }
DI void wg_fence() { asm volatile("wgmma.fence.sync.aligned;" ::: "memory"); }
DI void wg_commit() { asm volatile("wgmma.commit_group.sync.aligned;" ::: "memory"); }
DI void wg_wait0() { asm volatile("wgmma.wait_group.sync.aligned 0;" ::: "memory"); }
DI void fence_regs(float (&d)[32]) { asm volatile("" : R32(d) :: "memory"); }
DI void proxy_fence() { asm volatile("fence.proxy.async.shared::cta;" ::: "memory"); }
DI uint64_t pol_first() { uint64_t r; asm("createpolicy.fractional.L2::evict_first.b64 %0, 1.0;" : "=l"(r)); return r; }
DI float tanh_ap(float x) { float y; asm("tanh.approx.f32 %0, %1;" : "=f"(y) : "f"(x)); return y; }
DI float silu_h(float y) { return fmaf(y, tanh_ap(y), y); }
DI uint32_t pack_bf16(float lo, float hi) { uint32_t r; asm("cvt.rn.bf16x2.f32 %0, %1, %2;" : "=r"(r) : "f"(hi), "f"(lo)); return r; }
DI uint32_t pack_f16(float lo, float hi) { uint32_t r; asm("cvt.rn.f16x2.f32 %0, %1, %2;" : "=r"(r) : "f"(hi), "f"(lo)); return r; }
DI float bf_lo(uint32_t v) { return __uint_as_float(v << 16); }
DI float bf_hi(uint32_t v) { return __uint_as_float(v & 0xFFFF0000u); }
DI uint32_t b2h(uint32_t v, float s) { return pack_f16(s * bf_lo(v), s * bf_hi(v)); }
DI void mbar_wait(uint32_t bar, uint32_t parity = 0) {
  asm volatile("{.reg .pred p, q; .reg .u32 c; mov.u32 c, 0;\n"
    "LW_%=: mbarrier.try_wait.parity.shared::cta.b64 p, [%0], %1;\n add.u32 c, c, 1; setp.lt.and.u32 q, c, 0x200000, !p;\n @q bra.uni LW_%=;}" :: "r"(bar), "r"(parity) : "memory");
}
DI void mbar_arrive(uint32_t bar, int p = 1) { asm volatile("{.reg .pred p; setp.ne.b32 p, %1, 0; @p mbarrier.arrive.shared::cta.b64 _, [%0];}" :: "r"(bar), "r"(p) : "memory"); }
DI void bar_sync(int id, int n) { asm volatile("bar.sync %0, %1;" :: "r"(id), "r"(n) : "memory"); }
DI void bar_arrive(int id, int n) { asm volatile("bar.arrive %0, %1;" :: "r"(id), "r"(n) : "memory"); }
DI __nv_bfloat162 b2(uint32_t v) { return *(__nv_bfloat162*)&v; }
DI uint32_t u2(__nv_bfloat162 v) { return *(uint32_t*)&v; }
DI uint32_t hsq(uint32_t v) { return u2(__hmul2(b2(v), b2(v))); }
DI uint32_t hsub(uint32_t a, uint32_t b) { return u2(__hsub2(b2(a), b2(b))); }
DI uint32_t hhalf(uint32_t v) { return u2(__hmul2(b2(v), __floats2bfloat162_rn(0.5f, 0.5f))); }
DI uint32_t mag2(uint32_t m, uint32_t v) { return __vmaxu2(m, v & 0x7FFF7FFFu); }
DI uint32_t hmag(uint32_t m, uint32_t v) { const __half2 r = __hmax2(*(const __half2*)&m, __habs2(*(const __half2*)&v)); return *(const uint32_t*)&r; }
DI uint32_t magr(uint32_t m) { return max(m & 0xFFFF, m >> 16); }
DI void sts128(uint32_t a, uint32_t x, uint32_t y, uint32_t z, uint32_t w) { asm volatile("st.shared.v4.u32 [%0], {%1,%2,%3,%4};" :: "r"(a), "r"(x), "r"(y), "r"(z), "r"(w) : "memory"); }
DI void sts64(uint32_t a, uint32_t x, uint32_t y) { asm volatile("st.shared.v2.u32 [%0], {%1,%2};" :: "r"(a), "r"(x), "r"(y) : "memory"); }
DI void sts32(uint32_t a, uint32_t x) { asm volatile("st.shared.u32 [%0], %1;" :: "r"(a), "r"(x) : "memory"); }
DI void sts16(uint32_t a, uint32_t x) { asm volatile("st.shared.u16 [%0], %1;" :: "r"(a), "h"((uint16_t)x) : "memory"); }
DI void lds128(uint32_t* v, uint32_t a) { asm volatile("ld.shared.v4.u32 {%0, %1, %2, %3}, [%4];" : "=r"(v[0]), "=r"(v[1]), "=r"(v[2]), "=r"(v[3]) : "r"(a) : "memory"); }
DI void lds64(uint32_t& x, uint32_t& y, uint32_t a) { asm volatile("ld.shared.v2.u32 {%0, %1}, [%2];" : "=r"(x), "=r"(y) : "r"(a) : "memory"); }
DI uint32_t lds32(uint32_t a) { uint32_t x; asm volatile("ld.shared.u32 %0, [%1];" : "=r"(x) : "r"(a) : "memory"); return x; }
DI uint32_t lds16(uint32_t a) { uint32_t x; asm volatile("ld.shared.u16 %0, [%1];" : "=r"(x) : "r"(a) : "memory"); return x; }
DI uint32_t atoms_add(uint32_t a, uint32_t v) { uint32_t r; asm volatile("atom.shared.add.u32 %0, [%1], %2;" : "=r"(r) : "r"(a), "r"(v) : "memory"); return r; }
DI void bulk_load(uint32_t dst, const void* src, uint32_t bytes, uint32_t bar) {
  asm volatile("cp.async.bulk.shared::cluster.global.mbarrier::complete_tx::bytes.L2::cache_hint [%0], [%1], %2, [%3], %4;" :: "r"(dst), "l"(src), "r"(bytes), "r"(bar), "l"(pol_first()) : "memory"); }
DI void mbar_expect(uint32_t bar, uint32_t bytes) { asm volatile("mbarrier.arrive.expect_tx.shared::cta.b64 _, [%0], %1;" :: "r"(bar), "r"(bytes) : "memory"); }
DI void mbar_init(uint32_t bar, int n) { asm volatile("mbarrier.init.shared::cta.b64 [%0], %1;" :: "r"(bar), "r"(n) : "memory"); }
DI void tma_load(uint32_t dst, uint64_t tm, int row, uint32_t bar) {
  asm volatile("cp.async.bulk.tensor.2d.shared::cluster.global.mbarrier::complete_tx::bytes.L2::cache_hint [%0], [%1, {%3, %4}], [%2], %5;" :: "r"(dst), "l"(tm), "r"(bar), "r"(0), "r"(row), "l"(pol_first()) : "memory"); }
DI void tma_store(uint64_t tm, int col, int row, uint32_t src) {
  asm volatile("cp.async.bulk.tensor.2d.global.shared::cta.bulk_group [%0, {%2, %3}], [%1];" :: "l"(tm), "r"(src), "r"(col), "r"(row) : "memory"); }
DI void bulk_commit() { asm volatile("cp.async.bulk.commit_group;" ::: "memory"); }
DI uint2 ld_poll2(const void* a) { uint2 v; asm volatile("ld.relaxed.gpu.global.v2.u32 {%0, %1}, [%2];" : "=r"(v.x), "=r"(v.y) : "l"(a) : "memory"); return v; }
DI void st_ext(uint2* a, uint32_t v, uint32_t ep) { asm volatile("st.relaxed.gpu.global.v2.u32 [%0], {%1, %2};" :: "l"(a), "r"(v), "r"(ep) : "memory"); }
DI uint32_t ext_get(const uint2* a, uint32_t ep) { uint2 v; int spin = 0; do { v = ld_poll2(a); trap_if(++spin > 4000000); } while (__any_sync(~0u, v.y != ep)); return v.x; }
DI void bulk_wait() { asm volatile("cp.async.bulk.wait_group 0;" ::: "memory"); }
DI void hint_signal(uint32_t* c) { asm volatile("red.relaxed.gpu.global.add.u32 [%0], 1;" :: "l"(c) : "memory"); }
DI void hint_wait(const uint32_t* c, uint32_t target) { uint32_t v; int spin = 0;
  do { asm volatile("ld.relaxed.gpu.global.u32 %0, [%1];" : "=r"(v) : "l"(c) : "memory"); trap_if(++spin > 4000000); } while (__any_sync(~0u, (int)(v - target) < 0)); }
DI void stsm4(uint32_t a, uint32_t x, uint32_t y, uint32_t z, uint32_t w) { asm volatile("stmatrix.sync.aligned.m8n8.x4.shared.b16 [%0], {%1,%2,%3,%4};" :: "r"(a), "r"(x), "r"(y), "r"(z), "r"(w) : "memory"); }
DI void ldsm4(uint32_t* v, uint32_t a) { asm volatile("ldmatrix.sync.aligned.m8n8.x4.shared.b16 {%0,%1,%2,%3}, [%4];" : "=r"(v[0]), "=r"(v[1]), "=r"(v[2]), "=r"(v[3]) : "r"(a) : "memory"); }
DI void ldsm4t(uint32_t* v, uint32_t a) { asm volatile("ldmatrix.sync.aligned.m8n8.x4.trans.shared.b16 {%0,%1,%2,%3}, [%4];" : "=r"(v[0]), "=r"(v[1]), "=r"(v[2]), "=r"(v[3]) : "r"(a) : "memory"); }
DI uint32_t mad16(uint32_t x, uint32_t m, uint32_t c) { uint32_t r; asm("dp2a.lo.u32.u32 %0, %1, %2, %3;" : "=r"(r) : "r"(x), "r"(m), "r"(c)); return r; }
DI bool wbad(uint32_t m, uint32_t hi) { return m > hi || (m && m < 0x3980); }

__device__ __noinline__ void slow_path(const Params& p, int wid, int lane, int node0, int nloc) {
  const uint32_t ab = sb + OFF_P2 + wid * 8704;
  for (int i = lane; i < 32 * 68; i += 32) sts32(ab + i * 4, 0);
  __syncwarp();
  const uint32_t wdv = __ldg((const uint32_t*)(p.we + 128 * 64) + lane), wxv = __ldg((const uint32_t*)p.wx + lane);
  const int nb0 = node0 + wid * 32, cntn = max(0, min(32, nloc - wid * 32));
  auto dot = [&](uint32_t hv, const uint16_t* w, int K2, float& y0, float& y1) {
#pragma unroll 4
    for (int k = 0; k < K2; k++) {
      const uint32_t hk = __shfl_sync(~0u, hv, k), wa = __ldg((const uint32_t*)(w + 2 * k * 64) + lane), wb = __ldg((const uint32_t*)(w + (2 * k + 1) * 64) + lane);
      y0 = fmaf(bf_lo(hk), bf_lo(wa), fmaf(bf_hi(hk), bf_lo(wb), y0)); y1 = fmaf(bf_lo(hk), bf_hi(wa), fmaf(bf_hi(hk), bf_hi(wb), y1));
    }
  };
  auto silu = [](float x) { return x / (1.f + __expf(-x)); };
#pragma unroll 1
  for (int base = 0; base < p.E; base += 32) {
    const int e = base + lane;
    const uint32_t dl = e < p.E ? (uint32_t)(__ldg(p.dst + e) - nb0) : 0xFFFFFFFFu;
    uint32_t mk = __ballot_sync(~0u, dl < (uint32_t)cntn);
    while (mk) {
      const int l = __ffs(mk) - 1; mk &= mk - 1;
      const int ee = base + l, n = __shfl_sync(~0u, dl, l), s = __ldg(p.src + ee);
      const uint16_t *po = p.pos + (size_t)(nb0 + n) * 3, *pp = p.pos + (size_t)s * 3;
      const uint32_t dxy = hsub(__ldg(po) | (__ldg(po + 1) << 16), __ldg(pp) | (__ldg(pp + 1) << 16)), dz = hsub(__ldg(po + 2), __ldg(pp + 2));
      const uint32_t sq = hsq(dxy); const float d2 = bf_lo(sq) + bf_hi(sq) + bf_lo(hsq(dz));
      float y0 = d2 * bf_lo(wdv), y1 = d2 * bf_hi(wdv);
      dot(__ldg((const uint32_t*)(p.h + (size_t)(nb0 + n) * 8) + lane), p.we, 32, y0, y1);
      dot(__ldg((const uint32_t*)(p.h + (size_t)s * 8) + lane), p.we + 64 * 64, 32, y0, y1);
      dot(__ldg((const uint32_t*)(p.ea + (size_t)ee * 2) + (lane & 7)), p.we + 129 * 64, 8, y0, y1);
      const uint32_t mm = pack_bf16(silu(y0), silu(y1));
      float c = bf_lo(mm) * bf_lo(wxv) + bf_hi(mm) * bf_hi(wxv);
#pragma unroll
      for (int o = 16; o; o >>= 1) c += __shfl_xor_sync(~0u, c, o);
      const uint32_t a = ab + n * 272;
      uint32_t x0, x1; lds64(x0, x1, a + lane * 8);
      sts64(a + lane * 8, __float_as_uint(__uint_as_float(x0) + bf_lo(mm)), __float_as_uint(__uint_as_float(x1) + bf_hi(mm)));
      if (lane < 3) { const float df = lane == 0 ? bf_lo(dxy) : lane == 1 ? bf_hi(dxy) : bf_lo(dz); sts32(a + 256 + lane * 4, __float_as_uint(fmaf(c, df, __uint_as_float(lds32(a + 256 + lane * 4))))); }
    }
  }
  __syncwarp();
#pragma unroll 1
  for (int n = 0; n < cntn; n++) {
    uint32_t x0, x1; lds64(x0, x1, ab + n * 272 + lane * 8);
    const uint32_t hv = __ldg((const uint32_t*)(p.h + (size_t)(nb0 + n) * 8) + lane);
    float y0 = 0.f, y1 = 0.f;
    dot(hv, p.wh, 32, y0, y1); dot(pack_bf16(__uint_as_float(x0), __uint_as_float(x1)), p.wh + 64 * 64, 32, y0, y1);
    ((uint32_t*)p.out)[(size_t)(nb0 + n) * 32 + lane] = u2(__hadd2(b2(hv), b2(pack_bf16(silu(y0), silu(y1)))));
    if (lane < 3) p.out[(size_t)p.N * 64 + (size_t)(nb0 + n) * 3 + lane] = (uint16_t)pack_bf16(bf_lo(__ldg(p.pos + (size_t)(nb0 + n) * 3 + lane)) + __uint_as_float(lds32(ab + n * 272 + 256 + lane * 4)), 0.f);
  }
}

__global__ void __launch_bounds__(NTHR, 1) egnn_kernel(const __grid_constant__ Params p, const __grid_constant__ Maps maps) {
  extern __shared__ __align__(1024) unsigned char smraw[];
  const int tid = threadIdx.x, cta = blockIdx.x * CTAM % G;
  const int e0 = cta * p.EPC, n4 = max(0, min(p.EPC, p.E - e0)) >> 2;
  STAMP(0);
  asm volatile("{.reg .pred p; setp.lt.s32 p, %1, %2; setp.lt.and.s32 p, %3, %4, p; @p prefetch.global.L2 [%0];}" :: "l"(p.dst + e0 + tid * 32), "r"(tid), "n"(64), "r"(e0 + tid * 32), "r"(p.E));
  if (tid == NWK) {
#pragma unroll 1
    for (int k = 0; k < NCH; k++) { const int nb = max(0, min(NWK, n4 - k * NWK)) * 16;
      mbar_init(sb + BAR_DST + k * 8, 1);
      asm volatile("fence.mbarrier_init.release.cluster;" ::: "memory");
      mbar_expect(sb + BAR_DST + k * 8, nb);
      if (nb) bulk_load(sb + OFF_DST + k * NWK * 16, (const char*)(p.dst + e0) + k * NWK * 16, nb, sb + BAR_DST + k * 8); }
  }
  const int lane = tid & 31, wid = __shfl_sync(~0u, tid >> 5, 0), w = wid & 3;
  asm volatile("{.reg .pred p; setp.eq.u32 p, %2, 384; @p cp.async.cg.shared.global [%0], [%1], 16;}" :: "r"(sb + OFF_LEN - 192 + (tid >> 1)), "l"(p.sync), "r"(tid & 415) : "memory");
  if (__shfl_sync(~0u, tid, 1) - 384u < 96u) {
    asm volatile("cp.async.wait_all;" ::: "memory");
    __syncwarp();
    const uint32_t e = lds32(sb + OFF_LEN + 8 + w * 16) + 1, v = (((1 + e % 3) << 14) + 512 + (lane & 7) * 4) * 0x10001u;
    if (tid == 384) sts32(sb + OFF_MISC + 32, e);
#pragma unroll 1
    for (int i = 0; i < 12; i++) sts128(sb + OFF_SA - 6144 + tid * 16 + i * 1536, v, v + 0x10001u, v + 0x20002u, v + 0x30003u);
    bar_sync(6, 480);
    mbar_arrive(sb + BAR_EP, lane == 0);
  }
  asm volatile("pmevent 1;" ::: "memory");
  uint64_t tmb; asm volatile("mov.u64 %0, %1;" : "=l"(tmb) : "l"(&maps));

  auto first_node = [&](int c) { return (int)((c * p.inv + 0xFFFFFFFFull) >> 32); };
  const int node0 = first_node(cta), nloc = min(first_node(cta + 1), p.N) - node0;
  const uint32_t ealo = (uint32_t)(uint64_t)p.ea;
  const int epad = min(e0, p.E - 1);
  if (wid >= 12) {
    const int t = tid - 384;
    auto load_h = [&](int b) { mbar_expect(sb + BAR_T + b * 8, 8192); tma_load(sb + OFF_H + b * 8192, tmb + TM_H, node0 + b * 64, sb + BAR_T + b * 8); };
    uint32_t pv[9], ev = 0;
#pragma unroll
    for (int i = 0; i < 3; i++) { const uint16_t* pp = p.pos + (size_t)(node0 + t + 128 * i) * 3;
      pv[3 * i] = pv[3 * i + 1] = pv[3 * i + 2] = 0;
      asm volatile("{.reg .pred p; setp.lt.s32 p, %4, %5;\n @p ld.global.nc.u16 %0, [%3];\n @p ld.global.nc.u16 %1, [%3+2];\n @p ld.global.nc.u16 %2, [%3+4];}"
        : "+r"(pv[3 * i]), "+r"(pv[3 * i + 1]), "+r"(pv[3 * i + 2]) : "l"(pp), "r"(t + 128 * i), "r"(p.N - node0)); }
    asm volatile("{.reg .pred p; setp.lt.u32 p, %3, 8; @p ld.global.nc.u32 %0, [%1]; @p st.global.v4.u32 [%2], {%4, %4, %4, %4};}"
      : "+r"(ev) : "l"((const uint32_t*)(p.ea + (size_t)epad * 2) + t), "l"(p.q + (size_t)(p.N + cta * PADM) * 128 + t * 16), "r"(t), "r"(0xF700F700u) : "memory");
    asm volatile("cp.async.wait_all;" ::: "memory");
    __syncwarp();
    const uint32_t e = lds32(sb + OFF_LEN + 8 + w * 16) + 1;
    { const uint32_t tg = (1 + e % 3) << 30;
#pragma unroll
      for (int i = 0; i < 17; i++) sts128(sb + OFF_SB + t * 16 + i * 2048, tg, tg, tg, tg); }
    uint32_t mp = 0;
#pragma unroll
    for (int i = 0; i < 3; i++) { sts64(sb + OFF_POS + (t + 128 * i) * 8, pv[3 * i] | (pv[3 * i + 1] << 16), pv[3 * i + 2]); mp = mag2(mag2(mp, pv[3 * i] | (pv[3 * i + 1] << 16)), pv[3 * i + 2]); }
    proxy_fence();
    if (w == 3) bar_sync(14, 416);
    __syncwarp();
    mbar_arrive(sb + BAR_PS, lane == 0);
    mbar_wait(sb + BAR_W);
    {
      uint32_t v[4], u[4]; const int r = t >> 3, c = t & 7;
      lds128(v, sb + OFF_WS + 128 + t * 16); lds128(u, sb + OFF_WS + c * 16);
      const uint32_t x = lds32(sb + OFF_WS + 2176 + lane * 4);
      sts128(sb + OFF_W3 + r * 128 + ((c ^ (r & 7)) << 4), b2h(v[0], .5f), b2h(v[1], .5f), b2h(v[2], .5f), b2h(v[3], .5f));
      const float s = ((r & 1) || r == 6) ? 0.f : .5f;
      if (t < 64) sts128(sb + OFF_WD + r * 128 + ((c ^ r) << 4), b2h(u[0], s), b2h(u[1], s), b2h(u[2], s), b2h(u[3], s));
      if (t < 32) sts32(sb + OFF_WX + (t & 3) * 32 + (t >> 2) * 4, b2h(x, 1.f));
      const uint32_t m3 = __reduce_max_sync(~0u, magr(mag2(mag2(mag2(mag2(0, v[0]), v[1]), v[2]), v[3]))), md = __reduce_max_sync(~0u, magr(mag2(mag2(mag2(mag2(0, u[0]), u[1]), u[2]), u[3])));
      if (wbad(m3, 0x4000) || wbad(md, 0x4000) || wbad(__reduce_max_sync(~0u, magr(mag2(0, x))), 0x4700) || magr(mp) >= 0x4200 || magr(mag2(0, ev)) >= 0x4380) sts32(sb + OFF_MISC + 8, 1);
    }
    if (w == 1) {
#pragma unroll 1
      for (int b = 0; b < 3; b++) { mbar_wait(sb + BAR_SRC + b * 8); if (lane == 0) load_h(b); }
    }
    bar_sync(3, 128);
    const uint32_t frag = (w * 16 + (lane & 15)) * 128 + (((lane >> 4) ^ (lane & 7)) << 4);
    uint32_t mq = 0; int pfi = 0;
    auto prefetch_e = [&]() {
      const uint32_t nb = PFB;
      if (lane == 0 && nb) asm volatile("cp.async.bulk.prefetch.L2.global [%0], %1;" :: "l"((const char*)p.ea + (size_t)(pfi * G + cta) * nb), "r"(nb) : "memory");
      pfi++; };
#pragma unroll 1
    for (int b = 0; b < 6; b++) {
      float acc[32];
      const uint64_t da = DHI | (((sb + OFF_H) >> 4) + b * 512), db = DHI | ((sb + OFF_W) >> 4);
      const uint32_t v0 = lds16(sb + OFF_POS + b * 512 + w * 128 + lane * 2), v1 = lds16(sb + OFF_POS + 64 + b * 512 + w * 128 + lane * 2);
      mbar_wait(sb + BAR_T + b * 8);
      if (b == 0) STAMP(25);
      if (b == 5) STAMP(26);
      wg_fence();
      ss64<0>(acc, da, db); ss64<1>(acc, da + 2, db + 128); ss64<1>(acc, da + 4, db + 256); ss64<1>(acc, da + 6, db + 384);
      wg_commit();
      if (b == 0) mbar_wait(sb + BAR_AW);
      if (t == 32 && b < 2) { load_h(b * 2 + 3); if (!b) load_h(4); }
      if (w == 1) for (int k = PFE >> (4 * b) & 15; k > 0; k--) prefetch_e();
      __syncwarp();
      uint32_t ff[6], fg[6];
#pragma unroll
      for (int j = 0; j < 6; j++) { ff[j] = (__byte_perm((j & 1) ? v1 : v0, 0, 0x4140) >> (3 * (j >> 1))) & 0x00070007u; fg[j] = __vsub2(0x00040004u, ff[j]);
        asm volatile("" : "+r"(ff[j]), "+r"(fg[j])); }
      wg_wait0(); fence_regs(acc);
      uint32_t o[16];
#pragma unroll
      for (int j = 0; j < 16; j++) o[j] = pack_f16(.5f * acc[2 * j], .5f * acc[2 * j + 1]);
#pragma unroll
      for (int j = 0; j < 6; j++) {
        const uint32_t m = o[j] & 0x7FFF7FFFu; mq = __vmaxu2(mq, m);
        o[j] = (__viaddmax_s16x2(m, fg[j], 0) & 0xFFF8FFF8u) | ff[j] | (o[j] & 0x80008000u); }
      if (b == 4) mbar_wait(sb + BAR_AX);
      const uint32_t qs = sb + OFF_SA + b * 8192;
#pragma unroll
      for (int j = 0; j < 4; j++) stsm4((qs + frag) ^ (j << 5), o[4 * j], o[4 * j + 1], o[4 * j + 2], o[4 * j + 3]);
      proxy_fence();
      __syncwarp();
      if (lane == 0 && b * 64 + w * 16 < nloc) tma_store(tmb + TM_Q, 0, node0 + b * 64 + w * 16, qs + w * 2048);
    }
    if (lane == 0) bulk_commit();
    { const uint32_t m = __reduce_max_sync(~0u, magr(mq)); if (lane == 0) sts32(sb + OFF_MISC + 16 + w * 4, m); }
    asm volatile("setmaxnreg.dec.sync.aligned.u32 56;");
    bulk_wait();
    bar_sync(3, 128);
    if (w == 0) {
      STAMP(18);
      uint32_t mv[4]; lds128(mv, sb + OFF_MISC + 16);
      const uint32_t mx = max(max(mv[0], mv[1]), max(mv[2], mv[3]));
      mbar_arrive(sb + BAR_QR, lane == 0);
      STAMP(19);
      if (lane == 0) {
        if (nloc > 0 && (mx >= 0x7BF0 || mx < 0x1400)) asm volatile("st.relaxed.gpu.global.u32 [%0+4], %1;" :: "l"(p.sync), "r"(e) : "memory");
        asm volatile("red.release.gpu.global.add.u32 [%0], 1;" :: "l"(p.sync) : "memory");
      }
      __syncwarp();
      uint32_t c, f; int spin = 0;
      do { asm volatile("ld.acquire.gpu.global.v2.u32 {%0, %1}, [%2];" : "=r"(c), "=r"(f) : "l"(p.sync) : "memory"); trap_if(++spin > 4000000); } while (__any_sync(~0u, (int)(c - e * G) < 0));
      if (f == e) sts32(sb + OFF_MISC + 8, 1);
      if (cta == 0 && lane == 0) asm volatile("st.relaxed.gpu.global.u32 [%0+8], %1;" :: "l"(p.sync), "r"(e) : "memory");
      STAMP(20);
      __syncwarp();
      mbar_arrive(sb + BAR_QP, lane == 0);
    }
    if (w == 2) {
      const uint32_t tg = (1 + e % 3) << 30;
      hint_wait(p.sync + 5, e * G);
      if (lane == 0) { mbar_expect(sb + BAR_HB, XPAD);
#pragma unroll 1
        for (int o = 0; o < 4; o++) bulk_load(sb + OFF_XB + o * (G * 64), (const char*)p.xb + (size_t)(cta * 4 + o) * (G * 64), G * 64, sb + BAR_HB); }
      STAMP(21);
      bar_sync(7, 384);
      sts32(sb + OFF_XB + XPAD, tg + p.N + cta * PADM);
      const uint32_t nx = __shfl_sync(~0u, lds32(sb + OFF_MISC + 8) ? 0 : lds32(sb + OFF_MISC + 4), 0);
#pragma unroll 1
      for (uint32_t k = 0; k < nx; k += 32) {
        const uint32_t i = min(k + lane, nx - 1), xr = lds32(sb + OFF_EXT + i * 4), row = (xr >> 9) & 255;
        const uint32_t v = ext_get(p.xe + (cta * G + row) * 32 + ((xr >> 17) & 31), e), x = lds32(sb + OFF_CNT + (xr & 511) * 4) + (xr >> 22) * 16;
        sts32(sb + OFF_XB + XPAD + 4 + i * 4, v); sts16(sb + OFF_TS + x, XPAD + 4 + i * 4);
        sts32(sb + OFF_TE + x * 2, mad16(v, 0x2000u, ealo - (tg >> 11) + row * p.EPC * 32));
      }
      __syncwarp();
      mbar_arrive(sb + BAR_HB, lane == 0);
    }
    if (w == 1) {
#pragma unroll 1
      while (pfi < PFN) { prefetch_e(); __nanosleep(PFNS); }
    }
    if (t == 96) { mbar_expect(sb + BAR_U, 8192); tma_load(sb + OFF_W, tmb + TM_WH, 0, sb + BAR_U); }
    __syncwarp();
    bar_sync(4, NTHR);
    const bool fast = !__shfl_sync(~0u, lds32(sb + OFF_MISC + 8), 0);
    if (fast) {
      mp = 0;
#pragma unroll 1
      for (uint32_t todo = UORD; todo; todo >>= 4) {
        const uint32_t nd = lds16(sb + OFF_GP + (todo & 3) * 1024 + w * 256 + (lane & 15) * 8 + 134), hb = (todo >> 3) & 1;
        const uint64_t b1 = DHI | (((sb + OFF_W + 8192) >> 4) + hb * 4);
        uint32_t f[8]; float acc[16];
#pragma unroll
        for (int j = 0; j < 4; j += 2) {
          const uint32_t a = (sb + OFF_H + nd * 128 + (((nd & 7) << 4) ^ (lane & 16))) ^ (j << 5);
          ldsm4(f, a); ldsm4(f + 4, a ^ 32);
          wg_fence();
          if (j == 0) rs32b<0>(acc, f, b1); else rs32b<1>(acc, f, b1 + 256);
          rs32b<1>(acc, f + 4, b1 + 128 * j + 128);
          wg_commit(); wg_wait0(); fence_regs(acc);
        }
#pragma unroll
        for (int j = 0; j < 8; j++) { f[j] = pack_f16(.5f * acc[2 * j], .5f * acc[2 * j + 1]); mp = hmag(mp, f[j]); }
        const uint32_t a = (sb + OFF_P2 + (todo & 3) * 8192 + frag) ^ (hb << 6);
        stsm4(a, f[0], f[1], f[2], f[3]); stsm4(a ^ 32, f[4], f[5], f[6], f[7]);
      }
      if (magr(mp) >= 0x7000) sts32(sb + OFF_MISC + 12, 1);
    }
    bar_sync(3, 128);
    if (t == 96) { mbar_expect(sb + BAR_U, 8192); tma_load(sb + OFF_W + 8192, tmb + TM_WH, 64, sb + BAR_U); }
    __syncwarp();
    mbar_wait(sb + BAR_U);
    uint32_t mh = 0;
#pragma unroll 1
    for (int i = t; i < 1024; i += 128) {
      uint32_t v[4]; const uint32_t r = (i >> 3) & 7, j = (i ^ r) & 7;
#pragma unroll
      for (int k = 0; k < 4; k++) v[k] = lds32(sb + OFF_W + (i >> 3) * 128 + ((((j & 4) + k) ^ r) << 4) + (j & 3) * 4);
      __syncwarp();
      if (i < 512) sts128(sb + OFF_W + i * 16, hhalf(v[0]), hhalf(v[1]), hhalf(v[2]), hhalf(v[3]));
      else { sts128(sb + OFF_W + i * 16, b2h(v[0], .5f), b2h(v[1], .5f), b2h(v[2], .5f), b2h(v[3], .5f)); mh = mag2(mag2(mag2(mag2(mh, v[0]), v[1]), v[2]), v[3]); } }
    if (wbad(__reduce_max_sync(~0u, magr(mh)), 0x4700)) sts32(sb + OFF_MISC + 12, 1);
    proxy_fence();
    __syncwarp();
    mbar_arrive(sb + BAR_WH, lane == 0);
    if (fast) {
      mbar_wait(sb + BAR_WH);
      float chk = 0.f;
#pragma unroll 1
      for (uint32_t todo = UORD; todo; todo >>= 4) {
        const uint32_t nd = lds16(sb + OFF_GP + (todo & 3) * 1024 + w * 256 + (lane & 15) * 8 + 6), hb = (todo >> 3) & 1;
        const uint64_t b1 = DHI | (((sb + OFF_W) >> 4) + hb * 4);
        uint32_t f[8]; float acc[16];
#pragma unroll
        for (int j = 0; j < 8; j += 2) {
          const uint32_t a = j < 4 ? sb + OFF_H + nd * 128 + (((nd & 7) << 4) ^ (lane & 16)) : sb + OFF_P2 + (todo & 3) * 8192 + frag;
          if (j == 4) mbar_wait(sb + BAR_M + (todo & 3) * 8);
          ldsm4(f, a ^ ((j & 3) << 5)); ldsm4(f + 4, a ^ ((j & 3) << 5) ^ 32);
          wg_fence();
          if (j == 0) rs32b<0>(acc, f, b1); else if (j < 4) rs32b<1>(acc, f, b1 + 128 * j); else rs32h(acc, f, b1 + 128 * j);
          if (j < 4) rs32b<1>(acc, f + 4, b1 + 128 * j + 128); else rs32h(acc, f + 4, b1 + 128 * j + 128);
          wg_commit(); wg_wait0(); fence_regs(acc);
        }
        chk = fmaf(acc[0], 0.f, fmaf(acc[2], 0.f, chk));
#pragma unroll
        for (int k = 0; k < 2; k++) {
          const uint32_t o = __shfl_sync(~0u, nd, (lane >> 2) + 8 * k) * 128 + (lane & 3) * 16 + hb * 64;
          uint32_t x[4]; lds128(x, sb + OFF_H + (o ^ ((o >> 3) & 0x70)));
#pragma unroll
          for (int i = 0; i < 4; i++) x[i] = u2(__hadd2(b2(x[i]), b2(pack_bf16(silu_h(acc[4 * i + 2 * k]), silu_h(acc[4 * i + 2 * k + 1])))));
          if (o < nloc * 128) *(uint4*)((char*)p.out + (size_t)node0 * 128 + o) = make_uint4(x[0], x[1], x[2], x[3]);
        }
        __nanosleep(DEFNS);
      }
      uint32_t pa_[9];
#pragma unroll
      for (int k = 0; k < 9; k++) { const uint32_t i = t + 128 * k, n = (i * 43691u) >> 17; pa_[k] = lds16(sb + OFF_INV + n * 2) + (i - 3 * n) * 2; }
      uint16_t* po = p.out + (size_t)p.N * 64 + node0 * 3 + t;
      mbar_wait(sb + BAR_X);
#pragma unroll
      for (int k = 0; k < 9; k++) pa_[k] = lds16(sb + OFF_GP + pa_[k]);
#pragma unroll
      for (int k = 0; k < 9; k++) if (t + 128 * k < nloc * 3) po[128 * k] = pa_[k];
      asm volatile("{.reg .pred p, q; setp.neu.f32 p, %0, 0f00000000; bar.red.or.pred q, 5, 512, p;}" :: "f"(chk) : "memory");
    }
    return;
  }

  if (tid == 320) {
    mbar_init(sb + BAR_W, 1);
    asm volatile("fence.mbarrier_init.release.cluster;" ::: "memory");
    mbar_expect(sb + BAR_W, 2 * 8192 + 2304);
    tma_load(sb + OFF_W, tmb + TM_WE, 64, sb + BAR_W); tma_load(sb + OFF_W + 8192, tmb + TM_WE, 0, sb + BAR_W);
    bulk_load(sb + OFF_WS, p.we + 128 * 64, 2176, sb + BAR_W); bulk_load(sb + OFF_WS + 2176, p.wx, 128, sb + BAR_W);
  }
  if (tid == 288) {
#pragma unroll
    for (int a = BAR_SRC; a < BAR_END; a += 8) if (a != BAR_W) mbar_init(sb + a, a == BAR_X ? 12 : a >= BAR_WH || a == BAR_PS ? 4 : a == BAR_EP ? 3 : a == BAR_HB || a == BAR_U ? 2 : 1);
    asm volatile("fence.mbarrier_init.release.cluster;" ::: "memory");
    asm volatile("prefetch.tensormap [%0];" :: "l"(tmb + TM_XA)); asm volatile("prefetch.tensormap [%0];" :: "l"(tmb + TM_H));
    asm volatile("prefetch.tensormap [%0];" :: "l"(tmb + TM_XB)); asm volatile("prefetch.tensormap [%0];" :: "l"(tmb + TM_Q));
  }
  {
    if (tid < 144) sts128(sb + OFF_CNT + tid * 16, 0, 0, 0, 0);
    else if (tid <= 144 + G) sts32(sb + OFF_BC + (tid - 144) * 4, ((tid - 144) & 31) * 4);
    const uint32_t sp = XPAD * 0x10001u, em = first_node(G);
    if (wid < 7) {
#pragma unroll
      for (int i = 0; i < 4; i++) sts128(sb + OFF_TS + tid * 16 + i * 3584, sp, sp, sp, sp);
    }
    static_assert(SCAP * 32 == 4 * 3584, "fill");
#pragma unroll 1
    for (int i = n4 + tid; i < 1536; i += 384) sts128(sb + OFF_DST + i * 16, em, em, em, em);
    if (tid == 321) sts128(sb + OFF_MISC, 0, 0, p.force_slow, 0);
  }
  bar_arrive(6, 480);
  bar_arrive(14, 416);
  bar_sync(0, 384);
  uint32_t ep, tag, eb0, pk[12], r0[12], r1[12], cb;
  uint2 vb[12];
  auto get_tag = [&]() { mbar_wait(sb + BAR_EP); ep = lds32(sb + OFF_MISC + 32); tag = (1 + ep % 3) << 30; eb0 = ealo - (tag >> 11); };
  if (wid == 11) {
    trap_if(sb != (uint32_t)__cvta_generic_to_shared(smraw));
#pragma unroll 1
    for (int k = 0; k < 3; k++) { const int nb = max(0, min(8192, n4 * 16 - k * 8192));
      mbar_wait(sb + BAR_DST + (k ? k + 1 : 0) * 8);
      if (lane == 0) { mbar_expect(sb + BAR_SRC + k * 8, nb);
        if (nb) bulk_load(sb + OFF_SRCI + k * 8192, (const char*)(p.src + e0) + k * 8192, nb, sb + BAR_SRC + k * 8); } }
    proxy_fence();
    get_tag();
    mbar_wait(sb + BAR_PS);
    bar_sync(12, 384);
    uint32_t xm = 0;
#pragma unroll
    for (int k = 0; k < 5; k++) xm |= (lds32(sb + OFF_BC + min(lane + 32 * k, G - 1) * 4) >= (65 << 9) && lane + 32 * k < G) << k;
    auto ext_send = [&](int pl) {
      uint32_t x = xm;
      for (uint32_t m; (m = __ballot_sync(~0u, x));) {
        const uint32_t l = __ffs(m) - 1, j = l + 32 * (__ffs(__shfl_sync(~0u, x, l)) - 1);
        if (lane == l) x &= x - 1;
        const uint32_t e = min(lds16(sb + OFF_AX + j * 128 + ((4 * l + 2 * lane) & 126)), 6143u);
        if (pl) st_ext(p.xe + (j * G + cta) * 32 + lane, lds32(sb + OFF_SRCI + e * 4) + tag + (e << 16), ep);
        else { const uint32_t cn = lds32(sb + OFF_BC + j * 4) >> 9, v = cn > 96 ? 1 : lane + 64 < cn ? 512 | (lds32(sb + OFF_DST + e * 4) & 511) : 0;
          asm volatile("red.shared.xor.b32 [%0], %1;" :: "r"(sb + OFF_SA + j * 128 + ((l + lane) & 31) * 4), "r"(((v & 63) << 10) | ((v >> 6) << 26)) : "memory"); }
      }
    };
    if (__any_sync(~0u, xm)) { ext_send(0); proxy_fence(); __syncwarp(); }
    if (lane == 0) { tma_store(tmb + TM_XA, cta * 64, 0, sb + OFF_SA); bulk_commit(); mbar_arrive(sb + BAR_AI); bulk_wait(); hint_signal(p.sync + 4); mbar_arrive(sb + BAR_AW); STAMP(16); }
    __syncwarp();
    bar_sync(13, 384);
    ext_send(1);
    mbar_arrive(sb + BAR_AX, lane == 0);
    mbar_wait(sb + BAR_HA);
    mbar_wait(sb + BAR_T + BT * 8);
    __nanosleep(BDEL);
    if (lane == 0) {
#pragma unroll 1
      for (int k = 0; k < G / BROWS; k++) { const int r = (k + cta) % (G / BROWS) * BROWS; tma_store(tmb + TM_XB, cta * 64, r, sb + OFF_SB + r * 256); bulk_commit(); bulk_wait(); }
      hint_signal(p.sync + 5);
      STAMP(17);
    }
    __syncwarp();
  } else {
    {
      uint32_t d[4 * NCH], jj[4 * NCH], rr[4 * NCH];
      auto count = [&](int k) {
        mbar_wait(sb + BAR_DST + k * 8);
        lds128(d + 4 * k, sb + OFF_DST + (tid + NWK * k) * 16);
#pragma unroll
        for (int i = 4 * k; i < 4 * k + 4; i++) { jj[i] = d[i] * p.magic; rr[i] = atoms_add(__dp4a(jj[i], 0x04000000u, sb + OFF_BC), 0x202u); }
      };
      auto place = [&](int k) {
#pragma unroll
        for (int i = 4 * k; i < 4 * k + 4; i++) {
          const uint32_t o = __dp4a(jj[i], 0x80000000u, rr[i] & 0x807Eu);
          d[i] = (d[i] & 511) | (tag >> 16);
          asm("{.reg .pred p; setp.ge.u32 p, %1, 0x8000; @p add.u32 %0, %2, %3;}" : "+r"(d[i]) : "r"(o), "r"(tid * 4), "r"(NWK * k * 4 + (i & 3)));
          sts16(sb + OFF_SA + o, d[i]); jj[i] = __viaddmin_u32(o, o, G * 256);
        }
      };
      count(0); STAMP(1); count(1); get_tag(); place(0); count(2); place(1); count(3); place(2);
      if (wid < 4) { count(4); STAMP(15); place(3); place(4); } else place(3);
      proxy_fence();
      bar_arrive(12, 384);
      STAMP(2);
      mbar_wait(sb + BAR_AI);
      mbar_wait(sb + BAR_SRC); mbar_wait(sb + BAR_SRC + 8); mbar_wait(sb + BAR_SRC + 16);
      STAMP(12);
#pragma unroll
      for (int k = 0; k < NCH; k++) lds128(d + 4 * k, sb + OFF_SRCI + (tid + NWK * k) * 16);
      const uint32_t tb = tag + (tid << 18);
#pragma unroll
      for (int i = 0; i < 4 * NCH; i++) if (i < 4 * NCH - 4 || wid < 4) sts32(sb + OFF_SB + jj[i], d[i] + tb + ((NWK * (i >> 2) * 4 + (i & 3)) << 16));
      proxy_fence();
      bar_arrive(13, 384);
      STAMP(3);
    }
    const uint32_t rot = (lane + cta) & 31;
    cb = sb + OFF_CNT - (tag >> 14);
    {
      const uint32_t* xa = (const uint32_t*)(p.xa + (cta * G + wid) * 8) + rot;
      if (wid < 8) { const uint32_t e_ = ealo + epad * 32;
        mbar_wait(sb + BAR_AX);
#pragma unroll
        for (int i = 0; i < 7; i++) sts128(sb + OFF_TE + tid * 16 + i * 4096, e_, e_, e_, e_); }
      static_assert(SCAP * 64 == 7 * 4096, "fill");
      if (wid == 10) { hint_wait(p.sync + 4, ep * G); mbar_arrive(sb + BAR_HA, lane == 0); }
      mbar_wait(sb + BAR_HA);
      STAMP(14);
      const uint32_t tp = tag | (tag >> 16);
      uint32_t st;
#pragma unroll 1
      for (int spin = 0;; spin++) {
        st = 0;
#pragma unroll
        for (int k = 0; k < 12; k++) asm volatile("ld.relaxed.gpu.global.u32 %0, [%1];" : "=r"(pk[k]) : "l"(xa + k * 352) : "memory");
#pragma unroll
        for (int k = 0; k < 12; k++) st |= pk[k] ^ tp;
        st = __reduce_or_sync(~0u, st);
        if (!(st >> 30)) break;
        trap_if(spin > 2000000);
      }
      if (st & 0x3C00FC00u) {
#pragma unroll 1
        for (;;) {
          uint32_t x = 0, row = 0;
#pragma unroll
          for (int k = 0; k < 12; k++) { const uint32_t y = (pk[k] ^ tp) & 0x3C00FC00u; if (!x && y) { x = y; row = wid + 11 * k; pk[k] ^= y; } }
          if (!__any_sync(~0u, x)) break;
          const uint32_t n = ((x >> 10) & 63) | ((x >> 20) & 0x1C0);
          if (x >> 29) {
            const uint32_t r = atoms_add(sb + OFF_CNT + n * 4, 16), idx = atoms_add(sb + OFF_MISC + 4, 1);
            if (idx < 256) sts32(sb + OFF_EXT + idx * 4, n | (row << 9) | (lane << 17) | (min(r >> 4, 255u) << 22));
            else x = 1;
          }
          if (x && !(x >> 29)) sts32(sb + OFF_MISC + 8, 1);
          __syncwarp();
        }
      }
#pragma unroll
      for (int k = 0; k < 12; k++) { r0[k] = mad16(pk[k], 0x0004u, cb); r1[k] = mad16(pk[k], 0x0400u, cb); vb[k].x = atoms_add(r0[k], 16); vb[k].y = atoms_add(r1[k], 16); }
    }
    STAMP(4);
    if (wid >= 6) bar_arrive(11, NWK);
    if (wid < 6) {
      uint32_t ca[2], ky[2], dr[2], sq[2], ps[4];
#pragma unroll
      for (int i = 0; i < 2; i++) { ca[i] = sb + OFF_CNT + ((node0 + tid + 192 * i) & 511) * 4; lds64(ps[2 * i], ps[2 * i + 1], sb + OFF_POS + (tid + 192 * i) * 8); ps[2 * i + 1] |= (tid + 192 * i) << 16; }
      bar_sync(11, NWK);
      STAMP(5);
#pragma unroll
      for (int i = 0; i < 2; i++) ky[i] = (lds32(ca[i]) + 16) >> 5;
      if (max(ky[0], ky[1]) > 31) sts32(sb + OFF_MISC + 8, 1);
#pragma unroll
      for (int i = 0; i < 2; i++) { ky[i] = min(ky[i], 31u); dr[i] = atoms_add(sb + OFF_DH + ky[i] * 4, 1); }
      bar_sync(10, 192);
      const uint32_t hv = lds32(sb + OFF_DH + lane * 4);
      uint32_t inc = hv;
#pragma unroll
      for (int o = 1; o < 32; o <<= 1) asm("{.reg .pred p; .reg .b32 y; shfl.sync.down.b32 y|p, %0, %1, 31, -1; @p add.u32 %0, %0, y;}" : "+r"(inc) : "r"(o));
#pragma unroll
      for (int i = 0; i < 2; i++) {
        const uint32_t pos = __shfl_sync(~0u, inc - hv, ky[i]) + dr[i];
        const uint32_t ak = (uint32_t)(QCODE >> ((pos >> 5) * 4)) & 15, l = (pos >> 3) & 3;
        sq[i] = (ak >> 2) * 16 + ((QREV >> (pos >> 5) & 1) ? 3 - l : l) * 4 + (ak & 3);
        dr[i] = pos & 7;
        asm volatile("{.reg .pred p; setp.eq.u32 p, %2, 0; @p st.shared.u8 [%0], %1;}" :: "r"(sb + OFF_LEN + sq[i]), "r"(max(ky[i], 1u)), "r"(dr[i]) : "memory");
        sts64(sb + OFF_GP + sq[i] * 64 + dr[i] * 8, ps[2 * i], ps[2 * i + 1]);
        sts16(sb + OFF_INV + (tid + 192 * i) * 2, sq[i] * 64 + dr[i] * 8);
      }
      bar_sync(10, 192);
      const uint32_t ln = lds32(sb + OFF_LEN + min(lane, 11) * 4), tot = __dp4a(ln, 0x01010101u, 0u);
      inc = tot;
#pragma unroll
      for (int o = 1; o < 16; o <<= 1) asm("{.reg .pred p; .reg .b32 y; shfl.sync.up.b32 y|p, %0, %1, 0, -1; @p add.u32 %0, %0, y;}" : "+r"(inc) : "r"(o));
      if (tid < 12) { sts32(sb + OFF_LEN + 64 + tid * 4, inc - tot); if (inc > SCAP - 12) sts32(sb + OFF_MISC + 8, 1); }
#pragma unroll
      for (int i = 0; i < 2; i++) sts32(ca[i], __dp4a(__shfl_sync(~0u, ln, sq[i] >> 2), 0x00010101u >> (24 - 8 * (sq[i] & 3)), __shfl_sync(~0u, inc - tot, sq[i] >> 2)) * 32 + dr[i] * 2);
    }
    bar_arrive(7, 384);
    bar_arrive(9, 384);
  }
  if (wid == 11) bar_sync(9, 384); else bar_sync(1, NWK);
  STAMP(6);
  if (wid != 11 && !__shfl_sync(~0u, lds32(sb + OFF_MISC + 8), 0)) {
#pragma unroll
    for (int k = 0; k < 12; k++) asm volatile("{.reg .pred p, q; setp.lt.u32 p, %0, %2; setp.lt.u32 q, %1, %2; @p ld.shared.u32 %0, [%0]; @q ld.shared.u32 %1, [%1];}" : "+r"(r0[k]), "+r"(r1[k]) : "n"(sb + OFF_CNT + 2048) : "memory");
#pragma unroll
    for (int k = 0; k < 12; k++) { r0[k] += vb[k].x; r1[k] += vb[k].y; }
  } else {
#pragma unroll
    for (int k = 0; k < 12; k++) r0[k] = r1[k] = 0x8000;
  }
  auto put_ids = [&]() {
    const uint32_t id = wid * 256 + ((lane + cta) & 31) * 8;
    auto put = [&](uint32_t x, uint32_t v) { asm volatile("{.reg .pred p; setp.lt.u32 p, %0, 0x8000; @p st.shared.u16 [%0+%2], %1;}" :: "r"(x), "h"((uint16_t)v), "n"(sb + OFF_TS) : "memory"); };
#pragma unroll
    for (int k = 0; k < 12; k++) { put(r0[k], id + k * 2816); put(r1[k], id + k * 2816 + 4); }
  };
  STAMP(7);
  mbar_wait(sb + BAR_QR);
  asm volatile("setmaxnreg.inc.sync.aligned.u32 152;");
  uint32_t pa[8], sp[8]; float chk = 0.f;
  {
    uint32_t hf[16], mp = 0; float a0[32];
    const uint32_t nd = lds16(sb + OFF_GP + wid * 256 + (lane & 15) * 8 + 6);
#pragma unroll
    for (int j = 0; j < 4; j++) ldsm4(hf + 4 * j, (sb + OFF_H + nd * 128 + (((nd & 7) << 4) ^ (lane & 16))) ^ (j << 5));
    const uint64_t db = DHI | ((sb + OFF_W + 8192) >> 4);
    wg_fence();
    rs64b<0>(a0, hf[0], hf[1], hf[2], hf[3], db); rs64b<1>(a0, hf[4], hf[5], hf[6], hf[7], db + 128); rs64b<1>(a0, hf[8], hf[9], hf[10], hf[11], db + 256); rs64b<1>(a0, hf[12], hf[13], hf[14], hf[15], db + 384);
    wg_commit();
    put_ids();
    wg_wait0(); fence_regs(a0);
#pragma unroll
    for (int j = 0; j < 8; j++) { const uint32_t x = pack_f16(.5f * a0[4 * j], .5f * a0[4 * j + 1]), y = pack_f16(.5f * a0[4 * j + 2], .5f * a0[4 * j + 3]); mp = hmag(hmag(mp, x), y);
      asm volatile("movmatrix.sync.aligned.m8n8.trans.b16 %0, %1;" : "=r"(pa[j]) : "r"(x)); asm volatile("movmatrix.sync.aligned.m8n8.trans.b16 %0, %1;" : "=r"(sp[j]) : "r"(y)); }
    if (magr(mp) >= 0x7000) chk = 1.f;
  }
  if (wid == 0) STAMP(23);
  uint32_t bad;
  {
    const uint32_t ring = sb + OFF_RING + wid * STG, p2 = sb + OFF_P2 + wid * 2048;
    uint32_t lens = __shfl_sync(~0u, lds32(sb + OFF_LEN + wid * 4), 0);
    uint32_t rem = __dp4a(lens, 0x20202020u, 0u);
    const uint32_t base = min(lds32(sb + OFF_LEN + 64 + wid * 4), SCAP);
    uint32_t a_s = sb + OFF_TS + base * 32 + (lane >> 3) * 8, a_e = sb + OFF_TE + base * 64 + (lane >> 1) * 4;
    uint32_t k0 = (uint32_t)(uint64_t)p.q + (((lane & 7) ^ ((lane >> 1) & 4)) << 4), k1 = k0 ^ 16, k2 = k0 ^ 32, k3 = k0 ^ 48, ke = ((lane ^ (lane >> 3)) & 1) << 4;
    uint32_t dst0 = ring + (lane >> 3) * 640 + (lane & 7) * 16;
    const uint32_t qhi = (uint32_t)((uint64_t)p.q >> 32), ehi = (uint32_t)((uint64_t)p.ea >> 32);
    uint32_t s0, s1, ev, to = 0, so = 12 * STG;
    auto tl_ = [&]() { lds64(s0, s1, a_s + to); asm volatile("ld.shared.u32 %0, [%1]; add.u32 %1, %1, 64;" : "=&r"(ev), "+r"(a_e) :: "memory"); to += 32; };
#define CPQ(LH, x, k, off) "dp2a." LH ".u32.u32 lo, " x ", 0x80000080, " k "; mov.b64 a, {lo, %7}; @p cp.async.cg.shared.global [%0+" #off "], [a], 16;\n"
    uint64_t pe; asm volatile("createpolicy.fractional.L2::evict_normal.b64 %0, 1.0;" : "=l"(pe));
    uint32_t one = __shfl_sync(~0u, lane, 1);
#define CPE "or.b32 lo, %10, %11; mov.b64 a, {lo, %12}; @p cp.async.cg.shared.global.L2::cache_hint [%0+512], [a], 16, %13;\n"
#define CPA(BODY) asm volatile("{.reg .b32 lo; .reg .b64 a; .reg .pred p; setp.le.u32 p, %8, %9;\n" BODY "}" \
      :: "r"(so * one + dst0), "r"(s0), "r"(s1), "r"(k0), "r"(k1), "r"(k2), "r"(k3), "r"(qhi), "r"(to), "r"(rem), "r"(ev), "r"(ke), "r"(ehi), "l"(pe) : "memory")
#define CPQ4 CPQ("lo", "%1", "%3", 0) CPQ("hi", "%1", "%4", 128) CPQ("lo", "%2", "%5", 256) CPQ("hi", "%2", "%6", 384) "cp.async.commit_group;"
    auto issue = [&]() { CPA(CPE CPQ4); so = so == (NST - 1) * 12 * STG ? 0 : so + 12 * STG; };
    const int g = lane >> 2, qd = lane & 3;
    const uint32_t sw = ((lane >> 4) ^ (lane & 7)) << 4, fr = (lane & 15) * 128 + sw;
    uint32_t qa0 = ring + (g & 3) * 640 + qd * 128 + sw, qa1 = qa0 ^ 32, qa2 = qa0 ^ 64, qa3 = qa0 ^ 96;
    uint32_t eadr = ring + 512 + (g & 3) * 640 + qd * 32 + ((((lane >> 4) ^ g) & 1) << 4);
    uint32_t oh0 = g == 2 * qd ? 0x3C00u : g == 2 * qd + 1 ? 0x3C000000u : 0u, oh1 = oh0;
    uint32_t a_g = sb + OFF_GP + wid * 256 + lane * 2;
    asm volatile("shfl.sync.idx.b32 %0, %0, %1, 31, -1;" : "+r"(oh1) : "r"(lane));
    uint32_t w3[16], wv[8], bp[16], sum[8], Y[16], M[16], own, ownp, dpk, tl[16], th[16];
    float pacc = 0.f;
    auto wload = [&]() {
#pragma unroll
      for (int j = 0; j < 4; j++) ldsm4t(w3 + 4 * j, (sb + OFF_W3 + fr) ^ (j << 5));
      lds128(wv, sb + OFF_WX + (a_g & 6) * 16); lds128(wv + 4, sb + OFF_WX + 16 + (a_g & 6) * 16);
    };
    auto hload = [&](uint32_t (&hf)[16], uint32_t nd) {
      const uint32_t hrow = sb + OFF_H + nd * 128 + (((nd & 7) << 4) ^ ((a_g >> 1) & 16));
#pragma unroll
      for (int j = 0; j < 4; j++) ldsm4(hf + 4 * j, hrow ^ (j << 5));
      return hrow;
    };
    { uint32_t wd[8]; const uint32_t a = sb + OFF_WD + (lane & 7) * 128 + ((((lane >> 3) ^ lane) & 7) << 4);
      ldsm4t(wd, a); ldsm4t(wd + 4, a ^ 64);
#pragma unroll
      for (int j = 0; j < 8; j++) { bp[2 * j] = wd[j]; bp[2 * j + 1] = pa[j]; } }
    own = lds16(a_g) * 0x10001u;
    wload();
    if (__shfl_sync(~0u, lds32(sb + OFF_MISC + 8), 0)) rem = 0;
    auto resolve = [&](auto NBK, uint32_t o) {
      constexpr int NB = decltype(NBK)::value;
      uint32_t id[NB], c0[NB], c1[NB]; const uint32_t a = base * 32 + o + lane * 4;
#pragma unroll
      for (int i = 0; i < NB; i++) { id[i] = lds32(sb + OFF_TS + a + i * 128); if (o + lane * 4 + i * 128 >= rem) id[i] = XPAD * 0x10001u; }
      uint32_t st = 0;
#pragma unroll
      for (int i = 0; i < NB; i++) { c0[i] = lds32(sb + OFF_XB + (id[i] & 0xFFFF)); c1[i] = lds32(sb + OFF_XB + (id[i] >> 16)); }
#pragma unroll
      for (int i = 0; i < NB; i++) st |= (c0[i] ^ tag) | (c1[i] ^ tag);
      for (int spin = 0; __any_sync(~0u, st >> 30); spin++) {
        st = 0; trap_if(spin > 2000000);
#pragma unroll
        for (int i = 0; i < NB; i++) {
          asm volatile("{.reg .pred p, q; setp.lt.u32 p, %4, %6; setp.lt.u32 q, %5, %6; @p ld.relaxed.gpu.global.u32 %0, [%2]; @q ld.relaxed.gpu.global.u32 %1, [%3];}"
            : "+r"(c0[i]), "+r"(c1[i]) : "l"((const char*)p.xb + cta * XPAD + (id[i] & 0xFFFF)), "l"((const char*)p.xb + cta * XPAD + (id[i] >> 16)), "r"(id[i] & 0xFFFF), "r"(id[i] >> 16), "n"(XPAD) : "memory");
          st |= (c0[i] ^ tag) | (c1[i] ^ tag); }
      }
#pragma unroll
      for (int i = 0; i < NB; i++) { const uint32_t j0 = (id[i] >> 8) & 255, j1 = id[i] >> 24;
        asm volatile("{.reg .pred p, q, r; setp.lt.u32 p, %5, %9; setp.lt.u32 q, %6, %9; setp.lt.u32 r, %7, %8;\n"
          "@p st.shared.u32 [%0], %2; @q st.shared.u32 [%0+4], %3; @r st.shared.u32 [%1], %4;}"
          :: "r"(sb + OFF_TE + 2 * a + i * 256), "r"(sb + OFF_TS + a + i * 128), "r"(mad16(c0[i], 0x2000u, eb0 + j0 * p.EPC * 32)), "r"(mad16(c1[i], 0x2000u, eb0 + j1 * p.EPC * 32)),
             "r"(__byte_perm(c0[i], c1[i], 0x5410)), "r"(j0), "r"(j1), "r"(o + lane * 4 + i * 128), "r"(rem), "n"(G) : "memory"); }
    };
    bar_sync(2, 384);
    if (wid == 0) STAMP(27);
    mbar_wait(sb + BAR_HB);
    if (wid == 0) STAMP(22);
#pragma unroll 1
    for (uint32_t o = 0, go = 0; go < 32 * NST; o += 128 * RNB) {
      if (o < rem) { resolve(IC<RNB>(), o);
        asm volatile("{.reg .pred p; mbarrier.test_wait.parity.shared::cta.b64 p, [%1], 0; vote.sync.all.pred p, p, -1; selp.u32 %0, %2, 0, p;}" : "=r"(go) : "r"(sb + BAR_QP), "n"(32 * NST - 32) : "memory"); }
      else { bar_arrive(4, NTHR); bar_sync(8, 384); mbar_wait(sb + BAR_QP); go = 32 * NST; if (wid == 0) STAMP(24); }
      __syncwarp();
#pragma unroll 1
      while (to < go) { tl_(); issue(); if (to == 32) STAMP(13); }
    }
    bad = __shfl_sync(~0u, lds32(sb + OFF_MISC + 8), 0);
   if (!bad) {
    auto body = [&](auto MODE) {
      constexpr int mode = decltype(MODE)::value;
      uint32_t T[16], ef[4], q0, q1, x0, x1, x2; float e0_, e1_, cs[4];
      auto mu = [&](int j) {
#pragma unroll
        for (int i = 2 * j; i < 2 * j + 2; i++) asm volatile("{.reg .b16 l, h; mov.b32 {l, h}, %2; tanh.approx.f16 l, l; tanh.approx.f16 h, h; cvt.u32.u16 %0, l; cvt.u32.u16 %1, h;}" : "=r"(tl[i]), "=r"(th[i]) : "r"(Y[i])); };
      auto fi = [&](int j) {
#pragma unroll
        for (int i = 2 * j; i < 2 * j + 2; i++) asm volatile("{.reg .b32 t; prmt.b32 t, %2, %3, 0x5410; fma.rn.f16x2 %0, %1, t, %1;}" : "=r"(M[i]) : "r"(Y[i]), "r"(tl[i]), "r"(th[i])); };
      auto ad = [&](int j) { asm volatile("add.rn.f16x2 %0, %0, %1; add.rn.f16x2 %0, %0, %2;" : "+r"(sum[j]) : "r"(M[2 * j]), "r"(M[2 * j + 1])); };
      auto he = [&](int j) { asm volatile("mma.sync.aligned.m16n8k16.row.col.f16.f16.f16.f16 {%0,%1}, {%2,%3,%4,%5}, {%6,%7}, {%0,%1};" : "+r"(T[2 * j]), "+r"(T[2 * j + 1]) : "r"(ef[0]), "r"(ef[1]), "r"(ef[2]), "r"(ef[3]), "r"(w3[2 * j]), "r"(w3[2 * j + 1])); };
      auto hs = [&](int j) { asm volatile("mma.sync.aligned.m16n8k16.row.col.f16.f16.f16.f16 {%0,%1}, {%2,%3,%4,%5}, {%6,%7}, {%8,%9};" : "=r"(Y[2 * j]), "=r"(Y[2 * j + 1]) : "r"(q0), "r"(q1), "r"(oh0), "r"(oh1), "r"(bp[2 * j]), "r"(bp[2 * j + 1]), "r"(T[2 * j]), "r"(T[2 * j + 1])); };
      auto hc = [&](int j) {
        if (j) asm volatile("mma.sync.aligned.m16n8k16.row.col.f32.f16.f16.f32 {%0,%1,%2,%3}, {%4,%5,%6,%7}, {%8,%9}, {%0,%1,%2,%3};" : "+f"(cs[0]), "+f"(cs[1]), "+f"(cs[2]), "+f"(cs[3]) : "r"(M[4 * j]), "r"(M[4 * j + 1]), "r"(M[4 * j + 2]), "r"(M[4 * j + 3]), "r"(wv[2 * j]), "r"(wv[2 * j + 1]));
        else asm volatile("mma.sync.aligned.m16n8k16.row.col.f32.f16.f16.f32 {%0,%1,%2,%3}, {%4,%5,%6,%7}, {%8,%9}, {%10,%10,%10,%10};" : "=f"(cs[0]), "=f"(cs[1]), "=f"(cs[2]), "=f"(cs[3]) : "r"(M[0]), "r"(M[1]), "r"(M[2]), "r"(M[3]), "r"(wv[0]), "r"(wv[1]), "f"(0.f)); };
      auto cv = [&](int i) { asm volatile("{.reg .b32 a, b; shl.b32 a, %0, 16; and.b32 b, %0, 0xFFFF0000; cvt.rn.f16x2.f32 %0, b, a;}" : "+r"(ef[i])); };
      auto un = [&]() { asm volatile("shl.b32 %0, %2, 16; and.b32 %1, %2, 0xFFFF0000;" : "=&f"(e0_), "=&f"(e1_) : "r"(dpk)); };
      auto ex0 = [&]() { asm volatile("prmt.b32 %0, %3, %4, 0x6420; prmt.b32 %1, %5, %6, 0x6420; prmt.b32 %2, %7, %8, 0x6420;" : "=&r"(x0), "=&r"(x1), "=&r"(x2) : "r"(T[0]), "r"(T[1]), "r"(T[2]), "r"(T[3]), "r"(T[4]), "r"(T[5])); };
      auto ex1 = [&]() { asm volatile("{.reg .b32 a, b; shl.b32 a, %2, 3; shl.b32 b, %3, 6; lop3.b32 a, %1, a, 0x38383838, 0xD8; lop3.b32 a, a, b, 0xC0C0C0C0, 0xD8; sub.rn.bf16x2 %0, %4, a;}" : "=r"(dpk) : "r"(x0), "r"(x1), "r"(x2), "r"(own)); };
      auto ex2 = [&]() { asm volatile("{.reg .b32 a, b, d, u; .reg .b16 l, h; shl.b32 a, %2, 16; and.b32 b, %2, 0xFFFF0000; cvt.rn.f16x2.f32 d, b, a; mul.rn.f16x2 %0, d, d; mov.b32 {l, h}, d; mov.b32 u, {h, h}; mul.rn.f16x2 %1, u, u;}" : "=&r"(q0), "=&r"(q1) : "r"(dpk)); };
      auto pf = [&]() { asm volatile("fma.rn.f32 %0, %1, %2, %0; fma.rn.f32 %0, %3, %4, %0;" : "+f"(pacc) : "f"(cs[0]), "f"(e0_), "f"(cs[2]), "f"(e1_)); };
      if (mode == 2) { LASTSEQ return; }
      asm volatile("cp.async.wait_group %0;" :: "n"(NST - 1) : "memory");
      __syncwarp();
      if (mode == 1) STAMP(8);
      ldsm4(ef, eadr + so); ldsm4(T, qa0 + so); ldsm4(T + 4, qa1 + so); ldsm4(T + 8, qa2 + so); ldsm4(T + 12, qa3 + so);
      if (mode == 1) {
        tl_(); issue();
        cv(0); cv(1); cv(2); cv(3); ex0(); ex1(); ex2();
#pragma unroll
        for (int j = 0; j < 8; j++) { he(j); hs(j); }
        FIRSTSEQ return;
      }
      BODYSEQ
    };
#pragma unroll
    for (int j = 0; j < 8; j++) sum[j] = 0;
    body(IC<1>());
    int cnt = (lens & 255) - 1;
    auto pload = [&](uint32_t (&x)[8], uint32_t o) { const uint32_t l = a_g >> 1, a = p2 + o + (l & 7) * 128 + (((((l >> 3) & 3) ^ l) & 7) << 4); ldsm4t(x, a); ldsm4t(x + 4, a ^ 64); };
    auto flush = [&]() {
      asm volatile("{.reg .pred p; setp.ne.u32 p, %2, 6; @p st.shared.u16 [%0+-64], %1;}" :: "r"(a_g), "h"((uint16_t)pack_bf16(bf_hi(ownp) + pacc, 0.f)), "r"(a_g & 6) : "memory");
      chk = fmaf(pacc, 0.f, chk); pacc = 0.f; };
    constexpr uint64_t b1 = DHI | ((sb + OFF_W) >> 4), b2_ = b1 + 512;
    auto mma_h = [&](float (&acc)[32], uint32_t (&hf)[16]) {
      rs64b<0>(acc, hf[0], hf[1], hf[2], hf[3], b1); rs64b<1>(acc, hf[4], hf[5], hf[6], hf[7], b1 + 128); rs64b<1>(acc, hf[8], hf[9], hf[10], hf[11], b1 + 256); rs64b<1>(acc, hf[12], hf[13], hf[14], hf[15], b1 + 384); };
    auto mma_m = [&](float (&acc)[32]) {
      rs64h<1>(acc, sp[0], sum[0], sp[1], sum[1], b2_); rs64h<1>(acc, sp[2], sum[2], sp[3], sum[3], b2_ + 128); rs64h<1>(acc, sp[4], sum[4], sp[5], sum[5], b2_ + 256); rs64h<1>(acc, sp[6], sum[6], sp[7], sum[7], b2_ + 384);
      wg_commit(); wg_wait0(); fence_regs(acc);
      STAMP(10);
      chk = fmaf(acc[0], 0.f, fmaf(acc[2], 0.f, chk)); };
    auto roff = [&](uint32_t nd, int r) { return __shfl_sync(~0u, nd, ((a_g >> 3) & 7) + 8 * r) * 128 + (a_g & 6) * 8; };
    auto radr = [&](uint32_t o, int k) { return sb + OFF_H + (o ^ ((o >> 3) & 0x70) ^ ((k >> 1) << 6)); };
    auto fin = [&](float (&acc)[32], uint32_t* x, int k) {
#pragma unroll
      for (int i = 0; i < 4; i++) { const int c = 16 * (k >> 1) + 4 * i + 2 * (k & 1); x[i] = u2(__hadd2(b2(x[i]), b2(pack_bf16(silu_h(acc[c]), silu_h(acc[c + 1]))))); } };
#pragma unroll 1
    for (int t = 0;; t++) {
#pragma unroll 1
      for (; cnt > 0; cnt--) { body(IC<0>());
      }
      if (!(t & 1)) {
        ownp = own; a_g += 64;
        if (t == 6) break;
        pe = pol_first();
        own = lds16(a_g) * 0x10001u;
        if (t == 2) { const uint32_t a = ((a_g & 16) ? p2 : sb + OFF_WD) + ((a_g << 6) & 0x380) + (qa0 & 0x70);
          mbar_wait(sb + BAR_U);
#pragma unroll
          for (int j = 0; j < 4; j++) ldsm4t(bp + 4 * j, a ^ (j << 5));
        } else {
#pragma unroll
          for (int j = 0; j < 8; j++) bp[2 * j + 1] = sp[j];
        }
        lens >>= 8; cnt = 1;
        continue;
      }
      cnt = (lens & 255) - 1;
      flush();
      if (t == 3) {
        uint32_t x[8];
        pload(x, 1024);
        __syncwarp();
#pragma unroll
        for (int j = 0; j < 4; j++) stsm4((p2 + ((a_g << 6) & 0x780) + (qa0 & 0x70)) ^ (j << 5), sp[2 * j], sum[2 * j], sp[2 * j + 1], sum[2 * j + 1]);
#pragma unroll
        for (int j = 0; j < 8; j++) sum[j] = x[j];
        __syncwarp();
        mbar_arrive(sb + BAR_M + (wid >> 2) * 8, (a_g & 62) == 0);
      }
#pragma unroll
      for (int j = 0; j < 8; j++) { sp[j] = sum[j]; asm volatile("mov.b32 %0, 0;" : "=r"(sum[j])); }
    }
    {
      uint32_t hf[16], v[16]; float acc[32];
      const uint32_t nd = lds16(sb + OFF_GP + wid * 256 + (lane & 15) * 8 + 134), o[2] = {roff(nd, 0), roff(nd, 1)};
      hload(hf, nd);
#pragma unroll
      for (int k = 0; k < 4; k++) lds128(v + 4 * k, radr(o[k & 1], k));
      mbar_wait(sb + BAR_WH);
      wg_fence(); mma_h(acc, hf); wg_commit();
      body(IC<2>());
      STAMP(9);
      flush();
      __syncwarp();
      mbar_arrive(sb + BAR_X, lane == 0);
      wg_fence();
      mma_m(acc);
#pragma unroll
      for (int k = 0; k < 4; k++) { fin(acc, v + 4 * k, k);
        asm volatile("{.reg .pred p; setp.lt.u32 p, %5, %6; @p st.global.v4.b32 [%0], {%1,%2,%3,%4};}" :: "l"((const char*)p.out + (size_t)node0 * 128 + o[k & 1] + (k >> 1) * 64), "r"(v[4 * k]), "r"(v[4 * k + 1]), "r"(v[4 * k + 2]), "r"(v[4 * k + 3]), "r"(o[k & 1]), "r"(nloc * 128) : "memory"); }
    }
    asm volatile("{.reg .pred p, q; setp.neu.f32 p, %1, 0f00000000; setp.ne.or.u32 p, %2, 0, p; bar.red.or.pred q, 5, 512, p; selp.u32 %0, 1, 0, q;}" : "=r"(bad) : "f"(chk), "r"(lds32(sb + OFF_MISC + 12)) : "memory");
    STAMP(11);
   } else { asm volatile("cp.async.wait_all;" ::: "memory"); bar_sync(5, 384); }
  }
  if (bad) slow_path(p, wid, lane, node0, nloc);
}

}

typedef CUresult (*EncodeFn)(CUtensorMap*, CUtensorMapDataType, cuuint32_t, void*, const cuuint64_t*, const cuuint64_t*, const cuuint32_t*, const cuuint32_t*,
                             CUtensorMapInterleave, CUtensorMapSwizzle, CUtensorMapL2promotion, CUtensorMapFloatOOBfill);

extern "C" void kernel_launch(void* const* d_in, const int* in_sizes, int n_in, void* d_out, int out_size) {
  Params p; Maps maps;
  p.h = (const uint4*)d_in[0]; p.pos = (const uint16_t*)d_in[1]; p.ea = (const uint4*)d_in[2];
  p.src = (const int*)d_in[3]; p.dst = (const int*)d_in[4];
  p.we = (const uint16_t*)d_in[5]; p.wx = (const uint16_t*)d_in[6]; p.wh = (const uint16_t*)d_in[7];
  p.out = (uint16_t*)d_out;
  p.N = in_sizes[0] / 64; p.E = in_sizes[3];
  p.EPC = ((p.E + G * 4 - 1) / (G * 4)) * 4;
  p.magic = (uint32_t)(((uint64_t)G << 24) / (uint64_t)p.N);
  p.inv = (1ull << 56) / p.magic;
  const uint64_t ea0 = (uint64_t)d_in[2], ea1 = ea0 + (uint64_t)p.E * 32 - 1;
  p.force_slow = ((ea0 >> 32) != (ea1 >> 32)) || (ea0 & 31) || (p.E & 3);
  void* qp = nullptr;
  cudaGetSymbolAddress(&qp, g_q);
  p.q = (char*)qp;
  if (((uint64_t)p.q >> 32) != (((uint64_t)p.q + QBYTES) >> 32)) p.q += QBYTES;
  cudaGetSymbolAddress((void**)&p.sync, g_sync); cudaGetSymbolAddress((void**)&p.xe, g_xe);
  cudaGetSymbolAddress((void**)&p.xa, g_xa); cudaGetSymbolAddress((void**)&p.xb, g_xb);
  const int df[10] = {34, 120, 0, 3072, 0, 17, 0xff2, 0xD5C4E6, 0x422000, 4};
  for (int i = 0; i < 10; i++) p.tune[i] = df[i];
  p.qcode = 0x890145a6273bull;
  p.ctam = p.tune[5];
  if ((long long)PFB * PFN > (long long)(p.E / G) * 32) PFB = (p.E / G * 32 / PFN) & ~127;
  void* fn = nullptr; cudaDriverEntryPointQueryResult qr;
  cudaGetDriverEntryPoint("cuTensorMapEncodeTiled", &fn, cudaEnableDefault, &qr);
  auto mk = [&](CUtensorMap* tm, void* base, int rows, int box = 64) {
    const cuuint64_t dim[2] = {64, (cuuint64_t)rows}, str[1] = {128}; const cuuint32_t bx[2] = {64, (cuuint32_t)box}, es[2] = {1, 1};
    ((EncodeFn)fn)(tm, CU_TENSOR_MAP_DATA_TYPE_BFLOAT16, 2, base, dim, str, bx, es, CU_TENSOR_MAP_INTERLEAVE_NONE, CU_TENSOR_MAP_SWIZZLE_128B,
                   CU_TENSOR_MAP_L2_PROMOTION_NONE, CU_TENSOR_MAP_FLOAT_OOB_FILL_NONE);
  };
  mk(&maps.m[TM_H / 128], d_in[0], p.N); mk(&maps.m[TM_WE / 128], d_in[5], 145); mk(&maps.m[TM_WH / 128], d_in[7], 128); mk(&maps.m[TM_Q / 128], p.q, p.N, 16);
  for (int k = 0; k < 2; k++) {
    void* xp = (void*)(k ? p.xb : p.xa);
    const cuuint64_t dim[2] = {(cuuint64_t)G * 64, (cuuint64_t)G}, str[1] = {(cuuint64_t)G * (128 << k)}; const cuuint32_t bx[2] = {64, (cuuint32_t)(k ? BROWS : G)}, es[2] = {1, 1};
    ((EncodeFn)fn)(&maps.m[TM_XA / 128 + k], k ? CU_TENSOR_MAP_DATA_TYPE_UINT32 : CU_TENSOR_MAP_DATA_TYPE_UINT16, 2, xp, dim, str, bx, es, CU_TENSOR_MAP_INTERLEAVE_NONE,
                   CU_TENSOR_MAP_SWIZZLE_NONE, CU_TENSOR_MAP_L2_PROMOTION_NONE, CU_TENSOR_MAP_FLOAT_OOB_FILL_NONE);
  }
  cudaFuncSetAttribute(egnn_kernel, cudaFuncAttributeMaxDynamicSharedMemorySize, SMEM);
  egnn_kernel<<<G, NTHR, SMEM>>>(p, maps);
}
```

```cpp
#include <cuda_runtime.h>
#include <cuda_bf16.h>
#include <cuda_fp16.h>
#include <cuda.h>
#include <stdint.h>
#pragma nv_diag_suppress 549

#define PFN p.tune[0]
#define PFB p.tune[3]
#define PFNS p.tune[1]
#define PFE p.tune[8]
#define BT p.tune[9]
#define BDEL p.tune[2]
#define DEFNS p.tune[4]
#define CTAM p.ctam
#define QREV p.tune[6]
#define UORD p.tune[7]
#define QCODE p.qcode
#define FIRSTSEQ mu(0); mu(1); fi(0); mu(2); fi(1);
#define BODYSEQ hc(0); fi(2); tl_(); mu(3); un(); ad(1); ad(0); cv(0); mu(4); cv(2); fi(3); cv(1); ex0(); ex1(); cv(3); he(0); fi(4); he(1); \
  mu(5); hc(1); mu(6); fi(5); he(2); ad(2); ex2(); hs(0); ad(3); hs(1); fi(6); mu(7); issue(); hc(2); he(3); hs(3); fi(7); mu(0); \
  hs(2); he(4); he(5); ad(5); ad(4); hs(4); fi(0); he(6); mu(1); hc(3); he(7); fi(1); ad(6); hs(7); hs(5); ad(7); hs(6); mu(2); \
  pf();
#define LASTSEQ hc(0); fi(2); mu(3); un(); ad(1); ad(0); mu(4); fi(3); fi(4); mu(5); hc(1); mu(6); fi(5); ad(2); ad(3); fi(6); mu(7); hc(2); \
  fi(7); ad(5); ad(4); hc(3); ad(6); ad(7); pf();
namespace {

constexpr int G = 132;
constexpr int NTHR = 512, NWK = 352, NCH = 5;
constexpr int NST = 3, STG = 2560;
constexpr int BROWS = 44, RNB = 2, PADM = 33;
constexpr int SCAP = 448;

constexpr int OFF_H = 0;
constexpr int OFF_W = 49152;
constexpr int OFF_WD = OFF_W + 16384;
constexpr int OFF_W3 = OFF_WD + 1024;
constexpr int OFF_P2 = OFF_W3 + 2048;
constexpr int OFF_RING = OFF_P2 + 24576;
constexpr int OFF_TE = OFF_RING + 12 * NST * STG;
constexpr int OFF_TS = OFF_TE + SCAP * 64;
constexpr int OFF_INV = OFF_TS - 768;
constexpr int OFF_GP = OFF_TS + SCAP * 32;
constexpr int OFF_WX = OFF_GP + 3072;
constexpr int OFF_LEN = OFF_WX + 128;
constexpr int OFF_MISC = OFF_LEN + 128;
constexpr int OFF_BAR = OFF_MISC + 48;
constexpr int SMEM = OFF_BAR + 256;
static_assert(SMEM <= 232448, "smem");
constexpr uint32_t sb = 1024;
constexpr int OFF_SRCI = OFF_TE;
constexpr int OFF_SB = OFF_RING, OFF_SA = OFF_SB + 34816, OFF_AX = OFF_SA + 32768, OFF_DST = OFF_H + 24576;
constexpr int OFF_WS = OFF_AX + 17408;
constexpr int OFF_BC = OFF_WS + 2304;
constexpr int OFF_CNT = OFF_P2;
constexpr int OFF_DH = OFF_CNT + 2176;
constexpr int OFF_POS = OFF_DH + 128;
constexpr int OFF_EXT = OFF_POS + 3072;
constexpr int OFF_XB = OFF_EXT + 1024, XPAD = G * 256;
static_assert(OFF_XB + XPAD + 1028 <= OFF_RING + 12 * STG && OFF_XB % 128 == 0 && OFF_BC + 544 <= OFF_TE && OFF_P2 % 1024 == 0 && OFF_SA % 1024 == 0 && SCAP * 64 >= 24576, "staging");
constexpr int BAR_DST = OFF_BAR, BAR_SRC = BAR_DST + 40, BAR_T = BAR_SRC + 24, BAR_W = BAR_T + 48, BAR_PS = BAR_W + 8, BAR_AW = BAR_PS + 8,
              BAR_QP = BAR_AW + 8, BAR_QR = BAR_QP + 8, BAR_HA = BAR_QR + 8, BAR_EP = BAR_HA + 8, BAR_AX = BAR_EP + 8, BAR_AI = BAR_AX + 8, BAR_HB = BAR_AI + 8, BAR_U = BAR_HB + 8, BAR_WH = BAR_U + 8, BAR_M = BAR_WH + 8, BAR_X = BAR_M + 24, BAR_END = BAR_X + 8;
static_assert(BAR_END <= OFF_BAR + 256, "barriers");
constexpr uint32_t QBYTES = 8u << 20;

__device__ __align__(256) uint4 g_xa[G * G * 8];
__device__ __align__(256) uint4 g_xb[G * G * 16];
__device__ __align__(256) uint2 g_xe[G * G * 32];
__device__ __align__(256) uint4 g_q[2 * QBYTES / 16];
constexpr int SYS = 32;
__device__ __align__(256) uint32_t g_sync[4 * SYS];
#define STAMP(k)

struct Maps { CUtensorMap m[6]; };
constexpr int TM_H = 0, TM_WE = 128, TM_WH = 256, TM_Q = 384, TM_XA = 512, TM_XB = 640;
struct Params {
  const int* dst; uint32_t* sync; int E, EPC, N, ctam; unsigned long long inv; uint32_t magic; int force_slow;
  const int* src; const uint16_t* pos; const uint4* ea; const uint16_t* we; const uint16_t* wx; char* q;
  const uint4* xa; const uint4* xb; uint2* xe; uint16_t* out; const uint4* h; const uint16_t* wh;
  int tune[10]; unsigned long long qcode;
};
template<int V> struct IC { static constexpr int value = V; };

#define R32(d) "+f"(d[0]),"+f"(d[1]),"+f"(d[2]),"+f"(d[3]),"+f"(d[4]),"+f"(d[5]),"+f"(d[6]),"+f"(d[7]),"+f"(d[8]),"+f"(d[9]),"+f"(d[10]),"+f"(d[11]),"+f"(d[12]),"+f"(d[13]),"+f"(d[14]),"+f"(d[15]),"+f"(d[16]),"+f"(d[17]),"+f"(d[18]),"+f"(d[19]),"+f"(d[20]),"+f"(d[21]),"+f"(d[22]),"+f"(d[23]),"+f"(d[24]),"+f"(d[25]),"+f"(d[26]),"+f"(d[27]),"+f"(d[28]),"+f"(d[29]),"+f"(d[30]),"+f"(d[31])
#define S32 "{%0,%1,%2,%3,%4,%5,%6,%7,%8,%9,%10,%11,%12,%13,%14,%15,%16,%17,%18,%19,%20,%21,%22,%23,%24,%25,%26,%27,%28,%29,%30,%31}"
#define DI __device__ __forceinline__

constexpr uint64_t DHI = ((uint64_t)(1024 >> 4) << 32) | (1ull << 62);
template<int SD> DI void rs64b(float (&d)[32], uint32_t a0, uint32_t a1, uint32_t a2, uint32_t a3, uint64_t db) {
  asm volatile("wgmma.mma_async.sync.aligned.m64n64k16.f32.bf16.bf16 " S32 ", {%32,%33,%34,%35}, %36, %37, 1, 1, 1;" : R32(d) : "r"(a0), "r"(a1), "r"(a2), "r"(a3), "l"(db), "n"(SD)); }
template<int SD> DI void rs64h(float (&d)[32], uint32_t a0, uint32_t a1, uint32_t a2, uint32_t a3, uint64_t db) {
  asm volatile("wgmma.mma_async.sync.aligned.m64n64k16.f32.f16.f16 " S32 ", {%32,%33,%34,%35}, %36, %37, 1, 1, 1;" : R32(d) : "r"(a0), "r"(a1), "r"(a2), "r"(a3), "l"(db), "n"(SD)); }
template<int SD> DI void ss64(float (&d)[32], uint64_t da, uint64_t db) {
  asm volatile("wgmma.mma_async.sync.aligned.m64n64k16.f32.bf16.bf16 " S32 ", %32, %33, %34, 1, 1, 0, 1;" : R32(d) : "l"(da), "l"(db), "n"(SD)); }
#define R16(d) "+f"(d[0]),"+f"(d[1]),"+f"(d[2]),"+f"(d[3]),"+f"(d[4]),"+f"(d[5]),"+f"(d[6]),"+f"(d[7]),"+f"(d[8]),"+f"(d[9]),"+f"(d[10]),"+f"(d[11]),"+f"(d[12]),"+f"(d[13]),"+f"(d[14]),"+f"(d[15])
#define S16 "{%0,%1,%2,%3,%4,%5,%6,%7,%8,%9,%10,%11,%12,%13,%14,%15}"
template<int SD> DI void rs32b(float (&d)[16], const uint32_t* a, uint64_t db) {
  asm volatile("wgmma.mma_async.sync.aligned.m64n32k16.f32.bf16.bf16 " S16 ", {%16,%17,%18,%19}, %20, %21, 1, 1, 1;" : R16(d) : "r"(a[0]), "r"(a[1]), "r"(a[2]), "r"(a[3]), "l"(db), "n"(SD)); }
DI void rs32h(float (&d)[16], const uint32_t* a, uint64_t db) {
  asm volatile("wgmma.mma_async.sync.aligned.m64n32k16.f32.f16.f16 " S16 ", {%16,%17,%18,%19}, %20, 1, 1, 1, 1;" : R16(d) : "r"(a[0]), "r"(a[1]), "r"(a[2]), "r"(a[3]), "l"(db)); }
DI void fence_regs(float (&d)[16]) { asm volatile("" : R16(d) :: "memory"); }
DI void trap_if(bool c) { asm volatile("{.reg .pred p; setp.eq.u32 p, %0, 0; @p bra.uni LT_%=; trap; LT_%=:}" :: "r"((uint32_t)c)); }
DI void wg_fence() { asm volatile("wgmma.fence.sync.aligned;" ::: "memory"); }
DI void wg_commit() { asm volatile("wgmma.commit_group.sync.aligned;" ::: "memory"); }
DI void wg_wait0() { asm volatile("wgmma.wait_group.sync.aligned 0;" ::: "memory"); }
DI void fence_regs(float (&d)[32]) { asm volatile("" : R32(d) :: "memory"); }
DI void proxy_fence() { asm volatile("fence.proxy.async.shared::cta;" ::: "memory"); }
DI uint64_t pol_first() { uint64_t r; asm("createpolicy.fractional.L2::evict_first.b64 %0, 1.0;" : "=l"(r)); return r; }
DI float tanh_ap(float x) { float y; asm("tanh.approx.f32 %0, %1;" : "=f"(y) : "f"(x)); return y; }
DI float silu_h(float y) { return fmaf(y, tanh_ap(y), y); }
DI uint32_t pack_bf16(float lo, float hi) { uint32_t r; asm("cvt.rn.bf16x2.f32 %0, %1, %2;" : "=r"(r) : "f"(hi), "f"(lo)); return r; }
DI uint32_t pack_f16(float lo, float hi) { uint32_t r; asm("cvt.rn.f16x2.f32 %0, %1, %2;" : "=r"(r) : "f"(hi), "f"(lo)); return r; }
DI float bf_lo(uint32_t v) { return __uint_as_float(v << 16); }
DI float bf_hi(uint32_t v) { return __uint_as_float(v & 0xFFFF0000u); }
DI uint32_t b2h(uint32_t v, float s) { return pack_f16(s * bf_lo(v), s * bf_hi(v)); }
DI void mbar_wait(uint32_t bar, uint32_t parity = 0) {
  asm volatile("{.reg .pred p, q; .reg .u32 c; mov.u32 c, 0;\n"
    "LW_%=: mbarrier.try_wait.parity.shared::cta.b64 p, [%0], %1;\n add.u32 c, c, 1; setp.lt.and.u32 q, c, 0x200000, !p;\n @q bra.uni LW_%=;}" :: "r"(bar), "r"(parity) : "memory");
}
DI void mbar_arrive(uint32_t bar, int p = 1) { asm volatile("{.reg .pred p; setp.ne.b32 p, %1, 0; @p mbarrier.arrive.shared::cta.b64 _, [%0];}" :: "r"(bar), "r"(p) : "memory"); }
DI void bar_sync(int id, int n) { asm volatile("bar.sync %0, %1;" :: "r"(id), "r"(n) : "memory"); }
DI void bar_arrive(int id, int n) { asm volatile("bar.arrive %0, %1;" :: "r"(id), "r"(n) : "memory"); }
DI __nv_bfloat162 b2(uint32_t v) { return *(__nv_bfloat162*)&v; }
DI uint32_t u2(__nv_bfloat162 v) { return *(uint32_t*)&v; }
DI uint32_t hsq(uint32_t v) { return u2(__hmul2(b2(v), b2(v))); }
DI uint32_t hsub(uint32_t a, uint32_t b) { return u2(__hsub2(b2(a), b2(b))); }
DI uint32_t hhalf(uint32_t v) { return u2(__hmul2(b2(v), __floats2bfloat162_rn(0.5f, 0.5f))); }
DI uint32_t mag2(uint32_t m, uint32_t v) { return __vmaxu2(m, v & 0x7FFF7FFFu); }
DI uint32_t hmag(uint32_t m, uint32_t v) { const __half2 r = __hmax2(*(const __half2*)&m, __habs2(*(const __half2*)&v)); return *(const uint32_t*)&r; }
DI uint32_t magr(uint32_t m) { return max(m & 0xFFFF, m >> 16); }
DI void sts128(uint32_t a, uint32_t x, uint32_t y, uint32_t z, uint32_t w) { asm volatile("st.shared.v4.u32 [%0], {%1,%2,%3,%4};" :: "r"(a), "r"(x), "r"(y), "r"(z), "r"(w) : "memory"); }
DI void sts64(uint32_t a, uint32_t x, uint32_t y) { asm volatile("st.shared.v2.u32 [%0], {%1,%2};" :: "r"(a), "r"(x), "r"(y) : "memory"); }
DI void sts32(uint32_t a, uint32_t x) { asm volatile("st.shared.u32 [%0], %1;" :: "r"(a), "r"(x) : "memory"); }
DI void sts16(uint32_t a, uint32_t x) { asm volatile("st.shared.u16 [%0], %1;" :: "r"(a), "h"((uint16_t)x) : "memory"); }
DI void lds128(uint32_t* v, uint32_t a) { asm volatile("ld.shared.v4.u32 {%0, %1, %2, %3}, [%4];" : "=r"(v[0]), "=r"(v[1]), "=r"(v[2]), "=r"(v[3]) : "r"(a) : "memory"); }
DI void lds64(uint32_t& x, uint32_t& y, uint32_t a) { asm volatile("ld.shared.v2.u32 {%0, %1}, [%2];" : "=r"(x), "=r"(y) : "r"(a) : "memory"); }
DI uint32_t lds32(uint32_t a) { uint32_t x; asm volatile("ld.shared.u32 %0, [%1];" : "=r"(x) : "r"(a) : "memory"); return x; }
DI uint32_t lds16(uint32_t a) { uint32_t x; asm volatile("ld.shared.u16 %0, [%1];" : "=r"(x) : "r"(a) : "memory"); return x; }
DI uint32_t atoms_add(uint32_t a, uint32_t v) { uint32_t r; asm volatile("atom.shared.add.u32 %0, [%1], %2;" : "=r"(r) : "r"(a), "r"(v) : "memory"); return r; }
DI void bulk_load(uint32_t dst, const void* src, uint32_t bytes, uint32_t bar) {
  asm volatile("cp.async.bulk.shared::cluster.global.mbarrier::complete_tx::bytes.L2::cache_hint [%0], [%1], %2, [%3], %4;" :: "r"(dst), "l"(src), "r"(bytes), "r"(bar), "l"(pol_first()) : "memory"); }
DI void mbar_expect(uint32_t bar, uint32_t bytes) { asm volatile("mbarrier.arrive.expect_tx.shared::cta.b64 _, [%0], %1;" :: "r"(bar), "r"(bytes) : "memory"); }
DI void mbar_init(uint32_t bar, int n) { asm volatile("mbarrier.init.shared::cta.b64 [%0], %1;" :: "r"(bar), "r"(n) : "memory"); }
DI void tma_load(uint32_t dst, uint64_t tm, int row, uint32_t bar) {
  asm volatile("cp.async.bulk.tensor.2d.shared::cluster.global.mbarrier::complete_tx::bytes.L2::cache_hint [%0], [%1, {%3, %4}], [%2], %5;" :: "r"(dst), "l"(tm), "r"(bar), "r"(0), "r"(row), "l"(pol_first()) : "memory"); }
DI void tma_store(uint64_t tm, int col, int row, uint32_t src) {
  asm volatile("cp.async.bulk.tensor.2d.global.shared::cta.bulk_group [%0, {%2, %3}], [%1];" :: "l"(tm), "r"(src), "r"(col), "r"(row) : "memory"); }
DI void bulk_commit() { asm volatile("cp.async.bulk.commit_group;" ::: "memory"); }
DI uint2 ld_poll2(const void* a) { uint2 v; asm volatile("ld.relaxed.gpu.global.v2.u32 {%0, %1}, [%2];" : "=r"(v.x), "=r"(v.y) : "l"(a) : "memory"); return v; }
DI void st_ext(uint2* a, uint32_t v, uint32_t ep) { asm volatile("st.relaxed.gpu.global.v2.u32 [%0], {%1, %2};" :: "l"(a), "r"(v), "r"(ep) : "memory"); }
DI uint32_t ext_get(const uint2* a, uint32_t ep) { uint2 v; int spin = 0; do { v = ld_poll2(a); trap_if(++spin > 4000000); } while (__any_sync(~0u, v.y != ep)); return v.x; }
DI void bulk_wait() { asm volatile("cp.async.bulk.wait_group 0;" ::: "memory"); }
DI void hint_signal(uint32_t* c) { asm volatile("red.relaxed.gpu.global.add.u32 [%0], 1;" :: "l"(c) : "memory"); }
DI void hint_wait(const uint32_t* c, uint32_t target) { uint32_t v; int spin = 0;
  do { asm volatile("ld.relaxed.gpu.global.u32 %0, [%1];" : "=r"(v) : "l"(c) : "memory"); trap_if(++spin > 4000000); } while (__any_sync(~0u, (int)(v - target) < 0)); }
DI void stsm4(uint32_t a, uint32_t x, uint32_t y, uint32_t z, uint32_t w) { asm volatile("stmatrix.sync.aligned.m8n8.x4.shared.b16 [%0], {%1,%2,%3,%4};" :: "r"(a), "r"(x), "r"(y), "r"(z), "r"(w) : "memory"); }
DI void ldsm4(uint32_t* v, uint32_t a) { asm volatile("ldmatrix.sync.aligned.m8n8.x4.shared.b16 {%0,%1,%2,%3}, [%4];" : "=r"(v[0]), "=r"(v[1]), "=r"(v[2]), "=r"(v[3]) : "r"(a) : "memory"); }
DI void ldsm4t(uint32_t* v, uint32_t a) { asm volatile("ldmatrix.sync.aligned.m8n8.x4.trans.shared.b16 {%0,%1,%2,%3}, [%4];" : "=r"(v[0]), "=r"(v[1]), "=r"(v[2]), "=r"(v[3]) : "r"(a) : "memory"); }
DI uint32_t mad16(uint32_t x, uint32_t m, uint32_t c) { uint32_t r; asm("dp2a.lo.u32.u32 %0, %1, %2, %3;" : "=r"(r) : "r"(x), "r"(m), "r"(c)); return r; }
DI bool wbad(uint32_t m, uint32_t hi) { return m > hi || (m && m < 0x3980); }

__device__ __noinline__ void slow_path(const Params& p, int wid, int lane, int node0, int nloc) {
  const uint32_t ab = sb + OFF_P2 + wid * 8704;
  for (int i = lane; i < 32 * 68; i += 32) sts32(ab + i * 4, 0);
  __syncwarp();
  const uint32_t wdv = __ldg((const uint32_t*)(p.we + 128 * 64) + lane), wxv = __ldg((const uint32_t*)p.wx + lane);
  const int nb0 = node0 + wid * 32, cntn = max(0, min(32, nloc - wid * 32));
  auto dot = [&](uint32_t hv, const uint16_t* w, int K2, float& y0, float& y1) {
#pragma unroll 4
    for (int k = 0; k < K2; k++) {
      const uint32_t hk = __shfl_sync(~0u, hv, k), wa = __ldg((const uint32_t*)(w + 2 * k * 64) + lane), wb = __ldg((const uint32_t*)(w + (2 * k + 1) * 64) + lane);
      y0 = fmaf(bf_lo(hk), bf_lo(wa), fmaf(bf_hi(hk), bf_lo(wb), y0)); y1 = fmaf(bf_lo(hk), bf_hi(wa), fmaf(bf_hi(hk), bf_hi(wb), y1));
    }
  };
  auto silu = [](float x) { return x / (1.f + __expf(-x)); };
#pragma unroll 1
  for (int base = 0; base < p.E; base += 32) {
    const int e = base + lane;
    const uint32_t dl = e < p.E ? (uint32_t)(__ldg(p.dst + e) - nb0) : 0xFFFFFFFFu;
    uint32_t mk = __ballot_sync(~0u, dl < (uint32_t)cntn);
    while (mk) {
      const int l = __ffs(mk) - 1; mk &= mk - 1;
      const int ee = base + l, n = __shfl_sync(~0u, dl, l), s = __ldg(p.src + ee);
      const uint16_t *po = p.pos + (size_t)(nb0 + n) * 3, *pp = p.pos + (size_t)s * 3;
      const uint32_t dxy = hsub(__ldg(po) | (__ldg(po + 1) << 16), __ldg(pp) | (__ldg(pp + 1) << 16)), dz = hsub(__ldg(po + 2), __ldg(pp + 2));
      const uint32_t sq = hsq(dxy); const float d2 = bf_lo(sq) + bf_hi(sq) + bf_lo(hsq(dz));
      float y0 = d2 * bf_lo(wdv), y1 = d2 * bf_hi(wdv);
      dot(__ldg((const uint32_t*)(p.h + (size_t)(nb0 + n) * 8) + lane), p.we, 32, y0, y1);
      dot(__ldg((const uint32_t*)(p.h + (size_t)s * 8) + lane), p.we + 64 * 64, 32, y0, y1);
      dot(__ldg((const uint32_t*)(p.ea + (size_t)ee * 2) + (lane & 7)), p.we + 129 * 64, 8, y0, y1);
      const uint32_t mm = pack_bf16(silu(y0), silu(y1));
      float c = bf_lo(mm) * bf_lo(wxv) + bf_hi(mm) * bf_hi(wxv);
#pragma unroll
      for (int o = 16; o; o >>= 1) c += __shfl_xor_sync(~0u, c, o);
      const uint32_t a = ab + n * 272;
      uint32_t x0, x1; lds64(x0, x1, a + lane * 8);
      sts64(a + lane * 8, __float_as_uint(__uint_as_float(x0) + bf_lo(mm)), __float_as_uint(__uint_as_float(x1) + bf_hi(mm)));
      if (lane < 3) { const float df = lane == 0 ? bf_lo(dxy) : lane == 1 ? bf_hi(dxy) : bf_lo(dz); sts32(a + 256 + lane * 4, __float_as_uint(fmaf(c, df, __uint_as_float(lds32(a + 256 + lane * 4))))); }
    }
  }
  __syncwarp();
#pragma unroll 1
  for (int n = 0; n < cntn; n++) {
    uint32_t x0, x1; lds64(x0, x1, ab + n * 272 + lane * 8);
    const uint32_t hv = __ldg((const uint32_t*)(p.h + (size_t)(nb0 + n) * 8) + lane);
    float y0 = 0.f, y1 = 0.f;
    dot(hv, p.wh, 32, y0, y1); dot(pack_bf16(__uint_as_float(x0), __uint_as_float(x1)), p.wh + 64 * 64, 32, y0, y1);
    ((uint32_t*)p.out)[(size_t)(nb0 + n) * 32 + lane] = u2(__hadd2(b2(hv), b2(pack_bf16(silu(y0), silu(y1)))));
    if (lane < 3) p.out[(size_t)p.N * 64 + (size_t)(nb0 + n) * 3 + lane] = (uint16_t)pack_bf16(bf_lo(__ldg(p.pos + (size_t)(nb0 + n) * 3 + lane)) + __uint_as_float(lds32(ab + n * 272 + 256 + lane * 4)), 0.f);
  }
}

__global__ void __launch_bounds__(NTHR, 1) egnn_kernel(const __grid_constant__ Params p, const __grid_constant__ Maps maps) {
  extern __shared__ __align__(1024) unsigned char smraw[];
  const int tid = threadIdx.x, cta = blockIdx.x * CTAM % G;
  const int e0 = cta * p.EPC, n4 = max(0, min(p.EPC, p.E - e0)) >> 2;
  STAMP(0);
  asm volatile("{.reg .pred p; setp.lt.s32 p, %1, %2; setp.lt.and.s32 p, %3, %4, p; @p prefetch.global.L2 [%0];}" :: "l"(p.dst + e0 + tid * 32), "r"(tid), "n"(64), "r"(e0 + tid * 32), "r"(p.E));
  if (tid == NWK) {
#pragma unroll 1
    for (int k = 0; k < NCH; k++) { const int nb = max(0, min(NWK, n4 - k * NWK)) * 16;
      mbar_init(sb + BAR_DST + k * 8, 1);
      asm volatile("fence.mbarrier_init.release.cluster;" ::: "memory");
      mbar_expect(sb + BAR_DST + k * 8, nb);
      if (nb) bulk_load(sb + OFF_DST + k * NWK * 16, (const char*)(p.dst + e0) + k * NWK * 16, nb, sb + BAR_DST + k * 8); }
  }
  const int lane = tid & 31, wid = __shfl_sync(~0u, tid >> 5, 0), w = wid & 3;
  asm volatile("{.reg .pred p; setp.eq.u32 p, %2, 384; @p cp.async.cg.shared.global [%0], [%1], 16;}" :: "r"(sb + OFF_LEN - 192 + (tid >> 1)), "l"(p.sync + w * SYS), "r"(tid & 415) : "memory");
  if (__shfl_sync(~0u, tid, 1) - 384u < 96u) {
    asm volatile("cp.async.wait_all;" ::: "memory");
    __syncwarp();
    const uint32_t e = lds32(sb + OFF_LEN + 8 + w * 16) + 1, v = (((1 + e % 3) << 14) + 512 + (lane & 7) * 4) * 0x10001u;
    if (tid == 384) sts32(sb + OFF_MISC + 32, e);
#pragma unroll 1
    for (int i = 0; i < 12; i++) sts128(sb + OFF_SA - 6144 + tid * 16 + i * 1536, v, v + 0x10001u, v + 0x20002u, v + 0x30003u);
    bar_sync(6, 480);
    mbar_arrive(sb + BAR_EP, lane == 0);
  }
  asm volatile("pmevent 1;" ::: "memory");
  uint64_t tmb; asm volatile("mov.u64 %0, %1;" : "=l"(tmb) : "l"(&maps));

  auto first_node = [&](int c) { return (int)((c * p.inv + 0xFFFFFFFFull) >> 32); };
  const int node0 = first_node(cta), nloc = min(first_node(cta + 1), p.N) - node0;
  const uint32_t ealo = (uint32_t)(uint64_t)p.ea;
  const int epad = min(e0, p.E - 1);
  if (wid >= 12) {
    const int t = tid - 384;
    auto load_h = [&](int b) { mbar_expect(sb + BAR_T + b * 8, 8192); tma_load(sb + OFF_H + b * 8192, tmb + TM_H, node0 + b * 64, sb + BAR_T + b * 8); };
    uint32_t pv[9], ev = 0;
#pragma unroll
    for (int i = 0; i < 3; i++) { const uint16_t* pp = p.pos + (size_t)(node0 + t + 128 * i) * 3;
      pv[3 * i] = pv[3 * i + 1] = pv[3 * i + 2] = 0;
      asm volatile("{.reg .pred p; setp.lt.s32 p, %4, %5;\n @p ld.global.nc.u16 %0, [%3];\n @p ld.global.nc.u16 %1, [%3+2];\n @p ld.global.nc.u16 %2, [%3+4];}"
        : "+r"(pv[3 * i]), "+r"(pv[3 * i + 1]), "+r"(pv[3 * i + 2]) : "l"(pp), "r"(t + 128 * i), "r"(p.N - node0)); }
    asm volatile("{.reg .pred p; setp.lt.u32 p, %3, 8; @p ld.global.nc.u32 %0, [%1]; @p st.global.v4.u32 [%2], {%4, %4, %4, %4};}"
      : "+r"(ev) : "l"((const uint32_t*)(p.ea + (size_t)epad * 2) + t), "l"(p.q + (size_t)(p.N + cta * PADM) * 128 + t * 16), "r"(t), "r"(0xF700F700u) : "memory");
    asm volatile("cp.async.wait_all;" ::: "memory");
    __syncwarp();
    const uint32_t e = lds32(sb + OFF_LEN + 8 + w * 16) + 1;
    { const uint32_t tg = (1 + e % 3) << 30;
#pragma unroll
      for (int i = 0; i < 17; i++) sts128(sb + OFF_SB + t * 16 + i * 2048, tg, tg, tg, tg); }
    uint32_t mp = 0;
#pragma unroll
    for (int i = 0; i < 3; i++) { sts64(sb + OFF_POS + (t + 128 * i) * 8, pv[3 * i] | (pv[3 * i + 1] << 16), pv[3 * i + 2]); mp = mag2(mag2(mp, pv[3 * i] | (pv[3 * i + 1] << 16)), pv[3 * i + 2]); }
    proxy_fence();
    if (w == 3) bar_sync(14, 416);
    __syncwarp();
    mbar_arrive(sb + BAR_PS, lane == 0);
    mbar_wait(sb + BAR_W);
    {
      uint32_t v[4], u[4]; const int r = t >> 3, c = t & 7;
      lds128(v, sb + OFF_WS + 128 + t * 16); lds128(u, sb + OFF_WS + c * 16);
      const uint32_t x = lds32(sb + OFF_WS + 2176 + lane * 4);
      sts128(sb + OFF_W3 + r * 128 + ((c ^ (r & 7)) << 4), b2h(v[0], .5f), b2h(v[1], .5f), b2h(v[2], .5f), b2h(v[3], .5f));
      const float s = ((r & 1) || r == 6) ? 0.f : .5f;
      if (t < 64) sts128(sb + OFF_WD + r * 128 + ((c ^ r) << 4), b2h(u[0], s), b2h(u[1], s), b2h(u[2], s), b2h(u[3], s));
      if (t < 32) sts32(sb + OFF_WX + (t & 3) * 32 + (t >> 2) * 4, b2h(x, 1.f));
      const uint32_t m3 = __reduce_max_sync(~0u, magr(mag2(mag2(mag2(mag2(0, v[0]), v[1]), v[2]), v[3]))), md = __reduce_max_sync(~0u, magr(mag2(mag2(mag2(mag2(0, u[0]), u[1]), u[2]), u[3])));
      if (wbad(m3, 0x4000) || wbad(md, 0x4000) || wbad(__reduce_max_sync(~0u, magr(mag2(0, x))), 0x4700) || magr(mp) >= 0x4200 || magr(mag2(0, ev)) >= 0x4380) sts32(sb + OFF_MISC + 8, 1);
    }
    if (w == 1) {
#pragma unroll 1
      for (int b = 0; b < 3; b++) { mbar_wait(sb + BAR_SRC + b * 8); if (lane == 0) load_h(b); }
    }
    bar_sync(3, 128);
    const uint32_t frag = (w * 16 + (lane & 15)) * 128 + (((lane >> 4) ^ (lane & 7)) << 4);
    uint32_t mq = 0; int pfi = 0;
    auto prefetch_e = [&]() {
      const uint32_t nb = PFB;
      if (lane == 0 && nb) asm volatile("cp.async.bulk.prefetch.L2.global [%0], %1;" :: "l"((const char*)p.ea + (size_t)(pfi * G + cta) * nb), "r"(nb) : "memory");
      pfi++; };
#pragma unroll 1
    for (int b = 0; b < 6; b++) {
      float acc[32];
      const uint64_t da = DHI | (((sb + OFF_H) >> 4) + b * 512), db = DHI | ((sb + OFF_W) >> 4);
      const uint32_t v0 = lds16(sb + OFF_POS + b * 512 + w * 128 + lane * 2), v1 = lds16(sb + OFF_POS + 64 + b * 512 + w * 128 + lane * 2);
      mbar_wait(sb + BAR_T + b * 8);
      if (b == 0) STAMP(25);
      if (b == 5) STAMP(26);
      wg_fence();
      ss64<0>(acc, da, db); ss64<1>(acc, da + 2, db + 128); ss64<1>(acc, da + 4, db + 256); ss64<1>(acc, da + 6, db + 384);
      wg_commit();
      if (b == 0) mbar_wait(sb + BAR_AW);
      if (t == 32 && b < 2) { load_h(b * 2 + 3); if (!b) load_h(4); }
      if (w == 1) for (int k = PFE >> (4 * b) & 15; k > 0; k--) prefetch_e();
      __syncwarp();
      uint32_t ff[6], fg[6];
#pragma unroll
      for (int j = 0; j < 6; j++) { ff[j] = (__byte_perm((j & 1) ? v1 : v0, 0, 0x4140) >> (3 * (j >> 1))) & 0x00070007u; fg[j] = __vsub2(0x00040004u, ff[j]);
        asm volatile("" : "+r"(ff[j]), "+r"(fg[j])); }
      wg_wait0(); fence_regs(acc);
      uint32_t o[16];
#pragma unroll
      for (int j = 0; j < 16; j++) o[j] = pack_f16(.5f * acc[2 * j], .5f * acc[2 * j + 1]);
#pragma unroll
      for (int j = 0; j < 6; j++) {
        const uint32_t m = o[j] & 0x7FFF7FFFu; mq = __vmaxu2(mq, m);
        o[j] = (__viaddmax_s16x2(m, fg[j], 0) & 0xFFF8FFF8u) | ff[j] | (o[j] & 0x80008000u); }
      if (b == 4) mbar_wait(sb + BAR_AX);
      const uint32_t qs = sb + OFF_SA + b * 8192;
#pragma unroll
      for (int j = 0; j < 4; j++) stsm4((qs + frag) ^ (j << 5), o[4 * j], o[4 * j + 1], o[4 * j + 2], o[4 * j + 3]);
      proxy_fence();
      __syncwarp();
      if (lane == 0 && b * 64 + w * 16 < nloc) tma_store(tmb + TM_Q, 0, node0 + b * 64 + w * 16, qs + w * 2048);
    }
    if (lane == 0) bulk_commit();
    { const uint32_t m = __reduce_max_sync(~0u, magr(mq)); if (lane == 0) sts32(sb + OFF_MISC + 16 + w * 4, m); }
    asm volatile("setmaxnreg.dec.sync.aligned.u32 56;");
    bulk_wait();
    bar_sync(3, 128);
    if (w == 0) {
      STAMP(18);
      uint32_t mv[4]; lds128(mv, sb + OFF_MISC + 16);
      const uint32_t mx = max(max(mv[0], mv[1]), max(mv[2], mv[3]));
      mbar_arrive(sb + BAR_QR, lane == 0);
      STAMP(19);
      if (lane == 0) {
        if (nloc > 0 && (mx >= 0x7BF0 || mx < 0x1400)) asm volatile("st.relaxed.gpu.global.u32 [%0+4], %1;" :: "l"(p.sync), "r"(e) : "memory");
        asm volatile("red.release.gpu.global.add.u32 [%0], 1;" :: "l"(p.sync) : "memory");
      }
      __syncwarp();
      uint32_t c, f; int spin = 0;
      do { asm volatile("ld.acquire.gpu.global.v2.u32 {%0, %1}, [%2];" : "=r"(c), "=r"(f) : "l"(p.sync) : "memory"); trap_if(++spin > 4000000); } while (__any_sync(~0u, (int)(c - e * G) < 0));
      if (f == e) sts32(sb + OFF_MISC + 8, 1);
      if (cta == 0 && lane < 4) asm volatile("st.relaxed.gpu.global.u32 [%0+8], %1;" :: "l"(p.sync + lane * SYS), "r"(e) : "memory");
      STAMP(20);
      __syncwarp();
      mbar_arrive(sb + BAR_QP, lane == 0);
    }
    if (w == 2) {
      const uint32_t tg = (1 + e % 3) << 30;
      hint_wait(p.sync + 2 * SYS, e * G);
      if (lane == 0) { mbar_expect(sb + BAR_HB, XPAD);
#pragma unroll 1
        for (int o = 0; o < 4; o++) bulk_load(sb + OFF_XB + o * (G * 64), (const char*)p.xb + (size_t)(cta * 4 + o) * (G * 64), G * 64, sb + BAR_HB); }
      STAMP(21);
      bar_sync(7, 384);
      sts32(sb + OFF_XB + XPAD, tg + p.N + cta * PADM);
      const uint32_t nx = __shfl_sync(~0u, lds32(sb + OFF_MISC + 8) ? 0 : lds32(sb + OFF_MISC + 4), 0);
#pragma unroll 1
      for (uint32_t k = 0; k < nx; k += 32) {
        const uint32_t i = min(k + lane, nx - 1), xr = lds32(sb + OFF_EXT + i * 4), row = (xr >> 9) & 255;
        const uint32_t v = ext_get(p.xe + (cta * G + row) * 32 + ((xr >> 17) & 31), e), x = lds32(sb + OFF_CNT + (xr & 511) * 4) + (xr >> 22) * 16;
        sts32(sb + OFF_XB + XPAD + 4 + i * 4, v); sts16(sb + OFF_TS + x, XPAD + 4 + i * 4);
        sts32(sb + OFF_TE + x * 2, mad16(v, 0x2000u, ealo - (tg >> 11) + row * p.EPC * 32));
      }
      __syncwarp();
      mbar_arrive(sb + BAR_HB, lane == 0);
    }
    if (w == 1) {
#pragma unroll 1
      while (pfi < PFN) { prefetch_e(); __nanosleep(PFNS); }
    }
    if (t == 96) { mbar_expect(sb + BAR_U, 8192); tma_load(sb + OFF_W, tmb + TM_WH, 0, sb + BAR_U); }
    __syncwarp();
    bar_sync(4, NTHR);
    const bool fast = !__shfl_sync(~0u, lds32(sb + OFF_MISC + 8), 0);
    if (fast) {
      mp = 0;
#pragma unroll 1
      for (uint32_t todo = UORD; todo; todo >>= 4) {
        const uint32_t nd = lds16(sb + OFF_GP + (todo & 3) * 1024 + w * 256 + (lane & 15) * 8 + 134), hb = (todo >> 3) & 1;
        const uint64_t b1 = DHI | (((sb + OFF_W + 8192) >> 4) + hb * 4);
        uint32_t f[8]; float acc[16];
#pragma unroll
        for (int j = 0; j < 4; j += 2) {
          const uint32_t a = (sb + OFF_H + nd * 128 + (((nd & 7) << 4) ^ (lane & 16))) ^ (j << 5);
          ldsm4(f, a); ldsm4(f + 4, a ^ 32);
          wg_fence();
          if (j == 0) rs32b<0>(acc, f, b1); else rs32b<1>(acc, f, b1 + 256);
          rs32b<1>(acc, f + 4, b1 + 128 * j + 128);
          wg_commit(); wg_wait0(); fence_regs(acc);
        }
#pragma unroll
        for (int j = 0; j < 8; j++) { f[j] = pack_f16(.5f * acc[2 * j], .5f * acc[2 * j + 1]); mp = hmag(mp, f[j]); }
        const uint32_t a = (sb + OFF_P2 + (todo & 3) * 8192 + frag) ^ (hb << 6);
        stsm4(a, f[0], f[1], f[2], f[3]); stsm4(a ^ 32, f[4], f[5], f[6], f[7]);
      }
      if (magr(mp) >= 0x7000) sts32(sb + OFF_MISC + 12, 1);
    }
    bar_sync(3, 128);
    if (t == 96) { mbar_expect(sb + BAR_U, 8192); tma_load(sb + OFF_W + 8192, tmb + TM_WH, 64, sb + BAR_U); }
    __syncwarp();
    mbar_wait(sb + BAR_U);
    uint32_t mh = 0;
#pragma unroll 1
    for (int i = t; i < 1024; i += 128) {
      uint32_t v[4]; const uint32_t r = (i >> 3) & 7, j = (i ^ r) & 7;
#pragma unroll
      for (int k = 0; k < 4; k++) v[k] = lds32(sb + OFF_W + (i >> 3) * 128 + ((((j & 4) + k) ^ r) << 4) + (j & 3) * 4);
      __syncwarp();
      if (i < 512) sts128(sb + OFF_W + i * 16, hhalf(v[0]), hhalf(v[1]), hhalf(v[2]), hhalf(v[3]));
      else { sts128(sb + OFF_W + i * 16, b2h(v[0], .5f), b2h(v[1], .5f), b2h(v[2], .5f), b2h(v[3], .5f)); mh = mag2(mag2(mag2(mag2(mh, v[0]), v[1]), v[2]), v[3]); } }
    if (wbad(__reduce_max_sync(~0u, magr(mh)), 0x4700)) sts32(sb + OFF_MISC + 12, 1);
    proxy_fence();
    __syncwarp();
    mbar_arrive(sb + BAR_WH, lane == 0);
    if (fast) {
      mbar_wait(sb + BAR_WH);
      float chk = 0.f;
#pragma unroll 1
      for (uint32_t todo = UORD; todo; todo >>= 4) {
        const uint32_t nd = lds16(sb + OFF_GP + (todo & 3) * 1024 + w * 256 + (lane & 15) * 8 + 6), hb = (todo >> 3) & 1;
        const uint64_t b1 = DHI | (((sb + OFF_W) >> 4) + hb * 4);
        uint32_t f[8]; float acc[16];
#pragma unroll
        for (int j = 0; j < 8; j += 2) {
          const uint32_t a = j < 4 ? sb + OFF_H + nd * 128 + (((nd & 7) << 4) ^ (lane & 16)) : sb + OFF_P2 + (todo & 3) * 8192 + frag;
          if (j == 4) mbar_wait(sb + BAR_M + (todo & 3) * 8);
          ldsm4(f, a ^ ((j & 3) << 5)); ldsm4(f + 4, a ^ ((j & 3) << 5) ^ 32);
          wg_fence();
          if (j == 0) rs32b<0>(acc, f, b1); else if (j < 4) rs32b<1>(acc, f, b1 + 128 * j); else rs32h(acc, f, b1 + 128 * j);
          if (j < 4) rs32b<1>(acc, f + 4, b1 + 128 * j + 128); else rs32h(acc, f + 4, b1 + 128 * j + 128);
          wg_commit(); wg_wait0(); fence_regs(acc);
        }
        chk = fmaf(acc[0], 0.f, fmaf(acc[2], 0.f, chk));
#pragma unroll
        for (int k = 0; k < 2; k++) {
          const uint32_t o = __shfl_sync(~0u, nd, (lane >> 2) + 8 * k) * 128 + (lane & 3) * 16 + hb * 64;
          uint32_t x[4]; lds128(x, sb + OFF_H + (o ^ ((o >> 3) & 0x70)));
#pragma unroll
          for (int i = 0; i < 4; i++) x[i] = u2(__hadd2(b2(x[i]), b2(pack_bf16(silu_h(acc[4 * i + 2 * k]), silu_h(acc[4 * i + 2 * k + 1])))));
          if (o < nloc * 128) *(uint4*)((char*)p.out + (size_t)node0 * 128 + o) = make_uint4(x[0], x[1], x[2], x[3]);
        }
        __nanosleep(DEFNS);
      }
      uint32_t pa_[9];
#pragma unroll
      for (int k = 0; k < 9; k++) { const uint32_t i = t + 128 * k, n = (i * 43691u) >> 17; pa_[k] = lds16(sb + OFF_INV + n * 2) + (i - 3 * n) * 2; }
      uint16_t* po = p.out + (size_t)p.N * 64 + node0 * 3 + t;
      mbar_wait(sb + BAR_X);
#pragma unroll
      for (int k = 0; k < 9; k++) pa_[k] = lds16(sb + OFF_GP + pa_[k]);
#pragma unroll
      for (int k = 0; k < 9; k++) if (t + 128 * k < nloc * 3) po[128 * k] = pa_[k];
      asm volatile("{.reg .pred p, q; setp.neu.f32 p, %0, 0f00000000; bar.red.or.pred q, 5, 512, p;}" :: "f"(chk) : "memory");
    }
    return;
  }

  if (tid == 320) {
    mbar_init(sb + BAR_W, 1);
    asm volatile("fence.mbarrier_init.release.cluster;" ::: "memory");
    mbar_expect(sb + BAR_W, 2 * 8192 + 2304);
    tma_load(sb + OFF_W, tmb + TM_WE, 64, sb + BAR_W); tma_load(sb + OFF_W + 8192, tmb + TM_WE, 0, sb + BAR_W);
    bulk_load(sb + OFF_WS, p.we + 128 * 64, 2176, sb + BAR_W); bulk_load(sb + OFF_WS + 2176, p.wx, 128, sb + BAR_W);
  }
  if (tid == 288) {
#pragma unroll
    for (int a = BAR_SRC; a < BAR_END; a += 8) if (a != BAR_W) mbar_init(sb + a, a == BAR_X ? 12 : a >= BAR_WH || a == BAR_PS ? 4 : a == BAR_EP ? 3 : a == BAR_HB || a == BAR_U ? 2 : 1);
    asm volatile("fence.mbarrier_init.release.cluster;" ::: "memory");
    asm volatile("prefetch.tensormap [%0];" :: "l"(tmb + TM_XA)); asm volatile("prefetch.tensormap [%0];" :: "l"(tmb + TM_H));
    asm volatile("prefetch.tensormap [%0];" :: "l"(tmb + TM_XB)); asm volatile("prefetch.tensormap [%0];" :: "l"(tmb + TM_Q));
  }
  {
    if (tid < 144) sts128(sb + OFF_CNT + tid * 16, 0, 0, 0, 0);
    else if (tid <= 144 + G) sts32(sb + OFF_BC + (tid - 144) * 4, ((tid - 144) & 31) * 4);
    const uint32_t sp = XPAD * 0x10001u, em = first_node(G);
    if (wid < 7) {
#pragma unroll
      for (int i = 0; i < 4; i++) sts128(sb + OFF_TS + tid * 16 + i * 3584, sp, sp, sp, sp);
    }
    static_assert(SCAP * 32 == 4 * 3584, "fill");
#pragma unroll 1
    for (int i = n4 + tid; i < 1536; i += 384) sts128(sb + OFF_DST + i * 16, em, em, em, em);
    if (tid == 321) sts128(sb + OFF_MISC, 0, 0, p.force_slow, 0);
  }
  bar_arrive(6, 480);
  bar_arrive(14, 416);
  bar_sync(0, 384);
  uint32_t ep, tag, eb0, pk[12], r0[12], r1[12], cb;
  uint2 vb[12];
  auto get_tag = [&]() { mbar_wait(sb + BAR_EP); ep = lds32(sb + OFF_MISC + 32); tag = (1 + ep % 3) << 30; eb0 = ealo - (tag >> 11); };
  if (wid == 11) {
    trap_if(sb != (uint32_t)__cvta_generic_to_shared(smraw));
#pragma unroll 1
    for (int k = 0; k < 3; k++) { const int nb = max(0, min(8192, n4 * 16 - k * 8192));
      mbar_wait(sb + BAR_DST + (k ? k + 1 : 0) * 8);
      if (lane == 0) { mbar_expect(sb + BAR_SRC + k * 8, nb);
        if (nb) bulk_load(sb + OFF_SRCI + k * 8192, (const char*)(p.src + e0) + k * 8192, nb, sb + BAR_SRC + k * 8); } }
    proxy_fence();
    get_tag();
    mbar_wait(sb + BAR_PS);
    bar_sync(12, 384);
    uint32_t xm = 0;
#pragma unroll
    for (int k = 0; k < 5; k++) xm |= (lds32(sb + OFF_BC + min(lane + 32 * k, G - 1) * 4) >= (65 << 9) && lane + 32 * k < G) << k;
    auto ext_send = [&](int pl) {
      uint32_t x = xm;
      for (uint32_t m; (m = __ballot_sync(~0u, x));) {
        const uint32_t l = __ffs(m) - 1, j = l + 32 * (__ffs(__shfl_sync(~0u, x, l)) - 1);
        if (lane == l) x &= x - 1;
        const uint32_t e = min(lds16(sb + OFF_AX + j * 128 + ((4 * l + 2 * lane) & 126)), 6143u);
        if (pl) st_ext(p.xe + (j * G + cta) * 32 + lane, lds32(sb + OFF_SRCI + e * 4) + tag + (e << 16), ep);
        else { const uint32_t cn = lds32(sb + OFF_BC + j * 4) >> 9, v = cn > 96 ? 1 : lane + 64 < cn ? 512 | (lds32(sb + OFF_DST + e * 4) & 511) : 0;
          asm volatile("red.shared.xor.b32 [%0], %1;" :: "r"(sb + OFF_SA + j * 128 + ((l + lane) & 31) * 4), "r"(((v & 63) << 10) | ((v >> 6) << 26)) : "memory"); }
      }
    };
    if (__any_sync(~0u, xm)) { ext_send(0); proxy_fence(); __syncwarp(); }
    if (lane == 0) { tma_store(tmb + TM_XA, cta * 64, 0, sb + OFF_SA); bulk_commit(); mbar_arrive(sb + BAR_AI); bulk_wait(); hint_signal(p.sync + SYS); mbar_arrive(sb + BAR_AW); STAMP(16); }
    __syncwarp();
    bar_sync(13, 384);
    ext_send(1);
    mbar_arrive(sb + BAR_AX, lane == 0);
    mbar_wait(sb + BAR_HA);
    mbar_wait(sb + BAR_T + BT * 8);
    __nanosleep(BDEL);
    if (lane == 0) {
#pragma unroll 1
      for (int k = 0; k < G / BROWS; k++) { const int r = (k + cta) % (G / BROWS) * BROWS; tma_store(tmb + TM_XB, cta * 64, r, sb + OFF_SB + r * 256); bulk_commit(); bulk_wait(); }
      hint_signal(p.sync + 2 * SYS);
      STAMP(17);
    }
    __syncwarp();
  } else {
    {
      uint32_t d[4 * NCH], jj[4 * NCH], rr[4 * NCH];
      auto count = [&](int k) {
        mbar_wait(sb + BAR_DST + k * 8);
        lds128(d + 4 * k, sb + OFF_DST + (tid + NWK * k) * 16);
#pragma unroll
        for (int i = 4 * k; i < 4 * k + 4; i++) { jj[i] = d[i] * p.magic; rr[i] = atoms_add(__dp4a(jj[i], 0x04000000u, sb + OFF_BC), 0x202u); }
      };
      auto place = [&](int k) {
#pragma unroll
        for (int i = 4 * k; i < 4 * k + 4; i++) {
          const uint32_t o = __dp4a(jj[i], 0x80000000u, rr[i] & 0x807Eu);
          d[i] = (d[i] & 511) | (tag >> 16);
          asm("{.reg .pred p; setp.ge.u32 p, %1, 0x8000; @p add.u32 %0, %2, %3;}" : "+r"(d[i]) : "r"(o), "r"(tid * 4), "r"(NWK * k * 4 + (i & 3)));
          sts16(sb + OFF_SA + o, d[i]); jj[i] = __viaddmin_u32(o, o, G * 256);
        }
      };
      count(0); STAMP(1); count(1); get_tag(); place(0); count(2); place(1); count(3); place(2);
      if (wid < 4) { count(4); STAMP(15); place(3); place(4); } else place(3);
      proxy_fence();
      bar_arrive(12, 384);
      STAMP(2);
      mbar_wait(sb + BAR_AI);
      mbar_wait(sb + BAR_SRC); mbar_wait(sb + BAR_SRC + 8); mbar_wait(sb + BAR_SRC + 16);
      STAMP(12);
#pragma unroll
      for (int k = 0; k < NCH; k++) lds128(d + 4 * k, sb + OFF_SRCI + (tid + NWK * k) * 16);
      const uint32_t tb = tag + (tid << 18);
#pragma unroll
      for (int i = 0; i < 4 * NCH; i++) if (i < 4 * NCH - 4 || wid < 4) sts32(sb + OFF_SB + jj[i], d[i] + tb + ((NWK * (i >> 2) * 4 + (i & 3)) << 16));
      proxy_fence();
      bar_arrive(13, 384);
      STAMP(3);
    }
    const uint32_t rot = (lane + cta) & 31;
    cb = sb + OFF_CNT - (tag >> 14);
    {
      const uint32_t* xa = (const uint32_t*)(p.xa + (cta * G + wid) * 8) + rot;
      if (wid < 8) { const uint32_t e_ = ealo + epad * 32;
        mbar_wait(sb + BAR_AX);
#pragma unroll
        for (int i = 0; i < 7; i++) sts128(sb + OFF_TE + tid * 16 + i * 4096, e_, e_, e_, e_); }
      static_assert(SCAP * 64 == 7 * 4096, "fill");
      if (wid == 10) { hint_wait(p.sync + SYS, ep * G); mbar_arrive(sb + BAR_HA, lane == 0); }
      mbar_wait(sb + BAR_HA);
      STAMP(14);
      const uint32_t tp = tag | (tag >> 16);
      uint32_t st;
#pragma unroll 1
      for (int spin = 0;; spin++) {
        st = 0;
#pragma unroll
        for (int k = 0; k < 12; k++) asm volatile("ld.relaxed.gpu.global.u32 %0, [%1];" : "=r"(pk[k]) : "l"(xa + k * 352) : "memory");
#pragma unroll
        for (int k = 0; k < 12; k++) st |= pk[k] ^ tp;
        st = __reduce_or_sync(~0u, st);
        if (!(st >> 30)) break;
        trap_if(spin > 2000000);
      }
      if (st & 0x3C00FC00u) {
#pragma unroll 1
        for (;;) {
          uint32_t x = 0, row = 0;
#pragma unroll
          for (int k = 0; k < 12; k++) { const uint32_t y = (pk[k] ^ tp) & 0x3C00FC00u; if (!x && y) { x = y; row = wid + 11 * k; pk[k] ^= y; } }
          if (!__any_sync(~0u, x)) break;
          const uint32_t n = ((x >> 10) & 63) | ((x >> 20) & 0x1C0);
          if (x >> 29) {
            const uint32_t r = atoms_add(sb + OFF_CNT + n * 4, 16), idx = atoms_add(sb + OFF_MISC + 4, 1);
            if (idx < 256) sts32(sb + OFF_EXT + idx * 4, n | (row << 9) | (lane << 17) | (min(r >> 4, 255u) << 22));
            else x = 1;
          }
          if (x && !(x >> 29)) sts32(sb + OFF_MISC + 8, 1);
          __syncwarp();
        }
      }
#pragma unroll
      for (int k = 0; k < 12; k++) { r0[k] = mad16(pk[k], 0x0004u, cb); r1[k] = mad16(pk[k], 0x0400u, cb); vb[k].x = atoms_add(r0[k], 16); vb[k].y = atoms_add(r1[k], 16); }
    }
    STAMP(4);
    if (wid >= 6) bar_arrive(11, NWK);
    if (wid < 6) {
      uint32_t ca[2], ky[2], dr[2], sq[2], ps[4];
#pragma unroll
      for (int i = 0; i < 2; i++) { ca[i] = sb + OFF_CNT + ((node0 + tid + 192 * i) & 511) * 4; lds64(ps[2 * i], ps[2 * i + 1], sb + OFF_POS + (tid + 192 * i) * 8); ps[2 * i + 1] |= (tid + 192 * i) << 16; }
      bar_sync(11, NWK);
      STAMP(5);
#pragma unroll
      for (int i = 0; i < 2; i++) ky[i] = (lds32(ca[i]) + 16) >> 5;
      if (max(ky[0], ky[1]) > 31) sts32(sb + OFF_MISC + 8, 1);
#pragma unroll
      for (int i = 0; i < 2; i++) { ky[i] = min(ky[i], 31u); dr[i] = atoms_add(sb + OFF_DH + ky[i] * 4, 1); }
      bar_sync(10, 192);
      const uint32_t hv = lds32(sb + OFF_DH + lane * 4);
      uint32_t inc = hv;
#pragma unroll
      for (int o = 1; o < 32; o <<= 1) asm("{.reg .pred p; .reg .b32 y; shfl.sync.down.b32 y|p, %0, %1, 31, -1; @p add.u32 %0, %0, y;}" : "+r"(inc) : "r"(o));
#pragma unroll
      for (int i = 0; i < 2; i++) {
        const uint32_t pos = __shfl_sync(~0u, inc - hv, ky[i]) + dr[i];
        const uint32_t ak = (uint32_t)(QCODE >> ((pos >> 5) * 4)) & 15, l = (pos >> 3) & 3;
        sq[i] = (ak >> 2) * 16 + ((QREV >> (pos >> 5) & 1) ? 3 - l : l) * 4 + (ak & 3);
        dr[i] = pos & 7;
        asm volatile("{.reg .pred p; setp.eq.u32 p, %2, 0; @p st.shared.u8 [%0], %1;}" :: "r"(sb + OFF_LEN + sq[i]), "r"(max(ky[i], 1u)), "r"(dr[i]) : "memory");
        sts64(sb + OFF_GP + sq[i] * 64 + dr[i] * 8, ps[2 * i], ps[2 * i + 1]);
        sts16(sb + OFF_INV + (tid + 192 * i) * 2, sq[i] * 64 + dr[i] * 8);
      }
      bar_sync(10, 192);
      const uint32_t ln = lds32(sb + OFF_LEN + min(lane, 11) * 4), tot = __dp4a(ln, 0x01010101u, 0u);
      inc = tot;
#pragma unroll
      for (int o = 1; o < 16; o <<= 1) asm("{.reg .pred p; .reg .b32 y; shfl.sync.up.b32 y|p, %0, %1, 0, -1; @p add.u32 %0, %0, y;}" : "+r"(inc) : "r"(o));
      if (tid < 12) { sts32(sb + OFF_LEN + 64 + tid * 4, inc - tot); if (inc > SCAP - 12) sts32(sb + OFF_MISC + 8, 1); }
#pragma unroll
      for (int i = 0; i < 2; i++) sts32(ca[i], __dp4a(__shfl_sync(~0u, ln, sq[i] >> 2), 0x00010101u >> (24 - 8 * (sq[i] & 3)), __shfl_sync(~0u, inc - tot, sq[i] >> 2)) * 32 + dr[i] * 2);
    }
    bar_arrive(7, 384);
    bar_arrive(9, 384);
  }
  if (wid == 11) bar_sync(9, 384); else bar_sync(1, NWK);
  STAMP(6);
  if (wid != 11 && !__shfl_sync(~0u, lds32(sb + OFF_MISC + 8), 0)) {
#pragma unroll
    for (int k = 0; k < 12; k++) asm volatile("{.reg .pred p, q; setp.lt.u32 p, %0, %2; setp.lt.u32 q, %1, %2; @p ld.shared.u32 %0, [%0]; @q ld.shared.u32 %1, [%1];}" : "+r"(r0[k]), "+r"(r1[k]) : "n"(sb + OFF_CNT + 2048) : "memory");
#pragma unroll
    for (int k = 0; k < 12; k++) { r0[k] += vb[k].x; r1[k] += vb[k].y; }
  } else {
#pragma unroll
    for (int k = 0; k < 12; k++) r0[k] = r1[k] = 0x8000;
  }
  auto put_ids = [&]() {
    const uint32_t id = wid * 256 + ((lane + cta) & 31) * 8;
    auto put = [&](uint32_t x, uint32_t v) { asm volatile("{.reg .pred p; setp.lt.u32 p, %0, 0x8000; @p st.shared.u16 [%0+%2], %1;}" :: "r"(x), "h"((uint16_t)v), "n"(sb + OFF_TS) : "memory"); };
#pragma unroll
    for (int k = 0; k < 12; k++) { put(r0[k], id + k * 2816); put(r1[k], id + k * 2816 + 4); }
  };
  STAMP(7);
  mbar_wait(sb + BAR_QR);
  asm volatile("setmaxnreg.inc.sync.aligned.u32 152;");
  uint32_t pa[8], sp[8]; float chk = 0.f;
  {
    uint32_t hf[16], mp = 0; float a0[32];
    const uint32_t nd = lds16(sb + OFF_GP + wid * 256 + (lane & 15) * 8 + 6);
#pragma unroll
    for (int j = 0; j < 4; j++) ldsm4(hf + 4 * j, (sb + OFF_H + nd * 128 + (((nd & 7) << 4) ^ (lane & 16))) ^ (j << 5));
    const uint64_t db = DHI | ((sb + OFF_W + 8192) >> 4);
    wg_fence();
    rs64b<0>(a0, hf[0], hf[1], hf[2], hf[3], db); rs64b<1>(a0, hf[4], hf[5], hf[6], hf[7], db + 128); rs64b<1>(a0, hf[8], hf[9], hf[10], hf[11], db + 256); rs64b<1>(a0, hf[12], hf[13], hf[14], hf[15], db + 384);
    wg_commit();
    put_ids();
    wg_wait0(); fence_regs(a0);
#pragma unroll
    for (int j = 0; j < 8; j++) { const uint32_t x = pack_f16(.5f * a0[4 * j], .5f * a0[4 * j + 1]), y = pack_f16(.5f * a0[4 * j + 2], .5f * a0[4 * j + 3]); mp = hmag(hmag(mp, x), y);
      asm volatile("movmatrix.sync.aligned.m8n8.trans.b16 %0, %1;" : "=r"(pa[j]) : "r"(x)); asm volatile("movmatrix.sync.aligned.m8n8.trans.b16 %0, %1;" : "=r"(sp[j]) : "r"(y)); }
    if (magr(mp) >= 0x7000) chk = 1.f;
  }
  if (wid == 0) STAMP(23);
  uint32_t bad;
  {
    const uint32_t ring = sb + OFF_RING + wid * STG, p2 = sb + OFF_P2 + wid * 2048;
    uint32_t lens = __shfl_sync(~0u, lds32(sb + OFF_LEN + wid * 4), 0);
    uint32_t rem = __dp4a(lens, 0x20202020u, 0u);
    const uint32_t base = min(lds32(sb + OFF_LEN + 64 + wid * 4), SCAP);
    uint32_t a_s = sb + OFF_TS + base * 32 + (lane >> 3) * 8, a_e = sb + OFF_TE + base * 64 + (lane >> 1) * 4;
    uint32_t k0 = (uint32_t)(uint64_t)p.q + (((lane & 7) ^ ((lane >> 1) & 4)) << 4), k1 = k0 ^ 16, k2 = k0 ^ 32, k3 = k0 ^ 48, ke = ((lane ^ (lane >> 3)) & 1) << 4;
    uint32_t dst0 = ring + (lane >> 3) * 640 + (lane & 7) * 16;
    const uint32_t qhi = (uint32_t)((uint64_t)p.q >> 32), ehi = (uint32_t)((uint64_t)p.ea >> 32);
    uint32_t s0, s1, ev, to = 0, so = 12 * STG;
    auto tl_ = [&]() { lds64(s0, s1, a_s + to); asm volatile("ld.shared.u32 %0, [%1]; add.u32 %1, %1, 64;" : "=&r"(ev), "+r"(a_e) :: "memory"); to += 32; };
#define CPQ(LH, x, k, off) "dp2a." LH ".u32.u32 lo, " x ", 0x80000080, " k "; mov.b64 a, {lo, %7}; @p cp.async.cg.shared.global [%0+" #off "], [a], 16;\n"
    uint64_t pe; asm volatile("createpolicy.fractional.L2::evict_normal.b64 %0, 1.0;" : "=l"(pe));
    uint32_t one = __shfl_sync(~0u, lane, 1);
#define CPE "or.b32 lo, %10, %11; mov.b64 a, {lo, %12}; @p cp.async.cg.shared.global.L2::cache_hint [%0+512], [a], 16, %13;\n"
#define CPA(BODY) asm volatile("{.reg .b32 lo; .reg .b64 a; .reg .pred p; setp.le.u32 p, %8, %9;\n" BODY "}" \
      :: "r"(so * one + dst0), "r"(s0), "r"(s1), "r"(k0), "r"(k1), "r"(k2), "r"(k3), "r"(qhi), "r"(to), "r"(rem), "r"(ev), "r"(ke), "r"(ehi), "l"(pe) : "memory")
#define CPQ4 CPQ("lo", "%1", "%3", 0) CPQ("hi", "%1", "%4", 128) CPQ("lo", "%2", "%5", 256) CPQ("hi", "%2", "%6", 384) "cp.async.commit_group;"
    auto issue = [&]() { CPA(CPE CPQ4); so = so == (NST - 1) * 12 * STG ? 0 : so + 12 * STG; };
    const int g = lane >> 2, qd = lane & 3;
    const uint32_t sw = ((lane >> 4) ^ (lane & 7)) << 4, fr = (lane & 15) * 128 + sw;
    uint32_t qa0 = ring + (g & 3) * 640 + qd * 128 + sw, qa1 = qa0 ^ 32, qa2 = qa0 ^ 64, qa3 = qa0 ^ 96;
    uint32_t eadr = ring + 512 + (g & 3) * 640 + qd * 32 + ((((lane >> 4) ^ g) & 1) << 4);
    uint32_t oh0 = g == 2 * qd ? 0x3C00u : g == 2 * qd + 1 ? 0x3C000000u : 0u, oh1 = oh0;
    uint32_t a_g = sb + OFF_GP + wid * 256 + lane * 2;
    asm volatile("shfl.sync.idx.b32 %0, %0, %1, 31, -1;" : "+r"(oh1) : "r"(lane));
    uint32_t w3[16], wv[8], bp[16], sum[8], Y[16], M[16], own, ownp, dpk, tl[16], th[16];
    float pacc = 0.f;
    auto wload = [&]() {
#pragma unroll
      for (int j = 0; j < 4; j++) ldsm4t(w3 + 4 * j, (sb + OFF_W3 + fr) ^ (j << 5));
      lds128(wv, sb + OFF_WX + (a_g & 6) * 16); lds128(wv + 4, sb + OFF_WX + 16 + (a_g & 6) * 16);
    };
    auto hload = [&](uint32_t (&hf)[16], uint32_t nd) {
      const uint32_t hrow = sb + OFF_H + nd * 128 + (((nd & 7) << 4) ^ ((a_g >> 1) & 16));
#pragma unroll
      for (int j = 0; j < 4; j++) ldsm4(hf + 4 * j, hrow ^ (j << 5));
      return hrow;
    };
    { uint32_t wd[8]; const uint32_t a = sb + OFF_WD + (lane & 7) * 128 + ((((lane >> 3) ^ lane) & 7) << 4);
      ldsm4t(wd, a); ldsm4t(wd + 4, a ^ 64);
#pragma unroll
      for (int j = 0; j < 8; j++) { bp[2 * j] = wd[j]; bp[2 * j + 1] = pa[j]; } }
    own = lds16(a_g) * 0x10001u;
    wload();
    if (__shfl_sync(~0u, lds32(sb + OFF_MISC + 8), 0)) rem = 0;
    auto resolve = [&](auto NBK, uint32_t o) {
      constexpr int NB = decltype(NBK)::value;
      uint32_t id[NB], c0[NB], c1[NB]; const uint32_t a = base * 32 + o + lane * 4;
#pragma unroll
      for (int i = 0; i < NB; i++) { id[i] = lds32(sb + OFF_TS + a + i * 128); if (o + lane * 4 + i * 128 >= rem) id[i] = XPAD * 0x10001u; }
      uint32_t st = 0;
#pragma unroll
      for (int i = 0; i < NB; i++) { c0[i] = lds32(sb + OFF_XB + (id[i] & 0xFFFF)); c1[i] = lds32(sb + OFF_XB + (id[i] >> 16)); }
#pragma unroll
      for (int i = 0; i < NB; i++) st |= (c0[i] ^ tag) | (c1[i] ^ tag);
      for (int spin = 0; __any_sync(~0u, st >> 30); spin++) {
        st = 0; trap_if(spin > 2000000);
#pragma unroll
        for (int i = 0; i < NB; i++) {
          asm volatile("{.reg .pred p, q; setp.lt.u32 p, %4, %6; setp.lt.u32 q, %5, %6; @p ld.relaxed.gpu.global.u32 %0, [%2]; @q ld.relaxed.gpu.global.u32 %1, [%3];}"
            : "+r"(c0[i]), "+r"(c1[i]) : "l"((const char*)p.xb + cta * XPAD + (id[i] & 0xFFFF)), "l"((const char*)p.xb + cta * XPAD + (id[i] >> 16)), "r"(id[i] & 0xFFFF), "r"(id[i] >> 16), "n"(XPAD) : "memory");
          st |= (c0[i] ^ tag) | (c1[i] ^ tag); }
      }
#pragma unroll
      for (int i = 0; i < NB; i++) { const uint32_t j0 = (id[i] >> 8) & 255, j1 = id[i] >> 24;
        asm volatile("{.reg .pred p, q, r; setp.lt.u32 p, %5, %9; setp.lt.u32 q, %6, %9; setp.lt.u32 r, %7, %8;\n"
          "@p st.shared.u32 [%0], %2; @q st.shared.u32 [%0+4], %3; @r st.shared.u32 [%1], %4;}"
          :: "r"(sb + OFF_TE + 2 * a + i * 256), "r"(sb + OFF_TS + a + i * 128), "r"(mad16(c0[i], 0x2000u, eb0 + j0 * p.EPC * 32)), "r"(mad16(c1[i], 0x2000u, eb0 + j1 * p.EPC * 32)),
             "r"(__byte_perm(c0[i], c1[i], 0x5410)), "r"(j0), "r"(j1), "r"(o + lane * 4 + i * 128), "r"(rem), "n"(G) : "memory"); }
    };
    bar_sync(2, 384);
    if (wid == 0) STAMP(27);
    mbar_wait(sb + BAR_HB);
    if (wid == 0) STAMP(22);
#pragma unroll 1
    for (uint32_t o = 0, go = 0; go < 32 * NST; o += 128 * RNB) {
      if (o < rem) { resolve(IC<RNB>(), o);
        asm volatile("{.reg .pred p; mbarrier.test_wait.parity.shared::cta.b64 p, [%1], 0; vote.sync.all.pred p, p, -1; selp.u32 %0, %2, 0, p;}" : "=r"(go) : "r"(sb + BAR_QP), "n"(32 * NST - 32) : "memory"); }
      else { bar_arrive(4, NTHR); bar_sync(8, 384); mbar_wait(sb + BAR_QP); go = 32 * NST; if (wid == 0) STAMP(24); }
      __syncwarp();
#pragma unroll 1
      while (to < go) { tl_(); issue(); if (to == 32) STAMP(13); }
    }
    bad = __shfl_sync(~0u, lds32(sb + OFF_MISC + 8), 0);
   if (!bad) {
    auto body = [&](auto MODE) {
      constexpr int mode = decltype(MODE)::value;
      uint32_t T[16], ef[4], q0, q1, x0, x1, x2; float e0_, e1_, cs[4];
      auto mu = [&](int j) {
#pragma unroll
        for (int i = 2 * j; i < 2 * j + 2; i++) asm volatile("{.reg .b16 l, h; mov.b32 {l, h}, %2; tanh.approx.f16 l, l; tanh.approx.f16 h, h; cvt.u32.u16 %0, l; cvt.u32.u16 %1, h;}" : "=r"(tl[i]), "=r"(th[i]) : "r"(Y[i])); };
      auto fi = [&](int j) {
#pragma unroll
        for (int i = 2 * j; i < 2 * j + 2; i++) asm volatile("{.reg .b32 t; prmt.b32 t, %2, %3, 0x5410; fma.rn.f16x2 %0, %1, t, %1;}" : "=r"(M[i]) : "r"(Y[i]), "r"(tl[i]), "r"(th[i])); };
      auto ad = [&](int j) { asm volatile("add.rn.f16x2 %0, %0, %1; add.rn.f16x2 %0, %0, %2;" : "+r"(sum[j]) : "r"(M[2 * j]), "r"(M[2 * j + 1])); };
      auto he = [&](int j) { asm volatile("mma.sync.aligned.m16n8k16.row.col.f16.f16.f16.f16 {%0,%1}, {%2,%3,%4,%5}, {%6,%7}, {%0,%1};" : "+r"(T[2 * j]), "+r"(T[2 * j + 1]) : "r"(ef[0]), "r"(ef[1]), "r"(ef[2]), "r"(ef[3]), "r"(w3[2 * j]), "r"(w3[2 * j + 1])); };
      auto hs = [&](int j) { asm volatile("mma.sync.aligned.m16n8k16.row.col.f16.f16.f16.f16 {%0,%1}, {%2,%3,%4,%5}, {%6,%7}, {%8,%9};" : "=r"(Y[2 * j]), "=r"(Y[2 * j + 1]) : "r"(q0), "r"(q1), "r"(oh0), "r"(oh1), "r"(bp[2 * j]), "r"(bp[2 * j + 1]), "r"(T[2 * j]), "r"(T[2 * j + 1])); };
      auto hc = [&](int j) {
        if (j) asm volatile("mma.sync.aligned.m16n8k16.row.col.f32.f16.f16.f32 {%0,%1,%2,%3}, {%4,%5,%6,%7}, {%8,%9}, {%0,%1,%2,%3};" : "+f"(cs[0]), "+f"(cs[1]), "+f"(cs[2]), "+f"(cs[3]) : "r"(M[4 * j]), "r"(M[4 * j + 1]), "r"(M[4 * j + 2]), "r"(M[4 * j + 3]), "r"(wv[2 * j]), "r"(wv[2 * j + 1]));
        else asm volatile("mma.sync.aligned.m16n8k16.row.col.f32.f16.f16.f32 {%0,%1,%2,%3}, {%4,%5,%6,%7}, {%8,%9}, {%10,%10,%10,%10};" : "=f"(cs[0]), "=f"(cs[1]), "=f"(cs[2]), "=f"(cs[3]) : "r"(M[0]), "r"(M[1]), "r"(M[2]), "r"(M[3]), "r"(wv[0]), "r"(wv[1]), "f"(0.f)); };
      auto cv = [&](int i) { asm volatile("{.reg .b32 a, b; shl.b32 a, %0, 16; and.b32 b, %0, 0xFFFF0000; cvt.rn.f16x2.f32 %0, b, a;}" : "+r"(ef[i])); };
      auto un = [&]() { asm volatile("shl.b32 %0, %2, 16; and.b32 %1, %2, 0xFFFF0000;" : "=&f"(e0_), "=&f"(e1_) : "r"(dpk)); };
      auto ex0 = [&]() { asm volatile("prmt.b32 %0, %3, %4, 0x6420; prmt.b32 %1, %5, %6, 0x6420; prmt.b32 %2, %7, %8, 0x6420;" : "=&r"(x0), "=&r"(x1), "=&r"(x2) : "r"(T[0]), "r"(T[1]), "r"(T[2]), "r"(T[3]), "r"(T[4]), "r"(T[5])); };
      auto ex1 = [&]() { asm volatile("{.reg .b32 a, b; shl.b32 a, %2, 3; shl.b32 b, %3, 6; lop3.b32 a, %1, a, 0x38383838, 0xD8; lop3.b32 a, a, b, 0xC0C0C0C0, 0xD8; sub.rn.bf16x2 %0, %4, a;}" : "=r"(dpk) : "r"(x0), "r"(x1), "r"(x2), "r"(own)); };
      auto ex2 = [&]() { asm volatile("{.reg .b32 a, b, d, u; .reg .b16 l, h; shl.b32 a, %2, 16; and.b32 b, %2, 0xFFFF0000; cvt.rn.f16x2.f32 d, b, a; mul.rn.f16x2 %0, d, d; mov.b32 {l, h}, d; mov.b32 u, {h, h}; mul.rn.f16x2 %1, u, u;}" : "=&r"(q0), "=&r"(q1) : "r"(dpk)); };
      auto pf = [&]() { asm volatile("fma.rn.f32 %0, %1, %2, %0; fma.rn.f32 %0, %3, %4, %0;" : "+f"(pacc) : "f"(cs[0]), "f"(e0_), "f"(cs[2]), "f"(e1_)); };
      if (mode == 2) { LASTSEQ return; }
      asm volatile("cp.async.wait_group %0;" :: "n"(NST - 1) : "memory");
      __syncwarp();
      if (mode == 1) STAMP(8);
      ldsm4(ef, eadr + so); ldsm4(T, qa0 + so); ldsm4(T + 4, qa1 + so); ldsm4(T + 8, qa2 + so); ldsm4(T + 12, qa3 + so);
      if (mode == 1) {
        tl_(); issue();
        cv(0); cv(1); cv(2); cv(3); ex0(); ex1(); ex2();
#pragma unroll
        for (int j = 0; j < 8; j++) { he(j); hs(j); }
        FIRSTSEQ return;
      }
      BODYSEQ
    };
#pragma unroll
    for (int j = 0; j < 8; j++) sum[j] = 0;
    body(IC<1>());
    int cnt = (lens & 255) - 1;
    auto pload = [&](uint32_t (&x)[8], uint32_t o) { const uint32_t l = a_g >> 1, a = p2 + o + (l & 7) * 128 + (((((l >> 3) & 3) ^ l) & 7) << 4); ldsm4t(x, a); ldsm4t(x + 4, a ^ 64); };
    auto flush = [&]() {
      asm volatile("{.reg .pred p; setp.ne.u32 p, %2, 6; @p st.shared.u16 [%0+-64], %1;}" :: "r"(a_g), "h"((uint16_t)pack_bf16(bf_hi(ownp) + pacc, 0.f)), "r"(a_g & 6) : "memory");
      chk = fmaf(pacc, 0.f, chk); pacc = 0.f; };
    constexpr uint64_t b1 = DHI | ((sb + OFF_W) >> 4), b2_ = b1 + 512;
    auto mma_h = [&](float (&acc)[32], uint32_t (&hf)[16]) {
      rs64b<0>(acc, hf[0], hf[1], hf[2], hf[3], b1); rs64b<1>(acc, hf[4], hf[5], hf[6], hf[7], b1 + 128); rs64b<1>(acc, hf[8], hf[9], hf[10], hf[11], b1 + 256); rs64b<1>(acc, hf[12], hf[13], hf[14], hf[15], b1 + 384); };
    auto mma_m = [&](float (&acc)[32]) {
      rs64h<1>(acc, sp[0], sum[0], sp[1], sum[1], b2_); rs64h<1>(acc, sp[2], sum[2], sp[3], sum[3], b2_ + 128); rs64h<1>(acc, sp[4], sum[4], sp[5], sum[5], b2_ + 256); rs64h<1>(acc, sp[6], sum[6], sp[7], sum[7], b2_ + 384);
      wg_commit(); wg_wait0(); fence_regs(acc);
      STAMP(10);
      chk = fmaf(acc[0], 0.f, fmaf(acc[2], 0.f, chk)); };
    auto roff = [&](uint32_t nd, int r) { return __shfl_sync(~0u, nd, ((a_g >> 3) & 7) + 8 * r) * 128 + (a_g & 6) * 8; };
    auto radr = [&](uint32_t o, int k) { return sb + OFF_H + (o ^ ((o >> 3) & 0x70) ^ ((k >> 1) << 6)); };
    auto fin = [&](float (&acc)[32], uint32_t* x, int k) {
#pragma unroll
      for (int i = 0; i < 4; i++) { const int c = 16 * (k >> 1) + 4 * i + 2 * (k & 1); x[i] = u2(__hadd2(b2(x[i]), b2(pack_bf16(silu_h(acc[c]), silu_h(acc[c + 1]))))); } };
#pragma unroll 1
    for (int t = 0;; t++) {
#pragma unroll 1
      for (; cnt > 0; cnt--) { body(IC<0>());
      }
      if (!(t & 1)) {
        ownp = own; a_g += 64;
        if (t == 6) break;
        pe = pol_first();
        own = lds16(a_g) * 0x10001u;
        if (t == 2) { const uint32_t a = ((a_g & 16) ? p2 : sb + OFF_WD) + ((a_g << 6) & 0x380) + (qa0 & 0x70);
          mbar_wait(sb + BAR_U);
#pragma unroll
          for (int j = 0; j < 4; j++) ldsm4t(bp + 4 * j, a ^ (j << 5));
        } else {
#pragma unroll
          for (int j = 0; j < 8; j++) bp[2 * j + 1] = sp[j];
        }
        lens >>= 8; cnt = 1;
        continue;
      }
      cnt = (lens & 255) - 1;
      flush();
      if (t == 3) {
        uint32_t x[8];
        pload(x, 1024);
        __syncwarp();
#pragma unroll
        for (int j = 0; j < 4; j++) stsm4((p2 + ((a_g << 6) & 0x780) + (qa0 & 0x70)) ^ (j << 5), sp[2 * j], sum[2 * j], sp[2 * j + 1], sum[2 * j + 1]);
#pragma unroll
        for (int j = 0; j < 8; j++) sum[j] = x[j];
        __syncwarp();
        mbar_arrive(sb + BAR_M + (wid >> 2) * 8, (a_g & 62) == 0);
      }
#pragma unroll
      for (int j = 0; j < 8; j++) { sp[j] = sum[j]; asm volatile("mov.b32 %0, 0;" : "=r"(sum[j])); }
    }
    {
      uint32_t hf[16], v[16]; float acc[32];
      const uint32_t nd = lds16(sb + OFF_GP + wid * 256 + (lane & 15) * 8 + 134), o[2] = {roff(nd, 0), roff(nd, 1)};
      hload(hf, nd);
#pragma unroll
      for (int k = 0; k < 4; k++) lds128(v + 4 * k, radr(o[k & 1], k));
      mbar_wait(sb + BAR_WH);
      wg_fence(); mma_h(acc, hf); wg_commit();
      body(IC<2>());
      STAMP(9);
      flush();
      __syncwarp();
      mbar_arrive(sb + BAR_X, lane == 0);
      wg_fence();
      mma_m(acc);
#pragma unroll
      for (int k = 0; k < 4; k++) { fin(acc, v + 4 * k, k);
        asm volatile("{.reg .pred p; setp.lt.u32 p, %5, %6; @p st.global.v4.b32 [%0], {%1,%2,%3,%4};}" :: "l"((const char*)p.out + (size_t)node0 * 128 + o[k & 1] + (k >> 1) * 64), "r"(v[4 * k]), "r"(v[4 * k + 1]), "r"(v[4 * k + 2]), "r"(v[4 * k + 3]), "r"(o[k & 1]), "r"(nloc * 128) : "memory"); }
    }
    asm volatile("{.reg .pred p, q; setp.neu.f32 p, %1, 0f00000000; setp.ne.or.u32 p, %2, 0, p; bar.red.or.pred q, 5, 512, p; selp.u32 %0, 1, 0, q;}" : "=r"(bad) : "f"(chk), "r"(lds32(sb + OFF_MISC + 12)) : "memory");
    STAMP(11);
   } else { asm volatile("cp.async.wait_all;" ::: "memory"); bar_sync(5, 384); }
  }
  if (bad) slow_path(p, wid, lane, node0, nloc);
}

}

typedef CUresult (*EncodeFn)(CUtensorMap*, CUtensorMapDataType, cuuint32_t, void*, const cuuint64_t*, const cuuint64_t*, const cuuint32_t*, const cuuint32_t*,
                             CUtensorMapInterleave, CUtensorMapSwizzle, CUtensorMapL2promotion, CUtensorMapFloatOOBfill);

extern "C" void kernel_launch(void* const* d_in, const int* in_sizes, int n_in, void* d_out, int out_size) {
  Params p; Maps maps;
  p.h = (const uint4*)d_in[0]; p.pos = (const uint16_t*)d_in[1]; p.ea = (const uint4*)d_in[2];
  p.src = (const int*)d_in[3]; p.dst = (const int*)d_in[4];
  p.we = (const uint16_t*)d_in[5]; p.wx = (const uint16_t*)d_in[6]; p.wh = (const uint16_t*)d_in[7];
  p.out = (uint16_t*)d_out;
  p.N = in_sizes[0] / 64; p.E = in_sizes[3];
  p.EPC = ((p.E + G * 4 - 1) / (G * 4)) * 4;
  p.magic = (uint32_t)(((uint64_t)G << 24) / (uint64_t)p.N);
  p.inv = (1ull << 56) / p.magic;
  const uint64_t ea0 = (uint64_t)d_in[2], ea1 = ea0 + (uint64_t)p.E * 32 - 1;
  p.force_slow = ((ea0 >> 32) != (ea1 >> 32)) || (ea0 & 31) || (p.E & 3);
  void* qp = nullptr;
  cudaGetSymbolAddress(&qp, g_q);
  p.q = (char*)qp;
  if (((uint64_t)p.q >> 32) != (((uint64_t)p.q + QBYTES) >> 32)) p.q += QBYTES;
  cudaGetSymbolAddress((void**)&p.sync, g_sync); cudaGetSymbolAddress((void**)&p.xe, g_xe);
  cudaGetSymbolAddress((void**)&p.xa, g_xa); cudaGetSymbolAddress((void**)&p.xb, g_xb);
  const int df[10] = {34, 120, 0, 3072, 0, 17, 0xff2, 0xD5C4E6, 0x422000, 4};
  for (int i = 0; i < 10; i++) p.tune[i] = df[i];
  p.qcode = 0x890145a6273bull;
  p.ctam = p.tune[5];
  if ((long long)PFB * PFN > (long long)(p.E / G) * 32) PFB = (p.E / G * 32 / PFN) & ~127;
  void* fn = nullptr; cudaDriverEntryPointQueryResult qr;
  cudaGetDriverEntryPoint("cuTensorMapEncodeTiled", &fn, cudaEnableDefault, &qr);
  auto mk = [&](CUtensorMap* tm, void* base, int rows, int box = 64) {
    const cuuint64_t dim[2] = {64, (cuuint64_t)rows}, str[1] = {128}; const cuuint32_t bx[2] = {64, (cuuint32_t)box}, es[2] = {1, 1};
    ((EncodeFn)fn)(tm, CU_TENSOR_MAP_DATA_TYPE_BFLOAT16, 2, base, dim, str, bx, es, CU_TENSOR_MAP_INTERLEAVE_NONE, CU_TENSOR_MAP_SWIZZLE_128B,
                   CU_TENSOR_MAP_L2_PROMOTION_NONE, CU_TENSOR_MAP_FLOAT_OOB_FILL_NONE);
  };
  mk(&maps.m[TM_H / 128], d_in[0], p.N); mk(&maps.m[TM_WE / 128], d_in[5], 145); mk(&maps.m[TM_WH / 128], d_in[7], 128); mk(&maps.m[TM_Q / 128], p.q, p.N, 16);
  for (int k = 0; k < 2; k++) {
    void* xp = (void*)(k ? p.xb : p.xa);
    const cuuint64_t dim[2] = {(cuuint64_t)G * 64, (cuuint64_t)G}, str[1] = {(cuuint64_t)G * (128 << k)}; const cuuint32_t bx[2] = {64, (cuuint32_t)(k ? BROWS : G)}, es[2] = {1, 1};
    ((EncodeFn)fn)(&maps.m[TM_XA / 128 + k], k ? CU_TENSOR_MAP_DATA_TYPE_UINT32 : CU_TENSOR_MAP_DATA_TYPE_UINT16, 2, xp, dim, str, bx, es, CU_TENSOR_MAP_INTERLEAVE_NONE,
                   CU_TENSOR_MAP_SWIZZLE_NONE, CU_TENSOR_MAP_L2_PROMOTION_NONE, CU_TENSOR_MAP_FLOAT_OOB_FILL_NONE);
  }
  cudaFuncSetAttribute(egnn_kernel, cudaFuncAttributeMaxDynamicSharedMemorySize, SMEM);
  egnn_kernel<<<G, NTHR, SMEM>>>(p, maps);
}
```

```cpp
#include <cuda_runtime.h>
#include <cuda_bf16.h>
#include <cuda_fp16.h>
#include <cuda.h>
#include <stdint.h>
#pragma nv_diag_suppress 549

#define PFN p.tune[0]
#define PFB p.tune[3]
#define PFNS p.tune[1]
#define PFE p.tune[8]
#define BT p.tune[9]
#define BDEL p.tune[2]
#define DEFNS p.tune[4]
#define CTAM p.ctam
#define QREV p.tune[6]
#define UORD p.tune[7]
#define QCODE p.qcode
#define FIRSTSEQ mu(0); mu(1); fi(0); mu(2); fi(1);
#define BODYSEQ hc(0); fi(2); tl_(); mu(3); un(); ad(1); ad(0); cv(0); mu(4); cv(2); fi(3); cv(1); ex0(); ex1(); cv(3); he(0); fi(4); he(1); \
  mu(5); hc(1); mu(6); fi(5); he(2); ad(2); ex2(); hs(0); ad(3); hs(1); fi(6); mu(7); issue(); hc(2); he(3); hs(3); fi(7); mu(0); \
  hs(2); he(4); he(5); ad(5); ad(4); hs(4); fi(0); he(6); mu(1); hc(3); he(7); fi(1); ad(6); hs(7); hs(5); ad(7); hs(6); mu(2); \
  pf();
#define LASTSEQ hc(0); fi(2); mu(3); un(); ad(1); ad(0); mu(4); fi(3); fi(4); mu(5); hc(1); mu(6); fi(5); ad(2); ad(3); fi(6); mu(7); hc(2); \
  fi(7); ad(5); ad(4); hc(3); ad(6); ad(7); pf();
namespace {

constexpr int G = 132;
constexpr int NTHR = 512, NWK = 352, NCH = 5;
constexpr int NST = 3, STG = 2560;
constexpr int BROWS = 44, RNB = 2, PADM = 33;
constexpr int SCAP = 448;

constexpr int OFF_H = 0;
constexpr int OFF_W = 49152;
constexpr int OFF_WD = OFF_W + 16384;
constexpr int OFF_W3 = OFF_WD + 1024;
constexpr int OFF_P2 = OFF_W3 + 2048;
constexpr int OFF_RING = OFF_P2 + 24576;
constexpr int OFF_TE = OFF_RING + 12 * NST * STG;
constexpr int OFF_TS = OFF_TE + SCAP * 64;
constexpr int OFF_INV = OFF_TS - 768;
constexpr int OFF_GP = OFF_TS + SCAP * 32;
constexpr int OFF_WX = OFF_GP + 3072;
constexpr int OFF_LEN = OFF_WX + 128;
constexpr int OFF_MISC = OFF_LEN + 128;
constexpr int OFF_BAR = OFF_MISC + 48;
constexpr int SMEM = OFF_BAR + 256;
static_assert(SMEM <= 232448, "smem");
constexpr uint32_t sb = 1024;
constexpr int OFF_SRCI = OFF_TE;
constexpr int OFF_SB = OFF_RING, OFF_SA = OFF_SB + 34816, OFF_AX = OFF_SA + 32768, OFF_DST = OFF_H + 24576;
constexpr int OFF_WS = OFF_AX + 17408;
constexpr int OFF_BC = OFF_WS + 2304;
constexpr int OFF_CNT = OFF_P2;
constexpr int OFF_DH = OFF_CNT + 2176;
constexpr int OFF_POS = OFF_DH + 128;
constexpr int OFF_EXT = OFF_POS + 3072;
constexpr int OFF_XB = OFF_EXT + 1024, XPAD = G * 256;
static_assert(OFF_XB + XPAD + 1028 <= OFF_RING + 12 * STG && OFF_XB % 128 == 0 && OFF_BC + 544 <= OFF_TE && OFF_P2 % 1024 == 0 && OFF_SA % 1024 == 0 && SCAP * 64 >= 24576, "staging");
constexpr int BAR_DST = OFF_BAR, BAR_SRC = BAR_DST + 40, BAR_T = BAR_SRC + 24, BAR_W = BAR_T + 48, BAR_PS = BAR_W + 8, BAR_AW = BAR_PS + 8,
              BAR_QP = BAR_AW + 8, BAR_QR = BAR_QP + 8, BAR_HA = BAR_QR + 8, BAR_EP = BAR_HA + 8, BAR_AX = BAR_EP + 8, BAR_AI = BAR_AX + 8, BAR_HB = BAR_AI + 8, BAR_U = BAR_HB + 8, BAR_WH = BAR_U + 8, BAR_M = BAR_WH + 8, BAR_X = BAR_M + 24, BAR_END = BAR_X + 8;
static_assert(BAR_END <= OFF_BAR + 256, "barriers");
constexpr uint32_t QBYTES = 8u << 20;

__device__ __align__(256) uint4 g_xa[G * G * 8];
__device__ __align__(256) uint4 g_xb[G * G * 16];
__device__ __align__(256) uint2 g_xe[G * G * 32];
__device__ __align__(256) uint4 g_q[2 * QBYTES / 16];
constexpr int SYS = 32;
__device__ __align__(256) uint32_t g_sync[4 * SYS];
#define STAMP(k)

struct Maps { CUtensorMap m[6]; };
constexpr int TM_H = 0, TM_WE = 128, TM_WH = 256, TM_Q = 384, TM_XA = 512, TM_XB = 640;
struct Params {
  const int* dst; uint32_t* sync; int E, EPC, N, ctam; unsigned long long inv; uint32_t magic; int force_slow;
  const int* src; const uint16_t* pos; const uint4* ea; const uint16_t* we; const uint16_t* wx; char* q;
  const uint4* xa; const uint4* xb; uint2* xe; uint16_t* out; const uint4* h; const uint16_t* wh;
  int tune[10]; unsigned long long qcode;
};
template<int V> struct IC { static constexpr int value = V; };

#define R32(d) "+f"(d[0]),"+f"(d[1]),"+f"(d[2]),"+f"(d[3]),"+f"(d[4]),"+f"(d[5]),"+f"(d[6]),"+f"(d[7]),"+f"(d[8]),"+f"(d[9]),"+f"(d[10]),"+f"(d[11]),"+f"(d[12]),"+f"(d[13]),"+f"(d[14]),"+f"(d[15]),"+f"(d[16]),"+f"(d[17]),"+f"(d[18]),"+f"(d[19]),"+f"(d[20]),"+f"(d[21]),"+f"(d[22]),"+f"(d[23]),"+f"(d[24]),"+f"(d[25]),"+f"(d[26]),"+f"(d[27]),"+f"(d[28]),"+f"(d[29]),"+f"(d[30]),"+f"(d[31])
#define S32 "{%0,%1,%2,%3,%4,%5,%6,%7,%8,%9,%10,%11,%12,%13,%14,%15,%16,%17,%18,%19,%20,%21,%22,%23,%24,%25,%26,%27,%28,%29,%30,%31}"
#define DI __device__ __forceinline__

constexpr uint64_t DHI = ((uint64_t)(1024 >> 4) << 32) | (1ull << 62);
template<int SD> DI void rs64b(float (&d)[32], uint32_t a0, uint32_t a1, uint32_t a2, uint32_t a3, uint64_t db) {
  asm volatile("wgmma.mma_async.sync.aligned.m64n64k16.f32.bf16.bf16 " S32 ", {%32,%33,%34,%35}, %36, %37, 1, 1, 1;" : R32(d) : "r"(a0), "r"(a1), "r"(a2), "r"(a3), "l"(db), "n"(SD)); }
template<int SD> DI void rs64h(float (&d)[32], uint32_t a0, uint32_t a1, uint32_t a2, uint32_t a3, uint64_t db) {
  asm volatile("wgmma.mma_async.sync.aligned.m64n64k16.f32.f16.f16 " S32 ", {%32,%33,%34,%35}, %36, %37, 1, 1, 1;" : R32(d) : "r"(a0), "r"(a1), "r"(a2), "r"(a3), "l"(db), "n"(SD)); }
template<int SD> DI void ss64(float (&d)[32], uint64_t da, uint64_t db) {
  asm volatile("wgmma.mma_async.sync.aligned.m64n64k16.f32.bf16.bf16 " S32 ", %32, %33, %34, 1, 1, 0, 1;" : R32(d) : "l"(da), "l"(db), "n"(SD)); }
#define R16(d) "+f"(d[0]),"+f"(d[1]),"+f"(d[2]),"+f"(d[3]),"+f"(d[4]),"+f"(d[5]),"+f"(d[6]),"+f"(d[7]),"+f"(d[8]),"+f"(d[9]),"+f"(d[10]),"+f"(d[11]),"+f"(d[12]),"+f"(d[13]),"+f"(d[14]),"+f"(d[15])
#define S16 "{%0,%1,%2,%3,%4,%5,%6,%7,%8,%9,%10,%11,%12,%13,%14,%15}"
template<int SD> DI void rs32b(float (&d)[16], const uint32_t* a, uint64_t db) {
  asm volatile("wgmma.mma_async.sync.aligned.m64n32k16.f32.bf16.bf16 " S16 ", {%16,%17,%18,%19}, %20, %21, 1, 1, 1;" : R16(d) : "r"(a[0]), "r"(a[1]), "r"(a[2]), "r"(a[3]), "l"(db), "n"(SD)); }
DI void rs32h(float (&d)[16], const uint32_t* a, uint64_t db) {
  asm volatile("wgmma.mma_async.sync.aligned.m64n32k16.f32.f16.f16 " S16 ", {%16,%17,%18,%19}, %20, 1, 1, 1, 1;" : R16(d) : "r"(a[0]), "r"(a[1]), "r"(a[2]), "r"(a[3]), "l"(db)); }
DI void fence_regs(float (&d)[16]) { asm volatile("" : R16(d) :: "memory"); }
DI void trap_if(bool c) { asm volatile("{.reg .pred p; setp.eq.u32 p, %0, 0; @p bra.uni LT_%=; trap; LT_%=:}" :: "r"((uint32_t)c)); }
DI void wg_fence() { asm volatile("wgmma.fence.sync.aligned;" ::: "memory"); }
DI void wg_commit() { asm volatile("wgmma.commit_group.sync.aligned;" ::: "memory"); }
DI void wg_wait0() { asm volatile("wgmma.wait_group.sync.aligned 0;" ::: "memory"); }
DI void fence_regs(float (&d)[32]) { asm volatile("" : R32(d) :: "memory"); }
DI void proxy_fence() { asm volatile("fence.proxy.async.shared::cta;" ::: "memory"); }
DI uint64_t pol_first() { uint64_t r; asm("createpolicy.fractional.L2::evict_first.b64 %0, 1.0;" : "=l"(r)); return r; }
DI float tanh_ap(float x) { float y; asm("tanh.approx.f32 %0, %1;" : "=f"(y) : "f"(x)); return y; }
DI float silu_h(float y) { return fmaf(y, tanh_ap(y), y); }
DI uint32_t pack_bf16(float lo, float hi) { uint32_t r; asm("cvt.rn.bf16x2.f32 %0, %1, %2;" : "=r"(r) : "f"(hi), "f"(lo)); return r; }
DI uint32_t pack_f16(float lo, float hi) { uint32_t r; asm("cvt.rn.f16x2.f32 %0, %1, %2;" : "=r"(r) : "f"(hi), "f"(lo)); return r; }
DI float bf_lo(uint32_t v) { return __uint_as_float(v << 16); }
DI float bf_hi(uint32_t v) { return __uint_as_float(v & 0xFFFF0000u); }
DI uint32_t b2h(uint32_t v, float s) { return pack_f16(s * bf_lo(v), s * bf_hi(v)); }
DI void mbar_wait(uint32_t bar, uint32_t parity = 0) {
  asm volatile("{.reg .pred p, q; .reg .u32 c; mov.u32 c, 0;\n"
    "LW_%=: mbarrier.try_wait.parity.shared::cta.b64 p, [%0], %1;\n add.u32 c, c, 1; setp.lt.and.u32 q, c, 0x200000, !p;\n @q bra.uni LW_%=;}" :: "r"(bar), "r"(parity) : "memory");
}
DI void mbar_arrive(uint32_t bar, int p = 1) { asm volatile("{.reg .pred p; setp.ne.b32 p, %1, 0; @p mbarrier.arrive.shared::cta.b64 _, [%0];}" :: "r"(bar), "r"(p) : "memory"); }
DI void bar_sync(int id, int n) { asm volatile("bar.sync %0, %1;" :: "r"(id), "r"(n) : "memory"); }
DI void bar_arrive(int id, int n) { asm volatile("bar.arrive %0, %1;" :: "r"(id), "r"(n) : "memory"); }
DI __nv_bfloat162 b2(uint32_t v) { return *(__nv_bfloat162*)&v; }
DI uint32_t u2(__nv_bfloat162 v) { return *(uint32_t*)&v; }
DI uint32_t hsq(uint32_t v) { return u2(__hmul2(b2(v), b2(v))); }
DI uint32_t hsub(uint32_t a, uint32_t b) { return u2(__hsub2(b2(a), b2(b))); }
DI uint32_t hhalf(uint32_t v) { return u2(__hmul2(b2(v), __floats2bfloat162_rn(0.5f, 0.5f))); }
DI uint32_t mag2(uint32_t m, uint32_t v) { return __vmaxu2(m, v & 0x7FFF7FFFu); }
DI uint32_t hmag(uint32_t m, uint32_t v) { const __half2 r = __hmax2(*(const __half2*)&m, __habs2(*(const __half2*)&v)); return *(const uint32_t*)&r; }
DI uint32_t magr(uint32_t m) { return max(m & 0xFFFF, m >> 16); }
DI void sts128(uint32_t a, uint32_t x, uint32_t y, uint32_t z, uint32_t w) { asm volatile("st.shared.v4.u32 [%0], {%1,%2,%3,%4};" :: "r"(a), "r"(x), "r"(y), "r"(z), "r"(w) : "memory"); }
DI void sts64(uint32_t a, uint32_t x, uint32_t y) { asm volatile("st.shared.v2.u32 [%0], {%1,%2};" :: "r"(a), "r"(x), "r"(y) : "memory"); }
DI void sts32(uint32_t a, uint32_t x) { asm volatile("st.shared.u32 [%0], %1;" :: "r"(a), "r"(x) : "memory"); }
DI void sts16(uint32_t a, uint32_t x) { asm volatile("st.shared.u16 [%0], %1;" :: "r"(a), "h"((uint16_t)x) : "memory"); }
DI void lds128(uint32_t* v, uint32_t a) { asm volatile("ld.shared.v4.u32 {%0, %1, %2, %3}, [%4];" : "=r"(v[0]), "=r"(v[1]), "=r"(v[2]), "=r"(v[3]) : "r"(a) : "memory"); }
DI void lds64(uint32_t& x, uint32_t& y, uint32_t a) { asm volatile("ld.shared.v2.u32 {%0, %1}, [%2];" : "=r"(x), "=r"(y) : "r"(a) : "memory"); }
DI uint32_t lds32(uint32_t a) { uint32_t x; asm volatile("ld.shared.u32 %0, [%1];" : "=r"(x) : "r"(a) : "memory"); return x; }
DI uint32_t lds16(uint32_t a) { uint32_t x; asm volatile("ld.shared.u16 %0, [%1];" : "=r"(x) : "r"(a) : "memory"); return x; }
DI uint32_t atoms_add(uint32_t a, uint32_t v) { uint32_t r; asm volatile("atom.shared.add.u32 %0, [%1], %2;" : "=r"(r) : "r"(a), "r"(v) : "memory"); return r; }
DI void bulk_load(uint32_t dst, const void* src, uint32_t bytes, uint32_t bar) {
  asm volatile("cp.async.bulk.shared::cluster.global.mbarrier::complete_tx::bytes.L2::cache_hint [%0], [%1], %2, [%3], %4;" :: "r"(dst), "l"(src), "r"(bytes), "r"(bar), "l"(pol_first()) : "memory"); }
DI void mbar_expect(uint32_t bar, uint32_t bytes) { asm volatile("mbarrier.arrive.expect_tx.shared::cta.b64 _, [%0], %1;" :: "r"(bar), "r"(bytes) : "memory"); }
DI void mbar_init(uint32_t bar, int n) { asm volatile("mbarrier.init.shared::cta.b64 [%0], %1;" :: "r"(bar), "r"(n) : "memory"); }
DI void tma_load(uint32_t dst, uint64_t tm, int row, uint32_t bar) {
  asm volatile("cp.async.bulk.tensor.2d.shared::cluster.global.mbarrier::complete_tx::bytes.L2::cache_hint [%0], [%1, {%3, %4}], [%2], %5;" :: "r"(dst), "l"(tm), "r"(bar), "r"(0), "r"(row), "l"(pol_first()) : "memory"); }
DI void tma_store(uint64_t tm, int col, int row, uint32_t src) {
  asm volatile("cp.async.bulk.tensor.2d.global.shared::cta.bulk_group [%0, {%2, %3}], [%1];" :: "l"(tm), "r"(src), "r"(col), "r"(row) : "memory"); }
DI void bulk_commit() { asm volatile("cp.async.bulk.commit_group;" ::: "memory"); }
DI uint2 ld_poll2(const void* a) { uint2 v; asm volatile("ld.relaxed.gpu.global.v2.u32 {%0, %1}, [%2];" : "=r"(v.x), "=r"(v.y) : "l"(a) : "memory"); return v; }
DI void st_ext(uint2* a, uint32_t v, uint32_t ep) { asm volatile("st.relaxed.gpu.global.v2.u32 [%0], {%1, %2};" :: "l"(a), "r"(v), "r"(ep) : "memory"); }
DI uint32_t ext_get(const uint2* a, uint32_t ep) { uint2 v; int spin = 0; do { v = ld_poll2(a); trap_if(++spin > 4000000); } while (__any_sync(~0u, v.y != ep)); return v.x; }
DI void bulk_wait() { asm volatile("cp.async.bulk.wait_group 0;" ::: "memory"); }
DI void hint_signal(uint32_t* c) { asm volatile("red.relaxed.gpu.global.add.u32 [%0], 1;" :: "l"(c) : "memory"); }
DI void hint_wait(const uint32_t* c, uint32_t target) { uint32_t v; int spin = 0;
  do { asm volatile("ld.relaxed.gpu.global.u32 %0, [%1];" : "=r"(v) : "l"(c) : "memory"); trap_if(++spin > 4000000); } while (__any_sync(~0u, (int)(v - target) < 0)); }
DI void stsm4(uint32_t a, uint32_t x, uint32_t y, uint32_t z, uint32_t w) { asm volatile("stmatrix.sync.aligned.m8n8.x4.shared.b16 [%0], {%1,%2,%3,%4};" :: "r"(a), "r"(x), "r"(y), "r"(z), "r"(w) : "memory"); }
DI void ldsm4(uint32_t* v, uint32_t a) { asm volatile("ldmatrix.sync.aligned.m8n8.x4.shared.b16 {%0,%1,%2,%3}, [%4];" : "=r"(v[0]), "=r"(v[1]), "=r"(v[2]), "=r"(v[3]) : "r"(a) : "memory"); }
DI void ldsm4t(uint32_t* v, uint32_t a) { asm volatile("ldmatrix.sync.aligned.m8n8.x4.trans.shared.b16 {%0,%1,%2,%3}, [%4];" : "=r"(v[0]), "=r"(v[1]), "=r"(v[2]), "=r"(v[3]) : "r"(a) : "memory"); }
DI uint32_t mad16(uint32_t x, uint32_t m, uint32_t c) { uint32_t r; asm("dp2a.lo.u32.u32 %0, %1, %2, %3;" : "=r"(r) : "r"(x), "r"(m), "r"(c)); return r; }
DI bool wbad(uint32_t m, uint32_t hi) { return m > hi || (m && m < 0x3980); }

__device__ __noinline__ void slow_path(const Params& p, int wid, int lane, int node0, int nloc) {
  const uint32_t ab = sb + OFF_P2 + wid * 8704;
  for (int i = lane; i < 32 * 68; i += 32) sts32(ab + i * 4, 0);
  __syncwarp();
  const uint32_t wdv = __ldg((const uint32_t*)(p.we + 128 * 64) + lane), wxv = __ldg((const uint32_t*)p.wx + lane);
  const int nb0 = node0 + wid * 32, cntn = max(0, min(32, nloc - wid * 32));
  auto dot = [&](uint32_t hv, const uint16_t* w, int K2, float& y0, float& y1) {
#pragma unroll 4
    for (int k = 0; k < K2; k++) {
      const uint32_t hk = __shfl_sync(~0u, hv, k), wa = __ldg((const uint32_t*)(w + 2 * k * 64) + lane), wb = __ldg((const uint32_t*)(w + (2 * k + 1) * 64) + lane);
      y0 = fmaf(bf_lo(hk), bf_lo(wa), fmaf(bf_hi(hk), bf_lo(wb), y0)); y1 = fmaf(bf_lo(hk), bf_hi(wa), fmaf(bf_hi(hk), bf_hi(wb), y1));
    }
  };
  auto rb = [](float x) { return bf_lo(pack_bf16(x, 0.f)); };
  auto silu = [&](float x) { x = rb(x); return x / (1.f + expf(-x)); };
#pragma unroll 1
  for (int base = 0; base < p.E; base += 32) {
    const int e = base + lane;
    const uint32_t dl = e < p.E ? (uint32_t)(__ldg(p.dst + e) - nb0) : 0xFFFFFFFFu;
    uint32_t mk = __ballot_sync(~0u, dl < (uint32_t)cntn);
    while (mk) {
      const int l = __ffs(mk) - 1; mk &= mk - 1;
      const int ee = base + l, n = __shfl_sync(~0u, dl, l), s = __ldg(p.src + ee);
      const uint16_t *po = p.pos + (size_t)(nb0 + n) * 3, *pp = p.pos + (size_t)s * 3;
      const uint32_t dxy = hsub(__ldg(po) | (__ldg(po + 1) << 16), __ldg(pp) | (__ldg(pp + 1) << 16)), dz = hsub(__ldg(po + 2), __ldg(pp + 2));
      const uint32_t sq = hsq(dxy); const float d2 = rb(bf_lo(sq) + bf_hi(sq) + bf_lo(hsq(dz)));
      float y0 = d2 * bf_lo(wdv), y1 = d2 * bf_hi(wdv);
      dot(__ldg((const uint32_t*)(p.h + (size_t)(nb0 + n) * 8) + lane), p.we, 32, y0, y1);
      dot(__ldg((const uint32_t*)(p.h + (size_t)s * 8) + lane), p.we + 64 * 64, 32, y0, y1);
      dot(__ldg((const uint32_t*)(p.ea + (size_t)ee * 2) + (lane & 7)), p.we + 129 * 64, 8, y0, y1);
      const uint32_t mm = pack_bf16(silu(y0), silu(y1));
      float c = bf_lo(mm) * bf_lo(wxv) + bf_hi(mm) * bf_hi(wxv);
#pragma unroll
      for (int o = 16; o; o >>= 1) c += __shfl_xor_sync(~0u, c, o);
      const uint32_t a = ab + n * 272;
      uint32_t x0, x1; lds64(x0, x1, a + lane * 8);
      sts64(a + lane * 8, __float_as_uint(__uint_as_float(x0) + bf_lo(mm)), __float_as_uint(__uint_as_float(x1) + bf_hi(mm)));
      if (lane < 3) { const float df = lane == 0 ? bf_lo(dxy) : lane == 1 ? bf_hi(dxy) : bf_lo(dz); sts32(a + 256 + lane * 4, __float_as_uint(rb(rb(c) * df) + __uint_as_float(lds32(a + 256 + lane * 4)))); }
    }
  }
  __syncwarp();
#pragma unroll 1
  for (int n = 0; n < cntn; n++) {
    uint32_t x0, x1; lds64(x0, x1, ab + n * 272 + lane * 8);
    const uint32_t hv = __ldg((const uint32_t*)(p.h + (size_t)(nb0 + n) * 8) + lane);
    float y0 = 0.f, y1 = 0.f;
    dot(hv, p.wh, 32, y0, y1); dot(pack_bf16(__uint_as_float(x0), __uint_as_float(x1)), p.wh + 64 * 64, 32, y0, y1);
    ((uint32_t*)p.out)[(size_t)(nb0 + n) * 32 + lane] = u2(__hadd2(b2(hv), b2(pack_bf16(silu(y0), silu(y1)))));
    if (lane < 3) p.out[(size_t)p.N * 64 + (size_t)(nb0 + n) * 3 + lane] = (uint16_t)pack_bf16(bf_lo(__ldg(p.pos + (size_t)(nb0 + n) * 3 + lane)) + rb(__uint_as_float(lds32(ab + n * 272 + 256 + lane * 4))), 0.f);
  }
}

__global__ void __launch_bounds__(NTHR, 1) egnn_kernel(const __grid_constant__ Params p, const __grid_constant__ Maps maps) {
  extern __shared__ __align__(1024) unsigned char smraw[];
  const int tid = threadIdx.x, cta = blockIdx.x * CTAM % G;
  const int e0 = cta * p.EPC, n4 = max(0, min(p.EPC, p.E - e0)) >> 2;
  STAMP(0);
  asm volatile("{.reg .pred p; setp.lt.s32 p, %1, %2; setp.lt.and.s32 p, %3, %4, p; @p prefetch.global.L2 [%0];}" :: "l"(p.dst + e0 + tid * 32), "r"(tid), "n"(64), "r"(e0 + tid * 32), "r"(p.E));
  if (tid == NWK) {
#pragma unroll 1
    for (int k = 0; k < NCH; k++) { const int nb = max(0, min(NWK, n4 - k * NWK)) * 16;
      mbar_init(sb + BAR_DST + k * 8, 1);
      asm volatile("fence.mbarrier_init.release.cluster;" ::: "memory");
      mbar_expect(sb + BAR_DST + k * 8, nb);
      if (nb) bulk_load(sb + OFF_DST + k * NWK * 16, (const char*)(p.dst + e0) + k * NWK * 16, nb, sb + BAR_DST + k * 8); }
  }
  const int lane = tid & 31, wid = __shfl_sync(~0u, tid >> 5, 0), w = wid & 3;
  asm volatile("{.reg .pred p; setp.eq.u32 p, %2, 384; @p cp.async.cg.shared.global [%0], [%1], 16;}" :: "r"(sb + OFF_LEN - 192 + (tid >> 1)), "l"(p.sync + w * SYS), "r"(tid & 415) : "memory");
  if (__shfl_sync(~0u, tid, 1) - 384u < 96u) {
    asm volatile("cp.async.wait_all;" ::: "memory");
    __syncwarp();
    const uint32_t e = lds32(sb + OFF_LEN + 8 + w * 16) + 1, v = (((1 + e % 3) << 14) + 512 + (lane & 7) * 4) * 0x10001u;
    if (tid == 384) sts32(sb + OFF_MISC + 32, e);
#pragma unroll 1
    for (int i = 0; i < 12; i++) sts128(sb + OFF_SA - 6144 + tid * 16 + i * 1536, v, v + 0x10001u, v + 0x20002u, v + 0x30003u);
    bar_sync(6, 480);
    mbar_arrive(sb + BAR_EP, lane == 0);
  }
  asm volatile("pmevent 1;" ::: "memory");
  uint64_t tmb; asm volatile("mov.u64 %0, %1;" : "=l"(tmb) : "l"(&maps));

  auto first_node = [&](int c) { return (int)((c * p.inv + 0xFFFFFFFFull) >> 32); };
  const int node0 = first_node(cta), nloc = min(first_node(cta + 1), p.N) - node0;
  const uint32_t ealo = (uint32_t)(uint64_t)p.ea;
  const int epad = min(e0, p.E - 1);
  if (wid >= 12) {
    const int t = tid - 384;
    auto load_h = [&](int b) { mbar_expect(sb + BAR_T + b * 8, 8192); tma_load(sb + OFF_H + b * 8192, tmb + TM_H, node0 + b * 64, sb + BAR_T + b * 8); };
    uint32_t pv[9], ev = 0;
#pragma unroll
    for (int i = 0; i < 3; i++) { const uint16_t* pp = p.pos + (size_t)(node0 + t + 128 * i) * 3;
      pv[3 * i] = pv[3 * i + 1] = pv[3 * i + 2] = 0;
      asm volatile("{.reg .pred p; setp.lt.s32 p, %4, %5;\n @p ld.global.nc.u16 %0, [%3];\n @p ld.global.nc.u16 %1, [%3+2];\n @p ld.global.nc.u16 %2, [%3+4];}"
        : "+r"(pv[3 * i]), "+r"(pv[3 * i + 1]), "+r"(pv[3 * i + 2]) : "l"(pp), "r"(t + 128 * i), "r"(p.N - node0)); }
    asm volatile("{.reg .pred p; setp.lt.u32 p, %3, 8; @p ld.global.nc.u32 %0, [%1]; @p st.global.v4.u32 [%2], {%4, %4, %4, %4};}"
      : "+r"(ev) : "l"((const uint32_t*)(p.ea + (size_t)epad * 2) + t), "l"(p.q + (size_t)(p.N + cta * PADM) * 128 + t * 16), "r"(t), "r"(0xF700F700u) : "memory");
    asm volatile("cp.async.wait_all;" ::: "memory");
    __syncwarp();
    const uint32_t e = lds32(sb + OFF_LEN + 8 + w * 16) + 1;
    { const uint32_t tg = (1 + e % 3) << 30;
#pragma unroll
      for (int i = 0; i < 17; i++) sts128(sb + OFF_SB + t * 16 + i * 2048, tg, tg, tg, tg); }
    uint32_t mp = 0;
#pragma unroll
    for (int i = 0; i < 3; i++) { sts64(sb + OFF_POS + (t + 128 * i) * 8, pv[3 * i] | (pv[3 * i + 1] << 16), pv[3 * i + 2]); mp = mag2(mag2(mp, pv[3 * i] | (pv[3 * i + 1] << 16)), pv[3 * i + 2]); }
    proxy_fence();
    if (w == 3) bar_sync(14, 416);
    __syncwarp();
    mbar_arrive(sb + BAR_PS, lane == 0);
    mbar_wait(sb + BAR_W);
    {
      uint32_t v[4], u[4]; const int r = t >> 3, c = t & 7;
      lds128(v, sb + OFF_WS + 128 + t * 16); lds128(u, sb + OFF_WS + c * 16);
      const uint32_t x = lds32(sb + OFF_WS + 2176 + lane * 4);
      sts128(sb + OFF_W3 + r * 128 + ((c ^ (r & 7)) << 4), b2h(v[0], .5f), b2h(v[1], .5f), b2h(v[2], .5f), b2h(v[3], .5f));
      const float s = ((r & 1) || r == 6) ? 0.f : .5f;
      if (t < 64) sts128(sb + OFF_WD + r * 128 + ((c ^ r) << 4), b2h(u[0], s), b2h(u[1], s), b2h(u[2], s), b2h(u[3], s));
      if (t < 32) sts32(sb + OFF_WX + (t & 3) * 32 + (t >> 2) * 4, b2h(x, 1.f));
      const uint32_t m3 = __reduce_max_sync(~0u, magr(mag2(mag2(mag2(mag2(0, v[0]), v[1]), v[2]), v[3]))), md = __reduce_max_sync(~0u, magr(mag2(mag2(mag2(mag2(0, u[0]), u[1]), u[2]), u[3])));
      if (wbad(m3, 0x4000) || wbad(md, 0x4000) || wbad(__reduce_max_sync(~0u, magr(mag2(0, x))), 0x4700) || magr(mp) >= 0x4200 || magr(mag2(0, ev)) >= 0x4380) sts32(sb + OFF_MISC + 8, 1);
    }
    if (w == 1) {
#pragma unroll 1
      for (int b = 0; b < 3; b++) { mbar_wait(sb + BAR_SRC + b * 8); if (lane == 0) load_h(b); }
    }
    bar_sync(3, 128);
    const uint32_t frag = (w * 16 + (lane & 15)) * 128 + (((lane >> 4) ^ (lane & 7)) << 4);
    uint32_t mq = 0; int pfi = 0;
    auto prefetch_e = [&]() {
      const uint32_t nb = PFB;
      if (lane == 0 && nb) asm volatile("cp.async.bulk.prefetch.L2.global [%0], %1;" :: "l"((const char*)p.ea + (size_t)(pfi * G + cta) * nb), "r"(nb) : "memory");
      pfi++; };
#pragma unroll 1
    for (int b = 0; b < 6; b++) {
      float acc[32];
      const uint64_t da = DHI | (((sb + OFF_H) >> 4) + b * 512), db = DHI | ((sb + OFF_W) >> 4);
      const uint32_t v0 = lds16(sb + OFF_POS + b * 512 + w * 128 + lane * 2), v1 = lds16(sb + OFF_POS + 64 + b * 512 + w * 128 + lane * 2);
      mbar_wait(sb + BAR_T + b * 8);
      if (b == 0) STAMP(25);
      if (b == 5) STAMP(26);
      wg_fence();
      ss64<0>(acc, da, db); ss64<1>(acc, da + 2, db + 128); ss64<1>(acc, da + 4, db + 256); ss64<1>(acc, da + 6, db + 384);
      wg_commit();
      if (b == 0) mbar_wait(sb + BAR_AW);
      if (t == 32 && b < 2) { load_h(b * 2 + 3); if (!b) load_h(4); }
      if (w == 1) for (int k = PFE >> (4 * b) & 15; k > 0; k--) prefetch_e();
      __syncwarp();
      uint32_t ff[6], fg[6];
#pragma unroll
      for (int j = 0; j < 6; j++) { ff[j] = (__byte_perm((j & 1) ? v1 : v0, 0, 0x4140) >> (3 * (j >> 1))) & 0x00070007u; fg[j] = __vsub2(0x00040004u, ff[j]);
        asm volatile("" : "+r"(ff[j]), "+r"(fg[j])); }
      wg_wait0(); fence_regs(acc);
      uint32_t o[16];
#pragma unroll
      for (int j = 0; j < 16; j++) o[j] = pack_f16(.5f * acc[2 * j], .5f * acc[2 * j + 1]);
#pragma unroll
      for (int j = 0; j < 6; j++) {
        const uint32_t m = o[j] & 0x7FFF7FFFu; mq = __vmaxu2(mq, m);
        o[j] = (__viaddmax_s16x2(m, fg[j], 0) & 0xFFF8FFF8u) | ff[j] | (o[j] & 0x80008000u); }
      if (b == 4) mbar_wait(sb + BAR_AX);
      const uint32_t qs = sb + OFF_SA + b * 8192;
#pragma unroll
      for (int j = 0; j < 4; j++) stsm4((qs + frag) ^ (j << 5), o[4 * j], o[4 * j + 1], o[4 * j + 2], o[4 * j + 3]);
      proxy_fence();
      __syncwarp();
      if (lane == 0 && b * 64 + w * 16 < nloc) tma_store(tmb + TM_Q, 0, node0 + b * 64 + w * 16, qs + w * 2048);
    }
    if (lane == 0) bulk_commit();
    { const uint32_t m = __reduce_max_sync(~0u, magr(mq)); if (lane == 0) sts32(sb + OFF_MISC + 16 + w * 4, m); }
    asm volatile("setmaxnreg.dec.sync.aligned.u32 56;");
    bulk_wait();
    bar_sync(3, 128);
    if (w == 0) {
      STAMP(18);
      uint32_t mv[4]; lds128(mv, sb + OFF_MISC + 16);
      const uint32_t mx = max(max(mv[0], mv[1]), max(mv[2], mv[3]));
      mbar_arrive(sb + BAR_QR, lane == 0);
      STAMP(19);
      if (lane == 0) {
        if (nloc > 0 && (mx >= 0x7BF0 || mx < 0x1400)) asm volatile("st.relaxed.gpu.global.u32 [%0+4], %1;" :: "l"(p.sync), "r"(e) : "memory");
        asm volatile("red.release.gpu.global.add.u32 [%0], 1;" :: "l"(p.sync) : "memory");
      }
      __syncwarp();
      uint32_t c, f; int spin = 0;
      do { asm volatile("ld.acquire.gpu.global.v2.u32 {%0, %1}, [%2];" : "=r"(c), "=r"(f) : "l"(p.sync) : "memory"); trap_if(++spin > 4000000); } while (__any_sync(~0u, (int)(c - e * G) < 0));
      if (f == e) sts32(sb + OFF_MISC + 8, 1);
      if (cta == 0 && lane < 4) asm volatile("st.relaxed.gpu.global.u32 [%0+8], %1;" :: "l"(p.sync + lane * SYS), "r"(e) : "memory");
      STAMP(20);
      __syncwarp();
      mbar_arrive(sb + BAR_QP, lane == 0);
    }
    if (w == 2) {
      const uint32_t tg = (1 + e % 3) << 30;
      hint_wait(p.sync + 2 * SYS, e * G);
      if (lane == 0) { mbar_expect(sb + BAR_HB, XPAD);
#pragma unroll 1
        for (int o = 0; o < 4; o++) bulk_load(sb + OFF_XB + o * (G * 64), (const char*)p.xb + (size_t)(cta * 4 + o) * (G * 64), G * 64, sb + BAR_HB); }
      STAMP(21);
      bar_sync(7, 384);
      sts32(sb + OFF_XB + XPAD, tg + p.N + cta * PADM);
      const uint32_t nx = __shfl_sync(~0u, lds32(sb + OFF_MISC + 8) ? 0 : lds32(sb + OFF_MISC + 4), 0);
#pragma unroll 1
      for (uint32_t k = 0; k < nx; k += 32) {
        const uint32_t i = min(k + lane, nx - 1), xr = lds32(sb + OFF_EXT + i * 4), row = (xr >> 9) & 255;
        const uint32_t v = ext_get(p.xe + (cta * G + row) * 32 + ((xr >> 17) & 31), e), x = lds32(sb + OFF_CNT + (xr & 511) * 4) + (xr >> 22) * 16;
        sts32(sb + OFF_XB + XPAD + 4 + i * 4, v); sts16(sb + OFF_TS + x, XPAD + 4 + i * 4);
        sts32(sb + OFF_TE + x * 2, mad16(v, 0x2000u, ealo - (tg >> 11) + row * p.EPC * 32));
      }
      __syncwarp();
      mbar_arrive(sb + BAR_HB, lane == 0);
    }
    if (w == 1) {
#pragma unroll 1
      while (pfi < PFN) { prefetch_e(); __nanosleep(PFNS); }
    }
    if (t == 96) { mbar_expect(sb + BAR_U, 8192); tma_load(sb + OFF_W, tmb + TM_WH, 0, sb + BAR_U); }
    __syncwarp();
    bar_sync(4, NTHR);
    const bool fast = !__shfl_sync(~0u, lds32(sb + OFF_MISC + 8), 0);
    if (fast) {
      mp = 0;
#pragma unroll 1
      for (uint32_t todo = UORD; todo; todo >>= 4) {
        const uint32_t nd = lds16(sb + OFF_GP + (todo & 3) * 1024 + w * 256 + (lane & 15) * 8 + 134), hb = (todo >> 3) & 1;
        const uint64_t b1 = DHI | (((sb + OFF_W + 8192) >> 4) + hb * 4);
        uint32_t f[8]; float acc[16];
#pragma unroll
        for (int j = 0; j < 4; j += 2) {
          const uint32_t a = (sb + OFF_H + nd * 128 + (((nd & 7) << 4) ^ (lane & 16))) ^ (j << 5);
          ldsm4(f, a); ldsm4(f + 4, a ^ 32);
          wg_fence();
          if (j == 0) rs32b<0>(acc, f, b1); else rs32b<1>(acc, f, b1 + 256);
          rs32b<1>(acc, f + 4, b1 + 128 * j + 128);
          wg_commit(); wg_wait0(); fence_regs(acc);
        }
#pragma unroll
        for (int j = 0; j < 8; j++) { f[j] = pack_f16(.5f * acc[2 * j], .5f * acc[2 * j + 1]); mp = hmag(mp, f[j]); }
        const uint32_t a = (sb + OFF_P2 + (todo & 3) * 8192 + frag) ^ (hb << 6);
        stsm4(a, f[0], f[1], f[2], f[3]); stsm4(a ^ 32, f[4], f[5], f[6], f[7]);
      }
      if (magr(mp) >= 0x7000) sts32(sb + OFF_MISC + 12, 1);
    }
    bar_sync(3, 128);
    if (t == 96) { mbar_expect(sb + BAR_U, 8192); tma_load(sb + OFF_W + 8192, tmb + TM_WH, 64, sb + BAR_U); }
    __syncwarp();
    mbar_wait(sb + BAR_U);
    uint32_t mh = 0;
#pragma unroll 1
    for (int i = t; i < 1024; i += 128) {
      uint32_t v[4]; const uint32_t r = (i >> 3) & 7, j = (i ^ r) & 7;
#pragma unroll
      for (int k = 0; k < 4; k++) v[k] = lds32(sb + OFF_W + (i >> 3) * 128 + ((((j & 4) + k) ^ r) << 4) + (j & 3) * 4);
      __syncwarp();
      if (i < 512) sts128(sb + OFF_W + i * 16, hhalf(v[0]), hhalf(v[1]), hhalf(v[2]), hhalf(v[3]));
      else { sts128(sb + OFF_W + i * 16, b2h(v[0], .5f), b2h(v[1], .5f), b2h(v[2], .5f), b2h(v[3], .5f)); mh = mag2(mag2(mag2(mag2(mh, v[0]), v[1]), v[2]), v[3]); } }
    if (wbad(__reduce_max_sync(~0u, magr(mh)), 0x4700)) sts32(sb + OFF_MISC + 12, 1);
    proxy_fence();
    __syncwarp();
    mbar_arrive(sb + BAR_WH, lane == 0);
    if (fast) {
      mbar_wait(sb + BAR_WH);
      float chk = 0.f;
#pragma unroll 1
      for (uint32_t todo = UORD; todo; todo >>= 4) {
        const uint32_t nd = lds16(sb + OFF_GP + (todo & 3) * 1024 + w * 256 + (lane & 15) * 8 + 6), hb = (todo >> 3) & 1;
        const uint64_t b1 = DHI | (((sb + OFF_W) >> 4) + hb * 4);
        uint32_t f[8]; float acc[16];
#pragma unroll
        for (int j = 0; j < 8; j += 2) {
          const uint32_t a = j < 4 ? sb + OFF_H + nd * 128 + (((nd & 7) << 4) ^ (lane & 16)) : sb + OFF_P2 + (todo & 3) * 8192 + frag;
          if (j == 4) mbar_wait(sb + BAR_M + (todo & 3) * 8);
          ldsm4(f, a ^ ((j & 3) << 5)); ldsm4(f + 4, a ^ ((j & 3) << 5) ^ 32);
          wg_fence();
          if (j == 0) rs32b<0>(acc, f, b1); else if (j < 4) rs32b<1>(acc, f, b1 + 128 * j); else rs32h(acc, f, b1 + 128 * j);
          if (j < 4) rs32b<1>(acc, f + 4, b1 + 128 * j + 128); else rs32h(acc, f + 4, b1 + 128 * j + 128);
          wg_commit(); wg_wait0(); fence_regs(acc);
        }
        chk = fmaf(acc[0], 0.f, fmaf(acc[2], 0.f, chk));
#pragma unroll
        for (int k = 0; k < 2; k++) {
          const uint32_t o = __shfl_sync(~0u, nd, (lane >> 2) + 8 * k) * 128 + (lane & 3) * 16 + hb * 64;
          uint32_t x[4]; lds128(x, sb + OFF_H + (o ^ ((o >> 3) & 0x70)));
#pragma unroll
          for (int i = 0; i < 4; i++) x[i] = u2(__hadd2(b2(x[i]), b2(pack_bf16(silu_h(acc[4 * i + 2 * k]), silu_h(acc[4 * i + 2 * k + 1])))));
          if (o < nloc * 128) *(uint4*)((char*)p.out + (size_t)node0 * 128 + o) = make_uint4(x[0], x[1], x[2], x[3]);
        }
        __nanosleep(DEFNS);
      }
      uint32_t pa_[9];
#pragma unroll
      for (int k = 0; k < 9; k++) { const uint32_t i = t + 128 * k, n = (i * 43691u) >> 17; pa_[k] = lds16(sb + OFF_INV + n * 2) + (i - 3 * n) * 2; }
      uint16_t* po = p.out + (size_t)p.N * 64 + node0 * 3 + t;
      mbar_wait(sb + BAR_X);
#pragma unroll
      for (int k = 0; k < 9; k++) pa_[k] = lds16(sb + OFF_GP + pa_[k]);
#pragma unroll
      for (int k = 0; k < 9; k++) if (t + 128 * k < nloc * 3) po[128 * k] = pa_[k];
      asm volatile("{.reg .pred p, q; setp.neu.f32 p, %0, 0f00000000; bar.red.or.pred q, 5, 512, p;}" :: "f"(chk) : "memory");
    }
    return;
  }

  if (tid == 320) {
    mbar_init(sb + BAR_W, 1);
    asm volatile("fence.mbarrier_init.release.cluster;" ::: "memory");
    mbar_expect(sb + BAR_W, 2 * 8192 + 2304);
    tma_load(sb + OFF_W, tmb + TM_WE, 64, sb + BAR_W); tma_load(sb + OFF_W + 8192, tmb + TM_WE, 0, sb + BAR_W);
    bulk_load(sb + OFF_WS, p.we + 128 * 64, 2176, sb + BAR_W); bulk_load(sb + OFF_WS + 2176, p.wx, 128, sb + BAR_W);
  }
  if (tid == 288) {
#pragma unroll
    for (int a = BAR_SRC; a < BAR_END; a += 8) if (a != BAR_W) mbar_init(sb + a, a == BAR_X ? 12 : a >= BAR_WH || a == BAR_PS ? 4 : a == BAR_EP ? 3 : a == BAR_HB || a == BAR_U ? 2 : 1);
    asm volatile("fence.mbarrier_init.release.cluster;" ::: "memory");
    asm volatile("prefetch.tensormap [%0];" :: "l"(tmb + TM_XA)); asm volatile("prefetch.tensormap [%0];" :: "l"(tmb + TM_H));
    asm volatile("prefetch.tensormap [%0];" :: "l"(tmb + TM_XB)); asm volatile("prefetch.tensormap [%0];" :: "l"(tmb + TM_Q));
  }
  {
    if (tid < 144) sts128(sb + OFF_CNT + tid * 16, 0, 0, 0, 0);
    else if (tid <= 144 + G) sts32(sb + OFF_BC + (tid - 144) * 4, ((tid - 144) & 31) * 4);
    const uint32_t sp = XPAD * 0x10001u, em = first_node(G);
    if (wid < 7) {
#pragma unroll
      for (int i = 0; i < 4; i++) sts128(sb + OFF_TS + tid * 16 + i * 3584, sp, sp, sp, sp);
    }
    static_assert(SCAP * 32 == 4 * 3584, "fill");
#pragma unroll 1
    for (int i = n4 + tid; i < 1536; i += 384) sts128(sb + OFF_DST + i * 16, em, em, em, em);
    if (tid == 321) sts128(sb + OFF_MISC, 0, 0, p.force_slow, 0);
  }
  bar_arrive(6, 480);
  bar_arrive(14, 416);
  bar_sync(0, 384);
  uint32_t ep, tag, eb0, pk[12], r0[12], r1[12], cb;
  uint2 vb[12];
  auto get_tag = [&]() { mbar_wait(sb + BAR_EP); ep = lds32(sb + OFF_MISC + 32); tag = (1 + ep % 3) << 30; eb0 = ealo - (tag >> 11); };
  if (wid == 11) {
    trap_if(sb != (uint32_t)__cvta_generic_to_shared(smraw));
#pragma unroll 1
    for (int k = 0; k < 3; k++) { const int nb = max(0, min(8192, n4 * 16 - k * 8192));
      mbar_wait(sb + BAR_DST + (k ? k + 1 : 0) * 8);
      if (lane == 0) { mbar_expect(sb + BAR_SRC + k * 8, nb);
        if (nb) bulk_load(sb + OFF_SRCI + k * 8192, (const char*)(p.src + e0) + k * 8192, nb, sb + BAR_SRC + k * 8); } }
    proxy_fence();
    get_tag();
    mbar_wait(sb + BAR_PS);
    bar_sync(12, 384);
    uint32_t xm = 0;
#pragma unroll
    for (int k = 0; k < 5; k++) xm |= (lds32(sb + OFF_BC + min(lane + 32 * k, G - 1) * 4) >= (65 << 9) && lane + 32 * k < G) << k;
    auto ext_send = [&](int pl) {
      uint32_t x = xm;
      for (uint32_t m; (m = __ballot_sync(~0u, x));) {
        const uint32_t l = __ffs(m) - 1, j = l + 32 * (__ffs(__shfl_sync(~0u, x, l)) - 1);
        if (lane == l) x &= x - 1;
        const uint32_t e = min(lds16(sb + OFF_AX + j * 128 + ((4 * l + 2 * lane) & 126)), 6143u);
        if (pl) st_ext(p.xe + (j * G + cta) * 32 + lane, lds32(sb + OFF_SRCI + e * 4) + tag + (e << 16), ep);
        else { const uint32_t cn = lds32(sb + OFF_BC + j * 4) >> 9, v = cn > 96 ? 1 : lane + 64 < cn ? 512 | (lds32(sb + OFF_DST + e * 4) & 511) : 0;
          asm volatile("red.shared.xor.b32 [%0], %1;" :: "r"(sb + OFF_SA + j * 128 + ((l + lane) & 31) * 4), "r"(((v & 63) << 10) | ((v >> 6) << 26)) : "memory"); }
      }
    };
    if (__any_sync(~0u, xm)) { ext_send(0); proxy_fence(); __syncwarp(); }
    if (lane == 0) { tma_store(tmb + TM_XA, cta * 64, 0, sb + OFF_SA); bulk_commit(); mbar_arrive(sb + BAR_AI); bulk_wait(); hint_signal(p.sync + SYS); mbar_arrive(sb + BAR_AW); STAMP(16); }
    __syncwarp();
    bar_sync(13, 384);
    ext_send(1);
    mbar_arrive(sb + BAR_AX, lane == 0);
    mbar_wait(sb + BAR_HA);
    mbar_wait(sb + BAR_T + BT * 8);
    __nanosleep(BDEL);
    if (lane == 0) {
#pragma unroll 1
      for (int k = 0; k < G / BROWS; k++) { const int r = (k + cta) % (G / BROWS) * BROWS; tma_store(tmb + TM_XB, cta * 64, r, sb + OFF_SB + r * 256); bulk_commit(); bulk_wait(); }
      hint_signal(p.sync + 2 * SYS);
      STAMP(17);
    }
    __syncwarp();
  } else {
    {
      uint32_t d[4 * NCH], jj[4 * NCH], rr[4 * NCH];
      auto count = [&](int k) {
        mbar_wait(sb + BAR_DST + k * 8);
        lds128(d + 4 * k, sb + OFF_DST + (tid + NWK * k) * 16);
#pragma unroll
        for (int i = 4 * k; i < 4 * k + 4; i++) { jj[i] = d[i] * p.magic; rr[i] = atoms_add(__dp4a(jj[i], 0x04000000u, sb + OFF_BC), 0x202u); }
      };
      auto place = [&](int k) {
#pragma unroll
        for (int i = 4 * k; i < 4 * k + 4; i++) {
          const uint32_t o = __dp4a(jj[i], 0x80000000u, rr[i] & 0x807Eu);
          d[i] = (d[i] & 511) | (tag >> 16);
          asm("{.reg .pred p; setp.ge.u32 p, %1, 0x8000; @p add.u32 %0, %2, %3;}" : "+r"(d[i]) : "r"(o), "r"(tid * 4), "r"(NWK * k * 4 + (i & 3)));
          sts16(sb + OFF_SA + o, d[i]); jj[i] = __viaddmin_u32(o, o, G * 256);
        }
      };
      count(0); STAMP(1); count(1); get_tag(); place(0); count(2); place(1); count(3); place(2);
      if (wid < 4) { count(4); STAMP(15); place(3); place(4); } else place(3);
      proxy_fence();
      bar_arrive(12, 384);
      STAMP(2);
      mbar_wait(sb + BAR_AI);
      mbar_wait(sb + BAR_SRC); mbar_wait(sb + BAR_SRC + 8); mbar_wait(sb + BAR_SRC + 16);
      STAMP(12);
#pragma unroll
      for (int k = 0; k < NCH; k++) lds128(d + 4 * k, sb + OFF_SRCI + (tid + NWK * k) * 16);
      const uint32_t tb = tag + (tid << 18);
#pragma unroll
      for (int i = 0; i < 4 * NCH; i++) if (i < 4 * NCH - 4 || wid < 4) sts32(sb + OFF_SB + jj[i], d[i] + tb + ((NWK * (i >> 2) * 4 + (i & 3)) << 16));
      proxy_fence();
      bar_arrive(13, 384);
      STAMP(3);
    }
    const uint32_t rot = (lane + cta) & 31;
    cb = sb + OFF_CNT - (tag >> 14);
    {
      const uint32_t* xa = (const uint32_t*)(p.xa + (cta * G + wid) * 8) + rot;
      if (wid < 8) { const uint32_t e_ = ealo + epad * 32;
        mbar_wait(sb + BAR_AX);
#pragma unroll
        for (int i = 0; i < 7; i++) sts128(sb + OFF_TE + tid * 16 + i * 4096, e_, e_, e_, e_); }
      static_assert(SCAP * 64 == 7 * 4096, "fill");
      if (wid == 10) { hint_wait(p.sync + SYS, ep * G); mbar_arrive(sb + BAR_HA, lane == 0); }
      mbar_wait(sb + BAR_HA);
      STAMP(14);
      const uint32_t tp = tag | (tag >> 16);
      uint32_t st;
#pragma unroll 1
      for (int spin = 0;; spin++) {
        st = 0;
#pragma unroll
        for (int k = 0; k < 12; k++) asm volatile("ld.relaxed.gpu.global.u32 %0, [%1];" : "=r"(pk[k]) : "l"(xa + k * 352) : "memory");
#pragma unroll
        for (int k = 0; k < 12; k++) st |= pk[k] ^ tp;
        st = __reduce_or_sync(~0u, st);
        if (!(st >> 30)) break;
        trap_if(spin > 2000000);
      }
      if (st & 0x3C00FC00u) {
#pragma unroll 1
        for (;;) {
          uint32_t x = 0, row = 0;
#pragma unroll
          for (int k = 0; k < 12; k++) { const uint32_t y = (pk[k] ^ tp) & 0x3C00FC00u; if (!x && y) { x = y; row = wid + 11 * k; pk[k] ^= y; } }
          if (!__any_sync(~0u, x)) break;
          const uint32_t n = ((x >> 10) & 63) | ((x >> 20) & 0x1C0);
          if (x >> 29) {
            const uint32_t r = atoms_add(sb + OFF_CNT + n * 4, 16), idx = atoms_add(sb + OFF_MISC + 4, 1);
            if (idx < 256) sts32(sb + OFF_EXT + idx * 4, n | (row << 9) | (lane << 17) | (min(r >> 4, 255u) << 22));
            else x = 1;
          }
          if (x && !(x >> 29)) sts32(sb + OFF_MISC + 8, 1);
          __syncwarp();
        }
      }
#pragma unroll
      for (int k = 0; k < 12; k++) { r0[k] = mad16(pk[k], 0x0004u, cb); r1[k] = mad16(pk[k], 0x0400u, cb); vb[k].x = atoms_add(r0[k], 16); vb[k].y = atoms_add(r1[k], 16); }
    }
    STAMP(4);
    if (wid >= 6) bar_arrive(11, NWK);
    if (wid < 6) {
      uint32_t ca[2], ky[2], dr[2], sq[2], ps[4];
#pragma unroll
      for (int i = 0; i < 2; i++) { ca[i] = sb + OFF_CNT + ((node0 + tid + 192 * i) & 511) * 4; lds64(ps[2 * i], ps[2 * i + 1], sb + OFF_POS + (tid + 192 * i) * 8); ps[2 * i + 1] |= (tid + 192 * i) << 16; }
      bar_sync(11, NWK);
      STAMP(5);
#pragma unroll
      for (int i = 0; i < 2; i++) ky[i] = (lds32(ca[i]) + 16) >> 5;
      if (max(ky[0], ky[1]) > 31) sts32(sb + OFF_MISC + 8, 1);
#pragma unroll
      for (int i = 0; i < 2; i++) { ky[i] = min(ky[i], 31u); dr[i] = atoms_add(sb + OFF_DH + ky[i] * 4, 1); }
      bar_sync(10, 192);
      const uint32_t hv = lds32(sb + OFF_DH + lane * 4);
      uint32_t inc = hv;
#pragma unroll
      for (int o = 1; o < 32; o <<= 1) asm("{.reg .pred p; .reg .b32 y; shfl.sync.down.b32 y|p, %0, %1, 31, -1; @p add.u32 %0, %0, y;}" : "+r"(inc) : "r"(o));
#pragma unroll
      for (int i = 0; i < 2; i++) {
        const uint32_t pos = __shfl_sync(~0u, inc - hv, ky[i]) + dr[i];
        const uint32_t ak = (uint32_t)(QCODE >> ((pos >> 5) * 4)) & 15, l = (pos >> 3) & 3;
        sq[i] = (ak >> 2) * 16 + ((QREV >> (pos >> 5) & 1) ? 3 - l : l) * 4 + (ak & 3);
        dr[i] = pos & 7;
        asm volatile("{.reg .pred p; setp.eq.u32 p, %2, 0; @p st.shared.u8 [%0], %1;}" :: "r"(sb + OFF_LEN + sq[i]), "r"(max(ky[i], 1u)), "r"(dr[i]) : "memory");
        sts64(sb + OFF_GP + sq[i] * 64 + dr[i] * 8, ps[2 * i], ps[2 * i + 1]);
        sts16(sb + OFF_INV + (tid + 192 * i) * 2, sq[i] * 64 + dr[i] * 8);
      }
      bar_sync(10, 192);
      const uint32_t ln = lds32(sb + OFF_LEN + min(lane, 11) * 4), tot = __dp4a(ln, 0x01010101u, 0u);
      inc = tot;
#pragma unroll
      for (int o = 1; o < 16; o <<= 1) asm("{.reg .pred p; .reg .b32 y; shfl.sync.up.b32 y|p, %0, %1, 0, -1; @p add.u32 %0, %0, y;}" : "+r"(inc) : "r"(o));
      if (tid < 12) { sts32(sb + OFF_LEN + 64 + tid * 4, inc - tot); if (inc > SCAP - 12) sts32(sb + OFF_MISC + 8, 1); }
#pragma unroll
      for (int i = 0; i < 2; i++) sts32(ca[i], __dp4a(__shfl_sync(~0u, ln, sq[i] >> 2), 0x00010101u >> (24 - 8 * (sq[i] & 3)), __shfl_sync(~0u, inc - tot, sq[i] >> 2)) * 32 + dr[i] * 2);
    }
    bar_arrive(7, 384);
    bar_arrive(9, 384);
  }
  if (wid == 11) bar_sync(9, 384); else bar_sync(1, NWK);
  STAMP(6);
  if (wid != 11 && !__shfl_sync(~0u, lds32(sb + OFF_MISC + 8), 0)) {
#pragma unroll
    for (int k = 0; k < 12; k++) asm volatile("{.reg .pred p, q; setp.lt.u32 p, %0, %2; setp.lt.u32 q, %1, %2; @p ld.shared.u32 %0, [%0]; @q ld.shared.u32 %1, [%1];}" : "+r"(r0[k]), "+r"(r1[k]) : "n"(sb + OFF_CNT + 2048) : "memory");
#pragma unroll
    for (int k = 0; k < 12; k++) { r0[k] += vb[k].x; r1[k] += vb[k].y; }
  } else {
#pragma unroll
    for (int k = 0; k < 12; k++) r0[k] = r1[k] = 0x8000;
  }
  auto put_ids = [&]() {
    const uint32_t id = wid * 256 + ((lane + cta) & 31) * 8;
    auto put = [&](uint32_t x, uint32_t v) { asm volatile("{.reg .pred p; setp.lt.u32 p, %0, 0x8000; @p st.shared.u16 [%0+%2], %1;}" :: "r"(x), "h"((uint16_t)v), "n"(sb + OFF_TS) : "memory"); };
#pragma unroll
    for (int k = 0; k < 12; k++) { put(r0[k], id + k * 2816); put(r1[k], id + k * 2816 + 4); }
  };
  STAMP(7);
  mbar_wait(sb + BAR_QR);
  asm volatile("setmaxnreg.inc.sync.aligned.u32 152;");
  uint32_t pa[8], sp[8]; float chk = 0.f;
  {
    uint32_t hf[16], mp = 0; float a0[32];
    const uint32_t nd = lds16(sb + OFF_GP + wid * 256 + (lane & 15) * 8 + 6);
#pragma unroll
    for (int j = 0; j < 4; j++) ldsm4(hf + 4 * j, (sb + OFF_H + nd * 128 + (((nd & 7) << 4) ^ (lane & 16))) ^ (j << 5));
    const uint64_t db = DHI | ((sb + OFF_W + 8192) >> 4);
    wg_fence();
    rs64b<0>(a0, hf[0], hf[1], hf[2], hf[3], db); rs64b<1>(a0, hf[4], hf[5], hf[6], hf[7], db + 128); rs64b<1>(a0, hf[8], hf[9], hf[10], hf[11], db + 256); rs64b<1>(a0, hf[12], hf[13], hf[14], hf[15], db + 384);
    wg_commit();
    put_ids();
    wg_wait0(); fence_regs(a0);
#pragma unroll
    for (int j = 0; j < 8; j++) { const uint32_t x = pack_f16(.5f * a0[4 * j], .5f * a0[4 * j + 1]), y = pack_f16(.5f * a0[4 * j + 2], .5f * a0[4 * j + 3]); mp = hmag(hmag(mp, x), y);
      asm volatile("movmatrix.sync.aligned.m8n8.trans.b16 %0, %1;" : "=r"(pa[j]) : "r"(x)); asm volatile("movmatrix.sync.aligned.m8n8.trans.b16 %0, %1;" : "=r"(sp[j]) : "r"(y)); }
    if (magr(mp) >= 0x7000) chk = 1.f;
  }
  if (wid == 0) STAMP(23);
  uint32_t bad;
  {
    const uint32_t ring = sb + OFF_RING + wid * STG, p2 = sb + OFF_P2 + wid * 2048;
    uint32_t lens = __shfl_sync(~0u, lds32(sb + OFF_LEN + wid * 4), 0);
    uint32_t rem = __dp4a(lens, 0x20202020u, 0u);
    const uint32_t base = min(lds32(sb + OFF_LEN + 64 + wid * 4), SCAP);
    uint32_t a_s = sb + OFF_TS + base * 32 + (lane >> 3) * 8, a_e = sb + OFF_TE + base * 64 + (lane >> 1) * 4;
    uint32_t k0 = (uint32_t)(uint64_t)p.q + (((lane & 7) ^ ((lane >> 1) & 4)) << 4), k1 = k0 ^ 16, k2 = k0 ^ 32, k3 = k0 ^ 48, ke = ((lane ^ (lane >> 3)) & 1) << 4;
    uint32_t dst0 = ring + (lane >> 3) * 640 + (lane & 7) * 16;
    const uint32_t qhi = (uint32_t)((uint64_t)p.q >> 32), ehi = (uint32_t)((uint64_t)p.ea >> 32);
    uint32_t s0, s1, ev, to = 0, so = 12 * STG;
    auto tl_ = [&]() { lds64(s0, s1, a_s + to); asm volatile("ld.shared.u32 %0, [%1]; add.u32 %1, %1, 64;" : "=&r"(ev), "+r"(a_e) :: "memory"); to += 32; };
#define CPQ(LH, x, k, off) "dp2a." LH ".u32.u32 lo, " x ", 0x80000080, " k "; mov.b64 a, {lo, %7}; @p cp.async.cg.shared.global [%0+" #off "], [a], 16;\n"
    uint64_t pe; asm volatile("createpolicy.fractional.L2::evict_normal.b64 %0, 1.0;" : "=l"(pe));
    uint32_t one = __shfl_sync(~0u, lane, 1);
#define CPE "or.b32 lo, %10, %11; mov.b64 a, {lo, %12}; @p cp.async.cg.shared.global.L2::cache_hint [%0+512], [a], 16, %13;\n"
#define CPA(BODY) asm volatile("{.reg .b32 lo; .reg .b64 a; .reg .pred p; setp.le.u32 p, %8, %9;\n" BODY "}" \
      :: "r"(so * one + dst0), "r"(s0), "r"(s1), "r"(k0), "r"(k1), "r"(k2), "r"(k3), "r"(qhi), "r"(to), "r"(rem), "r"(ev), "r"(ke), "r"(ehi), "l"(pe) : "memory")
#define CPQ4 CPQ("lo", "%1", "%3", 0) CPQ("hi", "%1", "%4", 128) CPQ("lo", "%2", "%5", 256) CPQ("hi", "%2", "%6", 384) "cp.async.commit_group;"
    auto issue = [&]() { CPA(CPE CPQ4); so = so == (NST - 1) * 12 * STG ? 0 : so + 12 * STG; };
    const int g = lane >> 2, qd = lane & 3;
    const uint32_t sw = ((lane >> 4) ^ (lane & 7)) << 4, fr = (lane & 15) * 128 + sw;
    uint32_t qa0 = ring + (g & 3) * 640 + qd * 128 + sw, qa1 = qa0 ^ 32, qa2 = qa0 ^ 64, qa3 = qa0 ^ 96;
    uint32_t eadr = ring + 512 + (g & 3) * 640 + qd * 32 + ((((lane >> 4) ^ g) & 1) << 4);
    uint32_t oh0 = g == 2 * qd ? 0x3C00u : g == 2 * qd + 1 ? 0x3C000000u : 0u, oh1 = oh0;
    uint32_t a_g = sb + OFF_GP + wid * 256 + lane * 2;
    asm volatile("shfl.sync.idx.b32 %0, %0, %1, 31, -1;" : "+r"(oh1) : "r"(lane));
    uint32_t w3[16], wv[8], bp[16], sum[8], Y[16], M[16], own, ownp, dpk, tl[16], th[16];
    float pacc = 0.f;
    auto wload = [&]() {
#pragma unroll
      for (int j = 0; j < 4; j++) ldsm4t(w3 + 4 * j, (sb + OFF_W3 + fr) ^ (j << 5));
      lds128(wv, sb + OFF_WX + (a_g & 6) * 16); lds128(wv + 4, sb + OFF_WX + 16 + (a_g & 6) * 16);
    };
    auto hload = [&](uint32_t (&hf)[16], uint32_t nd) {
      const uint32_t hrow = sb + OFF_H + nd * 128 + (((nd & 7) << 4) ^ ((a_g >> 1) & 16));
#pragma unroll
      for (int j = 0; j < 4; j++) ldsm4(hf + 4 * j, hrow ^ (j << 5));
      return hrow;
    };
    { uint32_t wd[8]; const uint32_t a = sb + OFF_WD + (lane & 7) * 128 + ((((lane >> 3) ^ lane) & 7) << 4);
      ldsm4t(wd, a); ldsm4t(wd + 4, a ^ 64);
#pragma unroll
      for (int j = 0; j < 8; j++) { bp[2 * j] = wd[j]; bp[2 * j + 1] = pa[j]; } }
    own = lds16(a_g) * 0x10001u;
    wload();
    if (__shfl_sync(~0u, lds32(sb + OFF_MISC + 8), 0)) rem = 0;
    auto resolve = [&](auto NBK, uint32_t o) {
      constexpr int NB = decltype(NBK)::value;
      uint32_t id[NB], c0[NB], c1[NB]; const uint32_t a = base * 32 + o + lane * 4;
#pragma unroll
      for (int i = 0; i < NB; i++) { id[i] = lds32(sb + OFF_TS + a + i * 128); if (o + lane * 4 + i * 128 >= rem) id[i] = XPAD * 0x10001u; }
      uint32_t st = 0;
#pragma unroll
      for (int i = 0; i < NB; i++) { c0[i] = lds32(sb + OFF_XB + (id[i] & 0xFFFF)); c1[i] = lds32(sb + OFF_XB + (id[i] >> 16)); }
#pragma unroll
      for (int i = 0; i < NB; i++) st |= (c0[i] ^ tag) | (c1[i] ^ tag);
      for (int spin = 0; __any_sync(~0u, st >> 30); spin++) {
        st = 0; trap_if(spin > 2000000);
#pragma unroll
        for (int i = 0; i < NB; i++) {
          asm volatile("{.reg .pred p, q; setp.lt.u32 p, %4, %6; setp.lt.u32 q, %5, %6; @p ld.relaxed.gpu.global.u32 %0, [%2]; @q ld.relaxed.gpu.global.u32 %1, [%3];}"
            : "+r"(c0[i]), "+r"(c1[i]) : "l"((const char*)p.xb + cta * XPAD + (id[i] & 0xFFFF)), "l"((const char*)p.xb + cta * XPAD + (id[i] >> 16)), "r"(id[i] & 0xFFFF), "r"(id[i] >> 16), "n"(XPAD) : "memory");
          st |= (c0[i] ^ tag) | (c1[i] ^ tag); }
      }
#pragma unroll
      for (int i = 0; i < NB; i++) { const uint32_t j0 = (id[i] >> 8) & 255, j1 = id[i] >> 24;
        asm volatile("{.reg .pred p, q, r; setp.lt.u32 p, %5, %9; setp.lt.u32 q, %6, %9; setp.lt.u32 r, %7, %8;\n"
          "@p st.shared.u32 [%0], %2; @q st.shared.u32 [%0+4], %3; @r st.shared.u32 [%1], %4;}"
          :: "r"(sb + OFF_TE + 2 * a + i * 256), "r"(sb + OFF_TS + a + i * 128), "r"(mad16(c0[i], 0x2000u, eb0 + j0 * p.EPC * 32)), "r"(mad16(c1[i], 0x2000u, eb0 + j1 * p.EPC * 32)),
             "r"(__byte_perm(c0[i], c1[i], 0x5410)), "r"(j0), "r"(j1), "r"(o + lane * 4 + i * 128), "r"(rem), "n"(G) : "memory"); }
    };
    bar_sync(2, 384);
    if (wid == 0) STAMP(27);
    mbar_wait(sb + BAR_HB);
    if (wid == 0) STAMP(22);
#pragma unroll 1
    for (uint32_t o = 0, go = 0; go < 32 * NST; o += 128 * RNB) {
      if (o < rem) { resolve(IC<RNB>(), o);
        asm volatile("{.reg .pred p; mbarrier.test_wait.parity.shared::cta.b64 p, [%1], 0; vote.sync.all.pred p, p, -1; selp.u32 %0, %2, 0, p;}" : "=r"(go) : "r"(sb + BAR_QP), "n"(32 * NST - 32) : "memory"); }
      else { bar_arrive(4, NTHR); bar_sync(8, 384); mbar_wait(sb + BAR_QP); go = 32 * NST; if (wid == 0) STAMP(24); }
      __syncwarp();
#pragma unroll 1
      while (to < go) { tl_(); issue(); if (to == 32) STAMP(13); }
    }
    bad = __shfl_sync(~0u, lds32(sb + OFF_MISC + 8), 0);
   if (!bad) {
    auto body = [&](auto MODE) {
      constexpr int mode = decltype(MODE)::value;
      uint32_t T[16], ef[4], q0, q1, x0, x1, x2; float e0_, e1_, cs[4];
      auto mu = [&](int j) {
#pragma unroll
        for (int i = 2 * j; i < 2 * j + 2; i++) asm volatile("{.reg .b16 l, h; mov.b32 {l, h}, %2; tanh.approx.f16 l, l; tanh.approx.f16 h, h; cvt.u32.u16 %0, l; cvt.u32.u16 %1, h;}" : "=r"(tl[i]), "=r"(th[i]) : "r"(Y[i])); };
      auto fi = [&](int j) {
#pragma unroll
        for (int i = 2 * j; i < 2 * j + 2; i++) asm volatile("{.reg .b32 t; prmt.b32 t, %2, %3, 0x5410; fma.rn.f16x2 %0, %1, t, %1;}" : "=r"(M[i]) : "r"(Y[i]), "r"(tl[i]), "r"(th[i])); };
      auto ad = [&](int j) { asm volatile("add.rn.f16x2 %0, %0, %1; add.rn.f16x2 %0, %0, %2;" : "+r"(sum[j]) : "r"(M[2 * j]), "r"(M[2 * j + 1])); };
      auto he = [&](int j) { asm volatile("mma.sync.aligned.m16n8k16.row.col.f16.f16.f16.f16 {%0,%1}, {%2,%3,%4,%5}, {%6,%7}, {%0,%1};" : "+r"(T[2 * j]), "+r"(T[2 * j + 1]) : "r"(ef[0]), "r"(ef[1]), "r"(ef[2]), "r"(ef[3]), "r"(w3[2 * j]), "r"(w3[2 * j + 1])); };
      auto hs = [&](int j) { asm volatile("mma.sync.aligned.m16n8k16.row.col.f16.f16.f16.f16 {%0,%1}, {%2,%3,%4,%5}, {%6,%7}, {%8,%9};" : "=r"(Y[2 * j]), "=r"(Y[2 * j + 1]) : "r"(q0), "r"(q1), "r"(oh0), "r"(oh1), "r"(bp[2 * j]), "r"(bp[2 * j + 1]), "r"(T[2 * j]), "r"(T[2 * j + 1])); };
      auto hc = [&](int j) {
        if (j) asm volatile("mma.sync.aligned.m16n8k16.row.col.f32.f16.f16.f32 {%0,%1,%2,%3}, {%4,%5,%6,%7}, {%8,%9}, {%0,%1,%2,%3};" : "+f"(cs[0]), "+f"(cs[1]), "+f"(cs[2]), "+f"(cs[3]) : "r"(M[4 * j]), "r"(M[4 * j + 1]), "r"(M[4 * j + 2]), "r"(M[4 * j + 3]), "r"(wv[2 * j]), "r"(wv[2 * j + 1]));
        else asm volatile("mma.sync.aligned.m16n8k16.row.col.f32.f16.f16.f32 {%0,%1,%2,%3}, {%4,%5,%6,%7}, {%8,%9}, {%10,%10,%10,%10};" : "=f"(cs[0]), "=f"(cs[1]), "=f"(cs[2]), "=f"(cs[3]) : "r"(M[0]), "r"(M[1]), "r"(M[2]), "r"(M[3]), "r"(wv[0]), "r"(wv[1]), "f"(0.f)); };
      auto cv = [&](int i) { asm volatile("{.reg .b32 a, b; shl.b32 a, %0, 16; and.b32 b, %0, 0xFFFF0000; cvt.rn.f16x2.f32 %0, b, a;}" : "+r"(ef[i])); };
      auto un = [&]() { asm volatile("shl.b32 %0, %2, 16; and.b32 %1, %2, 0xFFFF0000;" : "=&f"(e0_), "=&f"(e1_) : "r"(dpk)); };
      auto ex0 = [&]() { asm volatile("prmt.b32 %0, %3, %4, 0x6420; prmt.b32 %1, %5, %6, 0x6420; prmt.b32 %2, %7, %8, 0x6420;" : "=&r"(x0), "=&r"(x1), "=&r"(x2) : "r"(T[0]), "r"(T[1]), "r"(T[2]), "r"(T[3]), "r"(T[4]), "r"(T[5])); };
      auto ex1 = [&]() { asm volatile("{.reg .b32 a, b; shl.b32 a, %2, 3; shl.b32 b, %3, 6; lop3.b32 a, %1, a, 0x38383838, 0xD8; lop3.b32 a, a, b, 0xC0C0C0C0, 0xD8; sub.rn.bf16x2 %0, %4, a;}" : "=r"(dpk) : "r"(x0), "r"(x1), "r"(x2), "r"(own)); };
      auto ex2 = [&]() { asm volatile("{.reg .b32 a, b, d, u; .reg .b16 l, h; shl.b32 a, %2, 16; and.b32 b, %2, 0xFFFF0000; cvt.rn.f16x2.f32 d, b, a; mul.rn.f16x2 %0, d, d; mov.b32 {l, h}, d; mov.b32 u, {h, h}; mul.rn.f16x2 %1, u, u;}" : "=&r"(q0), "=&r"(q1) : "r"(dpk)); };
      auto pf = [&]() { asm volatile("fma.rn.f32 %0, %1, %2, %0; fma.rn.f32 %0, %3, %4, %0;" : "+f"(pacc) : "f"(cs[0]), "f"(e0_), "f"(cs[2]), "f"(e1_)); };
      if (mode == 2) { LASTSEQ return; }
      asm volatile("cp.async.wait_group %0;" :: "n"(NST - 1) : "memory");
      __syncwarp();
      if (mode == 1) STAMP(8);
      ldsm4(ef, eadr + so); ldsm4(T, qa0 + so); ldsm4(T + 4, qa1 + so); ldsm4(T + 8, qa2 + so); ldsm4(T + 12, qa3 + so);
      if (mode == 1) {
        tl_(); issue();
        cv(0); cv(1); cv(2); cv(3); ex0(); ex1(); ex2();
#pragma unroll
        for (int j = 0; j < 8; j++) { he(j); hs(j); }
        FIRSTSEQ return;
      }
      BODYSEQ
    };
#pragma unroll
    for (int j = 0; j < 8; j++) sum[j] = 0;
    body(IC<1>());
    int cnt = (lens & 255) - 1;
    auto pload = [&](uint32_t (&x)[8], uint32_t o) { const uint32_t l = a_g >> 1, a = p2 + o + (l & 7) * 128 + (((((l >> 3) & 3) ^ l) & 7) << 4); ldsm4t(x, a); ldsm4t(x + 4, a ^ 64); };
    auto flush = [&]() {
      asm volatile("{.reg .pred p; setp.ne.u32 p, %2, 6; @p st.shared.u16 [%0+-64], %1;}" :: "r"(a_g), "h"((uint16_t)pack_bf16(bf_hi(ownp) + pacc, 0.f)), "r"(a_g & 6) : "memory");
      chk = fmaf(pacc, 0.f, chk); pacc = 0.f; };
    constexpr uint64_t b1 = DHI | ((sb + OFF_W) >> 4), b2_ = b1 + 512;
    auto mma_h = [&](float (&acc)[32], uint32_t (&hf)[16]) {
      rs64b<0>(acc, hf[0], hf[1], hf[2], hf[3], b1); rs64b<1>(acc, hf[4], hf[5], hf[6], hf[7], b1 + 128); rs64b<1>(acc, hf[8], hf[9], hf[10], hf[11], b1 + 256); rs64b<1>(acc, hf[12], hf[13], hf[14], hf[15], b1 + 384); };
    auto mma_m = [&](float (&acc)[32]) {
      rs64h<1>(acc, sp[0], sum[0], sp[1], sum[1], b2_); rs64h<1>(acc, sp[2], sum[2], sp[3], sum[3], b2_ + 128); rs64h<1>(acc, sp[4], sum[4], sp[5], sum[5], b2_ + 256); rs64h<1>(acc, sp[6], sum[6], sp[7], sum[7], b2_ + 384);
      wg_commit(); wg_wait0(); fence_regs(acc);
      STAMP(10);
      chk = fmaf(acc[0], 0.f, fmaf(acc[2], 0.f, chk)); };
    auto roff = [&](uint32_t nd, int r) { return __shfl_sync(~0u, nd, ((a_g >> 3) & 7) + 8 * r) * 128 + (a_g & 6) * 8; };
    auto radr = [&](uint32_t o, int k) { return sb + OFF_H + (o ^ ((o >> 3) & 0x70) ^ ((k >> 1) << 6)); };
    auto fin = [&](float (&acc)[32], uint32_t* x, int k) {
#pragma unroll
      for (int i = 0; i < 4; i++) { const int c = 16 * (k >> 1) + 4 * i + 2 * (k & 1); x[i] = u2(__hadd2(b2(x[i]), b2(pack_bf16(silu_h(acc[c]), silu_h(acc[c + 1]))))); } };
#pragma unroll 1
    for (int t = 0;; t++) {
#pragma unroll 1
      for (; cnt > 0; cnt--) { body(IC<0>());
      }
      if (!(t & 1)) {
        ownp = own; a_g += 64;
        if (t == 6) break;
        pe = pol_first();
        own = lds16(a_g) * 0x10001u;
        if (t == 2) { const uint32_t a = ((a_g & 16) ? p2 : sb + OFF_WD) + ((a_g << 6) & 0x380) + (qa0 & 0x70);
          mbar_wait(sb + BAR_U);
#pragma unroll
          for (int j = 0; j < 4; j++) ldsm4t(bp + 4 * j, a ^ (j << 5));
        } else {
#pragma unroll
          for (int j = 0; j < 8; j++) bp[2 * j + 1] = sp[j];
        }
        lens >>= 8; cnt = 1;
        continue;
      }
      cnt = (lens & 255) - 1;
      flush();
      if (t == 3) {
        uint32_t x[8];
        pload(x, 1024);
        __syncwarp();
#pragma unroll
        for (int j = 0; j < 4; j++) stsm4((p2 + ((a_g << 6) & 0x780) + (qa0 & 0x70)) ^ (j << 5), sp[2 * j], sum[2 * j], sp[2 * j + 1], sum[2 * j + 1]);
#pragma unroll
        for (int j = 0; j < 8; j++) sum[j] = x[j];
        __syncwarp();
        mbar_arrive(sb + BAR_M + (wid >> 2) * 8, (a_g & 62) == 0);
      }
#pragma unroll
      for (int j = 0; j < 8; j++) { sp[j] = sum[j]; asm volatile("mov.b32 %0, 0;" : "=r"(sum[j])); }
    }
    {
      uint32_t hf[16], v[16]; float acc[32];
      const uint32_t nd = lds16(sb + OFF_GP + wid * 256 + (lane & 15) * 8 + 134), o[2] = {roff(nd, 0), roff(nd, 1)};
      hload(hf, nd);
#pragma unroll
      for (int k = 0; k < 4; k++) lds128(v + 4 * k, radr(o[k & 1], k));
      mbar_wait(sb + BAR_WH);
      wg_fence(); mma_h(acc, hf); wg_commit();
      body(IC<2>());
      STAMP(9);
      flush();
      __syncwarp();
      mbar_arrive(sb + BAR_X, lane == 0);
      wg_fence();
      mma_m(acc);
#pragma unroll
      for (int k = 0; k < 4; k++) { fin(acc, v + 4 * k, k);
        asm volatile("{.reg .pred p; setp.lt.u32 p, %5, %6; @p st.global.v4.b32 [%0], {%1,%2,%3,%4};}" :: "l"((const char*)p.out + (size_t)node0 * 128 + o[k & 1] + (k >> 1) * 64), "r"(v[4 * k]), "r"(v[4 * k + 1]), "r"(v[4 * k + 2]), "r"(v[4 * k + 3]), "r"(o[k & 1]), "r"(nloc * 128) : "memory"); }
    }
    asm volatile("{.reg .pred p, q; setp.neu.f32 p, %1, 0f00000000; setp.ne.or.u32 p, %2, 0, p; bar.red.or.pred q, 5, 512, p; selp.u32 %0, 1, 0, q;}" : "=r"(bad) : "f"(chk), "r"(lds32(sb + OFF_MISC + 12)) : "memory");
    STAMP(11);
   } else { asm volatile("cp.async.wait_all;" ::: "memory"); bar_sync(5, 384); }
  }
  if (bad) slow_path(p, wid, lane, node0, nloc);
}

}

typedef CUresult (*EncodeFn)(CUtensorMap*, CUtensorMapDataType, cuuint32_t, void*, const cuuint64_t*, const cuuint64_t*, const cuuint32_t*, const cuuint32_t*,
                             CUtensorMapInterleave, CUtensorMapSwizzle, CUtensorMapL2promotion, CUtensorMapFloatOOBfill);

extern "C" void kernel_launch(void* const* d_in, const int* in_sizes, int n_in, void* d_out, int out_size) {
  Params p; Maps maps;
  p.h = (const uint4*)d_in[0]; p.pos = (const uint16_t*)d_in[1]; p.ea = (const uint4*)d_in[2];
  p.src = (const int*)d_in[3]; p.dst = (const int*)d_in[4];
  p.we = (const uint16_t*)d_in[5]; p.wx = (const uint16_t*)d_in[6]; p.wh = (const uint16_t*)d_in[7];
  p.out = (uint16_t*)d_out;
  p.N = in_sizes[0] / 64; p.E = in_sizes[3];
  p.EPC = ((p.E + G * 4 - 1) / (G * 4)) * 4;
  p.magic = (uint32_t)(((uint64_t)G << 24) / (uint64_t)p.N);
  p.inv = (1ull << 56) / p.magic;
  const uint64_t ea0 = (uint64_t)d_in[2], ea1 = ea0 + (uint64_t)p.E * 32 - 1;
  p.force_slow = ((ea0 >> 32) != (ea1 >> 32)) || (ea0 & 31) || (p.E & 3);
  void* qp = nullptr;
  cudaGetSymbolAddress(&qp, g_q);
  p.q = (char*)qp;
  if (((uint64_t)p.q >> 32) != (((uint64_t)p.q + QBYTES) >> 32)) p.q += QBYTES;
  cudaGetSymbolAddress((void**)&p.sync, g_sync); cudaGetSymbolAddress((void**)&p.xe, g_xe);
  cudaGetSymbolAddress((void**)&p.xa, g_xa); cudaGetSymbolAddress((void**)&p.xb, g_xb);
  const int df[10] = {34, 120, 0, 3072, 0, 17, 0xff2, 0xD5C4E6, 0x422000, 4};
  for (int i = 0; i < 10; i++) p.tune[i] = df[i];
  p.qcode = 0x890145a6273bull;
  p.ctam = p.tune[5];
  if ((long long)PFB * PFN > (long long)(p.E / G) * 32) PFB = (p.E / G * 32 / PFN) & ~127;
  void* fn = nullptr; cudaDriverEntryPointQueryResult qr;
  cudaGetDriverEntryPoint("cuTensorMapEncodeTiled", &fn, cudaEnableDefault, &qr);
  auto mk = [&](CUtensorMap* tm, void* base, int rows, int box = 64) {
    const cuuint64_t dim[2] = {64, (cuuint64_t)rows}, str[1] = {128}; const cuuint32_t bx[2] = {64, (cuuint32_t)box}, es[2] = {1, 1};
    ((EncodeFn)fn)(tm, CU_TENSOR_MAP_DATA_TYPE_BFLOAT16, 2, base, dim, str, bx, es, CU_TENSOR_MAP_INTERLEAVE_NONE, CU_TENSOR_MAP_SWIZZLE_128B,
                   CU_TENSOR_MAP_L2_PROMOTION_NONE, CU_TENSOR_MAP_FLOAT_OOB_FILL_NONE);
  };
  mk(&maps.m[TM_H / 128], d_in[0], p.N); mk(&maps.m[TM_WE / 128], d_in[5], 145); mk(&maps.m[TM_WH / 128], d_in[7], 128); mk(&maps.m[TM_Q / 128], p.q, p.N, 16);
  for (int k = 0; k < 2; k++) {
    void* xp = (void*)(k ? p.xb : p.xa);
    const cuuint64_t dim[2] = {(cuuint64_t)G * 64, (cuuint64_t)G}, str[1] = {(cuuint64_t)G * (128 << k)}; const cuuint32_t bx[2] = {64, (cuuint32_t)(k ? BROWS : G)}, es[2] = {1, 1};
    ((EncodeFn)fn)(&maps.m[TM_XA / 128 + k], k ? CU_TENSOR_MAP_DATA_TYPE_UINT32 : CU_TENSOR_MAP_DATA_TYPE_UINT16, 2, xp, dim, str, bx, es, CU_TENSOR_MAP_INTERLEAVE_NONE,
                   CU_TENSOR_MAP_SWIZZLE_NONE, CU_TENSOR_MAP_L2_PROMOTION_NONE, CU_TENSOR_MAP_FLOAT_OOB_FILL_NONE);
  }
  cudaFuncSetAttribute(egnn_kernel, cudaFuncAttributeMaxDynamicSharedMemorySize, SMEM);
  egnn_kernel<<<G, NTHR, SMEM>>>(p, maps);
}
```
